```python
import torch

def _softmax(x, axis=-1):
    return torch.softmax(x, dim=axis)
def _gelu(x):
    return torch.nn.functional.gelu(x, approximate="tanh")
def _silu(x):
    return torch.nn.functional.silu(x)
def _sigmoid(x):
    return torch.sigmoid(x)
def _layernorm(x, axis=-1, eps=1e-5):
    m = x.mean(dim=axis, keepdim=True)
    v = x.var(dim=axis, keepdim=True, unbiased=False)
    return (x - m) / torch.sqrt(v + eps)
def _scatter_add(tgt, idx, src, axis=0):
    return tgt.clone().index_add_(axis, idx, src)
def _segment_sum(src, seg, n):
    out = torch.zeros((n,) + src.shape[1:], dtype=src.dtype)
    return out.index_add_(0, seg, src)
def _pad(x, pw):
    flat = tuple(v for pair in reversed(pw) for v in pair)
    return torch.nn.functional.pad(x, flat)

kernel_name = 'gated_mix__softmax_full_mha__dense_activation_gelu__prompt'

def setup_inputs():

    _w = (lambda a: (lambda t: t.to(torch.bfloat16) if t.is_floating_point() else t)(torch.as_tensor(a)))
    def _A_setup():
        B, S, D = 1, 2048, 512
        return {
            "x": _w((lambda *s: torch.randn(*s, dtype=torch.bfloat16) * 0.05)(B, S, D)),
            "wqkv": _w((lambda *s: torch.randn(*s, dtype=torch.bfloat16) * 0.8)(D, 3 * D)),
            "wo": _w((lambda *s: torch.randn(*s, dtype=torch.bfloat16) * 0.05)(D, D)),
        }
    _A_in = _A_setup()

    def _B_setup():
        B, S, D, F = 1, 2048, 512, 1792
        return {
            "x": _w((lambda *s: torch.randn(*s, dtype=torch.bfloat16) * 0.05)(B, S, D)),
            "w1": _w((lambda *s: torch.randn(*s, dtype=torch.bfloat16) * 3.2)(D, F) * (D ** -0.5)),
            "b1": _w((lambda *s: torch.randn(*s, dtype=torch.bfloat16) * 3.2)(F) * 0.01),
            "w2": _w((lambda *s: torch.randn(*s, dtype=torch.bfloat16) * 0.8)(F, D) * (F ** -0.5)),
            "b2": _w((lambda *s: torch.randn(*s, dtype=torch.bfloat16) * 1.6)(D) * 0.01),
        }
    _B_in = _B_setup()

    return {
        "A_x": _A_in["x"],
        "A_wqkv": _A_in["wqkv"],
        "A_wo": _A_in["wo"],
        "B_x": _B_in["x"],
        "B_w1": _B_in["w1"],
        "B_b1": _B_in["b1"],
        "B_w2": _B_in["w2"],
        "B_b2": _B_in["b2"],
        "gate_w": _w((lambda *s: torch.randn(*s, dtype=torch.bfloat16) * 0.05)(512) * 16.0),
    }

def reference(A_x, A_wqkv, A_wo, B_x, B_w1, B_b1, B_w2, B_b2, gate_w):
    def _A_ref(x, wqkv, wo):
        B, S, D = x.shape
        H = 32; Dh = D // H
        qkv = (lambda x, *d: x.permute(*d))((x @ wqkv).reshape(B, S, 3, H, Dh), 2, 0, 3, 1, 4)
        q, k, v = qkv[0], qkv[1], qkv[2]
        scale = Dh ** -0.5
        scores = torch.einsum("bhqd,bhkd->bhqk", q, k) * scale
        p = _softmax(scores, axis=-1)
        o = torch.einsum("bhqk,bhkd->bhqd", p, v)
        return (lambda x, *d: x.permute(*d))(o, 0, 2, 1, 3).reshape(B, S, D) @ wo

    def _B_ref(x, w1, b1, w2, b2):
        h = torch.einsum("bsd,df->bsf", x, w1) + b1
        h = _gelu(h)
        return torch.einsum("bsf,fd->bsd", h, w2) + b2

    x = A_x
    g = _sigmoid((x * gate_w).sum(-1, keepdims=True))
    a = _A_ref(x, A_wqkv, A_wo)
    b = _B_ref(x, B_w1, B_b1, B_w2, B_b2)
    return g * a + (1 - g) * b
```

```cpp
#include <cuda_runtime.h>
#include <cuda_bf16.h>
#include <cuda_fp16.h>
#include <cuda.h>
#include <stdint.h>

#define SEQ 2048
#define DM 512
#define FF 1792
#define NH 32

__device__ __align__(1024) uint8_t gQ[NH * SEQ * 32];
__device__ __align__(1024) uint8_t gQb[NH * SEQ * 32];
__device__ __align__(1024) uint8_t gD[NH * SEQ * 32];
__device__ __align__(1024) uint8_t gKb[NH * SEQ * 32];
__device__ __align__(1024) uint8_t gV[NH * SEQ * 32];
__device__ __align__(1024) __nv_bfloat16 gH[SEQ * FF];
__device__ __align__(1024) __nv_bfloat16 gO[SEQ * DM];
__device__ float gG[SEQ];
__device__ float gN[3 * 8 * 128];
__device__ unsigned int gCnt[32];

__device__ __forceinline__ uint32_t smem_u32(const void* p) { return (uint32_t)__cvta_generic_to_shared(p); }
__device__ __forceinline__ void mbar_init(uint32_t a, uint32_t c) { asm volatile("mbarrier.init.shared::cta.b64 [%0], %1;" ::"r"(a), "r"(c)); }
__device__ __forceinline__ void mbar_expect(uint32_t a, uint32_t b) { asm volatile("mbarrier.arrive.expect_tx.shared::cta.b64 _, [%0], %1;" ::"r"(a), "r"(b) : "memory"); }
__device__ __forceinline__ void mbar_wait(uint32_t a, uint32_t ph) {
    asm volatile("{\n.reg .pred p;\n.reg .u32 n;\nmov.u32 n, 0;\nW_%=:\nmbarrier.try_wait.parity.shared::cta.b64 p, [%0], %1;\n@p bra D_%=;\n"
                 "add.u32 n, n, 1;\nsetp.lt.u32 p, n, 0x400000;\n@p bra W_%=;\ntrap;\nD_%=:\n}" ::"r"(a), "r"(ph) : "memory");
}
__device__ __forceinline__ void mbar_arrive_cluster(uint32_t a, uint32_t cta) {
    asm volatile("{\n.reg .b32 r;\nmapa.shared::cluster.u32 r, %0, %1;\nmbarrier.arrive.shared::cluster.b64 _, [r];\n}" ::"r"(a), "r"(cta) : "memory");
}
__device__ __forceinline__ void cluster_sync() { asm volatile("barrier.cluster.arrive.aligned;\nbarrier.cluster.wait.aligned;" ::: "memory"); }
__device__ __forceinline__ uint32_t cluster_rank() { uint32_t r; asm("mov.u32 %0, %%cluster_ctarank;" : "=r"(r)); return r; }
__device__ __forceinline__ void tma2d(uint32_t dst, const CUtensorMap* m, int c0, int c1, uint32_t bar) {
    asm volatile("cp.async.bulk.tensor.2d.shared::cluster.global.mbarrier::complete_tx::bytes [%0], [%1, {%3, %4}], [%2];"
                 ::"r"(dst), "l"(m), "r"(bar), "r"(c0), "r"(c1) : "memory");
}
__device__ __forceinline__ void tma2d_mc(uint32_t dst, const CUtensorMap* m, int c0, int c1, uint32_t bar) {
    asm volatile("cp.async.bulk.tensor.2d.shared::cluster.global.mbarrier::complete_tx::bytes.multicast::cluster [%0], [%1, {%3, %4}], [%2], %5;"
                 ::"r"(dst), "l"(m), "r"(bar), "r"(c0), "r"(c1), "h"((uint16_t)3) : "memory");
}
__device__ __forceinline__ void tma3d_mc(uint32_t dst, const CUtensorMap* m, int c0, int c1, int c2, uint32_t bar) {
    asm volatile("cp.async.bulk.tensor.3d.shared::cluster.global.mbarrier::complete_tx::bytes.multicast::cluster [%0], [%1, {%3, %4, %5}], [%2], %6;"
                 ::"r"(dst), "l"(m), "r"(bar), "r"(c0), "r"(c1), "r"(c2), "h"((uint16_t)3) : "memory");
}
__device__ __forceinline__ void tma5d_mc(uint32_t dst, const CUtensorMap* m, int c0, int c4, uint32_t bar) {
    asm volatile("cp.async.bulk.tensor.5d.shared::cluster.global.mbarrier::complete_tx::bytes.multicast::cluster [%0], [%1, {%3, %5, %5, %5, %4}], [%2], %6;"
                 ::"r"(dst), "l"(m), "r"(bar), "r"(c0), "r"(c4), "r"(0), "h"((uint16_t)3) : "memory");
}
__device__ __forceinline__ void bulk_mc(uint32_t dst, const void* src, uint32_t bytes, uint32_t bar) {
    asm volatile("cp.async.bulk.shared::cluster.global.mbarrier::complete_tx::bytes.multicast::cluster [%0], [%1], %2, [%3], %4;"
                 ::"r"(dst), "l"(src), "r"(bytes), "r"(bar), "h"((uint16_t)3) : "memory");
}
__device__ __forceinline__ void bulk_ld(uint32_t dst, const void* src, uint32_t bytes, uint32_t bar) {
    asm volatile("cp.async.bulk.shared::cluster.global.mbarrier::complete_tx::bytes [%0], [%1], %2, [%3];"
                 ::"r"(dst), "l"(src), "r"(bytes), "r"(bar) : "memory");
}
__device__ __forceinline__ void l2_prefetch(const void* src, uint32_t bytes) {
    asm volatile("cp.async.bulk.prefetch.L2.global [%0], %1;" ::"l"(src), "r"(bytes) : "memory");
}
__device__ __forceinline__ void wg_fence() { asm volatile("wgmma.fence.sync.aligned;" ::: "memory"); }
__device__ __forceinline__ void wg_commit() { asm volatile("wgmma.commit_group.sync.aligned;" ::: "memory"); }
template <int N> __device__ __forceinline__ void wg_wait() { asm volatile("wgmma.wait_group.sync.aligned %0;" ::"n"(N) : "memory"); }
template <int N> __device__ __forceinline__ void pin(float* s) {
#pragma unroll
    for (int i = 0; i < N; i++) asm volatile("" : "+f"(s[i])::"memory");
}
template <int N> __device__ __forceinline__ void pin(uint32_t* s) {
#pragma unroll
    for (int i = 0; i < N; i++) asm volatile("" : "+r"(s[i])::"memory");
}
__device__ __forceinline__ uint64_t mkdesc(uint32_t addr, uint32_t lbo, uint32_t sbo, uint32_t swz) {
    return (uint64_t)((addr & 0x3FFFF) >> 4) | ((uint64_t)(lbo >> 4) << 16) | ((uint64_t)(sbo >> 4) << 32) | ((uint64_t)swz << 62);
}
__device__ __forceinline__ float ex2f(float x) { float y; asm("ex2.approx.ftz.f32 %0, %1;" : "=f"(y) : "f"(x)); return y; }
__device__ __forceinline__ float tanhf_(float x) { float y; asm("tanh.approx.f32 %0, %1;" : "=f"(y) : "f"(x)); return y; }
__device__ __forceinline__ uint32_t pk_bf16(float lo, float hi) { uint32_t r; asm("cvt.rn.bf16x2.f32 %0, %1, %2;" : "=r"(r) : "f"(hi), "f"(lo)); return r; }
__device__ __forceinline__ uint32_t pk_f16(float lo, float hi) { uint32_t r; asm("cvt.rn.f16x2.f32 %0, %1, %2;" : "=r"(r) : "f"(hi), "f"(lo)); return r; }
__device__ __forceinline__ float bf_lo(uint32_t v) { return __uint_as_float(v << 16); }
__device__ __forceinline__ float bf_hi(uint32_t v) { return __uint_as_float(v & 0xffff0000u); }

__device__ __forceinline__ void wgmma_ss_n224(float* d, uint64_t da, uint64_t db) {
    asm volatile("wgmma.mma_async.sync.aligned.m64n224k16.f32.bf16.bf16 {"
        "%0, %1, %2, %3, %4, %5, %6, %7, %8, %9, %10, %11, %12, %13, %14, %15,"
        "%16, %17, %18, %19, %20, %21, %22, %23, %24, %25, %26, %27, %28, %29, %30, %31,"
        "%32, %33, %34, %35, %36, %37, %38, %39, %40, %41, %42, %43, %44, %45, %46, %47,"
        "%48, %49, %50, %51, %52, %53, %54, %55, %56, %57, %58, %59, %60, %61, %62, %63,"
        "%64, %65, %66, %67, %68, %69, %70, %71, %72, %73, %74, %75, %76, %77, %78, %79,"
        "%80, %81, %82, %83, %84, %85, %86, %87, %88, %89, %90, %91, %92, %93, %94, %95,"
        "%96, %97, %98, %99, %100, %101, %102, %103, %104, %105, %106, %107, %108, %109, %110, %111}, %112, %113, 1, 1, 1, 0, 1;\n"
        :
        "+f"(d[0]), "+f"(d[1]), "+f"(d[2]), "+f"(d[3]), "+f"(d[4]), "+f"(d[5]), "+f"(d[6]), "+f"(d[7]),
        "+f"(d[8]), "+f"(d[9]), "+f"(d[10]), "+f"(d[11]), "+f"(d[12]), "+f"(d[13]), "+f"(d[14]), "+f"(d[15]),
        "+f"(d[16]), "+f"(d[17]), "+f"(d[18]), "+f"(d[19]), "+f"(d[20]), "+f"(d[21]), "+f"(d[22]), "+f"(d[23]),
        "+f"(d[24]), "+f"(d[25]), "+f"(d[26]), "+f"(d[27]), "+f"(d[28]), "+f"(d[29]), "+f"(d[30]), "+f"(d[31]),
        "+f"(d[32]), "+f"(d[33]), "+f"(d[34]), "+f"(d[35]), "+f"(d[36]), "+f"(d[37]), "+f"(d[38]), "+f"(d[39]),
        "+f"(d[40]), "+f"(d[41]), "+f"(d[42]), "+f"(d[43]), "+f"(d[44]), "+f"(d[45]), "+f"(d[46]), "+f"(d[47]),
        "+f"(d[48]), "+f"(d[49]), "+f"(d[50]), "+f"(d[51]), "+f"(d[52]), "+f"(d[53]), "+f"(d[54]), "+f"(d[55]),
        "+f"(d[56]), "+f"(d[57]), "+f"(d[58]), "+f"(d[59]), "+f"(d[60]), "+f"(d[61]), "+f"(d[62]), "+f"(d[63]),
        "+f"(d[64]), "+f"(d[65]), "+f"(d[66]), "+f"(d[67]), "+f"(d[68]), "+f"(d[69]), "+f"(d[70]), "+f"(d[71]),
        "+f"(d[72]), "+f"(d[73]), "+f"(d[74]), "+f"(d[75]), "+f"(d[76]), "+f"(d[77]), "+f"(d[78]), "+f"(d[79]),
        "+f"(d[80]), "+f"(d[81]), "+f"(d[82]), "+f"(d[83]), "+f"(d[84]), "+f"(d[85]), "+f"(d[86]), "+f"(d[87]),
        "+f"(d[88]), "+f"(d[89]), "+f"(d[90]), "+f"(d[91]), "+f"(d[92]), "+f"(d[93]), "+f"(d[94]), "+f"(d[95]),
        "+f"(d[96]), "+f"(d[97]), "+f"(d[98]), "+f"(d[99]), "+f"(d[100]), "+f"(d[101]), "+f"(d[102]), "+f"(d[103]),
        "+f"(d[104]), "+f"(d[105]), "+f"(d[106]), "+f"(d[107]), "+f"(d[108]), "+f"(d[109]), "+f"(d[110]), "+f"(d[111])
        : "l"(da), "l"(db));
}
__device__ __forceinline__ void wgmma_ss_n192(float* d, uint64_t da, uint64_t db) {
    asm volatile("wgmma.mma_async.sync.aligned.m64n192k16.f32.bf16.bf16 {"
        "%0, %1, %2, %3, %4, %5, %6, %7, %8, %9, %10, %11, %12, %13, %14, %15,"
        "%16, %17, %18, %19, %20, %21, %22, %23, %24, %25, %26, %27, %28, %29, %30, %31,"
        "%32, %33, %34, %35, %36, %37, %38, %39, %40, %41, %42, %43, %44, %45, %46, %47,"
        "%48, %49, %50, %51, %52, %53, %54, %55, %56, %57, %58, %59, %60, %61, %62, %63,"
        "%64, %65, %66, %67, %68, %69, %70, %71, %72, %73, %74, %75, %76, %77, %78, %79,"
        "%80, %81, %82, %83, %84, %85, %86, %87, %88, %89, %90, %91, %92, %93, %94, %95}, %96, %97, 1, 1, 1, 0, 1;\n"
        :
        "+f"(d[0]), "+f"(d[1]), "+f"(d[2]), "+f"(d[3]), "+f"(d[4]), "+f"(d[5]), "+f"(d[6]), "+f"(d[7]),
        "+f"(d[8]), "+f"(d[9]), "+f"(d[10]), "+f"(d[11]), "+f"(d[12]), "+f"(d[13]), "+f"(d[14]), "+f"(d[15]),
        "+f"(d[16]), "+f"(d[17]), "+f"(d[18]), "+f"(d[19]), "+f"(d[20]), "+f"(d[21]), "+f"(d[22]), "+f"(d[23]),
        "+f"(d[24]), "+f"(d[25]), "+f"(d[26]), "+f"(d[27]), "+f"(d[28]), "+f"(d[29]), "+f"(d[30]), "+f"(d[31]),
        "+f"(d[32]), "+f"(d[33]), "+f"(d[34]), "+f"(d[35]), "+f"(d[36]), "+f"(d[37]), "+f"(d[38]), "+f"(d[39]),
        "+f"(d[40]), "+f"(d[41]), "+f"(d[42]), "+f"(d[43]), "+f"(d[44]), "+f"(d[45]), "+f"(d[46]), "+f"(d[47]),
        "+f"(d[48]), "+f"(d[49]), "+f"(d[50]), "+f"(d[51]), "+f"(d[52]), "+f"(d[53]), "+f"(d[54]), "+f"(d[55]),
        "+f"(d[56]), "+f"(d[57]), "+f"(d[58]), "+f"(d[59]), "+f"(d[60]), "+f"(d[61]), "+f"(d[62]), "+f"(d[63]),
        "+f"(d[64]), "+f"(d[65]), "+f"(d[66]), "+f"(d[67]), "+f"(d[68]), "+f"(d[69]), "+f"(d[70]), "+f"(d[71]),
        "+f"(d[72]), "+f"(d[73]), "+f"(d[74]), "+f"(d[75]), "+f"(d[76]), "+f"(d[77]), "+f"(d[78]), "+f"(d[79]),
        "+f"(d[80]), "+f"(d[81]), "+f"(d[82]), "+f"(d[83]), "+f"(d[84]), "+f"(d[85]), "+f"(d[86]), "+f"(d[87]),
        "+f"(d[88]), "+f"(d[89]), "+f"(d[90]), "+f"(d[91]), "+f"(d[92]), "+f"(d[93]), "+f"(d[94]), "+f"(d[95])
        : "l"(da), "l"(db));
}
__device__ __forceinline__ void wgmma_ss_n128(float* d, uint64_t da, uint64_t db) {
    asm volatile("wgmma.mma_async.sync.aligned.m64n128k16.f32.bf16.bf16 {"
        "%0, %1, %2, %3, %4, %5, %6, %7, %8, %9, %10, %11, %12, %13, %14, %15,"
        "%16, %17, %18, %19, %20, %21, %22, %23, %24, %25, %26, %27, %28, %29, %30, %31,"
        "%32, %33, %34, %35, %36, %37, %38, %39, %40, %41, %42, %43, %44, %45, %46, %47,"
        "%48, %49, %50, %51, %52, %53, %54, %55, %56, %57, %58, %59, %60, %61, %62, %63}, %64, %65, 1, 1, 1, 0, 1;\n"
        :
        "+f"(d[0]), "+f"(d[1]), "+f"(d[2]), "+f"(d[3]), "+f"(d[4]), "+f"(d[5]), "+f"(d[6]), "+f"(d[7]),
        "+f"(d[8]), "+f"(d[9]), "+f"(d[10]), "+f"(d[11]), "+f"(d[12]), "+f"(d[13]), "+f"(d[14]), "+f"(d[15]),
        "+f"(d[16]), "+f"(d[17]), "+f"(d[18]), "+f"(d[19]), "+f"(d[20]), "+f"(d[21]), "+f"(d[22]), "+f"(d[23]),
        "+f"(d[24]), "+f"(d[25]), "+f"(d[26]), "+f"(d[27]), "+f"(d[28]), "+f"(d[29]), "+f"(d[30]), "+f"(d[31]),
        "+f"(d[32]), "+f"(d[33]), "+f"(d[34]), "+f"(d[35]), "+f"(d[36]), "+f"(d[37]), "+f"(d[38]), "+f"(d[39]),
        "+f"(d[40]), "+f"(d[41]), "+f"(d[42]), "+f"(d[43]), "+f"(d[44]), "+f"(d[45]), "+f"(d[46]), "+f"(d[47]),
        "+f"(d[48]), "+f"(d[49]), "+f"(d[50]), "+f"(d[51]), "+f"(d[52]), "+f"(d[53]), "+f"(d[54]), "+f"(d[55]),
        "+f"(d[56]), "+f"(d[57]), "+f"(d[58]), "+f"(d[59]), "+f"(d[60]), "+f"(d[61]), "+f"(d[62]), "+f"(d[63])
        : "l"(da), "l"(db));
}
__device__ __forceinline__ void wgmma_qk_f16_acc(float* d, const uint32_t* a, uint64_t db) {
    asm volatile("wgmma.mma_async.sync.aligned.m64n64k16.f32.f16.f16 {"
        "%0, %1, %2, %3, %4, %5, %6, %7, %8, %9, %10, %11, %12, %13, %14, %15,"
        "%16, %17, %18, %19, %20, %21, %22, %23, %24, %25, %26, %27, %28, %29, %30, %31}, {%32, %33, %34, %35}, %36, 1, 1, 1, 0;\n"
        :
        "+f"(d[0]), "+f"(d[1]), "+f"(d[2]), "+f"(d[3]), "+f"(d[4]), "+f"(d[5]), "+f"(d[6]), "+f"(d[7]),
        "+f"(d[8]), "+f"(d[9]), "+f"(d[10]), "+f"(d[11]), "+f"(d[12]), "+f"(d[13]), "+f"(d[14]), "+f"(d[15]),
        "+f"(d[16]), "+f"(d[17]), "+f"(d[18]), "+f"(d[19]), "+f"(d[20]), "+f"(d[21]), "+f"(d[22]), "+f"(d[23]),
        "+f"(d[24]), "+f"(d[25]), "+f"(d[26]), "+f"(d[27]), "+f"(d[28]), "+f"(d[29]), "+f"(d[30]), "+f"(d[31])
        : "r"(a[0]), "r"(a[1]), "r"(a[2]), "r"(a[3]), "l"(db));
}
__device__ __forceinline__ void wgmma_qk_bf16_zero(float* d, const uint32_t* a, uint64_t db) {
    asm volatile("wgmma.mma_async.sync.aligned.m64n64k16.f32.bf16.bf16 {"
        "%0, %1, %2, %3, %4, %5, %6, %7, %8, %9, %10, %11, %12, %13, %14, %15,"
        "%16, %17, %18, %19, %20, %21, %22, %23, %24, %25, %26, %27, %28, %29, %30, %31}, {%32, %33, %34, %35}, %36, 0, 1, 1, 0;\n"
        :
        "=f"(d[0]), "=f"(d[1]), "=f"(d[2]), "=f"(d[3]), "=f"(d[4]), "=f"(d[5]), "=f"(d[6]), "=f"(d[7]),
        "=f"(d[8]), "=f"(d[9]), "=f"(d[10]), "=f"(d[11]), "=f"(d[12]), "=f"(d[13]), "=f"(d[14]), "=f"(d[15]),
        "=f"(d[16]), "=f"(d[17]), "=f"(d[18]), "=f"(d[19]), "=f"(d[20]), "=f"(d[21]), "=f"(d[22]), "=f"(d[23]),
        "=f"(d[24]), "=f"(d[25]), "=f"(d[26]), "=f"(d[27]), "=f"(d[28]), "=f"(d[29]), "=f"(d[30]), "=f"(d[31])
        : "r"(a[0]), "r"(a[1]), "r"(a[2]), "r"(a[3]), "l"(db));
}
__device__ __forceinline__ void wgmma_pv(float* d, const uint32_t* a, uint64_t db) {
    asm volatile("wgmma.mma_async.sync.aligned.m64n24k16.f32.bf16.bf16 {"
        "%0, %1, %2, %3, %4, %5, %6, %7, %8, %9, %10, %11}, {%12, %13, %14, %15}, %16, 1, 1, 1, 1;\n"
        :
        "+f"(d[0]), "+f"(d[1]), "+f"(d[2]), "+f"(d[3]), "+f"(d[4]), "+f"(d[5]), "+f"(d[6]), "+f"(d[7]),
        "+f"(d[8]), "+f"(d[9]), "+f"(d[10]), "+f"(d[11])
        : "r"(a[0]), "r"(a[1]), "r"(a[2]), "r"(a[3]), "l"(db));
}


#define K1_STAGE 28672
#define K1_NST 3
#define K1_SMEM (131072 + K1_NST * K1_STAGE + 256 + 1024)
#define QSCALE 0.36067376022224085f

__global__ void __cluster_dims__(2, 1, 1) __launch_bounds__(384, 1)
k1_proj(const __grid_constant__ CUtensorMap tmX, const __grid_constant__ CUtensorMap tmW1, const __grid_constant__ CUtensorMap tmWq,
        const __nv_bfloat16* __restrict__ x, const __nv_bfloat16* __restrict__ b1, const __nv_bfloat16* __restrict__ gate,
        const __nv_bfloat16* __restrict__ w2, const __nv_bfloat16* __restrict__ wo) {
    extern __shared__ uint8_t smem_raw[];
    const uint32_t sb = (smem_u32(smem_raw) + 1023) & ~1023u;
    const uint32_t sX = sb, sW = sb + 131072, sBar = sW + K1_NST * K1_STAGE;
    const uint32_t barX = sBar, barF = sBar + 64, barE = sBar + 96;
    const int tid = threadIdx.x, lane = tid & 31;
    const int warp = __shfl_sync(0xffffffffu, tid >> 5, 0);
    const uint32_t rank = cluster_rank();
    const int cl = blockIdx.x >> 1;
    const int nb = cl & 7, mb = (cl >> 3) * 2 + rank;

    if (tid == 0) {
        for (int i = 0; i < 8; i++) mbar_init(barX + 8 * i, 1);
        for (int i = 0; i < K1_NST; i++) { mbar_init(barF + 8 * i, 1); mbar_init(barE + 8 * i, 16); }
        asm volatile("fence.mbarrier_init.release.cluster;" ::: "memory");
    }
    __syncthreads();
    cluster_sync();
    asm volatile("griddepcontrol.launch_dependents;");

    if (warp >= 8) {
        if (warp == 8) {
            if (lane == 0) {
                for (int it = 0; it < 16; it++) {
                    const int s = it % K1_NST;
                    if (it >= K1_NST) mbar_wait(barE + 8 * s, ((it / K1_NST) - 1) & 1);
                    if (it < 8) {
                        mbar_expect(barF + 8 * s, 28672);
                        tma3d_mc(sW + s * K1_STAGE + rank * 14336, &tmW1, 0, it * 64 + rank * 32, nb * 7, barF + 8 * s);
                    } else {
                        mbar_expect(barF + 8 * s, 24576);
                        tma3d_mc(sW + s * K1_STAGE + rank * 12288, &tmWq, nb * 64, (it - 8) * 64 + rank * 32, 0, barF + 8 * s);
                    }
                    if (it < K1_NST) {
                        const int lo = it == 0 ? 0 : (it == 1 ? 1 : 2), hi = it == K1_NST - 1 ? 8 : lo + 1;
                        for (int c = lo; c < hi; c++) {
                            mbar_expect(barX + 8 * c, 16384);
                            tma2d(sX + c * 16384, &tmX, c * 64, mb * 128, barX + 8 * c);
                        }
                    }
                }
            }
        } else if (warp == 9) {
            float gw[16];
            {
                const uint4 a = *(const uint4*)(gate + lane * 8), b = *(const uint4*)(gate + 256 + lane * 8);
                const uint32_t u[8] = {a.x, a.y, a.z, a.w, b.x, b.y, b.z, b.w};
#pragma unroll
                for (int i = 0; i < 8; i++) { gw[2 * i] = bf_lo(u[i]); gw[2 * i + 1] = bf_hi(u[i]); }
            }
            const int r0 = mb * 128 + nb * 16;
#pragma unroll 4
            for (int r = 0; r < 16; r++) {
                const __nv_bfloat16* xr = x + (size_t)(r0 + r) * DM;
                const uint4 a = *(const uint4*)(xr + lane * 8), b = *(const uint4*)(xr + 256 + lane * 8);
                const uint32_t u[8] = {a.x, a.y, a.z, a.w, b.x, b.y, b.z, b.w};
                float acc = 0.f;
#pragma unroll
                for (int i = 0; i < 8; i++) { acc = fmaf(bf_lo(u[i]), gw[2 * i], acc); acc = fmaf(bf_hi(u[i]), gw[2 * i + 1], acc); }
#pragma unroll
                for (int o = 16; o; o >>= 1) acc += __shfl_xor_sync(0xffffffffu, acc, o);
                if (lane == 0) gG[r0 + r] = 1.f / (1.f + __expf(-acc));
            }
        } else if (warp == 10) {
            if (blockIdx.x == 0) gCnt[lane] = 0;
            if (lane == 0) {
                l2_prefetch((const uint8_t*)w2 + (size_t)blockIdx.x * 14336, 14336);
                l2_prefetch((const uint8_t*)wo + (size_t)blockIdx.x * 4096, 4096);
            }
        }
    } else {
        const int wg = warp >> 2, g = lane >> 2, t = lane & 3;
        const int row0 = mb * 128 + warp * 16 + g;
        const uint64_t dA0 = mkdesc(sX + wg * 8192, 16, 1024, 1);
        {
            float acc[112];
#pragma unroll
            for (int j = 0; j < 28; j++) {
                const uint32_t bv = *(const uint32_t*)(b1 + nb * 224 + j * 8 + t * 2);
                acc[4 * j] = acc[4 * j + 2] = bf_lo(bv);
                acc[4 * j + 1] = acc[4 * j + 3] = bf_hi(bv);
            }
            pin<112>(acc);
#pragma unroll 1
            for (int it = 0; it < 8; it++) {
                const int s = it % K1_NST;
                mbar_wait(barX + 8 * it, 0);
                mbar_wait(barF + 8 * s, (it / K1_NST) & 1);
                const uint64_t dA = dA0 + it * 1024;
                const uint64_t dB = mkdesc(sW + s * K1_STAGE, 2048, 512, 2);
                wg_fence();
#pragma unroll
                for (int kk = 0; kk < 4; kk++) wgmma_ss_n224(acc, dA + kk * 2, dB + (kk >> 1) * 896 + (kk & 1) * 64);
                wg_commit();
                if (it > 0) {
                    wg_wait<1>();
                    if (lane < 2) mbar_arrive_cluster(barE + 8 * ((it - 1) % K1_NST), lane);
                }
            }
            wg_wait<0>();
            pin<112>(acc);
            if (lane < 2) mbar_arrive_cluster(barE + 8 * (7 % K1_NST), lane);
            __nv_bfloat16* hp = gH + (size_t)row0 * FF + nb * 224 + t * 8;
#pragma unroll
            for (int G = 0; G < 7; G++) {
                uint32_t o[8];
#pragma unroll
                for (int j = 0; j < 4; j++) {
                    float y[4];
#pragma unroll
                    for (int i = 0; i < 4; i++) {
                        const float h = acc[16 * G + 4 * j + i];
                        const float z = h * fmaf(h * h, 0.035677408136300125f, 0.7978845608028654f);
                        const float hh = 0.5f * h;
                        y[i] = fmaf(hh, tanhf_(z), hh);
                    }
                    o[j] = pk_bf16(y[0], y[1]);
                    o[4 + j] = pk_bf16(y[2], y[3]);
                }
                *(uint4*)(hp + G * 32) = make_uint4(o[0], o[1], o[2], o[3]);
                *(uint4*)(hp + 8 * FF + G * 32) = make_uint4(o[4], o[5], o[6], o[7]);
            }
        }
        {
            float acc[96];
#pragma unroll
            for (int i = 0; i < 96; i++) acc[i] = 0.f;
#pragma unroll 1
            for (int it = 8; it < 16; it++) {
                const int s = it % K1_NST;
                mbar_wait(barF + 8 * s, (it / K1_NST) & 1);
                const uint64_t dA = dA0 + (it - 8) * 1024;
                const uint64_t dB = mkdesc(sW + s * K1_STAGE, 4096, 1024, 1);
                wg_fence();
#pragma unroll
                for (int kk = 0; kk < 4; kk++) wgmma_ss_n192(acc, dA + kk * 2, dB + (kk >> 1) * 768 + (kk & 1) * 128);
                wg_commit();
                if (it > 8 && it < 14) {
                    wg_wait<1>();
                    if (lane < 2) mbar_arrive_cluster(barE + 8 * ((it - 1) % K1_NST), lane);
                }
            }
            wg_wait<0>();
            pin<96>(acc);
            const int T = mb * 8 + warp;
            float qm = 0.f, km = 0.f, vm = 0.f;
            {
                const size_t off = (size_t)(nb * 4) * (SEQ * 32) + (size_t)row0 * 32 + t * 8;
#pragma unroll
                for (int h = 0; h < 4; h++) {
                    float v[8];
#pragma unroll
                    for (int i = 0; i < 8; i++) v[i] = acc[8 * h + i] * QSCALE;
                    qm = fmaxf(qm, fmaf(v[0], v[0], fmaf(v[1], v[1], fmaf(v[4], v[4], v[5] * v[5]))));
                    qm = fmaxf(qm, fmaf(v[2], v[2], fmaf(v[3], v[3], fmaf(v[6], v[6], v[7] * v[7]))));
                    if (!(fabsf(v[0]) + fabsf(v[1]) + fabsf(v[2]) + fabsf(v[3]) + fabsf(v[4]) + fabsf(v[5]) + fabsf(v[6]) + fabsf(v[7]) < 1e30f)) qm = 1e38f;
                    const size_t o = off + (size_t)h * (SEQ * 32);
                    *(uint2*)(gQ + o) = make_uint2(pk_f16(v[0], v[1]), pk_f16(v[4], v[5]));
                    *(uint2*)(gQ + o + 256) = make_uint2(pk_f16(v[2], v[3]), pk_f16(v[6], v[7]));
                    *(uint2*)(gQb + o) = make_uint2(pk_bf16(v[0], v[1]), pk_bf16(v[4], v[5]));
                    *(uint2*)(gQb + o + 256) = make_uint2(pk_bf16(v[2], v[3]), pk_bf16(v[6], v[7]));
                }
            }
            {
                const size_t off = (size_t)(nb * 4) * (SEQ * 32) + (size_t)((((T >> 6) * 16 + 2 * g) * 64 + (T & 63)) * 32) + ((t * 8) ^ (((T >> 2) & 1) << 4));
#pragma unroll
                for (int h = 0; h < 4; h++) {
                    const float* v = acc + 32 + 8 * h;
                    km = fmaxf(km, fmaf(v[0], v[0], fmaf(v[1], v[1], fmaf(v[4], v[4], v[5] * v[5]))));
                    km = fmaxf(km, fmaf(v[2], v[2], fmaf(v[3], v[3], fmaf(v[6], v[6], v[7] * v[7]))));
                    if (!(fabsf(v[0]) + fabsf(v[1]) + fabsf(v[2]) + fabsf(v[3]) + fabsf(v[4]) + fabsf(v[5]) + fabsf(v[6]) + fabsf(v[7]) < 1e30f)) km = 1e38f;
                    float p0 = __shfl_up_sync(0xffffffffu, v[2], 4), p1 = __shfl_up_sync(0xffffffffu, v[3], 4);
                    float p2 = __shfl_up_sync(0xffffffffu, v[6], 4), p3 = __shfl_up_sync(0xffffffffu, v[7], 4);
                    if (g == 0) { p0 = p1 = p2 = p3 = 0.f; }
                    const size_t o = off + (size_t)h * (SEQ * 32);
                    *(uint2*)(gD + o) = make_uint2(pk_f16(v[0] - p0, v[1] - p1), pk_f16(v[4] - p2, v[5] - p3));
                    *(uint2*)(gD + o + 2048) = make_uint2(pk_f16(v[2] - v[0], v[3] - v[1]), pk_f16(v[6] - v[4], v[7] - v[5]));
                    *(uint2*)(gKb + o) = make_uint2(pk_bf16(v[0], v[1]), pk_bf16(v[4], v[5]));
                    *(uint2*)(gKb + o + 2048) = make_uint2(pk_bf16(v[2], v[3]), pk_bf16(v[6], v[7]));
                    const float* u = acc + 64 + 8 * h;
#pragma unroll
                    for (int i = 0; i < 8; i++) vm = fmaxf(vm, fabsf(u[i]));
                    *(uint2*)(gV + o) = make_uint2(pk_bf16(u[0], u[1]), pk_bf16(u[4], u[5]));
                    *(uint2*)(gV + o + 2048) = make_uint2(pk_bf16(u[2], u[3]), pk_bf16(u[6], u[7]));
                }
            }
#pragma unroll
            for (int o = 4; o < 32; o <<= 1) {
                qm = fmaxf(qm, __shfl_xor_sync(0xffffffffu, qm, o));
                km = fmaxf(km, __shfl_xor_sync(0xffffffffu, km, o));
            }
#pragma unroll
            for (int o = 1; o < 4; o <<= 1) {
                qm += __shfl_xor_sync(0xffffffffu, qm, o);
                km += __shfl_xor_sync(0xffffffffu, km, o);
            }
            vm = __uint_as_float(__reduce_max_sync(0xffffffffu, __float_as_uint(vm)));
            if (lane == 0) {
                gN[nb * 128 + T] = qm;
                gN[1024 + nb * 128 + T] = km;
                gN[2048 + nb * 128 + T] = vm;
            }
        }
    }
    cluster_sync();
}

#define K2_STAGE 24576
#define K2_NST 4
#define K2_SMEM (131072 + K2_NST * K2_STAGE + 512 + 256 + 1024)
#define MAGIC 445.41763f
#define NMUFU 4
#define VSTEP ((uint64_t)((long long)32 - ((long long)32 << 16)))

__device__ __forceinline__ uint32_t exp2_pair(float a, float b) {
    const uint32_t w = __byte_perm(__float_as_uint(a), __float_as_uint(b), 0x6521);
    uint32_t m, r;
    asm("lop3.b32 %0, %1, 0x007f007f, 0x9f809f80, 0xEA;" : "=r"(m) : "r"(w));
    const uint32_t e = w - m;
    asm("fma.rn.bf16x2 %0, %1, %2, %3;" : "=r"(r) : "r"(w), "r"(m), "r"(e));
    return r;
}

__device__ __forceinline__ void load_q(uint32_t* q, const uint8_t* base, int h, int row, int t) {
    const uint8_t* p = base + (size_t)h * (SEQ * 32) + (size_t)row * 32 + t * 4;
    q[0] = *(const uint32_t*)p;
    q[1] = *(const uint32_t*)(p + 256);
    q[2] = *(const uint32_t*)(p + 16);
    q[3] = *(const uint32_t*)(p + 256 + 16);
}

__device__ __forceinline__ void store_o(const float* o, int h, int row, int t) {
    const float s0 = __fdividef(gG[row], o[8]), s1 = __fdividef(gG[row + 8], o[10]);
    __nv_bfloat16* p = gO + (size_t)row * DM + h * 16 + (t & 1) * 8 + (t >> 1) * 2;
    *(uint32_t*)p = pk_bf16(o[0] * s0, o[1] * s0);
    *(uint32_t*)(p + 4) = pk_bf16(o[4] * s0, o[5] * s0);
    *(uint32_t*)(p + 8 * DM) = pk_bf16(o[2] * s1, o[3] * s1);
    *(uint32_t*)(p + 8 * DM + 4) = pk_bf16(o[6] * s1, o[7] * s1);
}

__global__ void __cluster_dims__(2, 1, 1) __launch_bounds__(640, 1)
k2_attn(const __grid_constant__ CUtensorMap tmH, const __grid_constant__ CUtensorMap tmO, const __grid_constant__ CUtensorMap tmW2,
        const __grid_constant__ CUtensorMap tmWo, const __nv_bfloat16* __restrict__ b2, __nv_bfloat16* __restrict__ out) {
    extern __shared__ uint8_t smem_raw[];
    const uint32_t sb = (smem_u32(smem_raw) + 1023) & ~1023u;
    const uint32_t sK = sb, sV = sb + 65536, sR = sb + 131072, sOne = sR + K2_NST * K2_STAGE, sBar = sOne + 512;
    const uint32_t barKV = sBar, barF = sBar + 64, barE = sBar + 96, barS = sBar + 128;
    const int tid = threadIdx.x, lane = tid & 31;
    const int warp = __shfl_sync(0xffffffffu, tid >> 5, 0);
    const uint32_t rank = cluster_rank();
    const int cl = blockIdx.x >> 1;

    if (tid == 0) {
        for (int i = 0; i < 8; i++) mbar_init(barKV + 8 * i, 1);
        for (int i = 0; i < K2_NST; i++) { mbar_init(barF + 8 * i, 1); mbar_init(barE + 8 * i, 8); }
        mbar_init(barS, 1);
        asm volatile("fence.mbarrier_init.release.cluster;" ::: "memory");
    }
    if (tid < 128) {
        asm volatile("st.shared.u32 [%0], %1;" ::"r"(sOne + tid * 4), "r"(0x3f803f80u) : "memory");
        asm volatile("fence.proxy.async.shared::cta;" ::: "memory");
    }
    __syncthreads();
    cluster_sync();

    if (warp < 16) {
        const int h = cl >> 1, qd = (cl & 1) * 2 + rank, wg = warp >> 2;
        const int g = lane >> 2, t = lane & 3;
        asm volatile("griddepcontrol.wait;" ::: "memory");
        if (tid == 0) {
            const uint8_t* src = (rank == 0 ? gD : gV) + (size_t)h * (SEQ * 32);
            for (int c = 0; c < 8; c++) {
                mbar_expect(barKV + 8 * c, 16384);
                bulk_mc(sK + rank * 65536 + c * 8192, src + c * 8192, 8192, barKV + 8 * c);
            }
        }
        bool fast;
        {
            const int nb = h >> 2;
            const float4 kq = *(const float4*)(gN + 1024 + nb * 128 + lane * 4);
            const float4 vq = *(const float4*)(gN + 2048 + nb * 128 + lane * 4);
            const float qq = gN[nb * 128 + qd * 32 + lane];
            const uint32_t km = __reduce_max_sync(0xffffffffu, max(max(__float_as_uint(kq.x), __float_as_uint(kq.y)), max(__float_as_uint(kq.z), __float_as_uint(kq.w))));
            const uint32_t vm = __reduce_max_sync(0xffffffffu, max(max(__float_as_uint(vq.x), __float_as_uint(vq.y)), max(__float_as_uint(vq.z), __float_as_uint(vq.w))));
            const uint32_t qm = __reduce_max_sync(0xffffffffu, __float_as_uint(qq));
            const float kf = __uint_as_float(km), qf = __uint_as_float(qm);
            fast = (kf <= 1.0e6f) && (qf <= 1.0e6f) && (kf * qf <= 3400.f) && (__uint_as_float(vm) <= 1.0e12f);
        }
        const uint64_t kd0 = mkdesc(sK, 16, 256, 3);
        const uint64_t vd0 = mkdesc(sV, sOne - sV, 256, 3);
        if (fast) {
#pragma unroll 1
            for (int r = 0; r < 2; r++) {
                const int row = qd * 512 + r * 256 + warp * 16 + g;
                uint32_t q[4];
                load_q(q, gQ, h, row, t);
                float o[12];
#pragma unroll
                for (int i = 0; i < 12; i++) o[i] = 0.f;
                uint64_t kd = kd0, vd = vd0;
#pragma unroll 1
                for (int half = 0; half < 2; half++) {
                    float s[32];
#pragma unroll
                    for (int i = 0; i < 32; i++) s[i] = i < 2 * NMUFU ? 0.f : MAGIC;
#pragma unroll 1
                    for (int c = 0; c < 4; c++) {
                        mbar_wait(barKV + 8 * (half * 4 + c), 0);
#pragma unroll 1
                        for (int j = 0; j < 4; j++) {
                            uint32_t p[16];
                            wg_fence();
                            wgmma_qk_f16_acc(s, q, kd);
                            wg_commit();
                            wg_wait<0>();
                            pin<32>(s);
#pragma unroll
                            for (int i = 0; i < 16; i++)
                                p[i] = i < NMUFU ? pk_bf16(ex2f(s[2 * i]), ex2f(s[2 * i + 1])) : exp2_pair(s[2 * i], s[2 * i + 1]);
                            pin<16>(p);
                            wg_fence();
#pragma unroll
                            for (int u = 0; u < 4; u++) wgmma_pv(o, p + 4 * u, vd + u * VSTEP);
                            wg_commit();
                            kd += 128;
                            vd += 4 * VSTEP;
                        }
                    }
                    wg_wait<0>();
                }
                pin<12>(o);
                store_o(o, h, row, t);
                __threadfence();
                asm volatile("bar.sync %0, 128;" ::"r"(1 + wg) : "memory");
                if ((tid & 127) == 0) asm volatile("red.release.gpu.global.add.u32 [%0], 1;" ::"l"(gCnt + qd * 8 + r * 4 + wg) : "memory");
            }
        } else {
            for (int c = 0; c < 8; c++) mbar_wait(barKV + 8 * c, 0);
            if (tid == 0) {
                mbar_expect(barS, 65536);
                for (int c = 0; c < 4; c++) bulk_ld(sK + c * 16384, gKb + (size_t)h * (SEQ * 32) + c * 16384, 16384, barS);
            }
            mbar_wait(barS, 0);
#pragma unroll 1
            for (int r = 0; r < 2; r++) {
                const int row = qd * 512 + r * 256 + warp * 16 + g;
                uint32_t q[4];
                load_q(q, gQb, h, row, t);
                float o[12];
#pragma unroll
                for (int i = 0; i < 12; i++) o[i] = 0.f;
                float m0 = -INFINITY, m1 = -INFINITY;
                uint64_t kd = kd0, vd = vd0;
#pragma unroll 1
                for (int j = 0; j < 32; j++) {
                    float s[32];
                    uint32_t p[16];
                    wg_fence();
                    wgmma_qk_bf16_zero(s, q, kd);
                    wg_commit();
                    wg_wait<0>();
                    pin<32>(s);
                    pin<12>(o);
                    float n0 = m0, n1 = m1;
#pragma unroll
                    for (int i = 0; i < 8; i++) {
                        n0 = fmaxf(n0, fmaxf(s[4 * i], s[4 * i + 1]));
                        n1 = fmaxf(n1, fmaxf(s[4 * i + 2], s[4 * i + 3]));
                    }
                    n0 = fmaxf(n0, __shfl_xor_sync(0xffffffffu, n0, 1));
                    n1 = fmaxf(n1, __shfl_xor_sync(0xffffffffu, n1, 1));
                    n0 = fmaxf(n0, __shfl_xor_sync(0xffffffffu, n0, 2));
                    n1 = fmaxf(n1, __shfl_xor_sync(0xffffffffu, n1, 2));
                    const float c0 = ex2f(m0 - n0), c1 = ex2f(m1 - n1);
                    m0 = n0;
                    m1 = n1;
#pragma unroll
                    for (int i = 0; i < 3; i++) { o[4 * i] *= c0; o[4 * i + 1] *= c0; o[4 * i + 2] *= c1; o[4 * i + 3] *= c1; }
#pragma unroll
                    for (int i = 0; i < 8; i++) {
                        p[2 * i] = pk_bf16(ex2f(s[4 * i] - m0), ex2f(s[4 * i + 1] - m0));
                        p[2 * i + 1] = pk_bf16(ex2f(s[4 * i + 2] - m1), ex2f(s[4 * i + 3] - m1));
                    }
                    pin<16>(p);
                    pin<12>(o);
                    wg_fence();
#pragma unroll
                    for (int u = 0; u < 4; u++) wgmma_pv(o, p + 4 * u, vd + u * VSTEP);
                    wg_commit();
                    kd += 128;
                    vd += 4 * VSTEP;
                }
                wg_wait<0>();
                pin<12>(o);
                store_o(o, h, row, t);
                __threadfence();
                asm volatile("bar.sync %0, 128;" ::"r"(1 + wg) : "memory");
                if ((tid & 127) == 0) asm volatile("red.release.gpu.global.add.u32 [%0], 1;" ::"l"(gCnt + qd * 8 + r * 4 + wg) : "memory");
            }
        }
    } else {
        const int cb = cl & 3, rb = (cl >> 2) * 2 + rank;
        const int g = lane >> 2, t = lane & 3;
        const bool prod = tid == 512;
        auto loadB = [&](int it) {
            const int s = it % K2_NST;
            mbar_expect(barF + 8 * s, K2_STAGE);
            const uint32_t dst = sR + s * K2_STAGE + 8192 + rank * 8192;
            if (it < 28) tma5d_mc(dst, &tmW2, cb * 128 + rank * 64, it * 2, barF + 8 * s);
            else tma2d_mc(dst, &tmWo, cb * 128 + rank * 64, (it - 28) * 64, barF + 8 * s);
        };
        auto loadA = [&](int it) {
            const int s = it % K2_NST;
            if (it < 28) tma2d(sR + s * K2_STAGE, &tmH, it * 64, rb * 64, barF + 8 * s);
            else tma2d(sR + s * K2_STAGE, &tmO, (it - 28) * 64, rb * 64, barF + 8 * s);
        };
        if (prod) for (int it = 0; it < K2_NST; it++) loadB(it);
        asm volatile("griddepcontrol.wait;" ::: "memory");
        if (prod) for (int it = 0; it < K2_NST; it++) loadA(it);
        float acc[64];
#pragma unroll
        for (int i = 0; i < 64; i++) acc[i] = 0.f;
        const int row = rb * 64 + (warp - 16) * 16 + g;
#pragma unroll 1
        for (int ph = 0; ph < 2; ph++) {
            const int i0 = ph ? 28 : 0, i1 = ph ? 36 : 28;
#pragma unroll 1
            for (int it = i0; it < i1; it++) {
                const int s = it % K2_NST;
                mbar_wait(barF + 8 * s, (it / K2_NST) & 1);
                const uint64_t dA = mkdesc(sR + s * K2_STAGE, 16, 1024, 1);
                const uint64_t dB = mkdesc(sR + s * K2_STAGE + 8192, 8192, 1024, 1);
                wg_fence();
#pragma unroll
                for (int kk = 0; kk < 4; kk++) wgmma_ss_n128(acc, dA + kk * 2, dB + kk * 128);
                wg_commit();
                wg_wait<0>();
                const int nx = it + K2_NST;
                if (nx < 36) {
                    if (lane < 2) mbar_arrive_cluster(barE + 8 * s, lane);
                    if (prod) {
                        mbar_wait(barE + 8 * s, (it / K2_NST) & 1);
                        loadB(nx);
                        if (nx < 28 || ph) loadA(nx);
                    }
                    __syncwarp();
                }
            }
            pin<64>(acc);
            if (ph == 0) {
                const float g0 = 1.f - gG[row], g1 = 1.f - gG[row + 8];
#pragma unroll
                for (int j = 0; j < 16; j++) {
                    const uint32_t bv = *(const uint32_t*)(b2 + cb * 128 + j * 8 + t * 2);
                    acc[4 * j] = (acc[4 * j] + bf_lo(bv)) * g0;
                    acc[4 * j + 1] = (acc[4 * j + 1] + bf_hi(bv)) * g0;
                    acc[4 * j + 2] = (acc[4 * j + 2] + bf_lo(bv)) * g1;
                    acc[4 * j + 3] = (acc[4 * j + 3] + bf_hi(bv)) * g1;
                }
                if (prod) {
                    uint32_t v;
                    int spins = 0;
                    do {
                        asm volatile("ld.acquire.gpu.global.u32 %0, [%1];" : "=r"(v) : "l"(gCnt + rb) : "memory");
                        if (v < 32) __nanosleep(64);
                    } while (v < 32 && ++spins < (1 << 22));
                    asm volatile("fence.proxy.async;" ::: "memory");
                    for (int it = 28; it < 28 + K2_NST; it++) loadA(it);
                }
                __syncwarp();
            }
        }
        __nv_bfloat16* op = out + (size_t)row * DM + cb * 128 + t * 2;
#pragma unroll
        for (int j = 0; j < 16; j++) {
            *(uint32_t*)(op + j * 8) = pk_bf16(acc[4 * j], acc[4 * j + 1]);
            *(uint32_t*)(op + 8 * DM + j * 8) = pk_bf16(acc[4 * j + 2], acc[4 * j + 3]);
        }
    }
    cluster_sync();
}

typedef CUresult (*EncodeFn)(CUtensorMap*, CUtensorMapDataType, cuuint32_t, void*, const cuuint64_t*, const cuuint64_t*, const cuuint32_t*,
                             const cuuint32_t*, CUtensorMapInterleave, CUtensorMapSwizzle, CUtensorMapL2promotion, CUtensorMapFloatOOBfill);

static void make_map(EncodeFn enc, CUtensorMap* m, const void* p, int rank, const cuuint64_t* dims, const cuuint64_t* strides,
                     const cuuint32_t* box, CUtensorMapSwizzle swz) {
    const cuuint32_t es[5] = {1, 1, 1, 1, 1};
    enc(m, CU_TENSOR_MAP_DATA_TYPE_BFLOAT16, rank, (void*)p, dims, strides, box, es, CU_TENSOR_MAP_INTERLEAVE_NONE, swz,
        CU_TENSOR_MAP_L2_PROMOTION_L2_128B, CU_TENSOR_MAP_FLOAT_OOB_FILL_NONE);
}

extern "C" void kernel_launch(void* const* d_in, const int* in_sizes, int n_in, void* d_out, int out_size) {
    const __nv_bfloat16* x = (const __nv_bfloat16*)d_in[0];
    const __nv_bfloat16* wqkv = (const __nv_bfloat16*)d_in[1];
    const __nv_bfloat16* wo = (const __nv_bfloat16*)d_in[2];
    const __nv_bfloat16* w1 = (const __nv_bfloat16*)d_in[4];
    const __nv_bfloat16* b1 = (const __nv_bfloat16*)d_in[5];
    const __nv_bfloat16* w2 = (const __nv_bfloat16*)d_in[6];
    const __nv_bfloat16* b2 = (const __nv_bfloat16*)d_in[7];
    const __nv_bfloat16* gate = (const __nv_bfloat16*)d_in[8];

    void* fp = nullptr;
    cudaDriverEntryPointQueryResult qr;
    cudaGetDriverEntryPoint("cuTensorMapEncodeTiled", &fp, cudaEnableDefault, &qr);
    EncodeFn enc = (EncodeFn)fp;
    void *pH, *pO;
    cudaGetSymbolAddress(&pH, gH);
    cudaGetSymbolAddress(&pO, gO);

    CUtensorMap tmX, tmW1, tmWq, tmH, tmO, tmW2, tmWo;
    { cuuint64_t d[2] = {DM, SEQ}, s[1] = {DM * 2}; cuuint32_t b[2] = {64, 128}; make_map(enc, &tmX, x, 2, d, s, b, CU_TENSOR_MAP_SWIZZLE_128B); }
    { cuuint64_t d[3] = {32, DM, FF / 32}, s[2] = {FF * 2, 64}; cuuint32_t b[3] = {32, 32, 7}; make_map(enc, &tmW1, w1, 3, d, s, b, CU_TENSOR_MAP_SWIZZLE_64B); }
    { cuuint64_t d[3] = {DM, DM, 3}, s[2] = {3 * DM * 2, DM * 2}; cuuint32_t b[3] = {64, 32, 3}; make_map(enc, &tmWq, wqkv, 3, d, s, b, CU_TENSOR_MAP_SWIZZLE_128B); }
    { cuuint64_t d[2] = {FF, SEQ}, s[1] = {FF * 2}; cuuint32_t b[2] = {64, 64}; make_map(enc, &tmH, pH, 2, d, s, b, CU_TENSOR_MAP_SWIZZLE_128B); }
    { cuuint64_t d[2] = {DM, SEQ}, s[1] = {DM * 2}; cuuint32_t b[2] = {64, 64}; make_map(enc, &tmO, pO, 2, d, s, b, CU_TENSOR_MAP_SWIZZLE_128B); }
    { cuuint64_t d[5] = {DM, 2, 4, 4, FF / 32}, s[4] = {1024, 8 * 1024, 2 * 1024, 32 * 1024}; cuuint32_t b[5] = {64, 2, 4, 4, 2};
      make_map(enc, &tmW2, w2, 5, d, s, b, CU_TENSOR_MAP_SWIZZLE_128B); }
    { cuuint64_t d[2] = {DM, DM}, s[1] = {DM * 2}; cuuint32_t b[2] = {64, 64}; make_map(enc, &tmWo, wo, 2, d, s, b, CU_TENSOR_MAP_SWIZZLE_128B); }

    cudaFuncSetAttribute(k1_proj, cudaFuncAttributeMaxDynamicSharedMemorySize, K1_SMEM);
    cudaFuncSetAttribute(k2_attn, cudaFuncAttributeMaxDynamicSharedMemorySize, K2_SMEM);

    cudaStream_t st = cudaStreamPerThread;
    k1_proj<<<128, 384, K1_SMEM, st>>>(tmX, tmW1, tmWq, x, b1, gate, w2, wo);

    cudaLaunchConfig_t cfg = {};
    cfg.gridDim = dim3(128);
    cfg.blockDim = dim3(640);
    cfg.dynamicSmemBytes = K2_SMEM;
    cfg.stream = st;
    cudaLaunchAttribute at[1];
    at[0].id = cudaLaunchAttributeProgrammaticStreamSerialization;
    at[0].val.programmaticStreamSerializationAllowed = 1;
    cfg.attrs = at;
    cfg.numAttrs = 1;
    cudaLaunchKernelEx(&cfg, k2_attn, tmH, tmO, tmW2, tmWo, b2, (__nv_bfloat16*)d_out);
}
```

```cpp
#include <cuda_runtime.h>
#include <cuda_bf16.h>
#include <cuda_fp16.h>
#include <cuda.h>
#include <stdint.h>

#define SEQ 2048
#define DM 512
#define FF 1792
#define NH 32

__device__ __align__(1024) uint8_t gQ[NH * SEQ * 32];
__device__ __align__(1024) uint8_t gKV[NH * SEQ * 64];
__device__ __align__(1024) __nv_bfloat16 gH[SEQ * FF];
__device__ __align__(1024) __nv_bfloat16 gO[SEQ * DM];
__device__ float gG[SEQ];
__device__ float gN[3 * 8 * 128];
__device__ unsigned int gCntQ[8 * 32];
__device__ unsigned int gCntH[32 * 32];
__device__ unsigned int gCntO[32 * 32];
__device__ unsigned int gEpoch[128];

__device__ __forceinline__ uint32_t smem_u32(const void* p) { return (uint32_t)__cvta_generic_to_shared(p); }
__device__ __forceinline__ void mbar_init(uint32_t a, uint32_t c) { asm volatile("mbarrier.init.shared::cta.b64 [%0], %1;" ::"r"(a), "r"(c)); }
__device__ __forceinline__ void mbar_expect(uint32_t a, uint32_t b) { asm volatile("mbarrier.arrive.expect_tx.shared::cta.b64 _, [%0], %1;" ::"r"(a), "r"(b) : "memory"); }
__device__ __forceinline__ void mbar_arrive(uint32_t a) { asm volatile("mbarrier.arrive.shared::cta.b64 _, [%0];" ::"r"(a) : "memory"); }
__device__ __forceinline__ void mbar_wait(uint32_t a, uint32_t ph) {
    asm volatile("{\n.reg .pred p;\n.reg .u32 n;\nmov.u32 n, 0;\nW_%=:\nmbarrier.try_wait.parity.shared::cta.b64 p, [%0], %1;\n@p bra D_%=;\n"
                 "add.u32 n, n, 1;\nsetp.lt.u32 p, n, 0x400000;\n@p bra W_%=;\ntrap;\nD_%=:\n}" ::"r"(a), "r"(ph) : "memory");
}
__device__ __forceinline__ void mbar_arrive_cluster(uint32_t a, uint32_t cta) {
    asm volatile("{\n.reg .b32 r;\nmapa.shared::cluster.u32 r, %0, %1;\nmbarrier.arrive.shared::cluster.b64 _, [r];\n}" ::"r"(a), "r"(cta) : "memory");
}
__device__ __forceinline__ void bar_sync(int id, int n) { asm volatile("bar.sync %0, %1;" ::"r"(id), "r"(n) : "memory"); }
__device__ __forceinline__ void bar_arrive(int id, int n) { asm volatile("bar.arrive %0, %1;" ::"r"(id), "r"(n) : "memory"); }
__device__ __forceinline__ uint32_t cluster_rank() { uint32_t r; asm("mov.u32 %0, %%cluster_ctarank;" : "=r"(r)); return r; }
__device__ __forceinline__ void cnt_add(unsigned int* c) { asm volatile("red.release.gpu.global.add.u32 [%0], 1;" ::"l"(c) : "memory"); }
__device__ __forceinline__ void cnt_wait(const unsigned int* c, uint32_t target) {
    uint32_t v;
    int spins = 0;
    while (true) {
        asm volatile("ld.acquire.gpu.global.u32 %0, [%1];" : "=r"(v) : "l"(c) : "memory");
        if ((int)(v - target) >= 0) break;
        if (++spins > (1 << 22)) __trap();
        __nanosleep(40);
    }
}
__device__ __forceinline__ void tma2d(uint32_t dst, const CUtensorMap* m, int c0, int c1, uint32_t bar) {
    asm volatile("cp.async.bulk.tensor.2d.shared::cluster.global.mbarrier::complete_tx::bytes [%0], [%1, {%3, %4}], [%2];"
                 ::"r"(dst), "l"(m), "r"(bar), "r"(c0), "r"(c1) : "memory");
}
__device__ __forceinline__ void tma2d_mc(uint32_t dst, const CUtensorMap* m, int c0, int c1, uint32_t bar) {
    asm volatile("cp.async.bulk.tensor.2d.shared::cluster.global.mbarrier::complete_tx::bytes.multicast::cluster [%0], [%1, {%3, %4}], [%2], %5;"
                 ::"r"(dst), "l"(m), "r"(bar), "r"(c0), "r"(c1), "h"((uint16_t)3) : "memory");
}
__device__ __forceinline__ void tma3d_mc(uint32_t dst, const CUtensorMap* m, int c0, int c1, int c2, uint32_t bar) {
    asm volatile("cp.async.bulk.tensor.3d.shared::cluster.global.mbarrier::complete_tx::bytes.multicast::cluster [%0], [%1, {%3, %4, %5}], [%2], %6;"
                 ::"r"(dst), "l"(m), "r"(bar), "r"(c0), "r"(c1), "r"(c2), "h"((uint16_t)3) : "memory");
}
__device__ __forceinline__ void tma5d_mc(uint32_t dst, const CUtensorMap* m, int c0, int c4, uint32_t bar) {
    asm volatile("cp.async.bulk.tensor.5d.shared::cluster.global.mbarrier::complete_tx::bytes.multicast::cluster [%0], [%1, {%3, %5, %5, %5, %4}], [%2], %6;"
                 ::"r"(dst), "l"(m), "r"(bar), "r"(c0), "r"(c4), "r"(0), "h"((uint16_t)3) : "memory");
}
__device__ __forceinline__ void bulk_mc(uint32_t dst, const void* src, uint32_t bytes, uint32_t bar) {
    asm volatile("cp.async.bulk.shared::cluster.global.mbarrier::complete_tx::bytes.multicast::cluster [%0], [%1], %2, [%3], %4;"
                 ::"r"(dst), "l"(src), "r"(bytes), "r"(bar), "h"((uint16_t)3) : "memory");
}
__device__ __forceinline__ void l2_prefetch(const void* src, uint32_t bytes) {
    asm volatile("cp.async.bulk.prefetch.L2.global [%0], %1;" ::"l"(src), "r"(bytes) : "memory");
}
__device__ __forceinline__ void map_prefetch(const CUtensorMap* m) { asm volatile("prefetch.tensormap [%0];" ::"l"(m) : "memory"); }
__device__ __forceinline__ void wg_fence() { asm volatile("wgmma.fence.sync.aligned;" ::: "memory"); }
__device__ __forceinline__ void wg_commit() { asm volatile("wgmma.commit_group.sync.aligned;" ::: "memory"); }
template <int N> __device__ __forceinline__ void wg_wait() { asm volatile("wgmma.wait_group.sync.aligned %0;" ::"n"(N) : "memory"); }
template <int N> __device__ __forceinline__ void pin(float* s) {
#pragma unroll
    for (int i = 0; i < N; i++) asm volatile("" : "+f"(s[i])::"memory");
}
template <int N> __device__ __forceinline__ void pin(uint32_t* s) {
#pragma unroll
    for (int i = 0; i < N; i++) asm volatile("" : "+r"(s[i])::"memory");
}
__device__ __forceinline__ uint64_t mkdesc(uint32_t addr, uint32_t lbo, uint32_t sbo, uint32_t swz) {
    return (uint64_t)((addr & 0x3FFFF) >> 4) | ((uint64_t)(lbo >> 4) << 16) | ((uint64_t)(sbo >> 4) << 32) | ((uint64_t)swz << 62);
}
__device__ __forceinline__ float ex2f(float x) { float y; asm("ex2.approx.ftz.f32 %0, %1;" : "=f"(y) : "f"(x)); return y; }
__device__ __forceinline__ float tanhf_(float x) { float y; asm("tanh.approx.f32 %0, %1;" : "=f"(y) : "f"(x)); return y; }
__device__ __forceinline__ uint32_t pk_bf16(float lo, float hi) { uint32_t r; asm("cvt.rn.bf16x2.f32 %0, %1, %2;" : "=r"(r) : "f"(hi), "f"(lo)); return r; }
__device__ __forceinline__ uint32_t pk_f16(float lo, float hi) { uint32_t r; asm("cvt.rn.f16x2.f32 %0, %1, %2;" : "=r"(r) : "f"(hi), "f"(lo)); return r; }
__device__ __forceinline__ float bf_lo(uint32_t v) { return __uint_as_float(v << 16); }
__device__ __forceinline__ float bf_hi(uint32_t v) { return __uint_as_float(v & 0xffff0000u); }
__device__ __forceinline__ float ldcg_f(const float* p) { return __ldcg(p); }

#define TLM(k, slot) do {} while (0)
#define TLC(k, slot) do {} while (0)

__device__ __forceinline__ void wgmma_ss_n128(float* d, uint64_t da, uint64_t db) {
    asm volatile("wgmma.mma_async.sync.aligned.m64n128k16.f32.bf16.bf16 {"
        "%0, %1, %2, %3, %4, %5, %6, %7, %8, %9, %10, %11, %12, %13, %14, %15,"
        "%16, %17, %18, %19, %20, %21, %22, %23, %24, %25, %26, %27, %28, %29, %30, %31,"
        "%32, %33, %34, %35, %36, %37, %38, %39, %40, %41, %42, %43, %44, %45, %46, %47,"
        "%48, %49, %50, %51, %52, %53, %54, %55, %56, %57, %58, %59, %60, %61, %62, %63}, %64, %65, 1, 1, 1, 0, 1;\n"
        :
        "+f"(d[0]), "+f"(d[1]), "+f"(d[2]), "+f"(d[3]), "+f"(d[4]), "+f"(d[5]), "+f"(d[6]), "+f"(d[7]),
        "+f"(d[8]), "+f"(d[9]), "+f"(d[10]), "+f"(d[11]), "+f"(d[12]), "+f"(d[13]), "+f"(d[14]), "+f"(d[15]),
        "+f"(d[16]), "+f"(d[17]), "+f"(d[18]), "+f"(d[19]), "+f"(d[20]), "+f"(d[21]), "+f"(d[22]), "+f"(d[23]),
        "+f"(d[24]), "+f"(d[25]), "+f"(d[26]), "+f"(d[27]), "+f"(d[28]), "+f"(d[29]), "+f"(d[30]), "+f"(d[31]),
        "+f"(d[32]), "+f"(d[33]), "+f"(d[34]), "+f"(d[35]), "+f"(d[36]), "+f"(d[37]), "+f"(d[38]), "+f"(d[39]),
        "+f"(d[40]), "+f"(d[41]), "+f"(d[42]), "+f"(d[43]), "+f"(d[44]), "+f"(d[45]), "+f"(d[46]), "+f"(d[47]),
        "+f"(d[48]), "+f"(d[49]), "+f"(d[50]), "+f"(d[51]), "+f"(d[52]), "+f"(d[53]), "+f"(d[54]), "+f"(d[55]),
        "+f"(d[56]), "+f"(d[57]), "+f"(d[58]), "+f"(d[59]), "+f"(d[60]), "+f"(d[61]), "+f"(d[62]), "+f"(d[63])
        : "l"(da), "l"(db));
}
__device__ __forceinline__ void wgmma_ss_n96(float* d, uint64_t da, uint64_t db) {
    asm volatile("wgmma.mma_async.sync.aligned.m64n96k16.f32.bf16.bf16 {"
        "%0, %1, %2, %3, %4, %5, %6, %7, %8, %9, %10, %11, %12, %13, %14, %15,"
        "%16, %17, %18, %19, %20, %21, %22, %23, %24, %25, %26, %27, %28, %29, %30, %31,"
        "%32, %33, %34, %35, %36, %37, %38, %39, %40, %41, %42, %43, %44, %45, %46, %47}, %48, %49, 1, 1, 1, 0, 1;\n"
        :
        "+f"(d[0]), "+f"(d[1]), "+f"(d[2]), "+f"(d[3]), "+f"(d[4]), "+f"(d[5]), "+f"(d[6]), "+f"(d[7]),
        "+f"(d[8]), "+f"(d[9]), "+f"(d[10]), "+f"(d[11]), "+f"(d[12]), "+f"(d[13]), "+f"(d[14]), "+f"(d[15]),
        "+f"(d[16]), "+f"(d[17]), "+f"(d[18]), "+f"(d[19]), "+f"(d[20]), "+f"(d[21]), "+f"(d[22]), "+f"(d[23]),
        "+f"(d[24]), "+f"(d[25]), "+f"(d[26]), "+f"(d[27]), "+f"(d[28]), "+f"(d[29]), "+f"(d[30]), "+f"(d[31]),
        "+f"(d[32]), "+f"(d[33]), "+f"(d[34]), "+f"(d[35]), "+f"(d[36]), "+f"(d[37]), "+f"(d[38]), "+f"(d[39]),
        "+f"(d[40]), "+f"(d[41]), "+f"(d[42]), "+f"(d[43]), "+f"(d[44]), "+f"(d[45]), "+f"(d[46]), "+f"(d[47])
        : "l"(da), "l"(db));
}
__device__ __forceinline__ void wgmma_ss_n64(float* d, uint64_t da, uint64_t db) {
    asm volatile("wgmma.mma_async.sync.aligned.m64n64k16.f32.bf16.bf16 {"
        "%0, %1, %2, %3, %4, %5, %6, %7, %8, %9, %10, %11, %12, %13, %14, %15,"
        "%16, %17, %18, %19, %20, %21, %22, %23, %24, %25, %26, %27, %28, %29, %30, %31}, %32, %33, 1, 1, 1, 0, 1;\n"
        :
        "+f"(d[0]), "+f"(d[1]), "+f"(d[2]), "+f"(d[3]), "+f"(d[4]), "+f"(d[5]), "+f"(d[6]), "+f"(d[7]),
        "+f"(d[8]), "+f"(d[9]), "+f"(d[10]), "+f"(d[11]), "+f"(d[12]), "+f"(d[13]), "+f"(d[14]), "+f"(d[15]),
        "+f"(d[16]), "+f"(d[17]), "+f"(d[18]), "+f"(d[19]), "+f"(d[20]), "+f"(d[21]), "+f"(d[22]), "+f"(d[23]),
        "+f"(d[24]), "+f"(d[25]), "+f"(d[26]), "+f"(d[27]), "+f"(d[28]), "+f"(d[29]), "+f"(d[30]), "+f"(d[31])
        : "l"(da), "l"(db));
}
__device__ __forceinline__ void wgmma_qk_f16_acc(float* d, const uint32_t* a, uint64_t db) {
    asm volatile("wgmma.mma_async.sync.aligned.m64n64k16.f32.f16.f16 {"
        "%0, %1, %2, %3, %4, %5, %6, %7, %8, %9, %10, %11, %12, %13, %14, %15,"
        "%16, %17, %18, %19, %20, %21, %22, %23, %24, %25, %26, %27, %28, %29, %30, %31}, {%32, %33, %34, %35}, %36, 1, 1, 1, 0;\n"
        :
        "+f"(d[0]), "+f"(d[1]), "+f"(d[2]), "+f"(d[3]), "+f"(d[4]), "+f"(d[5]), "+f"(d[6]), "+f"(d[7]),
        "+f"(d[8]), "+f"(d[9]), "+f"(d[10]), "+f"(d[11]), "+f"(d[12]), "+f"(d[13]), "+f"(d[14]), "+f"(d[15]),
        "+f"(d[16]), "+f"(d[17]), "+f"(d[18]), "+f"(d[19]), "+f"(d[20]), "+f"(d[21]), "+f"(d[22]), "+f"(d[23]),
        "+f"(d[24]), "+f"(d[25]), "+f"(d[26]), "+f"(d[27]), "+f"(d[28]), "+f"(d[29]), "+f"(d[30]), "+f"(d[31])
        : "r"(a[0]), "r"(a[1]), "r"(a[2]), "r"(a[3]), "l"(db));
}
__device__ __forceinline__ void wgmma_qk_bf16_zero(float* d, const uint32_t* a, uint64_t db) {
    asm volatile("wgmma.mma_async.sync.aligned.m64n64k16.f32.bf16.bf16 {"
        "%0, %1, %2, %3, %4, %5, %6, %7, %8, %9, %10, %11, %12, %13, %14, %15,"
        "%16, %17, %18, %19, %20, %21, %22, %23, %24, %25, %26, %27, %28, %29, %30, %31}, {%32, %33, %34, %35}, %36, 0, 1, 1, 0;\n"
        :
        "=f"(d[0]), "=f"(d[1]), "=f"(d[2]), "=f"(d[3]), "=f"(d[4]), "=f"(d[5]), "=f"(d[6]), "=f"(d[7]),
        "=f"(d[8]), "=f"(d[9]), "=f"(d[10]), "=f"(d[11]), "=f"(d[12]), "=f"(d[13]), "=f"(d[14]), "=f"(d[15]),
        "=f"(d[16]), "=f"(d[17]), "=f"(d[18]), "=f"(d[19]), "=f"(d[20]), "=f"(d[21]), "=f"(d[22]), "=f"(d[23]),
        "=f"(d[24]), "=f"(d[25]), "=f"(d[26]), "=f"(d[27]), "=f"(d[28]), "=f"(d[29]), "=f"(d[30]), "=f"(d[31])
        : "r"(a[0]), "r"(a[1]), "r"(a[2]), "r"(a[3]), "l"(db));
}
__device__ __forceinline__ void wgmma_pv(float* d, const uint32_t* a, uint64_t db) {
    asm volatile("wgmma.mma_async.sync.aligned.m64n24k16.f32.bf16.bf16 {"
        "%0, %1, %2, %3, %4, %5, %6, %7, %8, %9, %10, %11}, {%12, %13, %14, %15}, %16, 1, 1, 1, 1;\n"
        :
        "+f"(d[0]), "+f"(d[1]), "+f"(d[2]), "+f"(d[3]), "+f"(d[4]), "+f"(d[5]), "+f"(d[6]), "+f"(d[7]),
        "+f"(d[8]), "+f"(d[9]), "+f"(d[10]), "+f"(d[11])
        : "r"(a[0]), "r"(a[1]), "r"(a[2]), "r"(a[3]), "l"(db));
}

template <int N> __device__ __forceinline__ void wgmma_ss(float* d, uint64_t a, uint64_t b) {
    if (N == 128) wgmma_ss_n128(d, a, b);
    if (N == 96) wgmma_ss_n96(d, a, b);
    if (N == 64) wgmma_ss_n64(d, a, b);
}

#define OFF_R 131072
#define OFF_ONE 229376
#define OFF_BAR 229888
#define SMEM_BYTES (OFF_BAR + 512)
#define B_X 0
#define B_F1 64
#define B_E1 112
#define B_KV 160
#define B_F2 224
#define B_E2 256
#define B_T 288
#define B_DONE 352

#define QSCALE 0.36067376022224085f
#define MAGIC 445.41763f
#define NMUFU 4
#define VSTEP ((uint64_t)((long long)32 - ((long long)32 << 16)))

template <int N, int IT0, int NST, int KK, int SUB, int KST, int LBO, int SBO, int SWZ, bool WAITX>
__device__ __forceinline__ void gemm_pass(float* acc, uint32_t sb, uint64_t dA0, int lane, int barNext) {
#pragma unroll 1
    for (int i = 0; i < NST; i++) {
        const int it = IT0 + i, s = it % 6;
        if (WAITX) mbar_wait(sb + OFF_BAR + B_X + 8 * i, 0);
        mbar_wait(sb + OFF_BAR + B_F1 + 8 * s, (it / 6) & 1);
        const uint64_t dA = dA0 + i * (KK / 4 * 1024);
        const uint64_t dB = mkdesc(sb + OFF_R + s * 16384, LBO, SBO, SWZ);
        wg_fence();
#pragma unroll
        for (int kk = 0; kk < KK; kk++)
            wgmma_ss<N>(acc, dA + (kk >> 2) * 1024 + (kk & 3) * 2, dB + ((kk / (KK / 2)) * SUB + (kk % (KK / 2)) * KST) / 16);
        wg_commit();
        if (i == NST - 1 && barNext) bar_arrive(barNext, 512);
        if (i > 0) {
            wg_wait<1>();
            if (lane < 2) mbar_arrive_cluster(sb + OFF_BAR + B_E1 + 8 * ((it - 1) % 6), lane);
        }
    }
    wg_wait<0>();
    if (lane < 2) mbar_arrive_cluster(sb + OFF_BAR + B_E1 + 8 * ((IT0 + NST - 1) % 6), lane);
    pin<N / 2>(acc);
}

template <int N> __device__ __forceinline__ void bias_init(float* acc, const __nv_bfloat16* b) {
#pragma unroll
    for (int j = 0; j < N / 8; j++) {
        const uint32_t bv = *(const uint32_t*)(b + j * 8);
        acc[4 * j] = acc[4 * j + 2] = bf_lo(bv);
        acc[4 * j + 1] = acc[4 * j + 3] = bf_hi(bv);
    }
    pin<N / 2>(acc);
}

template <int N> __device__ __forceinline__ void gelu_store(const float* acc, __nv_bfloat16* hp) {
#pragma unroll
    for (int G = 0; G < N / 32; G++) {
        uint32_t o[8];
#pragma unroll
        for (int j = 0; j < 4; j++) {
            float y[4];
#pragma unroll
            for (int i = 0; i < 4; i++) {
                const float h = acc[16 * G + 4 * j + i];
                const float z = h * fmaf(h * h, 0.035677408136300125f, 0.7978845608028654f);
                const float hh = 0.5f * h;
                y[i] = fmaf(hh, tanhf_(z), hh);
            }
            o[j] = pk_bf16(y[0], y[1]);
            o[4 + j] = pk_bf16(y[2], y[3]);
        }
        *(uint4*)(hp + G * 32) = make_uint4(o[0], o[1], o[2], o[3]);
        *(uint4*)(hp + 8 * FF + G * 32) = make_uint4(o[4], o[5], o[6], o[7]);
    }
}

__device__ __forceinline__ float norm_bound(const float* v, float sc) {
    uint32_t m = 0;
#pragma unroll
    for (int h = 0; h < 4; h++) {
        const float* u = v + 8 * h;
        m = max(m, __float_as_uint(fmaf(u[0], u[0], fmaf(u[1], u[1], fmaf(u[4], u[4], u[5] * u[5])))));
        m = max(m, __float_as_uint(fmaf(u[2], u[2], fmaf(u[3], u[3], fmaf(u[6], u[6], u[7] * u[7])))));
    }
#pragma unroll
    for (int o = 4; o < 32; o <<= 1) m = max(m, __shfl_xor_sync(0xffffffffu, m, o));
    float f = __uint_as_float(m);
    f += __shfl_xor_sync(0xffffffffu, f, 1);
    f += __shfl_xor_sync(0xffffffffu, f, 2);
    return f * sc;
}

__device__ __forceinline__ uint32_t exp2_pair(float a, float b) {
    const uint32_t w = __byte_perm(__float_as_uint(a), __float_as_uint(b), 0x6521);
    uint32_t m, r;
    asm("lop3.b32 %0, %1, 0x007f007f, 0x9f809f80, 0xEA;" : "=r"(m) : "r"(w));
    const uint32_t e = w - m;
    asm("fma.rn.bf16x2 %0, %1, %2, %3;" : "=r"(r) : "r"(w), "r"(m), "r"(e));
    return r;
}

__device__ __forceinline__ void store_o(const float* o, float g0, float g1, int h, int row, int t) {
    const float s0 = __fdividef(g0, o[8]), s1 = __fdividef(g1, o[10]);
    __nv_bfloat16* p = gO + (size_t)row * DM + h * 16 + (t & 1) * 8 + (t >> 1) * 2;
    *(uint32_t*)p = pk_bf16(o[0] * s0, o[1] * s0);
    *(uint32_t*)(p + 4) = pk_bf16(o[4] * s0, o[5] * s0);
    *(uint32_t*)(p + 8 * DM) = pk_bf16(o[2] * s1, o[3] * s1);
    *(uint32_t*)(p + 8 * DM + 4) = pk_bf16(o[6] * s1, o[7] * s1);
}

template <int NT>
__device__ __forceinline__ void proj16(float (*c)[8], const __nv_bfloat16* x, const __nv_bfloat16* w, int row0, int rstep, int col, int g, int t) {
#pragma unroll
    for (int i = 0; i < NT; i++)
#pragma unroll
        for (int j = 0; j < 8; j++) c[i][j] = 0.f;
    const unsigned short* wu = (const unsigned short*)w;
#pragma unroll 1
    for (int k = 0; k < DM; k += 16) {
        uint32_t b[4];
#pragma unroll
        for (int j = 0; j < 4; j++) {
            const int kr = k + 2 * t + (j & 1) * 8, cc = col + g + (j >> 1) * 8;
            b[j] = (uint32_t)wu[(size_t)kr * (3 * DM) + cc] | ((uint32_t)wu[(size_t)(kr + 1) * (3 * DM) + cc] << 16);
        }
#pragma unroll
        for (int i = 0; i < NT; i++) {
            const __nv_bfloat16* xp = x + (size_t)(row0 + i * rstep + g) * DM + k + 2 * t;
            const uint32_t a0 = *(const uint32_t*)xp, a1 = *(const uint32_t*)(xp + 8 * DM);
            const uint32_t a2 = *(const uint32_t*)(xp + 8), a3 = *(const uint32_t*)(xp + 8 * DM + 8);
#pragma unroll
            for (int j = 0; j < 2; j++)
                asm volatile("mma.sync.aligned.m16n8k16.row.col.f32.bf16.bf16.f32 {%0,%1,%2,%3}, {%4,%5,%6,%7}, {%8,%9}, {%0,%1,%2,%3};"
                             : "+f"(c[i][4 * j]), "+f"(c[i][4 * j + 1]), "+f"(c[i][4 * j + 2]), "+f"(c[i][4 * j + 3])
                             : "r"(a0), "r"(a1), "r"(a2), "r"(a3), "r"(b[2 * j]), "r"(b[2 * j + 1]));
        }
    }
}

struct Maps { CUtensorMap x, kv, q, f0, f1, h, o, w2, wo; };

__global__ void __cluster_dims__(2, 1, 1) __launch_bounds__(640, 1)
fused_kernel(const __grid_constant__ Maps tm, const __nv_bfloat16* __restrict__ x, const __nv_bfloat16* __restrict__ wqkv,
             const __nv_bfloat16* __restrict__ wo, const __nv_bfloat16* __restrict__ w1, const __nv_bfloat16* __restrict__ b1,
             const __nv_bfloat16* __restrict__ w2, const __nv_bfloat16* __restrict__ b2, const __nv_bfloat16* __restrict__ gate,
             __nv_bfloat16* __restrict__ out) {
    extern __shared__ __align__(1024) uint8_t smem_raw[];
    const uint32_t sb = smem_u32(smem_raw);
    const uint32_t bar = sb + OFF_BAR;
    const int tid = threadIdx.x, lane = tid & 31;
    const int warp = __shfl_sync(0xffffffffu, tid >> 5, 0);
    const uint32_t rank = cluster_rank();
    const int cl = blockIdx.x >> 1;
    const int nb = cl & 7, mb = (cl >> 3) * 2 + rank;
    const int g = lane >> 2, t = lane & 3;

    if (tid == 0) TLM(0, 0);
    if (tid == 512) {
        for (int i = 0; i < 8; i++) { mbar_init(bar + B_X + 8 * i, 1); mbar_init(bar + B_KV + 8 * i, 1); mbar_init(bar + B_T + 8 * i, 1); }
        for (int i = 0; i < 6; i++) { mbar_init(bar + B_F1 + 8 * i, 1); mbar_init(bar + B_E1 + 8 * i, 16); }
        for (int i = 0; i < 4; i++) { mbar_init(bar + B_F2 + 8 * i, 1); mbar_init(bar + B_E2 + 8 * i, 8); }
        mbar_init(bar + B_DONE, 16);
        asm volatile("fence.mbarrier_init.release.cluster;" ::: "memory");
        for (int c = 0; c < 8; c++) {
            mbar_expect(bar + B_X + 8 * c, 16384);
            tma2d(sb + c * 16384, &tm.x, c * 64, mb * 128, bar + B_X + 8 * c);
        }
    } else if (tid == 544) {
        l2_prefetch((const uint8_t*)wqkv + (size_t)blockIdx.x * 12288, 12288);
        l2_prefetch(x + (size_t)(mb * 128 + nb * 16) * DM, 16384);
        map_prefetch(&tm.kv); map_prefetch(&tm.q); map_prefetch(&tm.f0); map_prefetch(&tm.f1);
        l2_prefetch((const uint8_t*)w1 + (size_t)blockIdx.x * 14336, 14336);
    } else if (tid < 128) {
        asm volatile("st.shared.u32 [%0], %1;" ::"r"(sb + OFF_ONE + tid * 4), "r"(0x3f803f80u) : "memory");
        asm volatile("fence.proxy.async.shared::cta;" ::: "memory");
    }
    const uint32_t ep = gEpoch[blockIdx.x] + 1;
    __syncthreads();
    asm volatile("barrier.cluster.arrive.relaxed.aligned;\nbarrier.cluster.wait.aligned;" ::: "memory");
    if (tid == 0) { TLM(0, 1); TLC(0, 30); }

    if (warp < 16) {
        const int wg = warp >> 2;
        {
            const int w8 = warp & 7;
            const int T = mb * 8 + w8, row0 = T * 16 + g;
            const uint64_t dA0 = mkdesc(sb + (wg & 1) * 8192, 16, 1024, 1);
            if (wg < 2) {
                {
                    float acc[64];
#pragma unroll
                    for (int i = 0; i < 64; i++) acc[i] = 0.f;
                    gemm_pass<128, 0, 8, 4, 8192, 2048, 4096, 1024, 1, true>(acc, sb, dA0, lane, 5);
                    if (tid == 0) TLM(0, 2);
                    const int pos = ((T >> 6) * 16 + 2 * g) * 64 + (T & 63);
                    uint8_t* kp = gKV + (size_t)(nb * 4) * (SEQ * 64) + (pos >> 8) * 16384 + (pos & 255) * 32 + ((t * 8) ^ (((T >> 2) & 1) << 4));
                    float vm = 0.f;
#pragma unroll
                    for (int h = 0; h < 4; h++) {
                        const float* v = acc + 8 * h;
                        float p0 = __shfl_up_sync(0xffffffffu, v[2], 4), p1 = __shfl_up_sync(0xffffffffu, v[3], 4);
                        float p2 = __shfl_up_sync(0xffffffffu, v[6], 4), p3 = __shfl_up_sync(0xffffffffu, v[7], 4);
                        if (g == 0) { p0 = p1 = p2 = p3 = 0.f; }
                        uint8_t* o = kp + (size_t)h * (SEQ * 64);
                        *(uint2*)o = make_uint2(pk_f16(v[0] - p0, v[1] - p1), pk_f16(v[4] - p2, v[5] - p3));
                        *(uint2*)(o + 2048) = make_uint2(pk_f16(v[2] - v[0], v[3] - v[1]), pk_f16(v[6] - v[4], v[7] - v[5]));
                        const float* u = acc + 32 + 8 * h;
#pragma unroll
                        for (int i = 0; i < 8; i++) vm = fmaxf(vm, fabsf(u[i]));
                        *(uint2*)(o + 8192) = make_uint2(pk_bf16(u[0], u[1]), pk_bf16(u[4], u[5]));
                        *(uint2*)(o + 8192 + 2048) = make_uint2(pk_bf16(u[2], u[3]), pk_bf16(u[6], u[7]));
                    }
                    const float km = norm_bound(acc, 1.f);
                    vm = __uint_as_float(__reduce_max_sync(0xffffffffu, __float_as_uint(vm)));
                    if (lane == 0) { gN[1024 + nb * 128 + T] = km; gN[2048 + nb * 128 + T] = vm; }
                    bar_arrive(10, 288);
                }
                {
                    float acc[64];
                    bias_init<128>(acc, b1 + nb * 224 + t * 2);
                    if (tid == 0) TLM(0, 3);
                    bar_sync(6, 512);
                    gemm_pass<128, 12, 8, 4, 8192, 2048, 4096, 1024, 1, false>(acc, sb, dA0, lane, 7);
                    if (tid == 0) TLM(0, 4);
                    gelu_store<128>(acc, gH + (size_t)row0 * FF + nb * 224 + t * 8);
                    if (tid == 0) TLM(0, 5);
                }
            } else {
                {
                    float acc[32];
#pragma unroll
                    for (int i = 0; i < 32; i++) acc[i] = 0.f;
                    bar_sync(5, 512);
                    gemm_pass<64, 8, 4, 8, 8192, 2048, 16, 1024, 1, false>(acc, sb, dA0, lane, 6);
                    if (tid == 256) TLM(0, 6);
                    uint8_t* qp = gQ + (size_t)(nb * 4) * (SEQ * 32) + (size_t)row0 * 32 + t * 8;
#pragma unroll
                    for (int h = 0; h < 4; h++) {
                        const float* v = acc + 8 * h;
                        uint8_t* o = qp + (size_t)h * (SEQ * 32);
                        *(uint2*)o = make_uint2(pk_f16(v[0] * QSCALE, v[1] * QSCALE), pk_f16(v[4] * QSCALE, v[5] * QSCALE));
                        *(uint2*)(o + 256) = make_uint2(pk_f16(v[2] * QSCALE, v[3] * QSCALE), pk_f16(v[6] * QSCALE, v[7] * QSCALE));
                    }
                    const float qm = norm_bound(acc, QSCALE * QSCALE);
                    if (lane == 0) gN[nb * 128 + T] = qm;
                    bar_arrive(9, 288);
                }
                {
                    float acc[48];
                    bias_init<96>(acc, b1 + nb * 224 + 128 + t * 2);
                    bar_sync(7, 512);
                    gemm_pass<96, 20, 8, 4, 6144, 1024, 2048, 512, 2, false>(acc, sb, dA0, lane, 0);
                    if (tid == 256) TLM(0, 7);
                    gelu_store<96>(acc, gH + (size_t)row0 * FF + nb * 224 + 128 + t * 8);
                    if (tid == 256) TLM(0, 8);
                }
            }
            bar_arrive(11 + (wg >> 1), 288);
        }
        const int h = cl >> 1, qd = (cl & 1) * 2 + rank;
        if (lane == 0) cnt_wait(gCntQ + (h >> 2) * 32, ep * 32);
        __syncwarp();
        uint32_t q[4];
        {
            const uint8_t* p = gQ + (size_t)h * (SEQ * 32) + (size_t)(qd * 512 + warp * 16 + g) * 32 + t * 4;
            q[0] = __ldcg((const uint32_t*)p); q[1] = __ldcg((const uint32_t*)(p + 256));
            q[2] = __ldcg((const uint32_t*)(p + 16)); q[3] = __ldcg((const uint32_t*)(p + 272));
        }
        bool fast;
        {
            const int hb = h >> 2;
            const uint4 kq = __ldcg((const uint4*)(gN + 1024 + hb * 128 + lane * 4));
            const uint4 vq = __ldcg((const uint4*)(gN + 2048 + hb * 128 + lane * 4));
            const float qq = ldcg_f(gN + hb * 128 + qd * 32 + lane);
            const float kf = __uint_as_float(__reduce_max_sync(0xffffffffu, max(max(kq.x, kq.y), max(kq.z, kq.w))));
            const float vf = __uint_as_float(__reduce_max_sync(0xffffffffu, max(max(vq.x, vq.y), max(vq.z, vq.w))));
            const float qf = __uint_as_float(__reduce_max_sync(0xffffffffu, __float_as_uint(qq)));
            fast = (kf <= 1.0e6f) && (qf <= 1.0e6f) && (kf * qf <= 3400.f) && (vf <= 1.0e12f);
        }
        const uint64_t kd0 = mkdesc(sb, 16, 256, 3);
        const uint64_t vd0 = mkdesc(sb + 8192, OFF_ONE - 8192, 256, 3);
        if (fast) {
#pragma unroll 1
            for (int r = 0; r < 2; r++) {
                const int row = qd * 512 + r * 256 + warp * 16 + g;
                float o[12];
#pragma unroll
                for (int i = 0; i < 12; i++) o[i] = 0.f;
                uint64_t kd = kd0, vd = vd0;
#pragma unroll 1
                for (int half = 0; half < 2; half++) {
                    float s[32];
#pragma unroll
                    for (int i = 0; i < 32; i++) s[i] = i < 2 * NMUFU ? 0.f : MAGIC;
#pragma unroll 1
                    for (int c = 0; c < 4; c++) {
                        mbar_wait(bar + B_KV + 8 * (half * 4 + c), 0);
                        if ((tid & 255) == 0 && c == 0) TLM(1, (tid >> 8) * 4 + r * 2 + half);
#pragma unroll 1
                        for (int j = 0; j < 4; j++) {
                            uint32_t p[16];
                            wg_fence();
                            wgmma_qk_f16_acc(s, q, kd);
                            wg_commit();
                            wg_wait<0>();
                            pin<32>(s);
#pragma unroll
                            for (int i = 0; i < 16; i++)
                                p[i] = i < NMUFU ? pk_bf16(ex2f(s[2 * i]), ex2f(s[2 * i + 1])) : exp2_pair(s[2 * i], s[2 * i + 1]);
                            pin<16>(p);
                            wg_fence();
#pragma unroll
                            for (int u = 0; u < 4; u++) wgmma_pv(o, p + 4 * u, vd + u * VSTEP);
                            wg_commit();
                            kd += 128;
                            vd += 4 * VSTEP;
                        }
                        kd += 512;
                        vd += 16 * VSTEP;
                    }
                    wg_wait<0>();
                }
                pin<12>(o);
                if ((tid & 127) == 0 && r == 1) TLM(1, 8 + wg);
                if (r == 1 && lane == 0) mbar_arrive(bar + B_DONE);
                if (lane == 0) cnt_wait(gCntH + (row >> 6) * 32, ep * 20);
                __syncwarp();
                const float g0 = ldcg_f(gG + row), g1 = ldcg_f(gG + row + 8);
                if (r == 0) {
                    const uint8_t* p = gQ + (size_t)h * (SEQ * 32) + (size_t)(row + 256) * 32 + t * 4;
                    q[0] = __ldcg((const uint32_t*)p); q[1] = __ldcg((const uint32_t*)(p + 256));
                    q[2] = __ldcg((const uint32_t*)(p + 16)); q[3] = __ldcg((const uint32_t*)(p + 272));
                }
                store_o(o, g0, g1, h, row, t);
                bar_sync(1 + wg, 128);
                if ((tid & 127) == 0) cnt_add(gCntO + (row >> 6) * 32);
                if (tid == 0 && r == 1) { TLM(1, 12); TLC(0, 31); }
            }
        } else {
            for (int c = 0; c < 8; c++) mbar_wait(bar + B_KV + 8 * c, 0);
            {
                float kc[8][8];
                proj16<8>(kc, x, wqkv, warp * 16, 256, DM + h * 16, g, t);
#pragma unroll
                for (int i = 0; i < 8; i++) {
                    const int T = warp + i * 16;
                    const int pos = ((T >> 6) * 16 + 2 * g) * 64 + (T & 63);
                    const uint32_t a = sb + (pos >> 8) * 16384 + (pos & 255) * 32 + t * 4, sw = ((T >> 2) & 1) << 4;
                    asm volatile("st.shared.u32 [%0], %1;" ::"r"(a + sw), "r"(pk_bf16(kc[i][0], kc[i][1])) : "memory");
                    asm volatile("st.shared.u32 [%0], %1;" ::"r"(a + (sw ^ 16)), "r"(pk_bf16(kc[i][4], kc[i][5])) : "memory");
                    asm volatile("st.shared.u32 [%0], %1;" ::"r"(a + 2048 + sw), "r"(pk_bf16(kc[i][2], kc[i][3])) : "memory");
                    asm volatile("st.shared.u32 [%0], %1;" ::"r"(a + 2048 + (sw ^ 16)), "r"(pk_bf16(kc[i][6], kc[i][7])) : "memory");
                }
                asm volatile("fence.proxy.async.shared::cta;" ::: "memory");
                bar_sync(8, 512);
            }
#pragma unroll 1
            for (int r = 0; r < 2; r++) {
                const int row = qd * 512 + r * 256 + warp * 16 + g;
                {
                    float qc[1][8];
                    proj16<1>(qc, x, wqkv, row - g, 0, h * 16, g, t);
#pragma unroll
                    for (int i = 0; i < 4; i++) q[i] = pk_bf16(qc[0][2 * i] * QSCALE, qc[0][2 * i + 1] * QSCALE);
                }
                float o[12];
#pragma unroll
                for (int i = 0; i < 12; i++) o[i] = 0.f;
                float m0 = -INFINITY, m1 = -INFINITY;
#pragma unroll 1
                for (int j = 0; j < 32; j++) {
                    const uint64_t kd = kd0 + (j >> 2) * 1024 + (j & 3) * 128, vd = vd0 + ((j >> 2) * 32 + (j & 3) * 4) * VSTEP;
                    float s[32];
                    uint32_t p[16];
                    wg_fence();
                    wgmma_qk_bf16_zero(s, q, kd);
                    wg_commit();
                    wg_wait<0>();
                    pin<32>(s);
                    pin<12>(o);
                    float n0 = m0, n1 = m1;
#pragma unroll
                    for (int i = 0; i < 8; i++) {
                        n0 = fmaxf(n0, fmaxf(s[4 * i], s[4 * i + 1]));
                        n1 = fmaxf(n1, fmaxf(s[4 * i + 2], s[4 * i + 3]));
                    }
                    n0 = fmaxf(n0, __shfl_xor_sync(0xffffffffu, n0, 1));
                    n1 = fmaxf(n1, __shfl_xor_sync(0xffffffffu, n1, 1));
                    n0 = fmaxf(n0, __shfl_xor_sync(0xffffffffu, n0, 2));
                    n1 = fmaxf(n1, __shfl_xor_sync(0xffffffffu, n1, 2));
                    const float c0 = ex2f(m0 - n0), c1 = ex2f(m1 - n1);
                    m0 = n0;
                    m1 = n1;
#pragma unroll
                    for (int i = 0; i < 3; i++) { o[4 * i] *= c0; o[4 * i + 1] *= c0; o[4 * i + 2] *= c1; o[4 * i + 3] *= c1; }
#pragma unroll
                    for (int i = 0; i < 8; i++) {
                        p[2 * i] = pk_bf16(ex2f(s[4 * i] - m0), ex2f(s[4 * i + 1] - m0));
                        p[2 * i + 1] = pk_bf16(ex2f(s[4 * i + 2] - m1), ex2f(s[4 * i + 3] - m1));
                    }
                    pin<16>(p);
                    pin<12>(o);
                    wg_fence();
#pragma unroll
                    for (int u = 0; u < 4; u++) wgmma_pv(o, p + 4 * u, vd + u * VSTEP);
                    wg_commit();
                }
                wg_wait<0>();
                pin<12>(o);
                if (r == 1 && lane == 0) mbar_arrive(bar + B_DONE);
                if (lane == 0) cnt_wait(gCntH + (row >> 6) * 32, ep * 20);
                __syncwarp();
                store_o(o, ldcg_f(gG + row), ldcg_f(gG + row + 8), h, row, t);
                bar_sync(1 + wg, 128);
                if ((tid & 127) == 0) cnt_add(gCntO + (row >> 6) * 32);
            }
        }
    } else {
        const int cb = cl & 3, rb = (cl >> 2) * 2 + rank;
        const bool prod = tid == 512;
        auto load2 = [&](int it) {
            const int s = it & 3;
            mbar_expect(bar + B_F2 + 8 * s, 24576);
            tma5d_mc(sb + OFF_R + s * 24576 + 8192 + rank * 8192, &tm.w2, cb * 128 + rank * 64, it * 2, bar + B_F2 + 8 * s);
            tma2d(sb + OFF_R + s * 24576, &tm.h, it * 64, rb * 64, bar + B_F2 + 8 * s);
        };
        if (prod) {
#pragma unroll 1
            for (int it = 0; it < 28; it++) {
                const int s = it % 6;
                const uint32_t fb = bar + B_F1 + 8 * s, dst = sb + OFF_R + s * 16384;
                if (it >= 6) mbar_wait(bar + B_E1 + 8 * s, ((it / 6) - 1) & 1);
                mbar_expect(fb, it < 20 ? 16384 : 12288);
                if (it < 8) tma3d_mc(dst + rank * 8192, &tm.kv, nb * 64, it * 64 + rank * 32, 1, fb);
                else if (it < 12) tma2d_mc(dst + rank * 8192, &tm.q, nb * 64, (it - 8) * 128 + rank * 64, fb);
                else if (it < 20) tma3d_mc(dst + rank * 8192, &tm.f0, nb * 224, (it - 12) * 64 + rank * 32, 0, fb);
                else tma3d_mc(dst + rank * 6144, &tm.f1, 0, (it - 20) * 64 + rank * 32, nb * 7 + 4, fb);
            }
            const int h = cl >> 1;
            cnt_wait(gCntQ + (h >> 2) * 32, ep * 32);
            asm volatile("fence.proxy.async;" ::: "memory");
            TLM(0, 9);
#pragma unroll 1
            for (int c = 0; c < 8; c++) {
                const int it = 20 + c;
                if (c >= 2) mbar_wait(bar + B_E1 + 8 * (it % 6), (it / 6) & 1);
                mbar_expect(bar + B_KV + 8 * c, 16384);
                bulk_mc(sb + c * 16384 + rank * 8192, gKV + (size_t)h * (SEQ * 64) + c * 16384 + rank * 8192, 8192, bar + B_KV + 8 * c);
            }
            cnt_wait(gCntH + rb * 32, ep * 20);
            asm volatile("fence.proxy.async;" ::: "memory");
            TLM(1, 13);
            for (int it = 0; it < 4; it++) load2(it);
        } else if (warp == 17) {
            float gw[16];
            {
                const uint4 a = *(const uint4*)(gate + lane * 8), b = *(const uint4*)(gate + 256 + lane * 8);
                const uint32_t u[8] = {a.x, a.y, a.z, a.w, b.x, b.y, b.z, b.w};
#pragma unroll
                for (int i = 0; i < 8; i++) { gw[2 * i] = bf_lo(u[i]); gw[2 * i + 1] = bf_hi(u[i]); }
            }
            const int r0 = mb * 128 + nb * 16;
#pragma unroll 2
            for (int r = 0; r < 16; r++) {
                const __nv_bfloat16* xr = x + (size_t)(r0 + r) * DM;
                const uint4 a = *(const uint4*)(xr + lane * 8), b = *(const uint4*)(xr + 256 + lane * 8);
                const uint32_t u[8] = {a.x, a.y, a.z, a.w, b.x, b.y, b.z, b.w};
                float acc = 0.f;
#pragma unroll
                for (int i = 0; i < 8; i++) { acc = fmaf(bf_lo(u[i]), gw[2 * i], acc); acc = fmaf(bf_hi(u[i]), gw[2 * i + 1], acc); }
#pragma unroll
                for (int o = 16; o; o >>= 1) acc += __shfl_xor_sync(0xffffffffu, acc, o);
                if (lane == 0) gG[r0 + r] = 1.f / (1.f + __expf(-acc));
            }
            if (lane == 0) {
                cnt_add(gCntH + (r0 >> 6) * 32);
                l2_prefetch((const uint8_t*)w2 + (size_t)blockIdx.x * 14336, 14336);
                l2_prefetch((const uint8_t*)wo + (size_t)blockIdx.x * 4096, 4096);
                map_prefetch(&tm.h); map_prefetch(&tm.w2); map_prefetch(&tm.wo); map_prefetch(&tm.o);
            }
        } else if (warp >= 18) {
            bar_sync(28 - warp, 288);
            if (lane == 0) cnt_add(gCntQ + nb * 32);
            bar_sync(warp - 7, 288);
            if (lane < 2) cnt_add(gCntH + (mb * 2 + lane) * 32);
        }
        __syncwarp();
        float acc[64];
#pragma unroll
        for (int i = 0; i < 64; i++) acc[i] = 0.f;
        const int row = rb * 64 + (warp - 16) * 16 + g;
#pragma unroll 1
        for (int it = 0; it < 28; it++) {
            const int s = it & 3;
            mbar_wait(bar + B_F2 + 8 * s, (it >> 2) & 1);
            if (prod && (it == 0 || it == 14)) TLM(1, 14 + it / 14);
            const uint64_t dA = mkdesc(sb + OFF_R + s * 24576, 16, 1024, 1);
            const uint64_t dB = mkdesc(sb + OFF_R + s * 24576 + 8192, 8192, 1024, 1);
            wg_fence();
#pragma unroll
            for (int kk = 0; kk < 4; kk++) wgmma_ss_n128(acc, dA + kk * 2, dB + kk * 128);
            wg_commit();
            if (prod && it >= 2 && it < 26) {
                mbar_wait(bar + B_E2 + 8 * ((it - 2) & 3), ((it - 2) >> 2) & 1);
                load2(it + 2);
            }
            __syncwarp();
            wg_wait<1>();
            if (it >= 1 && lane < 2) mbar_arrive_cluster(bar + B_E2 + 8 * ((it - 1) & 3), lane);
        }
        wg_wait<0>();
        if (lane < 2) mbar_arrive_cluster(bar + B_E2 + 8 * 3, lane);
        pin<64>(acc);
        if (prod) {
            TLM(1, 16);
            for (int s = 0; s < 4; s++) mbar_wait(bar + B_E2 + 8 * s, 0);
            for (int i = 0; i < 8; i++) mbar_expect(bar + B_T + 8 * i, 24576);
            for (int i = 0; i < 6; i++) tma2d_mc(sb + OFF_R + i * 16384 + rank * 8192, &tm.wo, cb * 128 + rank * 64, i * 64, bar + B_T + 8 * i);
        }
        __syncwarp();
        {
            const float g0 = 1.f - ldcg_f(gG + row), g1 = 1.f - ldcg_f(gG + row + 8);
#pragma unroll
            for (int j = 0; j < 16; j++) {
                const uint32_t bv = *(const uint32_t*)(b2 + cb * 128 + j * 8 + t * 2);
                acc[4 * j] = (acc[4 * j] + bf_lo(bv)) * g0;
                acc[4 * j + 1] = (acc[4 * j + 1] + bf_hi(bv)) * g0;
                acc[4 * j + 2] = (acc[4 * j + 2] + bf_lo(bv)) * g1;
                acc[4 * j + 3] = (acc[4 * j + 3] + bf_hi(bv)) * g1;
            }
            pin<64>(acc);
        }
        if (prod) {
            mbar_wait(bar + B_DONE, 0);
            for (int i = 0; i < 4; i++)
                tma2d(sb + 65536 + i * 8192, &tm.wo, cb * 128 + (i & 1) * 64, (6 + (i >> 1)) * 64, bar + B_T + 8 * (6 + (i >> 1)));
            cnt_wait(gCntO + rb * 32, ep * 32);
            asm volatile("fence.proxy.async;" ::: "memory");
            TLM(1, 17);
            for (int i = 0; i < 8; i++) tma2d(sb + i * 8192, &tm.o, i * 64, rb * 64, bar + B_T + 8 * i);
        }
        __syncwarp();
#pragma unroll 1
        for (int i = 0; i < 8; i++) {
            mbar_wait(bar + B_T + 8 * i, 0);
            const uint64_t dA = mkdesc(sb + i * 8192, 16, 1024, 1);
            const uint64_t dB = mkdesc(i < 6 ? sb + OFF_R + i * 16384 : sb + 65536 + (i - 6) * 16384, 8192, 1024, 1);
            wg_fence();
#pragma unroll
            for (int kk = 0; kk < 4; kk++) wgmma_ss_n128(acc, dA + kk * 2, dB + kk * 128);
            wg_commit();
        }
        wg_wait<0>();
        pin<64>(acc);
        if (prod) TLM(1, 18);
        __nv_bfloat16* op = out + (size_t)row * DM + cb * 128 + t * 2;
#pragma unroll
        for (int j = 0; j < 16; j++) {
            *(uint32_t*)(op + j * 8) = pk_bf16(acc[4 * j], acc[4 * j + 1]);
            *(uint32_t*)(op + 8 * DM + j * 8) = pk_bf16(acc[4 * j + 2], acc[4 * j + 3]);
        }
        if (prod) { gEpoch[blockIdx.x] = ep; TLM(1, 19); }
    }
}

typedef CUresult (*EncodeFn)(CUtensorMap*, CUtensorMapDataType, cuuint32_t, void*, const cuuint64_t*, const cuuint64_t*, const cuuint32_t*,
                             const cuuint32_t*, CUtensorMapInterleave, CUtensorMapSwizzle, CUtensorMapL2promotion, CUtensorMapFloatOOBfill);

static void make_map(EncodeFn enc, CUtensorMap* m, const void* p, int rank, const cuuint64_t* dims, const cuuint64_t* strides,
                     const cuuint32_t* box, CUtensorMapSwizzle swz) {
    const cuuint32_t es[5] = {1, 1, 1, 1, 1};
    enc(m, CU_TENSOR_MAP_DATA_TYPE_BFLOAT16, rank, (void*)p, dims, strides, box, es, CU_TENSOR_MAP_INTERLEAVE_NONE, swz,
        CU_TENSOR_MAP_L2_PROMOTION_L2_128B, CU_TENSOR_MAP_FLOAT_OOB_FILL_NONE);
}

extern "C" void kernel_launch(void* const* d_in, const int* in_sizes, int n_in, void* d_out, int out_size) {
    const __nv_bfloat16* x = (const __nv_bfloat16*)d_in[0];
    const __nv_bfloat16* wqkv = (const __nv_bfloat16*)d_in[1];
    const __nv_bfloat16* wo = (const __nv_bfloat16*)d_in[2];
    const __nv_bfloat16* w1 = (const __nv_bfloat16*)d_in[4];
    const __nv_bfloat16* b1 = (const __nv_bfloat16*)d_in[5];
    const __nv_bfloat16* w2 = (const __nv_bfloat16*)d_in[6];
    const __nv_bfloat16* b2 = (const __nv_bfloat16*)d_in[7];
    const __nv_bfloat16* gate = (const __nv_bfloat16*)d_in[8];

    void* fp = nullptr;
    cudaDriverEntryPointQueryResult qr;
    cudaGetDriverEntryPoint("cuTensorMapEncodeTiled", &fp, cudaEnableDefault, &qr);
    EncodeFn enc = (EncodeFn)fp;
    void *pH, *pO;
    cudaGetSymbolAddress(&pH, gH);
    cudaGetSymbolAddress(&pO, gO);

    Maps tm;
    const CUtensorMapSwizzle S128 = CU_TENSOR_MAP_SWIZZLE_128B, S64 = CU_TENSOR_MAP_SWIZZLE_64B;
    { cuuint64_t d[2] = {DM, SEQ}, s[1] = {DM * 2}; cuuint32_t b[2] = {64, 128}; make_map(enc, &tm.x, x, 2, d, s, b, S128); }
    { cuuint64_t d[3] = {DM, DM, 3}, s[2] = {3 * DM * 2, DM * 2}; cuuint32_t b[3] = {64, 32, 2}; make_map(enc, &tm.kv, wqkv, 3, d, s, b, S128); }
    { cuuint64_t d[2] = {3 * DM, DM}, s[1] = {3 * DM * 2}; cuuint32_t b[2] = {64, 64}; make_map(enc, &tm.q, wqkv, 2, d, s, b, S128); }
    { cuuint64_t d[3] = {FF - 64, DM, 2}, s[2] = {FF * 2, 128}; cuuint32_t b[3] = {64, 32, 2}; make_map(enc, &tm.f0, w1, 3, d, s, b, S128); }
    { cuuint64_t d[3] = {32, DM, FF / 32}, s[2] = {FF * 2, 64}; cuuint32_t b[3] = {32, 32, 3}; make_map(enc, &tm.f1, w1, 3, d, s, b, S64); }
    { cuuint64_t d[2] = {FF, SEQ}, s[1] = {FF * 2}; cuuint32_t b[2] = {64, 64}; make_map(enc, &tm.h, pH, 2, d, s, b, S128); }
    { cuuint64_t d[2] = {DM, SEQ}, s[1] = {DM * 2}; cuuint32_t b[2] = {64, 64}; make_map(enc, &tm.o, pO, 2, d, s, b, S128); }
    { cuuint64_t d[5] = {DM, 2, 4, 4, FF / 32}, s[4] = {1024, 8 * 1024, 2 * 1024, 32 * 1024}; cuuint32_t b[5] = {64, 2, 4, 4, 2};
      make_map(enc, &tm.w2, w2, 5, d, s, b, S128); }
    { cuuint64_t d[2] = {DM, DM}, s[1] = {DM * 2}; cuuint32_t b[2] = {64, 64}; make_map(enc, &tm.wo, wo, 2, d, s, b, S128); }

    cudaFuncSetAttribute(fused_kernel, cudaFuncAttributeMaxDynamicSharedMemorySize, SMEM_BYTES);
    fused_kernel<<<128, 640, SMEM_BYTES, cudaStreamPerThread>>>(tm, x, wqkv, wo, w1, b1, w2, b2, gate, (__nv_bfloat16*)d_out);
}
```

```cpp
#include <cuda_runtime.h>
#include <cuda_bf16.h>
#include <cuda_fp16.h>
#include <cuda.h>
#include <stdint.h>

#define SEQ 2048
#define DM 512
#define FF 1792
#define NH 32

__device__ __align__(1024) uint8_t gQ[NH * SEQ * 32];
__device__ __align__(1024) uint8_t gKV[NH * SEQ * 64];
__device__ __align__(1024) __nv_bfloat16 gH[SEQ * FF];
__device__ __align__(1024) __nv_bfloat16 gO[SEQ * DM];
__device__ float gG[SEQ];
__device__ float gN[3 * 8 * 128];
__device__ unsigned int gCntQ[8 * 32];
__device__ unsigned int gCntH[32 * 32];
__device__ unsigned int gCntO[32 * 8 * 8];
__device__ unsigned int gEpoch[128];

__device__ __forceinline__ uint32_t smem_u32(const void* p) { return (uint32_t)__cvta_generic_to_shared(p); }
__device__ __forceinline__ void mbar_init(uint32_t a, uint32_t c) { asm volatile("mbarrier.init.shared::cta.b64 [%0], %1;" ::"r"(a), "r"(c)); }
__device__ __forceinline__ void mbar_expect(uint32_t a, uint32_t b) { asm volatile("mbarrier.arrive.expect_tx.shared::cta.b64 _, [%0], %1;" ::"r"(a), "r"(b) : "memory"); }
__device__ __forceinline__ void mbar_arrive(uint32_t a) { asm volatile("mbarrier.arrive.shared::cta.b64 _, [%0];" ::"r"(a) : "memory"); }
__device__ __forceinline__ void mbar_wait(uint32_t a, uint32_t ph) {
    asm volatile("{\n.reg .pred p;\n.reg .u32 n;\nmov.u32 n, 0;\nW_%=:\nmbarrier.try_wait.parity.shared::cta.b64 p, [%0], %1;\n@p bra D_%=;\n"
                 "add.u32 n, n, 1;\nsetp.lt.u32 p, n, 0x400000;\n@p bra W_%=;\ntrap;\nD_%=:\n}" ::"r"(a), "r"(ph) : "memory");
}
__device__ __forceinline__ void mbar_arrive_cluster(uint32_t a, uint32_t cta) {
    asm volatile("{\n.reg .b32 r;\nmapa.shared::cluster.u32 r, %0, %1;\nmbarrier.arrive.shared::cluster.b64 _, [r];\n}" ::"r"(a), "r"(cta) : "memory");
}
__device__ __forceinline__ void bar_sync(int id, int n) { asm volatile("bar.sync %0, %1;" ::"r"(id), "r"(n) : "memory"); }
__device__ __forceinline__ void bar_arrive(int id, int n) { asm volatile("bar.arrive %0, %1;" ::"r"(id), "r"(n) : "memory"); }
__device__ __forceinline__ uint32_t cluster_rank() { uint32_t r; asm("mov.u32 %0, %%cluster_ctarank;" : "=r"(r)); return r; }
__device__ __forceinline__ void cnt_add(unsigned int* c) { asm volatile("red.release.gpu.global.add.u32 [%0], 1;" ::"l"(c) : "memory"); }
__device__ __forceinline__ void cnt_wait(const unsigned int* c, uint32_t target) {
    uint32_t v;
    int spins = 0;
    while (true) {
        asm volatile("ld.acquire.gpu.global.u32 %0, [%1];" : "=r"(v) : "l"(c) : "memory");
        if ((int)(v - target) >= 0) break;
        if (++spins > (1 << 22)) __trap();
        __nanosleep(40);
    }
}
__device__ __forceinline__ void tma2d(uint32_t dst, const CUtensorMap* m, int c0, int c1, uint32_t bar) {
    asm volatile("cp.async.bulk.tensor.2d.shared::cluster.global.mbarrier::complete_tx::bytes [%0], [%1, {%3, %4}], [%2];"
                 ::"r"(dst), "l"(m), "r"(bar), "r"(c0), "r"(c1) : "memory");
}
__device__ __forceinline__ void tma2d_mc(uint32_t dst, const CUtensorMap* m, int c0, int c1, uint32_t bar) {
    asm volatile("cp.async.bulk.tensor.2d.shared::cluster.global.mbarrier::complete_tx::bytes.multicast::cluster [%0], [%1, {%3, %4}], [%2], %5;"
                 ::"r"(dst), "l"(m), "r"(bar), "r"(c0), "r"(c1), "h"((uint16_t)3) : "memory");
}
__device__ __forceinline__ void tma3d_mc(uint32_t dst, const CUtensorMap* m, int c0, int c1, int c2, uint32_t bar) {
    asm volatile("cp.async.bulk.tensor.3d.shared::cluster.global.mbarrier::complete_tx::bytes.multicast::cluster [%0], [%1, {%3, %4, %5}], [%2], %6;"
                 ::"r"(dst), "l"(m), "r"(bar), "r"(c0), "r"(c1), "r"(c2), "h"((uint16_t)3) : "memory");
}
__device__ __forceinline__ void tma5d_mc(uint32_t dst, const CUtensorMap* m, int c0, int c4, uint32_t bar) {
    asm volatile("cp.async.bulk.tensor.5d.shared::cluster.global.mbarrier::complete_tx::bytes.multicast::cluster [%0], [%1, {%3, %5, %5, %5, %4}], [%2], %6;"
                 ::"r"(dst), "l"(m), "r"(bar), "r"(c0), "r"(c4), "r"(0), "h"((uint16_t)3) : "memory");
}
__device__ __forceinline__ void bulk_mc(uint32_t dst, const void* src, uint32_t bytes, uint32_t bar) {
    asm volatile("cp.async.bulk.shared::cluster.global.mbarrier::complete_tx::bytes.multicast::cluster [%0], [%1], %2, [%3], %4;"
                 ::"r"(dst), "l"(src), "r"(bytes), "r"(bar), "h"((uint16_t)3) : "memory");
}
__device__ __forceinline__ void l2_prefetch(const void* src, uint32_t bytes) {
    asm volatile("cp.async.bulk.prefetch.L2.global [%0], %1;" ::"l"(src), "r"(bytes) : "memory");
}
__device__ __forceinline__ void map_prefetch(const CUtensorMap* m) { asm volatile("prefetch.tensormap [%0];" ::"l"(m) : "memory"); }
__device__ __forceinline__ void wg_fence() { asm volatile("wgmma.fence.sync.aligned;" ::: "memory"); }
__device__ __forceinline__ void wg_commit() { asm volatile("wgmma.commit_group.sync.aligned;" ::: "memory"); }
template <int N> __device__ __forceinline__ void wg_wait() { asm volatile("wgmma.wait_group.sync.aligned %0;" ::"n"(N) : "memory"); }
template <int N> __device__ __forceinline__ void pin(float* s) {
#pragma unroll
    for (int i = 0; i < N; i++) asm volatile("" : "+f"(s[i])::"memory");
}
template <int N> __device__ __forceinline__ void pin(uint32_t* s) {
#pragma unroll
    for (int i = 0; i < N; i++) asm volatile("" : "+r"(s[i])::"memory");
}
__device__ __forceinline__ uint64_t mkdesc(uint32_t addr, uint32_t lbo, uint32_t sbo, uint32_t swz) {
    return (uint64_t)((addr & 0x3FFFF) >> 4) | ((uint64_t)(lbo >> 4) << 16) | ((uint64_t)(sbo >> 4) << 32) | ((uint64_t)swz << 62);
}
__device__ __forceinline__ float ex2f(float x) { float y; asm("ex2.approx.ftz.f32 %0, %1;" : "=f"(y) : "f"(x)); return y; }
__device__ __forceinline__ float tanhf_(float x) { float y; asm("tanh.approx.f32 %0, %1;" : "=f"(y) : "f"(x)); return y; }
__device__ __forceinline__ uint32_t pk_bf16(float lo, float hi) { uint32_t r; asm("cvt.rn.bf16x2.f32 %0, %1, %2;" : "=r"(r) : "f"(hi), "f"(lo)); return r; }
__device__ __forceinline__ uint32_t pk_f16(float lo, float hi) { uint32_t r; asm("cvt.rn.f16x2.f32 %0, %1, %2;" : "=r"(r) : "f"(hi), "f"(lo)); return r; }
__device__ __forceinline__ float bf_lo(uint32_t v) { return __uint_as_float(v << 16); }
__device__ __forceinline__ float bf_hi(uint32_t v) { return __uint_as_float(v & 0xffff0000u); }
__device__ __forceinline__ float ldcg_f(const float* p) { return __ldcg(p); }

#define TLM(k, slot) do {} while (0)
#define TLC(k, slot) do {} while (0)

__device__ __forceinline__ void wgmma_ss_n128(float* d, uint64_t da, uint64_t db) {
    asm volatile("wgmma.mma_async.sync.aligned.m64n128k16.f32.bf16.bf16 {"
        "%0, %1, %2, %3, %4, %5, %6, %7, %8, %9, %10, %11, %12, %13, %14, %15,"
        "%16, %17, %18, %19, %20, %21, %22, %23, %24, %25, %26, %27, %28, %29, %30, %31,"
        "%32, %33, %34, %35, %36, %37, %38, %39, %40, %41, %42, %43, %44, %45, %46, %47,"
        "%48, %49, %50, %51, %52, %53, %54, %55, %56, %57, %58, %59, %60, %61, %62, %63}, %64, %65, 1, 1, 1, 0, 1;\n"
        :
        "+f"(d[0]), "+f"(d[1]), "+f"(d[2]), "+f"(d[3]), "+f"(d[4]), "+f"(d[5]), "+f"(d[6]), "+f"(d[7]),
        "+f"(d[8]), "+f"(d[9]), "+f"(d[10]), "+f"(d[11]), "+f"(d[12]), "+f"(d[13]), "+f"(d[14]), "+f"(d[15]),
        "+f"(d[16]), "+f"(d[17]), "+f"(d[18]), "+f"(d[19]), "+f"(d[20]), "+f"(d[21]), "+f"(d[22]), "+f"(d[23]),
        "+f"(d[24]), "+f"(d[25]), "+f"(d[26]), "+f"(d[27]), "+f"(d[28]), "+f"(d[29]), "+f"(d[30]), "+f"(d[31]),
        "+f"(d[32]), "+f"(d[33]), "+f"(d[34]), "+f"(d[35]), "+f"(d[36]), "+f"(d[37]), "+f"(d[38]), "+f"(d[39]),
        "+f"(d[40]), "+f"(d[41]), "+f"(d[42]), "+f"(d[43]), "+f"(d[44]), "+f"(d[45]), "+f"(d[46]), "+f"(d[47]),
        "+f"(d[48]), "+f"(d[49]), "+f"(d[50]), "+f"(d[51]), "+f"(d[52]), "+f"(d[53]), "+f"(d[54]), "+f"(d[55]),
        "+f"(d[56]), "+f"(d[57]), "+f"(d[58]), "+f"(d[59]), "+f"(d[60]), "+f"(d[61]), "+f"(d[62]), "+f"(d[63])
        : "l"(da), "l"(db));
}
__device__ __forceinline__ void wgmma_ss_n96(float* d, uint64_t da, uint64_t db) {
    asm volatile("wgmma.mma_async.sync.aligned.m64n96k16.f32.bf16.bf16 {"
        "%0, %1, %2, %3, %4, %5, %6, %7, %8, %9, %10, %11, %12, %13, %14, %15,"
        "%16, %17, %18, %19, %20, %21, %22, %23, %24, %25, %26, %27, %28, %29, %30, %31,"
        "%32, %33, %34, %35, %36, %37, %38, %39, %40, %41, %42, %43, %44, %45, %46, %47}, %48, %49, 1, 1, 1, 0, 1;\n"
        :
        "+f"(d[0]), "+f"(d[1]), "+f"(d[2]), "+f"(d[3]), "+f"(d[4]), "+f"(d[5]), "+f"(d[6]), "+f"(d[7]),
        "+f"(d[8]), "+f"(d[9]), "+f"(d[10]), "+f"(d[11]), "+f"(d[12]), "+f"(d[13]), "+f"(d[14]), "+f"(d[15]),
        "+f"(d[16]), "+f"(d[17]), "+f"(d[18]), "+f"(d[19]), "+f"(d[20]), "+f"(d[21]), "+f"(d[22]), "+f"(d[23]),
        "+f"(d[24]), "+f"(d[25]), "+f"(d[26]), "+f"(d[27]), "+f"(d[28]), "+f"(d[29]), "+f"(d[30]), "+f"(d[31]),
        "+f"(d[32]), "+f"(d[33]), "+f"(d[34]), "+f"(d[35]), "+f"(d[36]), "+f"(d[37]), "+f"(d[38]), "+f"(d[39]),
        "+f"(d[40]), "+f"(d[41]), "+f"(d[42]), "+f"(d[43]), "+f"(d[44]), "+f"(d[45]), "+f"(d[46]), "+f"(d[47])
        : "l"(da), "l"(db));
}
__device__ __forceinline__ void wgmma_ss_n64(float* d, uint64_t da, uint64_t db) {
    asm volatile("wgmma.mma_async.sync.aligned.m64n64k16.f32.bf16.bf16 {"
        "%0, %1, %2, %3, %4, %5, %6, %7, %8, %9, %10, %11, %12, %13, %14, %15,"
        "%16, %17, %18, %19, %20, %21, %22, %23, %24, %25, %26, %27, %28, %29, %30, %31}, %32, %33, 1, 1, 1, 0, 1;\n"
        :
        "+f"(d[0]), "+f"(d[1]), "+f"(d[2]), "+f"(d[3]), "+f"(d[4]), "+f"(d[5]), "+f"(d[6]), "+f"(d[7]),
        "+f"(d[8]), "+f"(d[9]), "+f"(d[10]), "+f"(d[11]), "+f"(d[12]), "+f"(d[13]), "+f"(d[14]), "+f"(d[15]),
        "+f"(d[16]), "+f"(d[17]), "+f"(d[18]), "+f"(d[19]), "+f"(d[20]), "+f"(d[21]), "+f"(d[22]), "+f"(d[23]),
        "+f"(d[24]), "+f"(d[25]), "+f"(d[26]), "+f"(d[27]), "+f"(d[28]), "+f"(d[29]), "+f"(d[30]), "+f"(d[31])
        : "l"(da), "l"(db));
}
__device__ __forceinline__ void wgmma_qk_f16_acc(float* d, const uint32_t* a, uint64_t db) {
    asm volatile("wgmma.mma_async.sync.aligned.m64n64k16.f32.f16.f16 {"
        "%0, %1, %2, %3, %4, %5, %6, %7, %8, %9, %10, %11, %12, %13, %14, %15,"
        "%16, %17, %18, %19, %20, %21, %22, %23, %24, %25, %26, %27, %28, %29, %30, %31}, {%32, %33, %34, %35}, %36, 1, 1, 1, 0;\n"
        :
        "+f"(d[0]), "+f"(d[1]), "+f"(d[2]), "+f"(d[3]), "+f"(d[4]), "+f"(d[5]), "+f"(d[6]), "+f"(d[7]),
        "+f"(d[8]), "+f"(d[9]), "+f"(d[10]), "+f"(d[11]), "+f"(d[12]), "+f"(d[13]), "+f"(d[14]), "+f"(d[15]),
        "+f"(d[16]), "+f"(d[17]), "+f"(d[18]), "+f"(d[19]), "+f"(d[20]), "+f"(d[21]), "+f"(d[22]), "+f"(d[23]),
        "+f"(d[24]), "+f"(d[25]), "+f"(d[26]), "+f"(d[27]), "+f"(d[28]), "+f"(d[29]), "+f"(d[30]), "+f"(d[31])
        : "r"(a[0]), "r"(a[1]), "r"(a[2]), "r"(a[3]), "l"(db));
}
__device__ __forceinline__ void wgmma_qk_bf16_zero(float* d, const uint32_t* a, uint64_t db) {
    asm volatile("wgmma.mma_async.sync.aligned.m64n64k16.f32.bf16.bf16 {"
        "%0, %1, %2, %3, %4, %5, %6, %7, %8, %9, %10, %11, %12, %13, %14, %15,"
        "%16, %17, %18, %19, %20, %21, %22, %23, %24, %25, %26, %27, %28, %29, %30, %31}, {%32, %33, %34, %35}, %36, 0, 1, 1, 0;\n"
        :
        "=f"(d[0]), "=f"(d[1]), "=f"(d[2]), "=f"(d[3]), "=f"(d[4]), "=f"(d[5]), "=f"(d[6]), "=f"(d[7]),
        "=f"(d[8]), "=f"(d[9]), "=f"(d[10]), "=f"(d[11]), "=f"(d[12]), "=f"(d[13]), "=f"(d[14]), "=f"(d[15]),
        "=f"(d[16]), "=f"(d[17]), "=f"(d[18]), "=f"(d[19]), "=f"(d[20]), "=f"(d[21]), "=f"(d[22]), "=f"(d[23]),
        "=f"(d[24]), "=f"(d[25]), "=f"(d[26]), "=f"(d[27]), "=f"(d[28]), "=f"(d[29]), "=f"(d[30]), "=f"(d[31])
        : "r"(a[0]), "r"(a[1]), "r"(a[2]), "r"(a[3]), "l"(db));
}
__device__ __forceinline__ void wgmma_pv(float* d, const uint32_t* a, uint64_t db) {
    asm volatile("wgmma.mma_async.sync.aligned.m64n24k16.f32.bf16.bf16 {"
        "%0, %1, %2, %3, %4, %5, %6, %7, %8, %9, %10, %11}, {%12, %13, %14, %15}, %16, 1, 1, 1, 1;\n"
        :
        "+f"(d[0]), "+f"(d[1]), "+f"(d[2]), "+f"(d[3]), "+f"(d[4]), "+f"(d[5]), "+f"(d[6]), "+f"(d[7]),
        "+f"(d[8]), "+f"(d[9]), "+f"(d[10]), "+f"(d[11])
        : "r"(a[0]), "r"(a[1]), "r"(a[2]), "r"(a[3]), "l"(db));
}

template <int N> __device__ __forceinline__ void wgmma_ss(float* d, uint64_t a, uint64_t b) {
    if (N == 128) wgmma_ss_n128(d, a, b);
    if (N == 96) wgmma_ss_n96(d, a, b);
    if (N == 64) wgmma_ss_n64(d, a, b);
}

#define OFF_R 131072
#define OFF_ONE 229376
#define OFF_BAR 229888
#define OFF_BIAS (OFF_BAR + 512)
#define SMEM_BYTES (OFF_BIAS + 768)
#define SBD 1024u
#define B_X 0
#define B_F1 64
#define B_E1 112
#define B_KV 160
#define B_F2 224
#define B_E2 256
#define B_T 288
#define B_DONE 352

#define QSCALE 0.36067376022224085f
#define MAGIC 445.41763f
#define NMUFU 4
#define VSTEP ((uint64_t)((long long)32 - ((long long)32 << 16)))

__host__ __device__ constexpr int strm_pos(int pass, int i) {
    return pass == 0 ? i + (i >> 1) : pass == 1 ? (i < 4 ? 3 * i + 2 : 8 + i) : pass == 2 ? 16 + i : 20 + i;
}
__host__ __device__ constexpr int strm_pass(int p) { return p < 12 ? (p % 3 == 2 ? 1 : 0) : p < 16 ? 1 : p < 20 ? 2 : 3; }
__host__ __device__ constexpr int strm_idx(int p) { return p < 12 ? (p % 3 == 2 ? p / 3 : p - p / 3) : p < 16 ? p - 8 : p < 20 ? p - 16 : p - 20; }

template <int N, int PASS, int NST, int KK, int SUB, int KST, int LBO, int SBO, int SWZ, bool WAITX>
__device__ __forceinline__ void gemm_pass(float* acc, uint32_t bar, uint64_t dA0, int lane, int barNext) {
    if (WAITX) mbar_wait(bar + B_X, 0);
    mbar_wait(bar + B_F1 + 8 * (strm_pos(PASS, 0) % 6), (strm_pos(PASS, 0) / 6) & 1);
#pragma unroll
    for (int i = 0; i < NST; i++) {
        const int it = strm_pos(PASS, i);
        if ((threadIdx.x & 255) == 0) { TLM(2, it); TLC(3, it); }
        const uint64_t dA = dA0 + i * (KK / 4 * 1024);
        const uint64_t dB = mkdesc(SBD + OFF_R + (it % 6) * 16384, LBO, SBO, SWZ);
        wg_fence();
#pragma unroll
        for (int kk = 0; kk < KK / 2; kk++) wgmma_ss<N>(acc, dA + (kk >> 2) * 1024 + (kk & 3) * 2, dB + kk * KST / 16);
        wg_commit();
        if (i > 0) {
            wg_wait<1>();
            if (lane < 2) mbar_arrive_cluster(bar + B_E1 + 8 * (strm_pos(PASS, i - 1) % 6), lane);
        }
#pragma unroll
        for (int kk = KK / 2; kk < KK; kk++) wgmma_ss<N>(acc, dA + (kk >> 2) * 1024 + (kk & 3) * 2, dB + (SUB + (kk - KK / 2) * KST) / 16);
        wg_commit();
        if (i + 1 < NST) {
            if (WAITX) mbar_wait(bar + B_X + 8 * (i + 1), 0);
            mbar_wait(bar + B_F1 + 8 * (strm_pos(PASS, i + 1) % 6), (strm_pos(PASS, i + 1) / 6) & 1);
        }
    }
    if (barNext) bar_arrive(barNext, 512);
    wg_wait<0>();
    if (lane < 2) mbar_arrive_cluster(bar + B_E1 + 8 * (strm_pos(PASS, NST - 1) % 6), lane);
    pin<N / 2>(acc);
}

__device__ __forceinline__ uint32_t lds32(uint32_t a) { uint32_t v; asm volatile("ld.shared.u32 %0, [%1];" : "=r"(v) : "r"(a)); return v; }
__device__ __forceinline__ bool elect() {
    uint32_t p;
    asm volatile("{\n.reg .pred p;\nelect.sync _|p, 0xffffffff;\nselp.u32 %0, 1, 0, p;\n}" : "=r"(p));
    return p;
}

template <int N> __device__ __forceinline__ void bias_init(float* acc, uint32_t b) {
#pragma unroll
    for (int j = 0; j < N / 8; j++) {
        const uint32_t bv = lds32(b + j * 16);
        acc[4 * j] = acc[4 * j + 2] = bf_lo(bv);
        acc[4 * j + 1] = acc[4 * j + 3] = bf_hi(bv);
    }
    pin<N / 2>(acc);
}

template <int N> __device__ __forceinline__ void gelu_store(const float* acc, __nv_bfloat16* hp) {
#pragma unroll
    for (int G = 0; G < N / 32; G++) {
        uint32_t o[8];
#pragma unroll
        for (int j = 0; j < 4; j++) {
            float y[4];
#pragma unroll
            for (int i = 0; i < 4; i++) {
                const float h = acc[16 * G + 4 * j + i];
                const float z = h * fmaf(h * h, 0.035677408136300125f, 0.7978845608028654f);
                const float hh = 0.5f * h;
                y[i] = fmaf(hh, tanhf_(z), hh);
            }
            o[j] = pk_bf16(y[0], y[1]);
            o[4 + j] = pk_bf16(y[2], y[3]);
        }
        *(uint4*)(hp + G * 32) = make_uint4(o[0], o[1], o[2], o[3]);
        *(uint4*)(hp + 8 * FF + G * 32) = make_uint4(o[4], o[5], o[6], o[7]);
    }
}

__device__ __forceinline__ float norm_bound(const float* v, float sc) {
    uint32_t m = 0;
#pragma unroll
    for (int h = 0; h < 4; h++) {
        const float* u = v + 8 * h;
        m = max(m, __float_as_uint(fmaf(u[0], u[0], fmaf(u[1], u[1], fmaf(u[4], u[4], u[5] * u[5])))));
        m = max(m, __float_as_uint(fmaf(u[2], u[2], fmaf(u[3], u[3], fmaf(u[6], u[6], u[7] * u[7])))));
    }
#pragma unroll
    for (int o = 4; o < 32; o <<= 1) m = max(m, __shfl_xor_sync(0xffffffffu, m, o));
    float f = __uint_as_float(m);
    f += __shfl_xor_sync(0xffffffffu, f, 1);
    f += __shfl_xor_sync(0xffffffffu, f, 2);
    return f * sc;
}

__device__ __forceinline__ uint32_t exp2_pair(float a, float b) {
    const uint32_t w = __byte_perm(__float_as_uint(a), __float_as_uint(b), 0x6521);
    uint32_t m, r;
    asm("lop3.b32 %0, %1, 0x007f007f, 0x9f809f80, 0xEA;" : "=r"(m) : "r"(w));
    const uint32_t e = w - m;
    asm("fma.rn.bf16x2 %0, %1, %2, %3;" : "=r"(r) : "r"(w), "r"(m), "r"(e));
    return r;
}

__device__ __forceinline__ void store_o(const float* o, float g0, float g1, int h, int row, int t) {
    const float s0 = __fdividef(g0, o[8]), s1 = __fdividef(g1, o[10]);
    __nv_bfloat16* p = gO + (size_t)row * DM + h * 16 + (t & 1) * 8 + (t >> 1) * 2;
    *(uint32_t*)p = pk_bf16(o[0] * s0, o[1] * s0);
    *(uint32_t*)(p + 4) = pk_bf16(o[4] * s0, o[5] * s0);
    *(uint32_t*)(p + 8 * DM) = pk_bf16(o[2] * s1, o[3] * s1);
    *(uint32_t*)(p + 8 * DM + 4) = pk_bf16(o[6] * s1, o[7] * s1);
}

template <int NT>
__device__ __forceinline__ void proj16(float (*c)[8], const __nv_bfloat16* x, const __nv_bfloat16* w, int row0, int rstep, int col, int g, int t) {
#pragma unroll
    for (int i = 0; i < NT; i++)
#pragma unroll
        for (int j = 0; j < 8; j++) c[i][j] = 0.f;
    const unsigned short* wu = (const unsigned short*)w;
#pragma unroll 1
    for (int k = 0; k < DM; k += 16) {
        uint32_t b[4];
#pragma unroll
        for (int j = 0; j < 4; j++) {
            const int kr = k + 2 * t + (j & 1) * 8, cc = col + g + (j >> 1) * 8;
            b[j] = (uint32_t)wu[(size_t)kr * (3 * DM) + cc] | ((uint32_t)wu[(size_t)(kr + 1) * (3 * DM) + cc] << 16);
        }
#pragma unroll
        for (int i = 0; i < NT; i++) {
            const __nv_bfloat16* xp = x + (size_t)(row0 + i * rstep + g) * DM + k + 2 * t;
            const uint32_t a0 = *(const uint32_t*)xp, a1 = *(const uint32_t*)(xp + 8 * DM);
            const uint32_t a2 = *(const uint32_t*)(xp + 8), a3 = *(const uint32_t*)(xp + 8 * DM + 8);
#pragma unroll
            for (int j = 0; j < 2; j++)
                asm volatile("mma.sync.aligned.m16n8k16.row.col.f32.bf16.bf16.f32 {%0,%1,%2,%3}, {%4,%5,%6,%7}, {%8,%9}, {%0,%1,%2,%3};"
                             : "+f"(c[i][4 * j]), "+f"(c[i][4 * j + 1]), "+f"(c[i][4 * j + 2]), "+f"(c[i][4 * j + 3])
                             : "r"(a0), "r"(a1), "r"(a2), "r"(a3), "r"(b[2 * j]), "r"(b[2 * j + 1]));
        }
    }
}

struct Maps { CUtensorMap x, kv, q, f0, f1, h, o, w2, wo; };

__global__ void __cluster_dims__(2, 1, 1) __launch_bounds__(640, 1)
fused_kernel(const __grid_constant__ Maps tm, const __nv_bfloat16* __restrict__ x, const __nv_bfloat16* __restrict__ wqkv,
             const __nv_bfloat16* __restrict__ wo, const __nv_bfloat16* __restrict__ w1, const __nv_bfloat16* __restrict__ b1,
             const __nv_bfloat16* __restrict__ w2, const __nv_bfloat16* __restrict__ b2, const __nv_bfloat16* __restrict__ gate,
             __nv_bfloat16* __restrict__ out) {
    extern __shared__ __align__(1024) uint8_t smem_raw[];
    const uint32_t sb = smem_u32(smem_raw);
    const uint32_t bar = sb + OFF_BAR;
    const int tid = threadIdx.x, lane = tid & 31;
    const int warp = __shfl_sync(0xffffffffu, tid >> 5, 0);
    const uint32_t rank = cluster_rank();
    const int cl = blockIdx.x >> 1;
    const int nb = cl & 7, mb = (cl >> 3) * 2 + rank;
    const int g = lane >> 2, t = lane & 3;

    const int cb = cl & 3, rb = (cl >> 2) * 2 + rank;
    if (tid == 0) TLM(0, 0);
    if (tid == 512) {
        mbar_init(bar + B_X, 1);
        asm volatile("fence.proxy.async.shared::cta;" ::: "memory");
        mbar_expect(bar + B_X, 16384);
        tma2d(sb, &tm.x, 0, mb * 128, bar + B_X);
        for (int i = 0; i < 8; i++) { if (i) mbar_init(bar + B_X + 8 * i, 1); mbar_init(bar + B_KV + 8 * i, 1); mbar_init(bar + B_T + 8 * i, 1); }
        for (int i = 0; i < 6; i++) { mbar_init(bar + B_F1 + 8 * i, 1); mbar_init(bar + B_E1 + 8 * i, 16); }
        for (int i = 0; i < 4; i++) { mbar_init(bar + B_F2 + 8 * i, 1); mbar_init(bar + B_E2 + 8 * i, 8); }
        mbar_init(bar + B_DONE, 16);
        asm volatile("fence.mbarrier_init.release.cluster;" ::: "memory");
    } else if (tid == 544) {
        map_prefetch(&tm.kv); map_prefetch(&tm.f0);
        l2_prefetch((const uint8_t*)wqkv + (size_t)blockIdx.x * 12288, 12288);
        l2_prefetch(x + (size_t)(mb * 128 + nb * 16) * DM, 16384);
        l2_prefetch((const uint8_t*)w1 + (size_t)blockIdx.x * 14336, 14336);
        map_prefetch(&tm.q); map_prefetch(&tm.f1);
    } else if (tid < 128) {
        asm volatile("st.shared.u32 [%0], %1;" ::"r"(sb + OFF_ONE + tid * 4), "r"(0x3f803f80u) : "memory");
        asm volatile("fence.proxy.async.shared::cta;" ::: "memory");
    }
    if ((sb & 0xFFFFFF) != SBD) __trap();
    __syncthreads();
    asm volatile("barrier.cluster.arrive.relaxed.aligned;\nbarrier.cluster.wait.aligned;" ::: "memory");
    const uint32_t ep = gEpoch[blockIdx.x] + 1;
    if (tid == 0) { TLM(0, 1); TLC(0, 30); }

    if (warp < 16) {
        const int wg = warp >> 2;
        {
            const int w8 = warp & 7;
            const int T = mb * 8 + w8, row0 = T * 16 + g;
            const uint64_t dA0 = mkdesc(SBD + (wg & 1) * 8192, 16, 1024, 1);
            if (wg < 2) {
                {
                    float acc[64];
#pragma unroll
                    for (int i = 0; i < 64; i++) acc[i] = 0.f;
                    gemm_pass<128, 0, 8, 4, 8192, 2048, 4096, 1024, 1, true>(acc, bar, dA0, lane, 0);
                    if (tid == 0) TLM(0, 2);
                    const int pos = ((T >> 6) * 16 + 2 * g) * 64 + (T & 63);
                    uint8_t* kp = gKV + (size_t)(nb * 4) * (SEQ * 64) + (pos >> 8) * 16384 + (pos & 255) * 32 + ((t * 8) ^ (((T >> 2) & 1) << 4));
                    float vm = 0.f;
#pragma unroll
                    for (int h = 0; h < 4; h++) {
                        const float* v = acc + 8 * h;
                        float p0 = __shfl_up_sync(0xffffffffu, v[2], 4), p1 = __shfl_up_sync(0xffffffffu, v[3], 4);
                        float p2 = __shfl_up_sync(0xffffffffu, v[6], 4), p3 = __shfl_up_sync(0xffffffffu, v[7], 4);
                        if (g == 0) { p0 = p1 = p2 = p3 = 0.f; }
                        uint8_t* o = kp + (size_t)h * (SEQ * 64);
                        *(uint2*)o = make_uint2(pk_f16(v[0] - p0, v[1] - p1), pk_f16(v[4] - p2, v[5] - p3));
                        *(uint2*)(o + 2048) = make_uint2(pk_f16(v[2] - v[0], v[3] - v[1]), pk_f16(v[6] - v[4], v[7] - v[5]));
                        const float* u = acc + 32 + 8 * h;
#pragma unroll
                        for (int i = 0; i < 8; i++) vm = fmaxf(vm, fabsf(u[i]));
                        *(uint2*)(o + 8192) = make_uint2(pk_bf16(u[0], u[1]), pk_bf16(u[4], u[5]));
                        *(uint2*)(o + 8192 + 2048) = make_uint2(pk_bf16(u[2], u[3]), pk_bf16(u[6], u[7]));
                    }
                    const float km = norm_bound(acc, 1.f);
                    vm = __uint_as_float(__reduce_max_sync(0xffffffffu, __float_as_uint(vm)));
                    if (lane == 0) { gN[1024 + nb * 128 + T] = km; gN[2048 + nb * 128 + T] = vm; }
                    if (tid == 0) TLM(0, 3);
                }
                {
                    float acc[32];
#pragma unroll
                    for (int i = 0; i < 32; i++) acc[i] = 0.f;
                    bar_sync(6, 512);
                    gemm_pass<64, 2, 4, 8, 8192, 2048, 16, 1024, 1, false>(acc, bar, dA0, lane, 7);
                    if (tid == 0) TLM(0, 4);
                    uint8_t* qp = gQ + (size_t)(nb * 4) * (SEQ * 32) + (size_t)row0 * 32 + t * 8;
#pragma unroll
                    for (int h = 0; h < 4; h++) {
                        const float* v = acc + 8 * h;
                        uint8_t* o = qp + (size_t)h * (SEQ * 32);
                        *(uint2*)o = make_uint2(pk_f16(v[0] * QSCALE, v[1] * QSCALE), pk_f16(v[4] * QSCALE, v[5] * QSCALE));
                        *(uint2*)(o + 256) = make_uint2(pk_f16(v[2] * QSCALE, v[3] * QSCALE), pk_f16(v[6] * QSCALE, v[7] * QSCALE));
                    }
                    const float qm = norm_bound(acc, QSCALE * QSCALE);
                    if (lane == 0) gN[nb * 128 + T] = qm;
                    bar_arrive(10, 288);
                    if (tid == 0) TLM(0, 5);
                }
            } else {
                if (tid < 256 + 176) {
                    const int i = tid - 256;
                    const uint32_t v = i < 112 ? *(const uint32_t*)(b1 + nb * 224 + i * 2) : *(const uint32_t*)(b2 + cb * 128 + (i - 112) * 2);
                    asm volatile("st.shared.u32 [%0], %1;" ::"r"(sb + OFF_BIAS + i * 4), "r"(v) : "memory");
                }
                bar_sync(5, 256);
                {
                    float acc[64];
                    bias_init<128>(acc, sb + OFF_BIAS + t * 4);
                    gemm_pass<128, 1, 8, 4, 8192, 2048, 4096, 1024, 1, true>(acc, bar, dA0, lane, 6);
                    if (tid == 256) TLM(0, 6);
                    gelu_store<128>(acc, gH + (size_t)row0 * FF + nb * 224 + t * 8);
                }
                {
                    float acc[48];
                    bias_init<96>(acc, sb + OFF_BIAS + 256 + t * 4);
                    if (tid == 256) TLM(0, 7);
                    bar_sync(7, 512);
                    gemm_pass<96, 3, 8, 4, 6144, 1024, 2048, 512, 2, false>(acc, bar, dA0, lane, 0);
                    if (tid == 256) TLM(0, 8);
                    gelu_store<96>(acc, gH + (size_t)row0 * FF + nb * 224 + 128 + t * 8);
                    bar_arrive(11, 288);
                    if (tid == 256) TLM(0, 10);
                }
            }
        }
        const int h = cl >> 1, qd = (cl & 1) * 2 + rank;
        if (lane == 0) cnt_wait(gCntQ + (h >> 2) * 32, ep * 16);
        __syncwarp();
        uint32_t q[4];
        {
            const uint8_t* p = gQ + (size_t)h * (SEQ * 32) + (size_t)(qd * 512 + warp * 16 + g) * 32 + t * 4;
            q[0] = __ldcg((const uint32_t*)p); q[1] = __ldcg((const uint32_t*)(p + 256));
            q[2] = __ldcg((const uint32_t*)(p + 16)); q[3] = __ldcg((const uint32_t*)(p + 272));
        }
        bool fast;
        {
            const int hb = h >> 2;
            const uint4 kq = __ldcg((const uint4*)(gN + 1024 + hb * 128 + lane * 4));
            const uint4 vq = __ldcg((const uint4*)(gN + 2048 + hb * 128 + lane * 4));
            const float qq = ldcg_f(gN + hb * 128 + qd * 32 + lane);
            const float kf = __uint_as_float(__reduce_max_sync(0xffffffffu, max(max(kq.x, kq.y), max(kq.z, kq.w))));
            const float vf = __uint_as_float(__reduce_max_sync(0xffffffffu, max(max(vq.x, vq.y), max(vq.z, vq.w))));
            const float qf = __uint_as_float(__reduce_max_sync(0xffffffffu, __float_as_uint(qq)));
            fast = (kf <= 1.0e6f) && (qf <= 1.0e6f) && (kf * qf <= 3400.f) && (vf <= 1.0e12f);
        }
        const uint64_t kd0 = mkdesc(SBD, 16, 256, 3);
        const uint64_t vd0 = mkdesc(SBD + 8192, OFF_ONE - 8192, 256, 3);
        if (fast) {
            float g0, g1;
#pragma unroll 1
            for (int r = 0; r < 2; r++) {
                const int row = qd * 512 + r * 256 + warp * 16 + g;
                float o[12];
#pragma unroll
                for (int i = 0; i < 12; i++) o[i] = 0.f;
                uint64_t kd = kd0, vd = vd0;
#pragma unroll 1
                for (int half = 0; half < 2; half++) {
                    float s[32];
#pragma unroll
                    for (int i = 0; i < 32; i++) s[i] = i < 2 * NMUFU ? 0.f : MAGIC;
#pragma unroll 1
                    for (int c = 0; c < 4; c++) {
                        mbar_wait(bar + B_KV + 8 * (half * 4 + c), 0);
                        if ((tid & 255) == 0 && c == 0) TLM(1, (tid >> 8) * 4 + r * 2 + half);
#pragma unroll 1
                        for (int j = 0; j < 4; j++) {
                            uint32_t p[16];
                            wg_fence();
                            wgmma_qk_f16_acc(s, q, kd);
                            wg_commit();
                            wg_wait<0>();
                            pin<32>(s);
#pragma unroll
                            for (int i = 0; i < 16; i++)
                                p[i] = i < NMUFU ? pk_bf16(ex2f(s[2 * i]), ex2f(s[2 * i + 1])) : exp2_pair(s[2 * i], s[2 * i + 1]);
                            pin<16>(p);
                            wg_fence();
#pragma unroll
                            for (int u = 0; u < 4; u++) wgmma_pv(o, p + 4 * u, vd + u * VSTEP);
                            wg_commit();
                            kd += 128;
                            vd += 4 * VSTEP;
                        }
                        kd += 512;
                        vd += 16 * VSTEP;
                    }
                    wg_wait<0>();
                }
                pin<12>(o);
                if ((tid & 127) == 0 && r == 1) TLM(1, 8 + wg);
                if (r == 1 && lane == 0) mbar_arrive(bar + B_DONE);
                if (r == 0) {
                    const uint8_t* p = gQ + (size_t)h * (SEQ * 32) + (size_t)(row + 256) * 32 + t * 4;
                    q[0] = __ldcg((const uint32_t*)p); q[1] = __ldcg((const uint32_t*)(p + 256));
                    q[2] = __ldcg((const uint32_t*)(p + 16)); q[3] = __ldcg((const uint32_t*)(p + 272));
                    if (lane < 2) cnt_wait(gCntH + ((row >> 6) + lane * 4) * 32, ep * 12);
                    __syncwarp();
                    g0 = ldcg_f(gG + row); g1 = ldcg_f(gG + row + 8);
                }
                store_o(o, g0, g1, h, row, t);
                if (r == 0) { g0 = ldcg_f(gG + row + 256); g1 = ldcg_f(gG + row + 264); }
                bar_sync(1 + wg, 128);
                if ((tid & 127) == 0) cnt_add(gCntO + ((row >> 6) * 8 + (h >> 2)) * 8);
                if (tid == 0 && r == 1) { TLM(1, 12); TLC(0, 31); }
            }
        } else {
            for (int c = 0; c < 8; c++) mbar_wait(bar + B_KV + 8 * c, 0);
            {
                float kc[8][8];
                proj16<8>(kc, x, wqkv, warp * 16, 256, DM + h * 16, g, t);
#pragma unroll
                for (int i = 0; i < 8; i++) {
                    const int T = warp + i * 16;
                    const int pos = ((T >> 6) * 16 + 2 * g) * 64 + (T & 63);
                    const uint32_t a = sb + (pos >> 8) * 16384 + (pos & 255) * 32 + t * 4, sw = ((T >> 2) & 1) << 4;
                    asm volatile("st.shared.u32 [%0], %1;" ::"r"(a + sw), "r"(pk_bf16(kc[i][0], kc[i][1])) : "memory");
                    asm volatile("st.shared.u32 [%0], %1;" ::"r"(a + (sw ^ 16)), "r"(pk_bf16(kc[i][4], kc[i][5])) : "memory");
                    asm volatile("st.shared.u32 [%0], %1;" ::"r"(a + 2048 + sw), "r"(pk_bf16(kc[i][2], kc[i][3])) : "memory");
                    asm volatile("st.shared.u32 [%0], %1;" ::"r"(a + 2048 + (sw ^ 16)), "r"(pk_bf16(kc[i][6], kc[i][7])) : "memory");
                }
                asm volatile("fence.proxy.async.shared::cta;" ::: "memory");
                bar_sync(8, 512);
            }
#pragma unroll 1
            for (int r = 0; r < 2; r++) {
                const int row = qd * 512 + r * 256 + warp * 16 + g;
                {
                    float qc[1][8];
                    proj16<1>(qc, x, wqkv, row - g, 0, h * 16, g, t);
#pragma unroll
                    for (int i = 0; i < 4; i++) q[i] = pk_bf16(qc[0][2 * i] * QSCALE, qc[0][2 * i + 1] * QSCALE);
                }
                float o[12];
#pragma unroll
                for (int i = 0; i < 12; i++) o[i] = 0.f;
                float m0 = -INFINITY, m1 = -INFINITY;
#pragma unroll 1
                for (int j = 0; j < 32; j++) {
                    const uint64_t kd = kd0 + (j >> 2) * 1024 + (j & 3) * 128, vd = vd0 + ((j >> 2) * 32 + (j & 3) * 4) * VSTEP;
                    float s[32];
                    uint32_t p[16];
                    wg_fence();
                    wgmma_qk_bf16_zero(s, q, kd);
                    wg_commit();
                    wg_wait<0>();
                    pin<32>(s);
                    pin<12>(o);
                    float n0 = m0, n1 = m1;
#pragma unroll
                    for (int i = 0; i < 8; i++) {
                        n0 = fmaxf(n0, fmaxf(s[4 * i], s[4 * i + 1]));
                        n1 = fmaxf(n1, fmaxf(s[4 * i + 2], s[4 * i + 3]));
                    }
                    n0 = fmaxf(n0, __shfl_xor_sync(0xffffffffu, n0, 1));
                    n1 = fmaxf(n1, __shfl_xor_sync(0xffffffffu, n1, 1));
                    n0 = fmaxf(n0, __shfl_xor_sync(0xffffffffu, n0, 2));
                    n1 = fmaxf(n1, __shfl_xor_sync(0xffffffffu, n1, 2));
                    const float c0 = ex2f(m0 - n0), c1 = ex2f(m1 - n1);
                    m0 = n0;
                    m1 = n1;
#pragma unroll
                    for (int i = 0; i < 3; i++) { o[4 * i] *= c0; o[4 * i + 1] *= c0; o[4 * i + 2] *= c1; o[4 * i + 3] *= c1; }
#pragma unroll
                    for (int i = 0; i < 8; i++) {
                        p[2 * i] = pk_bf16(ex2f(s[4 * i] - m0), ex2f(s[4 * i + 1] - m0));
                        p[2 * i + 1] = pk_bf16(ex2f(s[4 * i + 2] - m1), ex2f(s[4 * i + 3] - m1));
                    }
                    pin<16>(p);
                    pin<12>(o);
                    wg_fence();
#pragma unroll
                    for (int u = 0; u < 4; u++) wgmma_pv(o, p + 4 * u, vd + u * VSTEP);
                    wg_commit();
                }
                wg_wait<0>();
                pin<12>(o);
                if (r == 1 && lane == 0) mbar_arrive(bar + B_DONE);
                if (lane == 0) cnt_wait(gCntH + (row >> 6) * 32, ep * 12);
                __syncwarp();
                store_o(o, ldcg_f(gG + row), ldcg_f(gG + row + 8), h, row, t);
                bar_sync(1 + wg, 128);
                if ((tid & 127) == 0) cnt_add(gCntO + ((row >> 6) * 8 + (h >> 2)) * 8);
            }
        }
        if (warp < 9 && lane == 0) {
            mbar_wait(bar + B_DONE, 0);
            if (warp == 8) {
#pragma unroll
                for (int i = 0; i < 4; i++)
                    tma2d(sb + 65536 + i * 8192, &tm.wo, cb * 128 + (i & 1) * 64, (6 + (i >> 1)) * 64, bar + B_T + 8 * (6 + (i >> 1)));
            } else {
                cnt_wait(gCntO + (rb * 8 + warp) * 8, ep * 4);
                asm volatile("fence.proxy.async.global;" ::: "memory");
                tma2d(sb + warp * 8192, &tm.o, warp * 64, rb * 64, bar + B_T + 8 * warp);
                TLM(1, 20 + warp);
            }
        }
    } else {
        if (warp == 16) {
            if (elect()) {
#pragma unroll
                for (int it = 0; it < 28; it++) {
                    const int s = it % 6, ps = strm_pass(it), i = strm_idx(it);
                    const uint32_t fb = bar + B_F1 + 8 * s, dst = sb + OFF_R + s * 16384;
                    if (it >= 6) mbar_wait(bar + B_E1 + 8 * s, ((it / 6) - 1) & 1);
                    mbar_expect(fb, ps < 3 ? 16384 : 12288);
                    if (ps == 0) tma3d_mc(dst + rank * 8192, &tm.kv, nb * 64, i * 64 + rank * 32, 1, fb);
                    if (ps == 1) tma3d_mc(dst + rank * 8192, &tm.f0, nb * 224, i * 64 + rank * 32, 0, fb);
                    if (ps == 2) tma2d_mc(dst + rank * 8192, &tm.q, nb * 64, i * 128 + rank * 64, fb);
                    if (ps == 3) tma3d_mc(dst + rank * 6144, &tm.f1, 0, i * 64 + rank * 32, nb * 7 + 4, fb);
                    if (ps == 0 && i < 7) {
                        mbar_expect(bar + B_X + 8 * (i + 1), 16384);
                        tma2d(sb + (i + 1) * 16384, &tm.x, (i + 1) * 64, mb * 128, bar + B_X + 8 * (i + 1));
                    }
                }
                const int h = cl >> 1;
                cnt_wait(gCntQ + (h >> 2) * 32, ep * 16);
                asm volatile("fence.proxy.async.global;" ::: "memory");
                TLM(0, 9);
#pragma unroll
                for (int c = 0; c < 8; c++) {
                    const int it = 20 + c;
                    if (c >= 2) mbar_wait(bar + B_E1 + 8 * (it % 6), (it / 6) & 1);
                    mbar_expect(bar + B_KV + 8 * c, 16384);
                    bulk_mc(sb + c * 16384 + rank * 8192, gKV + (size_t)h * (SEQ * 64) + c * 16384 + rank * 8192, 8192, bar + B_KV + 8 * c);
                }
#pragma unroll
                for (int s = 0; s < 4; s++) {
                    mbar_expect(bar + B_F2 + 8 * s, 24576);
                    tma5d_mc(sb + OFF_R + s * 24576 + 8192 + rank * 8192, &tm.w2, cb * 128 + rank * 64, s * 2, bar + B_F2 + 8 * s);
                }
                cnt_wait(gCntH + rb * 32, ep * 12);
                asm volatile("fence.proxy.async.global;" ::: "memory");
                TLM(1, 13);
#pragma unroll
                for (int s = 0; s < 4; s++) tma2d(sb + OFF_R + s * 24576, &tm.h, s * 64, rb * 64, bar + B_F2 + 8 * s);
            }
        } else if (warp == 17) {
            float gw[16];
            {
                const uint4 a = *(const uint4*)(gate + lane * 8), b = *(const uint4*)(gate + 256 + lane * 8);
                const uint32_t u[8] = {a.x, a.y, a.z, a.w, b.x, b.y, b.z, b.w};
#pragma unroll
                for (int i = 0; i < 8; i++) { gw[2 * i] = bf_lo(u[i]); gw[2 * i + 1] = bf_hi(u[i]); }
            }
            const int r0 = mb * 128 + nb * 16;
#pragma unroll 2
            for (int r = 0; r < 16; r++) {
                const __nv_bfloat16* xr = x + (size_t)(r0 + r) * DM;
                const uint4 a = *(const uint4*)(xr + lane * 8), b = *(const uint4*)(xr + 256 + lane * 8);
                const uint32_t u[8] = {a.x, a.y, a.z, a.w, b.x, b.y, b.z, b.w};
                float acc = 0.f;
#pragma unroll
                for (int i = 0; i < 8; i++) { acc = fmaf(bf_lo(u[i]), gw[2 * i], acc); acc = fmaf(bf_hi(u[i]), gw[2 * i + 1], acc); }
#pragma unroll
                for (int o = 16; o; o >>= 1) acc += __shfl_xor_sync(0xffffffffu, acc, o);
                if (lane == 0) gG[r0 + r] = 1.f / (1.f + __expf(-acc));
            }
            if (lane == 0) {
                cnt_add(gCntH + (r0 >> 6) * 32);
                l2_prefetch((const uint8_t*)w2 + (size_t)blockIdx.x * 14336, 14336);
                l2_prefetch((const uint8_t*)wo + (size_t)blockIdx.x * 4096, 4096);
                map_prefetch(&tm.h); map_prefetch(&tm.w2); map_prefetch(&tm.wo); map_prefetch(&tm.o);
            }
        } else {
            bar_sync(warp - 8, 288);
            if (warp == 18) { if (lane == 0) cnt_add(gCntQ + nb * 32); }
            else if (lane < 2) cnt_add(gCntH + (mb * 2 + lane) * 32);
        }
        __syncwarp();
        float acc[64];
#pragma unroll
        for (int i = 0; i < 64; i++) acc[i] = 0.f;
        const int row = rb * 64 + (warp - 16) * 16 + g;
#pragma unroll 1
        for (int io = 0; io < 7; io++) {
#pragma unroll
            for (int s = 0; s < 4; s++) {
                const int it = io * 4 + s;
                mbar_wait(bar + B_F2 + 8 * s, io & 1);
                if (tid == 512 && s == 0 && (io == 0 || io == 4)) TLM(1, 14 + io / 4);
                const uint64_t dA = mkdesc(SBD + OFF_R + s * 24576, 16, 1024, 1);
                const uint64_t dB = mkdesc(SBD + OFF_R + s * 24576 + 8192, 8192, 1024, 1);
                wg_fence();
#pragma unroll
                for (int kk = 0; kk < 4; kk++) wgmma_ss_n128(acc, dA + kk * 2, dB + kk * 128);
                wg_commit();
                if (warp < 18 && it >= 2 && it < 26) {
                    const int s2 = (s + 2) & 3;
                    mbar_wait(bar + B_E2 + 8 * s2, (io - (s < 2)) & 1);
                    if (elect()) {
                        if (warp == 16) {
                            mbar_expect(bar + B_F2 + 8 * s2, 24576);
                            tma5d_mc(sb + OFF_R + s2 * 24576 + 8192 + rank * 8192, &tm.w2, cb * 128 + rank * 64, it * 2 + 4, bar + B_F2 + 8 * s2);
                        } else {
                            asm volatile("fence.proxy.async.global;" ::: "memory");
                            tma2d(sb + OFF_R + s2 * 24576, &tm.h, it * 64 + 128, rb * 64, bar + B_F2 + 8 * s2);
                        }
                    }
                    __syncwarp();
                }
                wg_wait<1>();
                if (it >= 1 && lane < 2) mbar_arrive_cluster(bar + B_E2 + 8 * ((s + 3) & 3), lane);
            }
        }
        wg_wait<0>();
        if (lane < 2) mbar_arrive_cluster(bar + B_E2 + 8 * 3, lane);
        pin<64>(acc);
        if (warp == 16) {
            if (lane == 0) TLM(1, 16);
            for (int s = 0; s < 4; s++) mbar_wait(bar + B_E2 + 8 * s, 0);
            if (elect()) {
#pragma unroll
                for (int i = 0; i < 8; i++) mbar_expect(bar + B_T + 8 * i, 24576);
#pragma unroll
                for (int i = 0; i < 6; i++) tma2d_mc(sb + OFF_R + i * 16384 + rank * 8192, &tm.wo, cb * 128 + rank * 64, i * 64, bar + B_T + 8 * i);
            }
            __syncwarp();
        }
        {
            const float g0 = 1.f - ldcg_f(gG + row), g1 = 1.f - ldcg_f(gG + row + 8);
#pragma unroll
            for (int j = 0; j < 16; j++) {
                const uint32_t bv = lds32(sb + OFF_BIAS + 448 + j * 16 + t * 4);
                acc[4 * j] = (acc[4 * j] + bf_lo(bv)) * g0;
                acc[4 * j + 1] = (acc[4 * j + 1] + bf_hi(bv)) * g0;
                acc[4 * j + 2] = (acc[4 * j + 2] + bf_lo(bv)) * g1;
                acc[4 * j + 3] = (acc[4 * j + 3] + bf_hi(bv)) * g1;
            }
            pin<64>(acc);
        }
        if (tid == 512) TLM(1, 17);
#pragma unroll
        for (int i = 0; i < 8; i++) {
            mbar_wait(bar + B_T + 8 * i, 0);
            const uint64_t dA = mkdesc(SBD + i * 8192, 16, 1024, 1);
            const uint64_t dB = mkdesc(i < 6 ? SBD + OFF_R + i * 16384 : SBD + 65536 + (i - 6) * 16384, 8192, 1024, 1);
            wg_fence();
#pragma unroll
            for (int kk = 0; kk < 4; kk++) wgmma_ss_n128(acc, dA + kk * 2, dB + kk * 128);
            wg_commit();
        }
        wg_wait<0>();
        pin<64>(acc);
        if (tid == 512) TLM(1, 18);
        {
            const uint32_t st = sb + 98304 + (warp - 16) * 4352;
            const uint32_t wa = st + (lane & 15) * 272 + (lane >> 4) * 16;
#pragma unroll
            for (int j = 0; j < 8; j++)
                asm volatile("stmatrix.sync.aligned.m8n8.x4.shared.b16 [%0], {%1, %2, %3, %4};" ::"r"(wa + j * 32),
                             "r"(pk_bf16(acc[8 * j], acc[8 * j + 1])), "r"(pk_bf16(acc[8 * j + 2], acc[8 * j + 3])),
                             "r"(pk_bf16(acc[8 * j + 4], acc[8 * j + 5])), "r"(pk_bf16(acc[8 * j + 6], acc[8 * j + 7])) : "memory");
            __syncwarp();
            __nv_bfloat16* op = out + (size_t)(rb * 64 + (warp - 16) * 16 + (lane >> 4)) * DM + cb * 128 + (lane & 15) * 8;
#pragma unroll
            for (int j = 0; j < 8; j++) {
                uint4 v;
                asm volatile("ld.shared.v4.u32 {%0, %1, %2, %3}, [%4];" : "=r"(v.x), "=r"(v.y), "=r"(v.z), "=r"(v.w)
                             : "r"(st + (2 * j + (lane >> 4)) * 272 + (lane & 15) * 16));
                *(uint4*)(op + (size_t)j * 2 * DM) = v;
            }
        }
        if (tid == 512) { gEpoch[blockIdx.x] = ep; TLM(1, 19); }
    }
}

typedef CUresult (*EncodeFn)(CUtensorMap*, CUtensorMapDataType, cuuint32_t, void*, const cuuint64_t*, const cuuint64_t*, const cuuint32_t*,
                             const cuuint32_t*, CUtensorMapInterleave, CUtensorMapSwizzle, CUtensorMapL2promotion, CUtensorMapFloatOOBfill);

static void make_map(EncodeFn enc, CUtensorMap* m, const void* p, int rank, const cuuint64_t* dims, const cuuint64_t* strides,
                     const cuuint32_t* box, CUtensorMapSwizzle swz) {
    const cuuint32_t es[5] = {1, 1, 1, 1, 1};
    enc(m, CU_TENSOR_MAP_DATA_TYPE_BFLOAT16, rank, (void*)p, dims, strides, box, es, CU_TENSOR_MAP_INTERLEAVE_NONE, swz,
        CU_TENSOR_MAP_L2_PROMOTION_L2_128B, CU_TENSOR_MAP_FLOAT_OOB_FILL_NONE);
}

extern "C" void kernel_launch(void* const* d_in, const int* in_sizes, int n_in, void* d_out, int out_size) {
    const __nv_bfloat16* x = (const __nv_bfloat16*)d_in[0];
    const __nv_bfloat16* wqkv = (const __nv_bfloat16*)d_in[1];
    const __nv_bfloat16* wo = (const __nv_bfloat16*)d_in[2];
    const __nv_bfloat16* w1 = (const __nv_bfloat16*)d_in[4];
    const __nv_bfloat16* b1 = (const __nv_bfloat16*)d_in[5];
    const __nv_bfloat16* w2 = (const __nv_bfloat16*)d_in[6];
    const __nv_bfloat16* b2 = (const __nv_bfloat16*)d_in[7];
    const __nv_bfloat16* gate = (const __nv_bfloat16*)d_in[8];

    void* fp = nullptr;
    cudaDriverEntryPointQueryResult qr;
    cudaGetDriverEntryPoint("cuTensorMapEncodeTiled", &fp, cudaEnableDefault, &qr);
    EncodeFn enc = (EncodeFn)fp;
    void *pH, *pO;
    cudaGetSymbolAddress(&pH, gH);
    cudaGetSymbolAddress(&pO, gO);

    Maps tm;
    const CUtensorMapSwizzle S128 = CU_TENSOR_MAP_SWIZZLE_128B, S64 = CU_TENSOR_MAP_SWIZZLE_64B;
    { cuuint64_t d[2] = {DM, SEQ}, s[1] = {DM * 2}; cuuint32_t b[2] = {64, 128}; make_map(enc, &tm.x, x, 2, d, s, b, S128); }
    { cuuint64_t d[3] = {DM, DM, 3}, s[2] = {3 * DM * 2, DM * 2}; cuuint32_t b[3] = {64, 32, 2}; make_map(enc, &tm.kv, wqkv, 3, d, s, b, S128); }
    { cuuint64_t d[2] = {3 * DM, DM}, s[1] = {3 * DM * 2}; cuuint32_t b[2] = {64, 64}; make_map(enc, &tm.q, wqkv, 2, d, s, b, S128); }
    { cuuint64_t d[3] = {FF - 64, DM, 2}, s[2] = {FF * 2, 128}; cuuint32_t b[3] = {64, 32, 2}; make_map(enc, &tm.f0, w1, 3, d, s, b, S128); }
    { cuuint64_t d[3] = {32, DM, FF / 32}, s[2] = {FF * 2, 64}; cuuint32_t b[3] = {32, 32, 3}; make_map(enc, &tm.f1, w1, 3, d, s, b, S64); }
    { cuuint64_t d[2] = {FF, SEQ}, s[1] = {FF * 2}; cuuint32_t b[2] = {64, 64}; make_map(enc, &tm.h, pH, 2, d, s, b, S128); }
    { cuuint64_t d[2] = {DM, SEQ}, s[1] = {DM * 2}; cuuint32_t b[2] = {64, 64}; make_map(enc, &tm.o, pO, 2, d, s, b, S128); }
    { cuuint64_t d[5] = {DM, 2, 4, 4, FF / 32}, s[4] = {1024, 8 * 1024, 2 * 1024, 32 * 1024}; cuuint32_t b[5] = {64, 2, 4, 4, 2};
      make_map(enc, &tm.w2, w2, 5, d, s, b, S128); }
    { cuuint64_t d[2] = {DM, DM}, s[1] = {DM * 2}; cuuint32_t b[2] = {64, 64}; make_map(enc, &tm.wo, wo, 2, d, s, b, S128); }

    cudaFuncSetAttribute(fused_kernel, cudaFuncAttributeMaxDynamicSharedMemorySize, SMEM_BYTES);
    fused_kernel<<<128, 640, SMEM_BYTES, cudaStreamPerThread>>>(tm, x, wqkv, wo, w1, b1, w2, b2, gate, (__nv_bfloat16*)d_out);
}
```

```cpp
#include <cuda_runtime.h>
#include <cuda_bf16.h>
#include <cuda_fp16.h>
#include <cuda.h>
#include <stdint.h>

#define SEQ 2048
#define DM 512
#define FF 1792
#define NH 32

__device__ __align__(1024) uint8_t gQ[NH * SEQ * 32];
__device__ __align__(1024) uint8_t gKV[NH * SEQ * 64];
__device__ __align__(1024) __nv_bfloat16 gH[SEQ * FF];
__device__ __align__(1024) uint4 gO[32 * NH * 128];
__device__ float gG[SEQ];
__device__ float gN[3 * 8 * 128];
__device__ unsigned int gCntQ[8 * 32];
__device__ unsigned int gCntH[32 * 32];
__device__ unsigned int gEpoch[128];

__device__ __forceinline__ uint32_t smem_u32(const void* p) { return (uint32_t)__cvta_generic_to_shared(p); }
__device__ __forceinline__ void mbar_init(uint32_t a, uint32_t c) { asm volatile("mbarrier.init.shared::cta.b64 [%0], %1;" ::"r"(a), "r"(c)); }
__device__ __forceinline__ void mbar_expect(uint32_t a, uint32_t b) { asm volatile("mbarrier.arrive.expect_tx.shared::cta.b64 _, [%0], %1;" ::"r"(a), "r"(b) : "memory"); }
__device__ __forceinline__ void mbar_arrive(uint32_t a) { asm volatile("mbarrier.arrive.shared::cta.b64 _, [%0];" ::"r"(a) : "memory"); }
__device__ __forceinline__ void mbar_wait(uint32_t a, uint32_t ph) {
    asm volatile("{\n.reg .pred p;\n.reg .u32 n;\nmov.u32 n, 0;\nW_%=:\nmbarrier.try_wait.parity.shared::cta.b64 p, [%0], %1;\n@p bra D_%=;\n"
                 "add.u32 n, n, 1;\nsetp.lt.u32 p, n, 0x400000;\n@p bra W_%=;\ntrap;\nD_%=:\n}" ::"r"(a), "r"(ph) : "memory");
}
__device__ __forceinline__ void mbar_arrive_cluster(uint32_t a, uint32_t cta) {
    asm volatile("{\n.reg .b32 r;\nmapa.shared::cluster.u32 r, %0, %1;\nmbarrier.arrive.shared::cluster.b64 _, [r];\n}" ::"r"(a), "r"(cta) : "memory");
}
__device__ __forceinline__ void bar_sync(int id, int n) { asm volatile("bar.sync %0, %1;" ::"r"(id), "r"(n) : "memory"); }
__device__ __forceinline__ void bar_arrive(int id, int n) { asm volatile("bar.arrive %0, %1;" ::"r"(id), "r"(n) : "memory"); }
__device__ __forceinline__ uint32_t cluster_rank() { uint32_t r; asm("mov.u32 %0, %%cluster_ctarank;" : "=r"(r)); return r; }
__device__ __forceinline__ void cnt_add(unsigned int* c) { asm volatile("red.release.gpu.global.add.u32 [%0], 1;" ::"l"(c) : "memory"); }
__device__ __forceinline__ void cnt_wait(const unsigned int* c, uint32_t target) {
    uint32_t v;
    int spins = 0;
    while (true) {
        asm volatile("ld.acquire.gpu.global.u32 %0, [%1];" : "=r"(v) : "l"(c) : "memory");
        if ((int)(v - target) >= 0) break;
        if (++spins > (1 << 22)) __trap();
        __nanosleep(40);
    }
}
__device__ __forceinline__ void tma2d(uint32_t dst, const CUtensorMap* m, int c0, int c1, uint32_t bar) {
    asm volatile("cp.async.bulk.tensor.2d.shared::cluster.global.mbarrier::complete_tx::bytes [%0], [%1, {%3, %4}], [%2];"
                 ::"r"(dst), "l"(m), "r"(bar), "r"(c0), "r"(c1) : "memory");
}
__device__ __forceinline__ void tma2d_mc(uint32_t dst, const CUtensorMap* m, int c0, int c1, uint32_t bar) {
    asm volatile("cp.async.bulk.tensor.2d.shared::cluster.global.mbarrier::complete_tx::bytes.multicast::cluster [%0], [%1, {%3, %4}], [%2], %5;"
                 ::"r"(dst), "l"(m), "r"(bar), "r"(c0), "r"(c1), "h"((uint16_t)3) : "memory");
}
__device__ __forceinline__ void tma3d_mc(uint32_t dst, const CUtensorMap* m, int c0, int c1, int c2, uint32_t bar) {
    asm volatile("cp.async.bulk.tensor.3d.shared::cluster.global.mbarrier::complete_tx::bytes.multicast::cluster [%0], [%1, {%3, %4, %5}], [%2], %6;"
                 ::"r"(dst), "l"(m), "r"(bar), "r"(c0), "r"(c1), "r"(c2), "h"((uint16_t)3) : "memory");
}
__device__ __forceinline__ void tma5d_mc(uint32_t dst, const CUtensorMap* m, int c0, int c4, uint32_t bar) {
    asm volatile("cp.async.bulk.tensor.5d.shared::cluster.global.mbarrier::complete_tx::bytes.multicast::cluster [%0], [%1, {%3, %5, %5, %5, %4}], [%2], %6;"
                 ::"r"(dst), "l"(m), "r"(bar), "r"(c0), "r"(c4), "r"(0), "h"((uint16_t)3) : "memory");
}
__device__ __forceinline__ void bulk_mc(uint32_t dst, const void* src, uint32_t bytes, uint32_t bar) {
    asm volatile("cp.async.bulk.shared::cluster.global.mbarrier::complete_tx::bytes.multicast::cluster [%0], [%1], %2, [%3], %4;"
                 ::"r"(dst), "l"(src), "r"(bytes), "r"(bar), "h"((uint16_t)3) : "memory");
}
__device__ __forceinline__ void l2_prefetch(const void* src, uint32_t bytes) {
    asm volatile("cp.async.bulk.prefetch.L2.global [%0], %1;" ::"l"(src), "r"(bytes) : "memory");
}
__device__ __forceinline__ void map_prefetch(const CUtensorMap* m) { asm volatile("prefetch.tensormap [%0];" ::"l"(m) : "memory"); }
__device__ __forceinline__ void wg_fence() { asm volatile("wgmma.fence.sync.aligned;" ::: "memory"); }
__device__ __forceinline__ void wg_commit() { asm volatile("wgmma.commit_group.sync.aligned;" ::: "memory"); }
template <int N> __device__ __forceinline__ void wg_wait() { asm volatile("wgmma.wait_group.sync.aligned %0;" ::"n"(N) : "memory"); }
template <int N> __device__ __forceinline__ void pin(float* s) {
#pragma unroll
    for (int i = 0; i < N; i++) asm volatile("" : "+f"(s[i])::"memory");
}
template <int N> __device__ __forceinline__ void pin(uint32_t* s) {
#pragma unroll
    for (int i = 0; i < N; i++) asm volatile("" : "+r"(s[i])::"memory");
}
__device__ __forceinline__ uint64_t mkdesc(uint32_t addr, uint32_t lbo, uint32_t sbo, uint32_t swz) {
    return (uint64_t)((addr & 0x3FFFF) >> 4) | ((uint64_t)(lbo >> 4) << 16) | ((uint64_t)(sbo >> 4) << 32) | ((uint64_t)swz << 62);
}
__device__ __forceinline__ float ex2f(float x) { float y; asm("ex2.approx.ftz.f32 %0, %1;" : "=f"(y) : "f"(x)); return y; }
__device__ __forceinline__ float tanhf_(float x) { float y; asm("tanh.approx.f32 %0, %1;" : "=f"(y) : "f"(x)); return y; }
__device__ __forceinline__ uint32_t pk_bf16(float lo, float hi) { uint32_t r; asm("cvt.rn.bf16x2.f32 %0, %1, %2;" : "=r"(r) : "f"(hi), "f"(lo)); return r; }
__device__ __forceinline__ uint32_t pk_f16(float lo, float hi) { uint32_t r; asm("cvt.rn.f16x2.f32 %0, %1, %2;" : "=r"(r) : "f"(hi), "f"(lo)); return r; }
__device__ __forceinline__ float bf_lo(uint32_t v) { return __uint_as_float(v << 16); }
__device__ __forceinline__ float bf_hi(uint32_t v) { return __uint_as_float(v & 0xffff0000u); }
__device__ __forceinline__ float ldcg_f(const float* p) { return __ldcg(p); }

#define TLM(k, slot) do {} while (0)
#define TLC(k, slot) do {} while (0)

__device__ __forceinline__ void wgmma_ss_n128(float* d, uint64_t da, uint64_t db) {
    asm volatile("wgmma.mma_async.sync.aligned.m64n128k16.f32.bf16.bf16 {"
        "%0, %1, %2, %3, %4, %5, %6, %7, %8, %9, %10, %11, %12, %13, %14, %15,"
        "%16, %17, %18, %19, %20, %21, %22, %23, %24, %25, %26, %27, %28, %29, %30, %31,"
        "%32, %33, %34, %35, %36, %37, %38, %39, %40, %41, %42, %43, %44, %45, %46, %47,"
        "%48, %49, %50, %51, %52, %53, %54, %55, %56, %57, %58, %59, %60, %61, %62, %63}, %64, %65, 1, 1, 1, 0, 1;\n"
        :
        "+f"(d[0]), "+f"(d[1]), "+f"(d[2]), "+f"(d[3]), "+f"(d[4]), "+f"(d[5]), "+f"(d[6]), "+f"(d[7]),
        "+f"(d[8]), "+f"(d[9]), "+f"(d[10]), "+f"(d[11]), "+f"(d[12]), "+f"(d[13]), "+f"(d[14]), "+f"(d[15]),
        "+f"(d[16]), "+f"(d[17]), "+f"(d[18]), "+f"(d[19]), "+f"(d[20]), "+f"(d[21]), "+f"(d[22]), "+f"(d[23]),
        "+f"(d[24]), "+f"(d[25]), "+f"(d[26]), "+f"(d[27]), "+f"(d[28]), "+f"(d[29]), "+f"(d[30]), "+f"(d[31]),
        "+f"(d[32]), "+f"(d[33]), "+f"(d[34]), "+f"(d[35]), "+f"(d[36]), "+f"(d[37]), "+f"(d[38]), "+f"(d[39]),
        "+f"(d[40]), "+f"(d[41]), "+f"(d[42]), "+f"(d[43]), "+f"(d[44]), "+f"(d[45]), "+f"(d[46]), "+f"(d[47]),
        "+f"(d[48]), "+f"(d[49]), "+f"(d[50]), "+f"(d[51]), "+f"(d[52]), "+f"(d[53]), "+f"(d[54]), "+f"(d[55]),
        "+f"(d[56]), "+f"(d[57]), "+f"(d[58]), "+f"(d[59]), "+f"(d[60]), "+f"(d[61]), "+f"(d[62]), "+f"(d[63])
        : "l"(da), "l"(db));
}
__device__ __forceinline__ void wgmma_ss_n96(float* d, uint64_t da, uint64_t db) {
    asm volatile("wgmma.mma_async.sync.aligned.m64n96k16.f32.bf16.bf16 {"
        "%0, %1, %2, %3, %4, %5, %6, %7, %8, %9, %10, %11, %12, %13, %14, %15,"
        "%16, %17, %18, %19, %20, %21, %22, %23, %24, %25, %26, %27, %28, %29, %30, %31,"
        "%32, %33, %34, %35, %36, %37, %38, %39, %40, %41, %42, %43, %44, %45, %46, %47}, %48, %49, 1, 1, 1, 0, 1;\n"
        :
        "+f"(d[0]), "+f"(d[1]), "+f"(d[2]), "+f"(d[3]), "+f"(d[4]), "+f"(d[5]), "+f"(d[6]), "+f"(d[7]),
        "+f"(d[8]), "+f"(d[9]), "+f"(d[10]), "+f"(d[11]), "+f"(d[12]), "+f"(d[13]), "+f"(d[14]), "+f"(d[15]),
        "+f"(d[16]), "+f"(d[17]), "+f"(d[18]), "+f"(d[19]), "+f"(d[20]), "+f"(d[21]), "+f"(d[22]), "+f"(d[23]),
        "+f"(d[24]), "+f"(d[25]), "+f"(d[26]), "+f"(d[27]), "+f"(d[28]), "+f"(d[29]), "+f"(d[30]), "+f"(d[31]),
        "+f"(d[32]), "+f"(d[33]), "+f"(d[34]), "+f"(d[35]), "+f"(d[36]), "+f"(d[37]), "+f"(d[38]), "+f"(d[39]),
        "+f"(d[40]), "+f"(d[41]), "+f"(d[42]), "+f"(d[43]), "+f"(d[44]), "+f"(d[45]), "+f"(d[46]), "+f"(d[47])
        : "l"(da), "l"(db));
}
__device__ __forceinline__ void wgmma_ss_n64(float* d, uint64_t da, uint64_t db) {
    asm volatile("wgmma.mma_async.sync.aligned.m64n64k16.f32.bf16.bf16 {"
        "%0, %1, %2, %3, %4, %5, %6, %7, %8, %9, %10, %11, %12, %13, %14, %15,"
        "%16, %17, %18, %19, %20, %21, %22, %23, %24, %25, %26, %27, %28, %29, %30, %31}, %32, %33, 1, 1, 1, 0, 1;\n"
        :
        "+f"(d[0]), "+f"(d[1]), "+f"(d[2]), "+f"(d[3]), "+f"(d[4]), "+f"(d[5]), "+f"(d[6]), "+f"(d[7]),
        "+f"(d[8]), "+f"(d[9]), "+f"(d[10]), "+f"(d[11]), "+f"(d[12]), "+f"(d[13]), "+f"(d[14]), "+f"(d[15]),
        "+f"(d[16]), "+f"(d[17]), "+f"(d[18]), "+f"(d[19]), "+f"(d[20]), "+f"(d[21]), "+f"(d[22]), "+f"(d[23]),
        "+f"(d[24]), "+f"(d[25]), "+f"(d[26]), "+f"(d[27]), "+f"(d[28]), "+f"(d[29]), "+f"(d[30]), "+f"(d[31])
        : "l"(da), "l"(db));
}
__device__ __forceinline__ void wgmma_qk_f16_acc(float* d, const uint32_t* a, uint64_t db) {
    asm volatile("wgmma.mma_async.sync.aligned.m64n64k16.f32.f16.f16 {"
        "%0, %1, %2, %3, %4, %5, %6, %7, %8, %9, %10, %11, %12, %13, %14, %15,"
        "%16, %17, %18, %19, %20, %21, %22, %23, %24, %25, %26, %27, %28, %29, %30, %31}, {%32, %33, %34, %35}, %36, 1, 1, 1, 0;\n"
        :
        "+f"(d[0]), "+f"(d[1]), "+f"(d[2]), "+f"(d[3]), "+f"(d[4]), "+f"(d[5]), "+f"(d[6]), "+f"(d[7]),
        "+f"(d[8]), "+f"(d[9]), "+f"(d[10]), "+f"(d[11]), "+f"(d[12]), "+f"(d[13]), "+f"(d[14]), "+f"(d[15]),
        "+f"(d[16]), "+f"(d[17]), "+f"(d[18]), "+f"(d[19]), "+f"(d[20]), "+f"(d[21]), "+f"(d[22]), "+f"(d[23]),
        "+f"(d[24]), "+f"(d[25]), "+f"(d[26]), "+f"(d[27]), "+f"(d[28]), "+f"(d[29]), "+f"(d[30]), "+f"(d[31])
        : "r"(a[0]), "r"(a[1]), "r"(a[2]), "r"(a[3]), "l"(db));
}
__device__ __forceinline__ void wgmma_qk_bf16_zero(float* d, const uint32_t* a, uint64_t db) {
    asm volatile("wgmma.mma_async.sync.aligned.m64n64k16.f32.bf16.bf16 {"
        "%0, %1, %2, %3, %4, %5, %6, %7, %8, %9, %10, %11, %12, %13, %14, %15,"
        "%16, %17, %18, %19, %20, %21, %22, %23, %24, %25, %26, %27, %28, %29, %30, %31}, {%32, %33, %34, %35}, %36, 0, 1, 1, 0;\n"
        :
        "=f"(d[0]), "=f"(d[1]), "=f"(d[2]), "=f"(d[3]), "=f"(d[4]), "=f"(d[5]), "=f"(d[6]), "=f"(d[7]),
        "=f"(d[8]), "=f"(d[9]), "=f"(d[10]), "=f"(d[11]), "=f"(d[12]), "=f"(d[13]), "=f"(d[14]), "=f"(d[15]),
        "=f"(d[16]), "=f"(d[17]), "=f"(d[18]), "=f"(d[19]), "=f"(d[20]), "=f"(d[21]), "=f"(d[22]), "=f"(d[23]),
        "=f"(d[24]), "=f"(d[25]), "=f"(d[26]), "=f"(d[27]), "=f"(d[28]), "=f"(d[29]), "=f"(d[30]), "=f"(d[31])
        : "r"(a[0]), "r"(a[1]), "r"(a[2]), "r"(a[3]), "l"(db));
}
__device__ __forceinline__ void wgmma_pv(float* d, const uint32_t* a, uint64_t db) {
    asm volatile("wgmma.mma_async.sync.aligned.m64n24k16.f32.bf16.bf16 {"
        "%0, %1, %2, %3, %4, %5, %6, %7, %8, %9, %10, %11}, {%12, %13, %14, %15}, %16, 1, 1, 1, 1;\n"
        :
        "+f"(d[0]), "+f"(d[1]), "+f"(d[2]), "+f"(d[3]), "+f"(d[4]), "+f"(d[5]), "+f"(d[6]), "+f"(d[7]),
        "+f"(d[8]), "+f"(d[9]), "+f"(d[10]), "+f"(d[11])
        : "r"(a[0]), "r"(a[1]), "r"(a[2]), "r"(a[3]), "l"(db));
}

template <int N> __device__ __forceinline__ void wgmma_ss(float* d, uint64_t a, uint64_t b) {
    if (N == 128) wgmma_ss_n128(d, a, b);
    if (N == 96) wgmma_ss_n96(d, a, b);
    if (N == 64) wgmma_ss_n64(d, a, b);
}

#define OFF_R 131072
#define OFF_ONE 229376
#define OFF_BAR 229888
#define OFF_BIAS (OFF_BAR + 512)
#define OFF_G (OFF_BIAS + 768)
#define SMEM_BYTES (OFF_G + 272)
#define SBD 1024u
#define B_X 0
#define B_F1 64
#define B_E1 112
#define B_KV 160
#define B_F2 224
#define B_E2 256
#define B_T 288
#define B_DONE 352
#define B_G 360
#define B_G2 368

#define PF 0
#define EXP_FKK 4
#define QSCALE 0.36067376022224085f
#define MAGIC 445.41763f
#define NMUFU 4
#define VSTEP ((uint64_t)((long long)32 - ((long long)32 << 16)))

__host__ __device__ constexpr int strm_pos(int pass, int i) {
    return pass == 0 ? i + (i >> 1) : pass == 1 ? (i < 4 ? 3 * i + 2 : 8 + i) : pass == 2 ? 16 + i : 20 + i;
}
__host__ __device__ constexpr int strm_pass(int p) { return p < 12 ? (p % 3 == 2 ? 1 : 0) : p < 16 ? 1 : p < 20 ? 2 : 3; }
__host__ __device__ constexpr int strm_idx(int p) { return p < 12 ? (p % 3 == 2 ? p / 3 : p - p / 3) : p < 16 ? p - 8 : p < 20 ? p - 16 : p - 20; }

template <int N, int PASS, int NST, int KK, int SUB, int KST, int LBO, int SBO, int SWZ, bool WAITX>
__device__ __forceinline__ void gemm_pass(float* acc, uint32_t bar, uint64_t dA0, int lane, int barNext) {
    if (WAITX) mbar_wait(bar + B_X, 0);
    mbar_wait(bar + B_F1 + 8 * (strm_pos(PASS, 0) % 6), (strm_pos(PASS, 0) / 6) & 1);
#pragma unroll
    for (int i = 0; i < NST; i++) {
        const int it = strm_pos(PASS, i);
        const uint64_t dA = dA0 + i * (KK / 4 * 1024);
        const uint64_t dB = mkdesc(SBD + OFF_R + (it % 6) * 16384, LBO, SBO, SWZ);
        wg_fence();
#pragma unroll
        for (int kk = 0; kk < KK / 2; kk++) wgmma_ss<N>(acc, dA + (kk >> 2) * 1024 + (kk & 3) * 2, dB + kk * KST / 16);
        wg_commit();
        if (i > 0) {
            wg_wait<1>();
            if (lane < 2) mbar_arrive_cluster(bar + B_E1 + 8 * (strm_pos(PASS, i - 1) % 6), lane);
        }
#pragma unroll
        for (int kk = KK / 2; kk < KK; kk++) wgmma_ss<N>(acc, dA + (kk >> 2) * 1024 + (kk & 3) * 2, dB + (SUB + (kk - KK / 2) * KST) / 16);
        wg_commit();
        if (i + 1 < NST) {
            if (WAITX) mbar_wait(bar + B_X + 8 * (i + 1), 0);
            mbar_wait(bar + B_F1 + 8 * (strm_pos(PASS, i + 1) % 6), (strm_pos(PASS, i + 1) / 6) & 1);
        }
    }
    if (barNext) bar_arrive(barNext, 512);
    wg_wait<0>();
    if (lane < 2) mbar_arrive_cluster(bar + B_E1 + 8 * (strm_pos(PASS, NST - 1) % 6), lane);
    pin<N / 2>(acc);
}

__device__ __forceinline__ uint32_t lds32(uint32_t a) { uint32_t v; asm volatile("ld.shared.u32 %0, [%1];" : "=r"(v) : "r"(a)); return v; }
__device__ __forceinline__ bool elect() {
    uint32_t p;
    asm volatile("{\n.reg .pred p;\nelect.sync _|p, 0xffffffff;\nselp.u32 %0, 1, 0, p;\n}" : "=r"(p));
    return p;
}

template <int N> __device__ __forceinline__ void bias_init(float* acc, uint32_t b) {
#pragma unroll
    for (int j = 0; j < N / 8; j++) {
        const uint32_t bv = lds32(b + j * 16);
        acc[4 * j] = acc[4 * j + 2] = bf_lo(bv);
        acc[4 * j + 1] = acc[4 * j + 3] = bf_hi(bv);
    }
    pin<N / 2>(acc);
}

template <int G0, int G1> __device__ __forceinline__ void gelu_store(const float* acc, __nv_bfloat16* hp) {
#pragma unroll
    for (int G = G0; G < G1; G++) {
        uint32_t o[8];
#pragma unroll
        for (int j = 0; j < 4; j++) {
            float y[4];
#pragma unroll
            for (int i = 0; i < 4; i++) {
                const float h = acc[16 * G + 4 * j + i];
                const float z = h * fmaf(h * h, 0.035677408136300125f, 0.7978845608028654f);
                const float hh = 0.5f * h;
                y[i] = fmaf(hh, tanhf_(z), hh);
            }
            o[j] = pk_bf16(y[0], y[1]);
            o[4 + j] = pk_bf16(y[2], y[3]);
        }
        *(uint4*)(hp + G * 32) = make_uint4(o[0], o[1], o[2], o[3]);
        *(uint4*)(hp + 8 * FF + G * 32) = make_uint4(o[4], o[5], o[6], o[7]);
    }
}

__device__ __forceinline__ float norm_bound(const float* v, float sc) {
    uint32_t m = 0;
#pragma unroll
    for (int h = 0; h < 4; h++) {
        const float* u = v + 8 * h;
        m = max(m, __float_as_uint(fmaf(u[0], u[0], fmaf(u[1], u[1], fmaf(u[4], u[4], u[5] * u[5])))));
        m = max(m, __float_as_uint(fmaf(u[2], u[2], fmaf(u[3], u[3], fmaf(u[6], u[6], u[7] * u[7])))));
    }
#pragma unroll
    for (int o = 4; o < 32; o <<= 1) m = max(m, __shfl_xor_sync(0xffffffffu, m, o));
    float f = __uint_as_float(m);
    f += __shfl_xor_sync(0xffffffffu, f, 1);
    f += __shfl_xor_sync(0xffffffffu, f, 2);
    return f * sc;
}

__device__ __forceinline__ uint32_t exp2_pair(float a, float b) {
    const uint32_t w = __byte_perm(__float_as_uint(a), __float_as_uint(b), 0x6521);
    uint32_t m, r;
    asm("lop3.b32 %0, %1, 0x007f007f, 0x9f809f80, 0xEA;" : "=r"(m) : "r"(w));
    const uint32_t e = w - m;
    asm("fma.rn.bf16x2 %0, %1, %2, %3;" : "=r"(r) : "r"(w), "r"(m), "r"(e));
    return r;
}

__device__ __forceinline__ void store_o(const float* o, uint4* dst, uint32_t par) {
    const float s0 = __fdividef(1.f, o[8]), s1 = __fdividef(1.f, o[10]);
    const uint32_t d0 = (pk_bf16(o[0] * s0, o[1] * s0) & ~1u) | par;
    asm volatile("{\n.reg .b128 t;\nmov.b128 t, {%0, %1, %2, %3};\nst.relaxed.gpu.global.b128 [%4], t;\n}" ::"r"(d0),
                 "r"(pk_bf16(o[4] * s0, o[5] * s0)), "r"(pk_bf16(o[2] * s1, o[3] * s1)), "r"(pk_bf16(o[6] * s1, o[7] * s1)), "l"(dst) : "memory");
}
__device__ __forceinline__ uint4 load_o(const uint4* src) {
    uint4 v;
    asm volatile("{\n.reg .b128 t;\nld.relaxed.gpu.global.b128 t, [%4];\nmov.b128 {%0, %1, %2, %3}, t;\n}"
                 : "=r"(v.x), "=r"(v.y), "=r"(v.z), "=r"(v.w) : "l"(src) : "memory");
    return v;
}
__device__ __forceinline__ uint32_t bmul2(uint32_t a, uint32_t b) { uint32_t r; asm("mul.rn.bf16x2 %0, %1, %2;" : "=r"(r) : "r"(a), "r"(b)); return r; }
__device__ __forceinline__ void sts32(uint32_t a, uint32_t v) { asm volatile("st.shared.u32 [%0], %1;" ::"r"(a), "r"(v) : "memory"); }
__device__ __forceinline__ void load_q(uint32_t* q, int h, int row, int t) {
    const uint8_t* p = gQ + (size_t)h * (SEQ * 32) + (size_t)row * 32 + t * 4;
    q[0] = __ldcg((const uint32_t*)p); q[1] = __ldcg((const uint32_t*)(p + 256));
    q[2] = __ldcg((const uint32_t*)(p + 16)); q[3] = __ldcg((const uint32_t*)(p + 272));
}

template <int NT>
__device__ __forceinline__ void proj16(float (*c)[8], const __nv_bfloat16* x, const __nv_bfloat16* w, int row0, int rstep, int col, int g, int t) {
#pragma unroll
    for (int i = 0; i < NT; i++)
#pragma unroll
        for (int j = 0; j < 8; j++) c[i][j] = 0.f;
    const unsigned short* wu = (const unsigned short*)w;
#pragma unroll 1
    for (int k = 0; k < DM; k += 16) {
        uint32_t b[4];
#pragma unroll
        for (int j = 0; j < 4; j++) {
            const int kr = k + 2 * t + (j & 1) * 8, cc = col + g + (j >> 1) * 8;
            b[j] = (uint32_t)wu[(size_t)kr * (3 * DM) + cc] | ((uint32_t)wu[(size_t)(kr + 1) * (3 * DM) + cc] << 16);
        }
#pragma unroll
        for (int i = 0; i < NT; i++) {
            const __nv_bfloat16* xp = x + (size_t)(row0 + i * rstep + g) * DM + k + 2 * t;
            const uint32_t a0 = *(const uint32_t*)xp, a1 = *(const uint32_t*)(xp + 8 * DM);
            const uint32_t a2 = *(const uint32_t*)(xp + 8), a3 = *(const uint32_t*)(xp + 8 * DM + 8);
#pragma unroll
            for (int j = 0; j < 2; j++)
                asm volatile("mma.sync.aligned.m16n8k16.row.col.f32.bf16.bf16.f32 {%0,%1,%2,%3}, {%4,%5,%6,%7}, {%8,%9}, {%0,%1,%2,%3};"
                             : "+f"(c[i][4 * j]), "+f"(c[i][4 * j + 1]), "+f"(c[i][4 * j + 2]), "+f"(c[i][4 * j + 3])
                             : "r"(a0), "r"(a1), "r"(a2), "r"(a3), "r"(b[2 * j]), "r"(b[2 * j + 1]));
        }
    }
}

struct Maps { CUtensorMap x, kv, q, f0, f1, h, w2, wo; };

__global__ void __cluster_dims__(2, 1, 1) __launch_bounds__(640, 1)
fused_kernel(const __grid_constant__ Maps tm, const __nv_bfloat16* __restrict__ x, const __nv_bfloat16* __restrict__ wqkv,
             const __nv_bfloat16* __restrict__ wo, const __nv_bfloat16* __restrict__ w1, const __nv_bfloat16* __restrict__ b1,
             const __nv_bfloat16* __restrict__ w2, const __nv_bfloat16* __restrict__ b2, const __nv_bfloat16* __restrict__ gate,
             __nv_bfloat16* __restrict__ out) {
    extern __shared__ __align__(1024) uint8_t smem_raw[];
    const uint32_t sb = smem_u32(smem_raw);
    const uint32_t bar = sb + OFF_BAR;
    const int tid = threadIdx.x, lane = tid & 31;
    const int warp = __shfl_sync(0xffffffffu, tid >> 5, 0);
    const uint32_t rank = cluster_rank();
    const int cl = blockIdx.x >> 1;
    const int nb = cl & 7, mb = (cl >> 3) * 2 + rank;
    const int g = lane >> 2, t = lane & 3;

    const int cb = cl & 3, rb = (cl >> 2) * 2 + rank;
    if (tid == 0) TLM(0, 0);
    if (tid == 512) {
        mbar_init(bar + B_X, 1);
        asm volatile("fence.proxy.async.shared::cta;" ::: "memory");
        mbar_expect(bar + B_X, 16384);
        tma2d(sb, &tm.x, 0, mb * 128, bar + B_X);
        for (int i = 0; i < 8; i++) { if (i) mbar_init(bar + B_X + 8 * i, 1); mbar_init(bar + B_KV + 8 * i, 1); mbar_init(bar + B_T + 8 * i, 5); }
        for (int i = 0; i < 6; i++) { mbar_init(bar + B_F1 + 8 * i, 1); mbar_init(bar + B_E1 + 8 * i, 16); }
        for (int i = 0; i < 4; i++) { mbar_init(bar + B_F2 + 8 * i, 1); mbar_init(bar + B_E2 + 8 * i, 8); }
        mbar_init(bar + B_DONE, 16);
        mbar_init(bar + B_G, 1);
        mbar_init(bar + B_G2, 4);
        asm volatile("fence.mbarrier_init.release.cluster;" ::: "memory");
    } else if (tid == 544) {
        map_prefetch(&tm.kv); map_prefetch(&tm.f0);
        l2_prefetch((const uint8_t*)wqkv + (size_t)blockIdx.x * 12288, 12288);
        l2_prefetch(x + (size_t)(mb * 128 + nb * 16) * DM, 16384);
        l2_prefetch((const uint8_t*)w1 + (size_t)blockIdx.x * 14336, 14336);
        map_prefetch(&tm.q); map_prefetch(&tm.f1);
    } else if (tid < 128) {
        asm volatile("st.shared.u32 [%0], %1;" ::"r"(sb + OFF_ONE + tid * 4), "r"(0x3f803f80u) : "memory");
        asm volatile("fence.proxy.async.shared::cta;" ::: "memory");
    }
    if ((sb & 0xFFFFFF) != SBD) __trap();
    __syncthreads();
    asm volatile("barrier.cluster.arrive.relaxed.aligned;\nbarrier.cluster.wait.aligned;" ::: "memory");
    const uint32_t ep = gEpoch[blockIdx.x] + 1;
    if (tid == 0) { TLM(0, 1); TLC(0, 30); }

    if (warp < 16) {
        const int wg = warp >> 2;
        const int h = cl >> 1, qd = (cl & 1) * 2 + rank;
        uint32_t q[4];
        {
            const int w8 = warp & 7;
            const int T = mb * 8 + w8, row0 = T * 16 + g;
            const uint64_t dA0 = mkdesc(SBD + (wg & 1) * 8192, 16, 1024, 1);
            if (wg < 2) {
                {
                    float acc[64];
#pragma unroll
                    for (int i = 0; i < 64; i++) acc[i] = 0.f;
                    gemm_pass<128, 0, 8, 4, 8192, 2048, 4096, 1024, 1, true>(acc, bar, dA0, lane, 0);
                    if (tid == 0) TLM(0, 2);
                    const int pos = ((T >> 6) * 16 + 2 * g) * 64 + (T & 63);
                    uint8_t* kp = gKV + (size_t)(nb * 4) * (SEQ * 64) + (pos >> 8) * 16384 + (pos & 255) * 32 + ((t * 8) ^ (((T >> 2) & 1) << 4));
                    float vm = 0.f;
#pragma unroll
                    for (int h = 0; h < 4; h++) {
                        const float* v = acc + 8 * h;
                        float p0 = __shfl_up_sync(0xffffffffu, v[2], 4), p1 = __shfl_up_sync(0xffffffffu, v[3], 4);
                        float p2 = __shfl_up_sync(0xffffffffu, v[6], 4), p3 = __shfl_up_sync(0xffffffffu, v[7], 4);
                        if (g == 0) { p0 = p1 = p2 = p3 = 0.f; }
                        uint8_t* o = kp + (size_t)h * (SEQ * 64);
                        *(uint2*)o = make_uint2(pk_f16(v[0] - p0, v[1] - p1), pk_f16(v[4] - p2, v[5] - p3));
                        *(uint2*)(o + 2048) = make_uint2(pk_f16(v[2] - v[0], v[3] - v[1]), pk_f16(v[6] - v[4], v[7] - v[5]));
                        const float* u = acc + 32 + 8 * h;
#pragma unroll
                        for (int i = 0; i < 8; i++) vm = fmaxf(vm, fabsf(u[i]));
                        *(uint2*)(o + 8192) = make_uint2(pk_bf16(u[0], u[1]), pk_bf16(u[4], u[5]));
                        *(uint2*)(o + 8192 + 2048) = make_uint2(pk_bf16(u[2], u[3]), pk_bf16(u[6], u[7]));
                    }
                    const float km = norm_bound(acc, 1.f);
                    vm = __uint_as_float(__reduce_max_sync(0xffffffffu, __float_as_uint(vm)));
                    if (lane == 0) { gN[1024 + nb * 128 + T] = km; gN[2048 + nb * 128 + T] = vm; }
                    if (tid == 0) TLM(0, 3);
                }
                {
                    float acc[32];
#pragma unroll
                    for (int i = 0; i < 32; i++) acc[i] = 0.f;
                    bar_sync(6, 512);
                    gemm_pass<64, 2, 4, 8, 8192, 2048, 16, 1024, 1, false>(acc, bar, dA0, lane, 7);
                    if (tid == 0) TLM(0, 4);
                    uint8_t* qp = gQ + (size_t)(nb * 4) * (SEQ * 32) + (size_t)row0 * 32 + t * 8;
#pragma unroll
                    for (int h = 0; h < 4; h++) {
                        const float* v = acc + 8 * h;
                        uint8_t* o = qp + (size_t)h * (SEQ * 32);
                        *(uint2*)o = make_uint2(pk_f16(v[0] * QSCALE, v[1] * QSCALE), pk_f16(v[4] * QSCALE, v[5] * QSCALE));
                        *(uint2*)(o + 256) = make_uint2(pk_f16(v[2] * QSCALE, v[3] * QSCALE), pk_f16(v[6] * QSCALE, v[7] * QSCALE));
                    }
                    const float qm = norm_bound(acc, QSCALE * QSCALE);
                    if (lane == 0) gN[nb * 128 + T] = qm;
                    bar_arrive(10, 288);
                    if (tid == 0) TLM(0, 5);
                    mbar_wait(bar + B_G, 0);
                    load_q(q, h, qd * 512 + warp * 16 + g, t);
                }
            } else {
                if (tid < 256 + 176) {
                    const int i = tid - 256;
                    const uint32_t v = i < 112 ? *(const uint32_t*)(b1 + nb * 224 + i * 2) : *(const uint32_t*)(b2 + cb * 128 + (i - 112) * 2);
                    asm volatile("st.shared.u32 [%0], %1;" ::"r"(sb + OFF_BIAS + i * 4), "r"(v) : "memory");
                }
                bar_sync(5, 256);
                {
                    float acc[64];
                    bias_init<128>(acc, sb + OFF_BIAS + t * 4);
                    gemm_pass<128, 1, 8, 4, 8192, 2048, 4096, 1024, 1, true>(acc, bar, dA0, lane, 6);
                    if (tid == 256) TLM(0, 6);
                    gelu_store<0, 4>(acc, gH + (size_t)row0 * FF + nb * 224 + t * 8);
                }
                {
                    float acc[48];
                    bias_init<96>(acc, sb + OFF_BIAS + 256 + t * 4);
                    if (tid == 256) TLM(0, 7);
                    bar_sync(7, 512);
                    gemm_pass<96, 3, 8, 4, 6144, 1024, 2048, 512, 2, false>(acc, bar, dA0, lane, 0);
                    if (tid == 256) TLM(0, 8);
                    gelu_store<0, 1>(acc, gH + (size_t)row0 * FF + nb * 224 + 128 + t * 8);
                    mbar_wait(bar + B_G, 0);
                    load_q(q, h, qd * 512 + warp * 16 + g, t);
                    gelu_store<1, 3>(acc, gH + (size_t)row0 * FF + nb * 224 + 128 + t * 8);
                    bar_arrive(11, 288);
                    if (tid == 256) TLM(0, 10);
                }
            }
        }
        const bool fast = lds32(sb + OFF_G + 256) != 0;
        uint4* const op = gO + ((qd * 8 + wg) * NH + h) * 128 + (tid & 127);
        const uint64_t kd0 = mkdesc(SBD, 16, 256, 3);
        const uint64_t vd0 = mkdesc(SBD + 8192, OFF_ONE - 8192, 256, 3);
        if (fast) {
#pragma unroll 1
            for (int r = 0; r < 2; r++) {
                float o[12];
#pragma unroll
                for (int i = 0; i < 12; i++) o[i] = 0.f;
                uint64_t kd = kd0, vd = vd0;
                uint32_t qn[4];
#pragma unroll 1
                for (int half = 0; half < 2; half++) {
                    float s[32];
#pragma unroll
                    for (int i = 0; i < 32; i++) s[i] = i < 2 * NMUFU ? 0.f : MAGIC;
#pragma unroll 1
                    for (int c = 0; c < 4; c++) {
                        if (r == 0) mbar_wait(bar + B_KV + 8 * (half * 4 + c), 0);
                        if ((tid & 255) == 0 && c == 0) TLM(1, (tid >> 8) * 4 + r * 2 + half);
                        if (half == 1 && c == 3) {
                            if (r == 0) load_q(qn, h, qd * 512 + 256 + warp * 16 + g, t);
                            else if (lane == 0) mbar_arrive(bar + B_DONE);
                        }
#pragma unroll 1
                        for (int j = 0; j < 4; j++) {
                            uint32_t p[16];
                            wg_fence();
                            wgmma_qk_f16_acc(s, q, kd);
                            wg_commit();
                            wg_wait<0>();
                            pin<32>(s);
#pragma unroll
                            for (int i = 0; i < 16; i++)
                                p[i] = i < NMUFU ? pk_bf16(ex2f(s[2 * i]), ex2f(s[2 * i + 1])) : exp2_pair(s[2 * i], s[2 * i + 1]);
                            pin<16>(p);
                            wg_fence();
#pragma unroll
                            for (int u = 0; u < 4; u++) wgmma_pv(o, p + 4 * u, vd + u * VSTEP);
                            wg_commit();
                            kd += 128;
                            vd += 4 * VSTEP;
                        }
                        kd += 512;
                        vd += 16 * VSTEP;
                    }
                    wg_wait<0>();
                }
                pin<12>(o);
                if ((tid & 127) == 0 && r == 1) TLM(1, 8 + wg);
                store_o(o, op + r * (4 * NH * 128), ep & 1);
#pragma unroll
                for (int i = 0; i < 4; i++) q[i] = qn[i];
            }
            if (tid == 0) { TLM(1, 12); TLC(0, 31); }
        } else {
            for (int c = 0; c < 8; c++) mbar_wait(bar + B_KV + 8 * c, 0);
            {
                float kc[8][8];
                proj16<8>(kc, x, wqkv, warp * 16, 256, DM + h * 16, g, t);
#pragma unroll
                for (int i = 0; i < 8; i++) {
                    const int T = warp + i * 16;
                    const int pos = ((T >> 6) * 16 + 2 * g) * 64 + (T & 63);
                    const uint32_t a = sb + (pos >> 8) * 16384 + (pos & 255) * 32 + t * 4, sw = ((T >> 2) & 1) << 4;
                    asm volatile("st.shared.u32 [%0], %1;" ::"r"(a + sw), "r"(pk_bf16(kc[i][0], kc[i][1])) : "memory");
                    asm volatile("st.shared.u32 [%0], %1;" ::"r"(a + (sw ^ 16)), "r"(pk_bf16(kc[i][4], kc[i][5])) : "memory");
                    asm volatile("st.shared.u32 [%0], %1;" ::"r"(a + 2048 + sw), "r"(pk_bf16(kc[i][2], kc[i][3])) : "memory");
                    asm volatile("st.shared.u32 [%0], %1;" ::"r"(a + 2048 + (sw ^ 16)), "r"(pk_bf16(kc[i][6], kc[i][7])) : "memory");
                }
                asm volatile("fence.proxy.async.shared::cta;" ::: "memory");
                bar_sync(8, 512);
            }
#pragma unroll 1
            for (int r = 0; r < 2; r++) {
                const int row = qd * 512 + r * 256 + warp * 16 + g;
                {
                    float qc[1][8];
                    proj16<1>(qc, x, wqkv, row - g, 0, h * 16, g, t);
#pragma unroll
                    for (int i = 0; i < 4; i++) q[i] = pk_bf16(qc[0][2 * i] * QSCALE, qc[0][2 * i + 1] * QSCALE);
                }
                float o[12];
#pragma unroll
                for (int i = 0; i < 12; i++) o[i] = 0.f;
                float m0 = -INFINITY, m1 = -INFINITY;
#pragma unroll 1
                for (int j = 0; j < 32; j++) {
                    const uint64_t kd = kd0 + (j >> 2) * 1024 + (j & 3) * 128, vd = vd0 + ((j >> 2) * 32 + (j & 3) * 4) * VSTEP;
                    float s[32];
                    uint32_t p[16];
                    wg_fence();
                    wgmma_qk_bf16_zero(s, q, kd);
                    wg_commit();
                    wg_wait<0>();
                    pin<32>(s);
                    pin<12>(o);
                    float n0 = m0, n1 = m1;
#pragma unroll
                    for (int i = 0; i < 8; i++) {
                        n0 = fmaxf(n0, fmaxf(s[4 * i], s[4 * i + 1]));
                        n1 = fmaxf(n1, fmaxf(s[4 * i + 2], s[4 * i + 3]));
                    }
                    n0 = fmaxf(n0, __shfl_xor_sync(0xffffffffu, n0, 1));
                    n1 = fmaxf(n1, __shfl_xor_sync(0xffffffffu, n1, 1));
                    n0 = fmaxf(n0, __shfl_xor_sync(0xffffffffu, n0, 2));
                    n1 = fmaxf(n1, __shfl_xor_sync(0xffffffffu, n1, 2));
                    const float c0 = ex2f(m0 - n0), c1 = ex2f(m1 - n1);
                    m0 = n0;
                    m1 = n1;
#pragma unroll
                    for (int i = 0; i < 3; i++) { o[4 * i] *= c0; o[4 * i + 1] *= c0; o[4 * i + 2] *= c1; o[4 * i + 3] *= c1; }
#pragma unroll
                    for (int i = 0; i < 8; i++) {
                        p[2 * i] = pk_bf16(ex2f(s[4 * i] - m0), ex2f(s[4 * i + 1] - m0));
                        p[2 * i + 1] = pk_bf16(ex2f(s[4 * i + 2] - m1), ex2f(s[4 * i + 3] - m1));
                    }
                    pin<16>(p);
                    pin<12>(o);
                    wg_fence();
#pragma unroll
                    for (int u = 0; u < 4; u++) wgmma_pv(o, p + 4 * u, vd + u * VSTEP);
                    wg_commit();
                }
                wg_wait<0>();
                pin<12>(o);
                if (r == 1 && lane == 0) mbar_arrive(bar + B_DONE);
                store_o(o, op + r * (4 * NH * 128), ep & 1);
            }
        }
        {
            const uint4* src = gO + (rb * NH + wg * 8) * 128 + (tid & 127);
            uint4 v[8];
#pragma unroll
            for (int i = 0; i < 8; i++) v[i] = load_o(src + i * 128);
            mbar_wait(bar + B_DONE, 0);
            mbar_wait(bar + B_G2, 0);
            const int lr = (warp & 3) * 16 + g;
            const uint32_t g0 = lds32(sb + OFF_G + lr * 4), g1 = lds32(sb + OFF_G + lr * 4 + 32);
            const uint32_t a0 = sb + wg * 16384 + lr * 128 + (t >> 1) * 4;
#pragma unroll
            for (int i = 0; i < 8; i++) {
                int spins = 0;
                while (((v[i].x ^ ep) & 1) != 0) {
                    if (++spins > (1 << 22)) __trap();
                    v[i] = load_o(src + i * 128);
                }
                const uint32_t a = a0 + (i >> 2) * 8192 + ((((i & 3) * 2 + (t & 1)) ^ g) << 4);
                sts32(a, bmul2(v[i].x, g0));
                sts32(a + 8, bmul2(v[i].y, g0));
                sts32(a + 1024, bmul2(v[i].z, g1));
                sts32(a + 1024 + 8, bmul2(v[i].w, g1));
                if ((i & 3) == 3) {
                    asm volatile("fence.proxy.async.shared::cta;" ::: "memory");
                    __syncwarp();
                    if (lane == 0) mbar_arrive(bar + B_T + 8 * (wg * 2 + (i >> 2)));
                    if ((tid & 127) == 0) TLM(1, 20 + wg * 2 + (i >> 2));
                }
            }
        }
    } else {
        if (warp == 16) {
            if (elect()) {
#pragma unroll
                for (int it = 0; it < 28; it++) {
                    const int s = it % 6, ps = strm_pass(it), i = strm_idx(it);
                    const uint32_t fb = bar + B_F1 + 8 * s, dst = sb + OFF_R + s * 16384;
                    if (it >= 6) mbar_wait(bar + B_E1 + 8 * s, ((it / 6) - 1) & 1);
                    mbar_expect(fb, ps < 3 ? 16384 : 12288);
                    if (ps == 0) tma3d_mc(dst + rank * 8192, &tm.kv, nb * 64, i * 64 + rank * 32, 1, fb);
                    if (ps == 1) tma3d_mc(dst + rank * 8192, &tm.f0, nb * 224, i * 64 + rank * 32, 0, fb);
                    if (ps == 2) tma2d_mc(dst + rank * 8192, &tm.q, nb * 64, i * 128 + rank * 64, fb);
                    if (ps == 3) tma3d_mc(dst + rank * 6144, &tm.f1, 0, i * 64 + rank * 32, nb * 7 + 4, fb);
                    if (ps == 0 && i < 7) {
                        mbar_expect(bar + B_X + 8 * (i + 1), 16384);
                        tma2d(sb + (i + 1) * 16384, &tm.x, (i + 1) * 64, mb * 128, bar + B_X + 8 * (i + 1));
                    }
                }
                const int h = cl >> 1;
                cnt_wait(gCntQ + (h >> 2) * 32, ep * 16);
                asm volatile("fence.proxy.async.global;" ::: "memory");
                TLM(0, 9);
#pragma unroll
                for (int c = 0; c < 8; c++) {
                    const int it = 20 + c;
                    if (c >= 2) mbar_wait(bar + B_E1 + 8 * (it % 6), (it / 6) & 1);
                    mbar_expect(bar + B_KV + 8 * c, 16384);
                    bulk_mc(sb + c * 16384 + rank * 8192, gKV + (size_t)h * (SEQ * 64) + c * 16384 + rank * 8192, 8192, bar + B_KV + 8 * c);
                }
#pragma unroll
                for (int s = 0; s < 4; s++) {
                    mbar_expect(bar + B_F2 + 8 * s, 24576);
                    tma5d_mc(sb + OFF_R + s * 24576 + 8192 + rank * 8192, &tm.w2, cb * 128 + rank * 64, s * 2, bar + B_F2 + 8 * s);
                }
                cnt_wait(gCntH + rb * 32, ep * 12);
                asm volatile("fence.proxy.async.global;" ::: "memory");
                TLM(1, 13);
#pragma unroll
                for (int s = 0; s < 4; s++) tma2d(sb + OFF_R + s * 24576, &tm.h, s * 64, rb * 64, bar + B_F2 + 8 * s);
            }
        } else if (warp == 17) {
            float gw[16];
            {
                const uint4 a = *(const uint4*)(gate + lane * 8), b = *(const uint4*)(gate + 256 + lane * 8);
                const uint32_t u[8] = {a.x, a.y, a.z, a.w, b.x, b.y, b.z, b.w};
#pragma unroll
                for (int i = 0; i < 8; i++) { gw[2 * i] = bf_lo(u[i]); gw[2 * i + 1] = bf_hi(u[i]); }
            }
            const int r0 = mb * 128 + nb * 16;
#pragma unroll 4
            for (int r = 0; r < 16; r++) {
                const __nv_bfloat16* xr = x + (size_t)(r0 + r) * DM;
                const uint4 a = *(const uint4*)(xr + lane * 8), b = *(const uint4*)(xr + 256 + lane * 8);
                const uint32_t u[8] = {a.x, a.y, a.z, a.w, b.x, b.y, b.z, b.w};
                float acc = 0.f;
#pragma unroll
                for (int i = 0; i < 8; i++) { acc = fmaf(bf_lo(u[i]), gw[2 * i], acc); acc = fmaf(bf_hi(u[i]), gw[2 * i + 1], acc); }
#pragma unroll
                for (int o = 16; o; o >>= 1) acc += __shfl_xor_sync(0xffffffffu, acc, o);
                if (lane == 0) gG[r0 + r] = 1.f / (1.f + __expf(-acc));
            }
            if (lane == 0) {
                cnt_add(gCntH + (r0 >> 6) * 32);
                l2_prefetch((const uint8_t*)w2 + (size_t)blockIdx.x * 14336, 14336);
                l2_prefetch((const uint8_t*)wo + (size_t)blockIdx.x * 4096, 4096);
                map_prefetch(&tm.h); map_prefetch(&tm.w2); map_prefetch(&tm.wo);
                TLM(0, 11);
            }
            const int h = cl >> 1, qd = (cl & 1) * 2 + rank;
            if (lane == 0) cnt_wait(gCntQ + (h >> 2) * 32, ep * 16);
            __syncwarp();
            const int hb = h >> 2;
            const uint4 kq = __ldcg((const uint4*)(gN + 1024 + hb * 128 + lane * 4));
            const uint4 vq = __ldcg((const uint4*)(gN + 2048 + hb * 128 + lane * 4));
            const float qq = ldcg_f(gN + hb * 128 + qd * 32 + lane);
            const float kf = __uint_as_float(__reduce_max_sync(0xffffffffu, max(max(kq.x, kq.y), max(kq.z, kq.w))));
            const float vf = __uint_as_float(__reduce_max_sync(0xffffffffu, max(max(vq.x, vq.y), max(vq.z, vq.w))));
            const float qf = __uint_as_float(__reduce_max_sync(0xffffffffu, __float_as_uint(qq)));
            if (lane == 0) {
                sts32(sb + OFF_G + 256, (kf <= 1.0e6f) && (qf <= 1.0e6f) && (kf * qf <= 3400.f) && (vf <= 1.0e12f));
                mbar_arrive(bar + B_G);
            }
        } else {
            bar_sync(warp - 8, 288);
            if (warp == 18) { if (lane == 0) cnt_add(gCntQ + nb * 32); }
            else if (lane < 2) cnt_add(gCntH + (mb * 2 + lane) * 32);
        }
        __syncwarp();
        float acc[64];
#pragma unroll
        for (int i = 0; i < 64; i++) acc[i] = 0.f;
        const int row = rb * 64 + (warp - 16) * 16 + g;
#pragma unroll 1
        for (int io = 0; io < 7; io++) {
#pragma unroll
            for (int s = 0; s < 4; s++) {
                const int it = io * 4 + s;
                mbar_wait(bar + B_F2 + 8 * s, io & 1);
                if (tid == 512 && s == 0 && (io == 0 || io == 4)) TLM(1, 14 + io / 4);
                const uint64_t dA = mkdesc(SBD + OFF_R + s * 24576, 16, 1024, 1);
                const uint64_t dB = mkdesc(SBD + OFF_R + s * 24576 + 8192, 8192, 1024, 1);
                wg_fence();
#pragma unroll
                for (int kk = 0; kk < EXP_FKK; kk++) wgmma_ss_n128(acc, dA + kk * 2, dB + kk * 128);
                wg_commit();
                if (warp < 18 && it >= 2 && it < 26) {
                    const int s2 = (s + 2) & 3;
                    mbar_wait(bar + B_E2 + 8 * s2, (io - (s < 2)) & 1);
                    if (elect()) {
                        if (warp == 16) {
                            mbar_expect(bar + B_F2 + 8 * s2, 24576);
                            tma5d_mc(sb + OFF_R + s2 * 24576 + 8192 + rank * 8192, &tm.w2, cb * 128 + rank * 64, it * 2 + 4, bar + B_F2 + 8 * s2);
                        } else {
                            asm volatile("fence.proxy.async.global;" ::: "memory");
                            tma2d(sb + OFF_R + s2 * 24576, &tm.h, it * 64 + 128, rb * 64, bar + B_F2 + 8 * s2);
                        }
                    }
                    __syncwarp();
                }
                wg_wait<1>();
                if (it >= 1 && lane < 2) mbar_arrive_cluster(bar + B_E2 + 8 * ((s + 3) & 3), lane);
            }
        }
        wg_wait<0>();
        if (lane < 2) mbar_arrive_cluster(bar + B_E2 + 8 * 3, lane);
        pin<64>(acc);
        if (warp == 16) {
            if (lane == 0) TLM(1, 16);
            for (int s = 0; s < 4; s++) mbar_wait(bar + B_E2 + 8 * s, 0);
            if (elect()) {
#pragma unroll
                for (int i = 0; i < 8; i++) mbar_expect(bar + B_T + 8 * i, 16384);
#pragma unroll
                for (int i = 0; i < 6; i++) tma2d_mc(sb + OFF_R + i * 16384 + rank * 8192, &tm.wo, cb * 128 + rank * 64, i * 64, bar + B_T + 8 * i);
            }
            __syncwarp();
        }
        {
            const float ga = ldcg_f(gG + row), gb = ldcg_f(gG + row + 8);
            if (t == 0) {
                sts32(sb + OFF_G + ((warp - 16) * 16 + g) * 4, pk_bf16(ga, ga));
                sts32(sb + OFF_G + ((warp - 16) * 16 + g) * 4 + 32, pk_bf16(gb, gb));
            }
            __syncwarp();
            if (lane == 0) mbar_arrive(bar + B_G2);
            const float g0 = 1.f - ga, g1 = 1.f - gb;
#pragma unroll
            for (int j = 0; j < 16; j++) {
                const uint32_t bv = lds32(sb + OFF_BIAS + 448 + j * 16 + t * 4);
                acc[4 * j] = (acc[4 * j] + bf_lo(bv)) * g0;
                acc[4 * j + 1] = (acc[4 * j + 1] + bf_hi(bv)) * g0;
                acc[4 * j + 2] = (acc[4 * j + 2] + bf_lo(bv)) * g1;
                acc[4 * j + 3] = (acc[4 * j + 3] + bf_hi(bv)) * g1;
            }
            pin<64>(acc);
        }
        if (warp == 17) {
            mbar_wait(bar + B_DONE, 0);
            if (elect()) {
#pragma unroll
                for (int i = 0; i < 4; i++)
                    tma2d(sb + 65536 + i * 8192, &tm.wo, cb * 128 + (i & 1) * 64, (6 + (i >> 1)) * 64, bar + B_T + 8 * (6 + (i >> 1)));
            }
            __syncwarp();
        }
        if (tid == 512) TLM(1, 17);
#pragma unroll
        for (int i = 0; i < 8; i++) {
            mbar_wait(bar + B_T + 8 * i, 0);
            const uint64_t dA = mkdesc(SBD + i * 8192, 16, 1024, 1);
            const uint64_t dB = mkdesc(i < 6 ? SBD + OFF_R + i * 16384 : SBD + 65536 + (i - 6) * 16384, 8192, 1024, 1);
            wg_fence();
#pragma unroll
            for (int kk = 0; kk < 4; kk++) wgmma_ss_n128(acc, dA + kk * 2, dB + kk * 128);
            wg_commit();
        }
        wg_wait<0>();
        pin<64>(acc);
        if (tid == 512) TLM(1, 18);
        {
            const uint32_t st = sb + 98304 + (warp - 16) * 4352;
            const uint32_t wa = st + (lane & 15) * 272 + (lane >> 4) * 16;
#pragma unroll
            for (int j = 0; j < 8; j++)
                asm volatile("stmatrix.sync.aligned.m8n8.x4.shared.b16 [%0], {%1, %2, %3, %4};" ::"r"(wa + j * 32),
                             "r"(pk_bf16(acc[8 * j], acc[8 * j + 1])), "r"(pk_bf16(acc[8 * j + 2], acc[8 * j + 3])),
                             "r"(pk_bf16(acc[8 * j + 4], acc[8 * j + 5])), "r"(pk_bf16(acc[8 * j + 6], acc[8 * j + 7])) : "memory");
            __syncwarp();
            __nv_bfloat16* op = out + (size_t)(rb * 64 + (warp - 16) * 16 + (lane >> 4)) * DM + cb * 128 + (lane & 15) * 8;
#pragma unroll
            for (int j = 0; j < 8; j++) {
                uint4 v;
                asm volatile("ld.shared.v4.u32 {%0, %1, %2, %3}, [%4];" : "=r"(v.x), "=r"(v.y), "=r"(v.z), "=r"(v.w)
                             : "r"(st + (2 * j + (lane >> 4)) * 272 + (lane & 15) * 16));
                *(uint4*)(op + (size_t)j * 2 * DM) = v;
            }
        }
        if (tid == 512) { gEpoch[blockIdx.x] = ep; TLM(1, 19); }
    }
}

typedef CUresult (*EncodeFn)(CUtensorMap*, CUtensorMapDataType, cuuint32_t, void*, const cuuint64_t*, const cuuint64_t*, const cuuint32_t*,
                             const cuuint32_t*, CUtensorMapInterleave, CUtensorMapSwizzle, CUtensorMapL2promotion, CUtensorMapFloatOOBfill);

static void make_map(EncodeFn enc, CUtensorMap* m, const void* p, int rank, const cuuint64_t* dims, const cuuint64_t* strides,
                     const cuuint32_t* box, CUtensorMapSwizzle swz) {
    const cuuint32_t es[5] = {1, 1, 1, 1, 1};
    enc(m, CU_TENSOR_MAP_DATA_TYPE_BFLOAT16, rank, (void*)p, dims, strides, box, es, CU_TENSOR_MAP_INTERLEAVE_NONE, swz,
        CU_TENSOR_MAP_L2_PROMOTION_L2_128B, CU_TENSOR_MAP_FLOAT_OOB_FILL_NONE);
}

extern "C" void kernel_launch(void* const* d_in, const int* in_sizes, int n_in, void* d_out, int out_size) {
    const __nv_bfloat16* x = (const __nv_bfloat16*)d_in[0];
    const __nv_bfloat16* wqkv = (const __nv_bfloat16*)d_in[1];
    const __nv_bfloat16* wo = (const __nv_bfloat16*)d_in[2];
    const __nv_bfloat16* w1 = (const __nv_bfloat16*)d_in[4];
    const __nv_bfloat16* b1 = (const __nv_bfloat16*)d_in[5];
    const __nv_bfloat16* w2 = (const __nv_bfloat16*)d_in[6];
    const __nv_bfloat16* b2 = (const __nv_bfloat16*)d_in[7];
    const __nv_bfloat16* gate = (const __nv_bfloat16*)d_in[8];

    void* fp = nullptr;
    cudaDriverEntryPointQueryResult qr;
    cudaGetDriverEntryPoint("cuTensorMapEncodeTiled", &fp, cudaEnableDefault, &qr);
    EncodeFn enc = (EncodeFn)fp;
    void* pH;
    cudaGetSymbolAddress(&pH, gH);

    Maps tm;
    const CUtensorMapSwizzle S128 = CU_TENSOR_MAP_SWIZZLE_128B, S64 = CU_TENSOR_MAP_SWIZZLE_64B;
    { cuuint64_t d[2] = {DM, SEQ}, s[1] = {DM * 2}; cuuint32_t b[2] = {64, 128}; make_map(enc, &tm.x, x, 2, d, s, b, S128); }
    { cuuint64_t d[3] = {DM, DM, 3}, s[2] = {3 * DM * 2, DM * 2}; cuuint32_t b[3] = {64, 32, 2}; make_map(enc, &tm.kv, wqkv, 3, d, s, b, S128); }
    { cuuint64_t d[2] = {3 * DM, DM}, s[1] = {3 * DM * 2}; cuuint32_t b[2] = {64, 64}; make_map(enc, &tm.q, wqkv, 2, d, s, b, S128); }
    { cuuint64_t d[3] = {FF - 64, DM, 2}, s[2] = {FF * 2, 128}; cuuint32_t b[3] = {64, 32, 2}; make_map(enc, &tm.f0, w1, 3, d, s, b, S128); }
    { cuuint64_t d[3] = {32, DM, FF / 32}, s[2] = {FF * 2, 64}; cuuint32_t b[3] = {32, 32, 3}; make_map(enc, &tm.f1, w1, 3, d, s, b, S64); }
    { cuuint64_t d[2] = {FF, SEQ}, s[1] = {FF * 2}; cuuint32_t b[2] = {64, 64}; make_map(enc, &tm.h, pH, 2, d, s, b, S128); }
    { cuuint64_t d[5] = {DM, 2, 4, 4, FF / 32}, s[4] = {1024, 8 * 1024, 2 * 1024, 32 * 1024}; cuuint32_t b[5] = {64, 2, 4, 4, 2};
      make_map(enc, &tm.w2, w2, 5, d, s, b, S128); }
    { cuuint64_t d[2] = {DM, DM}, s[1] = {DM * 2}; cuuint32_t b[2] = {64, 64}; make_map(enc, &tm.wo, wo, 2, d, s, b, S128); }

    cudaFuncSetAttribute(fused_kernel, cudaFuncAttributeMaxDynamicSharedMemorySize, SMEM_BYTES);
    fused_kernel<<<128, 640, SMEM_BYTES, cudaStreamPerThread>>>(tm, x, wqkv, wo, w1, b1, w2, b2, gate, (__nv_bfloat16*)d_out);
}
```

```cpp
#include <cuda_runtime.h>
#include <cuda_bf16.h>
#include <cuda_fp16.h>
#include <cuda.h>
#include <stdint.h>

#define SEQ 2048
#define DM 512
#define FF 1792
#define NH 32

__device__ __align__(1024) uint8_t gQ[NH * SEQ * 32];
__device__ __align__(1024) uint8_t gKV[NH * SEQ * 64];
__device__ __align__(1024) __nv_bfloat16 gH[SEQ * FF];
__device__ __align__(1024) uint4 gO[32 * NH * 128];
__device__ float gN[3 * 8 * 128];
__device__ unsigned int gCntQ[8 * 32];
__device__ unsigned int gCntH[32 * 32];
__device__ unsigned int gEpoch[128];

__device__ __forceinline__ uint32_t smem_u32(const void* p) { return (uint32_t)__cvta_generic_to_shared(p); }
__device__ __forceinline__ void mbar_init(uint32_t a, uint32_t c) { asm volatile("mbarrier.init.shared::cta.b64 [%0], %1;" ::"r"(a), "r"(c)); }
__device__ __forceinline__ void mbar_expect(uint32_t a, uint32_t b) { asm volatile("mbarrier.arrive.expect_tx.shared::cta.b64 _, [%0], %1;" ::"r"(a), "r"(b) : "memory"); }
__device__ __forceinline__ void mbar_arrive(uint32_t a) { asm volatile("mbarrier.arrive.shared::cta.b64 _, [%0];" ::"r"(a) : "memory"); }
__device__ __forceinline__ void mbar_wait(uint32_t a, uint32_t ph) {
    asm volatile("{\n.reg .pred p;\n.reg .u32 n;\nmov.u32 n, 0;\nW_%=:\nmbarrier.try_wait.parity.shared::cta.b64 p, [%0], %1;\n@p bra D_%=;\n"
                 "add.u32 n, n, 1;\nsetp.lt.u32 p, n, 0x400000;\n@p bra W_%=;\ntrap;\nD_%=:\n}" ::"r"(a), "r"(ph) : "memory");
}
__device__ __forceinline__ void mbar_arrive_cluster(uint32_t a, uint32_t cta) {
    asm volatile("{\n.reg .b32 r;\nmapa.shared::cluster.u32 r, %0, %1;\nmbarrier.arrive.shared::cluster.b64 _, [r];\n}" ::"r"(a), "r"(cta) : "memory");
}
__device__ __forceinline__ void bar_sync(int id, int n) { asm volatile("bar.sync %0, %1;" ::"r"(id), "r"(n) : "memory"); }
__device__ __forceinline__ void bar_arrive(int id, int n) { asm volatile("bar.arrive %0, %1;" ::"r"(id), "r"(n) : "memory"); }
__device__ __forceinline__ uint32_t cluster_rank() { uint32_t r; asm("mov.u32 %0, %%cluster_ctarank;" : "=r"(r)); return r; }
__device__ __forceinline__ void cnt_add(unsigned int* c) { asm volatile("red.release.gpu.global.add.u32 [%0], 1;" ::"l"(c) : "memory"); }
__device__ __forceinline__ void cnt_wait(const unsigned int* c, uint32_t target) {
    uint32_t v;
    int spins = 0;
    while (true) {
        asm volatile("ld.acquire.gpu.global.u32 %0, [%1];" : "=r"(v) : "l"(c) : "memory");
        if ((int)(v - target) >= 0) break;
        if (++spins > (1 << 22)) __trap();
        __nanosleep(40);
    }
}
__device__ __forceinline__ void tma2d(uint32_t dst, const CUtensorMap* m, int c0, int c1, uint32_t bar) {
    asm volatile("cp.async.bulk.tensor.2d.shared::cluster.global.mbarrier::complete_tx::bytes [%0], [%1, {%3, %4}], [%2];"
                 ::"r"(dst), "l"(m), "r"(bar), "r"(c0), "r"(c1) : "memory");
}
__device__ __forceinline__ void tma2d_mc(uint32_t dst, const CUtensorMap* m, int c0, int c1, uint32_t bar) {
    asm volatile("cp.async.bulk.tensor.2d.shared::cluster.global.mbarrier::complete_tx::bytes.multicast::cluster [%0], [%1, {%3, %4}], [%2], %5;"
                 ::"r"(dst), "l"(m), "r"(bar), "r"(c0), "r"(c1), "h"((uint16_t)3) : "memory");
}
__device__ __forceinline__ void tma3d_mc(uint32_t dst, const CUtensorMap* m, int c0, int c1, int c2, uint32_t bar) {
    asm volatile("cp.async.bulk.tensor.3d.shared::cluster.global.mbarrier::complete_tx::bytes.multicast::cluster [%0], [%1, {%3, %4, %5}], [%2], %6;"
                 ::"r"(dst), "l"(m), "r"(bar), "r"(c0), "r"(c1), "r"(c2), "h"((uint16_t)3) : "memory");
}
__device__ __forceinline__ void tma5d_mc(uint32_t dst, const CUtensorMap* m, int c0, int c4, uint32_t bar) {
    asm volatile("cp.async.bulk.tensor.5d.shared::cluster.global.mbarrier::complete_tx::bytes.multicast::cluster [%0], [%1, {%3, %5, %5, %5, %4}], [%2], %6;"
                 ::"r"(dst), "l"(m), "r"(bar), "r"(c0), "r"(c4), "r"(0), "h"((uint16_t)3) : "memory");
}
__device__ __forceinline__ void bulk_mc(uint32_t dst, const void* src, uint32_t bytes, uint32_t bar) {
    asm volatile("cp.async.bulk.shared::cluster.global.mbarrier::complete_tx::bytes.multicast::cluster [%0], [%1], %2, [%3], %4;"
                 ::"r"(dst), "l"(src), "r"(bytes), "r"(bar), "h"((uint16_t)3) : "memory");
}
__device__ __forceinline__ void l2_prefetch(const void* src, uint32_t bytes) {
    asm volatile("cp.async.bulk.prefetch.L2.global [%0], %1;" ::"l"(src), "r"(bytes) : "memory");
}
__device__ __forceinline__ void map_prefetch(const CUtensorMap* m) { asm volatile("prefetch.tensormap [%0];" ::"l"(m) : "memory"); }
__device__ __forceinline__ void wg_fence() { asm volatile("wgmma.fence.sync.aligned;" ::: "memory"); }
__device__ __forceinline__ void wg_commit() { asm volatile("wgmma.commit_group.sync.aligned;" ::: "memory"); }
template <int N> __device__ __forceinline__ void wg_wait() { asm volatile("wgmma.wait_group.sync.aligned %0;" ::"n"(N) : "memory"); }
template <int N> __device__ __forceinline__ void pin(float* s) {
#pragma unroll
    for (int i = 0; i < N; i++) asm volatile("" : "+f"(s[i])::"memory");
}
template <int N> __device__ __forceinline__ void pin(uint32_t* s) {
#pragma unroll
    for (int i = 0; i < N; i++) asm volatile("" : "+r"(s[i])::"memory");
}
__device__ __forceinline__ uint64_t mkdesc(uint32_t addr, uint32_t lbo, uint32_t sbo, uint32_t swz) {
    return (uint64_t)((addr & 0x3FFFF) >> 4) | ((uint64_t)(lbo >> 4) << 16) | ((uint64_t)(sbo >> 4) << 32) | ((uint64_t)swz << 62);
}
__device__ __forceinline__ float ex2f(float x) { float y; asm("ex2.approx.ftz.f32 %0, %1;" : "=f"(y) : "f"(x)); return y; }
__device__ __forceinline__ float tanhf_(float x) { float y; asm("tanh.approx.f32 %0, %1;" : "=f"(y) : "f"(x)); return y; }
__device__ __forceinline__ uint32_t pk_bf16(float lo, float hi) { uint32_t r; asm("cvt.rn.bf16x2.f32 %0, %1, %2;" : "=r"(r) : "f"(hi), "f"(lo)); return r; }
__device__ __forceinline__ uint32_t pk_f16(float lo, float hi) { uint32_t r; asm("cvt.rn.f16x2.f32 %0, %1, %2;" : "=r"(r) : "f"(hi), "f"(lo)); return r; }
__device__ __forceinline__ float bf_lo(uint32_t v) { return __uint_as_float(v << 16); }
__device__ __forceinline__ float bf_hi(uint32_t v) { return __uint_as_float(v & 0xffff0000u); }
__device__ __forceinline__ float ldcg_f(const float* p) { return __ldcg(p); }

#define TLM(k, slot) do {} while (0)
#define TLC(k, slot) do {} while (0)

__device__ __forceinline__ void wgmma_ss_n128(float* d, uint64_t da, uint64_t db) {
    asm volatile("wgmma.mma_async.sync.aligned.m64n128k16.f32.bf16.bf16 {"
        "%0, %1, %2, %3, %4, %5, %6, %7, %8, %9, %10, %11, %12, %13, %14, %15,"
        "%16, %17, %18, %19, %20, %21, %22, %23, %24, %25, %26, %27, %28, %29, %30, %31,"
        "%32, %33, %34, %35, %36, %37, %38, %39, %40, %41, %42, %43, %44, %45, %46, %47,"
        "%48, %49, %50, %51, %52, %53, %54, %55, %56, %57, %58, %59, %60, %61, %62, %63}, %64, %65, 1, 1, 1, 0, 1;\n"
        :
        "+f"(d[0]), "+f"(d[1]), "+f"(d[2]), "+f"(d[3]), "+f"(d[4]), "+f"(d[5]), "+f"(d[6]), "+f"(d[7]),
        "+f"(d[8]), "+f"(d[9]), "+f"(d[10]), "+f"(d[11]), "+f"(d[12]), "+f"(d[13]), "+f"(d[14]), "+f"(d[15]),
        "+f"(d[16]), "+f"(d[17]), "+f"(d[18]), "+f"(d[19]), "+f"(d[20]), "+f"(d[21]), "+f"(d[22]), "+f"(d[23]),
        "+f"(d[24]), "+f"(d[25]), "+f"(d[26]), "+f"(d[27]), "+f"(d[28]), "+f"(d[29]), "+f"(d[30]), "+f"(d[31]),
        "+f"(d[32]), "+f"(d[33]), "+f"(d[34]), "+f"(d[35]), "+f"(d[36]), "+f"(d[37]), "+f"(d[38]), "+f"(d[39]),
        "+f"(d[40]), "+f"(d[41]), "+f"(d[42]), "+f"(d[43]), "+f"(d[44]), "+f"(d[45]), "+f"(d[46]), "+f"(d[47]),
        "+f"(d[48]), "+f"(d[49]), "+f"(d[50]), "+f"(d[51]), "+f"(d[52]), "+f"(d[53]), "+f"(d[54]), "+f"(d[55]),
        "+f"(d[56]), "+f"(d[57]), "+f"(d[58]), "+f"(d[59]), "+f"(d[60]), "+f"(d[61]), "+f"(d[62]), "+f"(d[63])
        : "l"(da), "l"(db));
}
__device__ __forceinline__ void wgmma_ss_n96(float* d, uint64_t da, uint64_t db) {
    asm volatile("wgmma.mma_async.sync.aligned.m64n96k16.f32.bf16.bf16 {"
        "%0, %1, %2, %3, %4, %5, %6, %7, %8, %9, %10, %11, %12, %13, %14, %15,"
        "%16, %17, %18, %19, %20, %21, %22, %23, %24, %25, %26, %27, %28, %29, %30, %31,"
        "%32, %33, %34, %35, %36, %37, %38, %39, %40, %41, %42, %43, %44, %45, %46, %47}, %48, %49, 1, 1, 1, 0, 1;\n"
        :
        "+f"(d[0]), "+f"(d[1]), "+f"(d[2]), "+f"(d[3]), "+f"(d[4]), "+f"(d[5]), "+f"(d[6]), "+f"(d[7]),
        "+f"(d[8]), "+f"(d[9]), "+f"(d[10]), "+f"(d[11]), "+f"(d[12]), "+f"(d[13]), "+f"(d[14]), "+f"(d[15]),
        "+f"(d[16]), "+f"(d[17]), "+f"(d[18]), "+f"(d[19]), "+f"(d[20]), "+f"(d[21]), "+f"(d[22]), "+f"(d[23]),
        "+f"(d[24]), "+f"(d[25]), "+f"(d[26]), "+f"(d[27]), "+f"(d[28]), "+f"(d[29]), "+f"(d[30]), "+f"(d[31]),
        "+f"(d[32]), "+f"(d[33]), "+f"(d[34]), "+f"(d[35]), "+f"(d[36]), "+f"(d[37]), "+f"(d[38]), "+f"(d[39]),
        "+f"(d[40]), "+f"(d[41]), "+f"(d[42]), "+f"(d[43]), "+f"(d[44]), "+f"(d[45]), "+f"(d[46]), "+f"(d[47])
        : "l"(da), "l"(db));
}
__device__ __forceinline__ void wgmma_ss_n64(float* d, uint64_t da, uint64_t db) {
    asm volatile("wgmma.mma_async.sync.aligned.m64n64k16.f32.bf16.bf16 {"
        "%0, %1, %2, %3, %4, %5, %6, %7, %8, %9, %10, %11, %12, %13, %14, %15,"
        "%16, %17, %18, %19, %20, %21, %22, %23, %24, %25, %26, %27, %28, %29, %30, %31}, %32, %33, 1, 1, 1, 0, 1;\n"
        :
        "+f"(d[0]), "+f"(d[1]), "+f"(d[2]), "+f"(d[3]), "+f"(d[4]), "+f"(d[5]), "+f"(d[6]), "+f"(d[7]),
        "+f"(d[8]), "+f"(d[9]), "+f"(d[10]), "+f"(d[11]), "+f"(d[12]), "+f"(d[13]), "+f"(d[14]), "+f"(d[15]),
        "+f"(d[16]), "+f"(d[17]), "+f"(d[18]), "+f"(d[19]), "+f"(d[20]), "+f"(d[21]), "+f"(d[22]), "+f"(d[23]),
        "+f"(d[24]), "+f"(d[25]), "+f"(d[26]), "+f"(d[27]), "+f"(d[28]), "+f"(d[29]), "+f"(d[30]), "+f"(d[31])
        : "l"(da), "l"(db));
}
__device__ __forceinline__ void wgmma_qk_f16_acc(float* d, const uint32_t* a, uint64_t db) {
    asm volatile("wgmma.mma_async.sync.aligned.m64n64k16.f32.f16.f16 {"
        "%0, %1, %2, %3, %4, %5, %6, %7, %8, %9, %10, %11, %12, %13, %14, %15,"
        "%16, %17, %18, %19, %20, %21, %22, %23, %24, %25, %26, %27, %28, %29, %30, %31}, {%32, %33, %34, %35}, %36, 1, 1, 1, 0;\n"
        :
        "+f"(d[0]), "+f"(d[1]), "+f"(d[2]), "+f"(d[3]), "+f"(d[4]), "+f"(d[5]), "+f"(d[6]), "+f"(d[7]),
        "+f"(d[8]), "+f"(d[9]), "+f"(d[10]), "+f"(d[11]), "+f"(d[12]), "+f"(d[13]), "+f"(d[14]), "+f"(d[15]),
        "+f"(d[16]), "+f"(d[17]), "+f"(d[18]), "+f"(d[19]), "+f"(d[20]), "+f"(d[21]), "+f"(d[22]), "+f"(d[23]),
        "+f"(d[24]), "+f"(d[25]), "+f"(d[26]), "+f"(d[27]), "+f"(d[28]), "+f"(d[29]), "+f"(d[30]), "+f"(d[31])
        : "r"(a[0]), "r"(a[1]), "r"(a[2]), "r"(a[3]), "l"(db));
}
__device__ __forceinline__ void wgmma_qk_bf16_zero(float* d, const uint32_t* a, uint64_t db) {
    asm volatile("wgmma.mma_async.sync.aligned.m64n64k16.f32.bf16.bf16 {"
        "%0, %1, %2, %3, %4, %5, %6, %7, %8, %9, %10, %11, %12, %13, %14, %15,"
        "%16, %17, %18, %19, %20, %21, %22, %23, %24, %25, %26, %27, %28, %29, %30, %31}, {%32, %33, %34, %35}, %36, 0, 1, 1, 0;\n"
        :
        "=f"(d[0]), "=f"(d[1]), "=f"(d[2]), "=f"(d[3]), "=f"(d[4]), "=f"(d[5]), "=f"(d[6]), "=f"(d[7]),
        "=f"(d[8]), "=f"(d[9]), "=f"(d[10]), "=f"(d[11]), "=f"(d[12]), "=f"(d[13]), "=f"(d[14]), "=f"(d[15]),
        "=f"(d[16]), "=f"(d[17]), "=f"(d[18]), "=f"(d[19]), "=f"(d[20]), "=f"(d[21]), "=f"(d[22]), "=f"(d[23]),
        "=f"(d[24]), "=f"(d[25]), "=f"(d[26]), "=f"(d[27]), "=f"(d[28]), "=f"(d[29]), "=f"(d[30]), "=f"(d[31])
        : "r"(a[0]), "r"(a[1]), "r"(a[2]), "r"(a[3]), "l"(db));
}
__device__ __forceinline__ void wgmma_pv(float* d, const uint32_t* a, uint64_t db) {
    asm volatile("wgmma.mma_async.sync.aligned.m64n24k16.f32.bf16.bf16 {"
        "%0, %1, %2, %3, %4, %5, %6, %7, %8, %9, %10, %11}, {%12, %13, %14, %15}, %16, 1, 1, 1, 1;\n"
        :
        "+f"(d[0]), "+f"(d[1]), "+f"(d[2]), "+f"(d[3]), "+f"(d[4]), "+f"(d[5]), "+f"(d[6]), "+f"(d[7]),
        "+f"(d[8]), "+f"(d[9]), "+f"(d[10]), "+f"(d[11])
        : "r"(a[0]), "r"(a[1]), "r"(a[2]), "r"(a[3]), "l"(db));
}

template <int N> __device__ __forceinline__ void wgmma_ss(float* d, uint64_t a, uint64_t b) {
    if (N == 128) wgmma_ss_n128(d, a, b);
    if (N == 96) wgmma_ss_n96(d, a, b);
    if (N == 64) wgmma_ss_n64(d, a, b);
}

#define OFF_R 131072
#define OFF_ONE 229376
#define OFF_BAR 229888
#define OFF_BIAS (OFF_BAR + 512)
#define OFF_G (OFF_BIAS + 768)
#define SMEM_BYTES (OFF_G + 272)
#define SBD 1024u
#define B_X 0
#define B_F1 64
#define B_E1 112
#define B_KV 160
#define B_F2 224
#define B_E2 256
#define B_T 288
#define B_DONE 352
#define B_G 360
#define B_G2 368

#define PF 1
#define EXP_FKK 4
#define QSCALE 0.36067376022224085f
#define MAGIC 445.41763f
#define NMUFU 4
#define VSTEP ((uint64_t)((long long)32 - ((long long)32 << 16)))

__host__ __device__ constexpr int strm_pos(int pass, int i) {
    return pass == 0 ? i + (i >> 1) : pass == 1 ? (i < 4 ? 3 * i + 2 : 8 + i) : pass == 2 ? 16 + i : 20 + i;
}
__host__ __device__ constexpr int strm_pass(int p) { return p < 12 ? (p % 3 == 2 ? 1 : 0) : p < 16 ? 1 : p < 20 ? 2 : 3; }
__host__ __device__ constexpr int strm_idx(int p) { return p < 12 ? (p % 3 == 2 ? p / 3 : p - p / 3) : p < 16 ? p - 8 : p < 20 ? p - 16 : p - 20; }

template <int N, int PASS, int NST, int KK, int SUB, int KST, int LBO, int SBO, int SWZ, bool WAITX>
__device__ __forceinline__ void gemm_pass(float* acc, uint32_t bar, uint64_t dA0, int lane, int barNext) {
    if (WAITX) mbar_wait(bar + B_X, 0);
    mbar_wait(bar + B_F1 + 8 * (strm_pos(PASS, 0) % 6), (strm_pos(PASS, 0) / 6) & 1);
#pragma unroll
    for (int i = 0; i < NST; i++) {
        const int it = strm_pos(PASS, i);
        const uint64_t dA = dA0 + i * (KK / 4 * 1024);
        const uint64_t dB = mkdesc(SBD + OFF_R + (it % 6) * 16384, LBO, SBO, SWZ);
        wg_fence();
#pragma unroll
        for (int kk = 0; kk < KK / 2; kk++) wgmma_ss<N>(acc, dA + (kk >> 2) * 1024 + (kk & 3) * 2, dB + kk * KST / 16);
        wg_commit();
        if (i > 0) {
            wg_wait<1>();
            if (lane < 2) mbar_arrive_cluster(bar + B_E1 + 8 * (strm_pos(PASS, i - 1) % 6), lane);
        }
#pragma unroll
        for (int kk = KK / 2; kk < KK; kk++) wgmma_ss<N>(acc, dA + (kk >> 2) * 1024 + (kk & 3) * 2, dB + (SUB + (kk - KK / 2) * KST) / 16);
        wg_commit();
        if (i + 1 < NST) {
            if (WAITX) mbar_wait(bar + B_X + 8 * (i + 1), 0);
            mbar_wait(bar + B_F1 + 8 * (strm_pos(PASS, i + 1) % 6), (strm_pos(PASS, i + 1) / 6) & 1);
        }
    }
    if (barNext) bar_arrive(barNext, 512);
    wg_wait<0>();
    if (lane < 2) mbar_arrive_cluster(bar + B_E1 + 8 * (strm_pos(PASS, NST - 1) % 6), lane);
    pin<N / 2>(acc);
}

__device__ __forceinline__ uint32_t lds32(uint32_t a) { uint32_t v; asm volatile("ld.shared.u32 %0, [%1];" : "=r"(v) : "r"(a)); return v; }
__device__ __forceinline__ bool elect() {
    uint32_t p;
    asm volatile("{\n.reg .pred p;\nelect.sync _|p, 0xffffffff;\nselp.u32 %0, 1, 0, p;\n}" : "=r"(p));
    return p;
}

template <int N> __device__ __forceinline__ void bias_init(float* acc, uint32_t b) {
#pragma unroll
    for (int j = 0; j < N / 8; j++) {
        const uint32_t bv = lds32(b + j * 16);
        acc[4 * j] = acc[4 * j + 2] = bf_lo(bv);
        acc[4 * j + 1] = acc[4 * j + 3] = bf_hi(bv);
    }
    pin<N / 2>(acc);
}

template <int G0, int G1> __device__ __forceinline__ void gelu_store(const float* acc, __nv_bfloat16* hp) {
#pragma unroll
    for (int G = G0; G < G1; G++) {
        uint32_t o[8];
#pragma unroll
        for (int j = 0; j < 4; j++) {
            float y[4];
#pragma unroll
            for (int i = 0; i < 4; i++) {
                const float h = acc[16 * G + 4 * j + i];
                const float z = h * fmaf(h * h, 0.035677408136300125f, 0.7978845608028654f);
                const float hh = 0.5f * h;
                y[i] = fmaf(hh, tanhf_(z), hh);
            }
            o[j] = pk_bf16(y[0], y[1]);
            o[4 + j] = pk_bf16(y[2], y[3]);
        }
        *(uint4*)(hp + G * 32) = make_uint4(o[0], o[1], o[2], o[3]);
        *(uint4*)(hp + 8 * FF + G * 32) = make_uint4(o[4], o[5], o[6], o[7]);
    }
}

__device__ __forceinline__ float norm_bound(const float* v, float sc) {
    uint32_t m = 0;
#pragma unroll
    for (int h = 0; h < 4; h++) {
        const float* u = v + 8 * h;
        m = max(m, __float_as_uint(fmaf(u[0], u[0], fmaf(u[1], u[1], fmaf(u[4], u[4], u[5] * u[5])))));
        m = max(m, __float_as_uint(fmaf(u[2], u[2], fmaf(u[3], u[3], fmaf(u[6], u[6], u[7] * u[7])))));
    }
#pragma unroll
    for (int o = 4; o < 32; o <<= 1) m = max(m, __shfl_xor_sync(0xffffffffu, m, o));
    float f = __uint_as_float(m);
    f += __shfl_xor_sync(0xffffffffu, f, 1);
    f += __shfl_xor_sync(0xffffffffu, f, 2);
    return f * sc;
}

__device__ __forceinline__ uint32_t exp2_pair(float a, float b) {
    const uint32_t w = __byte_perm(__float_as_uint(a), __float_as_uint(b), 0x6521);
    uint32_t m, r;
    asm("lop3.b32 %0, %1, 0x007f007f, 0x9f809f80, 0xEA;" : "=r"(m) : "r"(w));
    const uint32_t e = w - m;
    asm("fma.rn.bf16x2 %0, %1, %2, %3;" : "=r"(r) : "r"(w), "r"(m), "r"(e));
    return r;
}

__device__ __forceinline__ void store_o(const float* o, uint4* dst, uint32_t par) {
    const float s0 = __fdividef(1.f, o[8]), s1 = __fdividef(1.f, o[10]);
    const uint32_t d0 = (pk_bf16(o[0] * s0, o[1] * s0) & ~1u) | par;
    asm volatile("{\n.reg .b128 t;\nmov.b128 t, {%0, %1, %2, %3};\nst.relaxed.gpu.global.b128 [%4], t;\n}" ::"r"(d0),
                 "r"(pk_bf16(o[4] * s0, o[5] * s0)), "r"(pk_bf16(o[2] * s1, o[3] * s1)), "r"(pk_bf16(o[6] * s1, o[7] * s1)), "l"(dst) : "memory");
}
__device__ __forceinline__ uint4 load_o(const uint4* src) {
    uint4 v;
    asm volatile("{\n.reg .b128 t;\nld.relaxed.gpu.global.b128 t, [%4];\nmov.b128 {%0, %1, %2, %3}, t;\n}"
                 : "=r"(v.x), "=r"(v.y), "=r"(v.z), "=r"(v.w) : "l"(src) : "memory");
    return v;
}
__device__ __forceinline__ uint32_t bmul2(uint32_t a, uint32_t b) { uint32_t r; asm("mul.rn.bf16x2 %0, %1, %2;" : "=r"(r) : "r"(a), "r"(b)); return r; }
__device__ __forceinline__ void sts32(uint32_t a, uint32_t v) { asm volatile("st.shared.u32 [%0], %1;" ::"r"(a), "r"(v) : "memory"); }
__device__ __forceinline__ void load_q(uint32_t* q, int h, int row, int t) {
    const uint8_t* p = gQ + (size_t)h * (SEQ * 32) + (size_t)row * 32 + t * 4;
    q[0] = __ldcg((const uint32_t*)p); q[1] = __ldcg((const uint32_t*)(p + 256));
    q[2] = __ldcg((const uint32_t*)(p + 16)); q[3] = __ldcg((const uint32_t*)(p + 272));
}

template <int NT>
__device__ __forceinline__ void proj16(float (*c)[8], const __nv_bfloat16* x, const __nv_bfloat16* w, int row0, int rstep, int col, int g, int t) {
#pragma unroll
    for (int i = 0; i < NT; i++)
#pragma unroll
        for (int j = 0; j < 8; j++) c[i][j] = 0.f;
    const unsigned short* wu = (const unsigned short*)w;
#pragma unroll 1
    for (int k = 0; k < DM; k += 16) {
        uint32_t b[4];
#pragma unroll
        for (int j = 0; j < 4; j++) {
            const int kr = k + 2 * t + (j & 1) * 8, cc = col + g + (j >> 1) * 8;
            b[j] = (uint32_t)wu[(size_t)kr * (3 * DM) + cc] | ((uint32_t)wu[(size_t)(kr + 1) * (3 * DM) + cc] << 16);
        }
#pragma unroll
        for (int i = 0; i < NT; i++) {
            const __nv_bfloat16* xp = x + (size_t)(row0 + i * rstep + g) * DM + k + 2 * t;
            const uint32_t a0 = *(const uint32_t*)xp, a1 = *(const uint32_t*)(xp + 8 * DM);
            const uint32_t a2 = *(const uint32_t*)(xp + 8), a3 = *(const uint32_t*)(xp + 8 * DM + 8);
#pragma unroll
            for (int j = 0; j < 2; j++)
                asm volatile("mma.sync.aligned.m16n8k16.row.col.f32.bf16.bf16.f32 {%0,%1,%2,%3}, {%4,%5,%6,%7}, {%8,%9}, {%0,%1,%2,%3};"
                             : "+f"(c[i][4 * j]), "+f"(c[i][4 * j + 1]), "+f"(c[i][4 * j + 2]), "+f"(c[i][4 * j + 3])
                             : "r"(a0), "r"(a1), "r"(a2), "r"(a3), "r"(b[2 * j]), "r"(b[2 * j + 1]));
        }
    }
}

struct Maps { CUtensorMap x, kv, q, f0, f1, h, w2, wo; };

__global__ void __cluster_dims__(2, 1, 1) __launch_bounds__(640, 1)
fused_kernel(const __grid_constant__ Maps tm, const __nv_bfloat16* __restrict__ x, const __nv_bfloat16* __restrict__ wqkv,
             const __nv_bfloat16* __restrict__ wo, const __nv_bfloat16* __restrict__ w1, const __nv_bfloat16* __restrict__ b1,
             const __nv_bfloat16* __restrict__ w2, const __nv_bfloat16* __restrict__ b2, const __nv_bfloat16* __restrict__ gate,
             __nv_bfloat16* __restrict__ out) {
    extern __shared__ __align__(1024) uint8_t smem_raw[];
    const uint32_t sb = smem_u32(smem_raw);
    const uint32_t bar = sb + OFF_BAR;
    const int tid = threadIdx.x, lane = tid & 31;
    const int warp = __shfl_sync(0xffffffffu, tid >> 5, 0);
    const uint32_t rank = cluster_rank();
    const int cl = blockIdx.x >> 1;
    const int nb = cl & 7, mb = (cl >> 3) * 2 + rank;
    const int g = lane >> 2, t = lane & 3;

    const int cb = nb & 3, rb = mb * 2 + (nb >> 2);
    if (tid == 0) TLM(0, 0);
    if (tid == 512) {
        mbar_init(bar + B_X, 1);
        asm volatile("fence.proxy.async.shared::cta;" ::: "memory");
        mbar_expect(bar + B_X, 16384);
        tma2d(sb, &tm.x, 0, mb * 128, bar + B_X);
        for (int i = 0; i < 8; i++) { if (i) mbar_init(bar + B_X + 8 * i, 1); mbar_init(bar + B_KV + 8 * i, 1); mbar_init(bar + B_T + 8 * i, 5); }
        for (int i = 0; i < 6; i++) { mbar_init(bar + B_F1 + 8 * i, 1); mbar_init(bar + B_E1 + 8 * i, 16); }
        for (int i = 0; i < 4; i++) { mbar_init(bar + B_F2 + 8 * i, 1); mbar_init(bar + B_E2 + 8 * i, 8); }
        mbar_init(bar + B_DONE, 16);
        mbar_init(bar + B_G, 1);
        mbar_init(bar + B_G2, 2);
        asm volatile("fence.mbarrier_init.release.cluster;" ::: "memory");
    } else if (tid == 544) {
        map_prefetch(&tm.kv); map_prefetch(&tm.f0);
        l2_prefetch((const uint8_t*)wqkv + (size_t)blockIdx.x * 3072 + 1024, 2048);
        l2_prefetch((const uint8_t*)w1 + (size_t)blockIdx.x * 1792, 1792);
        map_prefetch(&tm.q); map_prefetch(&tm.f1);
    } else if (tid < 128) {
        asm volatile("st.shared.u32 [%0], %1;" ::"r"(sb + OFF_ONE + tid * 4), "r"(0x3f803f80u) : "memory");
        asm volatile("fence.proxy.async.shared::cta;" ::: "memory");
    }
    if ((sb & 0xFFFFFF) != SBD) __trap();
    __syncthreads();
    asm volatile("barrier.cluster.arrive.relaxed.aligned;\nbarrier.cluster.wait.aligned;" ::: "memory");
    const uint32_t ep = gEpoch[blockIdx.x] + 1;
    if (tid == 0) { TLM(0, 1); TLC(0, 30); }

    if (warp < 16) {
        const int wg = warp >> 2;
        const int h = cl >> 1, qd = (cl & 1) * 2 + rank;
        uint32_t q[4];
        {
            const int w8 = warp & 7;
            const int T = mb * 8 + w8, row0 = T * 16 + g;
            const uint64_t dA0 = mkdesc(SBD + (wg & 1) * 8192, 16, 1024, 1);
            if (wg < 2) {
                {
                    float acc[64];
#pragma unroll
                    for (int i = 0; i < 64; i++) acc[i] = 0.f;
                    gemm_pass<128, 0, 8, 4, 8192, 2048, 4096, 1024, 1, true>(acc, bar, dA0, lane, 0);
                    if (tid == 0) TLM(0, 2);
                    const int pos = ((T >> 6) * 16 + 2 * g) * 64 + (T & 63);
                    uint8_t* kp = gKV + (size_t)(nb * 4) * (SEQ * 64) + (pos >> 8) * 16384 + (pos & 255) * 32 + ((t * 8) ^ (((T >> 2) & 1) << 4));
                    float vm = 0.f;
#pragma unroll
                    for (int h = 0; h < 4; h++) {
                        const float* v = acc + 8 * h;
                        float p0 = __shfl_up_sync(0xffffffffu, v[2], 4), p1 = __shfl_up_sync(0xffffffffu, v[3], 4);
                        float p2 = __shfl_up_sync(0xffffffffu, v[6], 4), p3 = __shfl_up_sync(0xffffffffu, v[7], 4);
                        if (g == 0) { p0 = p1 = p2 = p3 = 0.f; }
                        uint8_t* o = kp + (size_t)h * (SEQ * 64);
                        *(uint2*)o = make_uint2(pk_f16(v[0] - p0, v[1] - p1), pk_f16(v[4] - p2, v[5] - p3));
                        *(uint2*)(o + 2048) = make_uint2(pk_f16(v[2] - v[0], v[3] - v[1]), pk_f16(v[6] - v[4], v[7] - v[5]));
                        const float* u = acc + 32 + 8 * h;
#pragma unroll
                        for (int i = 0; i < 8; i++) vm = fmaxf(vm, fabsf(u[i]));
                        *(uint2*)(o + 8192) = make_uint2(pk_bf16(u[0], u[1]), pk_bf16(u[4], u[5]));
                        *(uint2*)(o + 8192 + 2048) = make_uint2(pk_bf16(u[2], u[3]), pk_bf16(u[6], u[7]));
                    }
                    const float km = norm_bound(acc, 1.f);
                    vm = __uint_as_float(__reduce_max_sync(0xffffffffu, __float_as_uint(vm)));
                    if (lane == 0) { gN[1024 + nb * 128 + T] = km; gN[2048 + nb * 128 + T] = vm; }
                    if (tid == 0) TLM(0, 3);
                }
                {
                    float acc[32];
#pragma unroll
                    for (int i = 0; i < 32; i++) acc[i] = 0.f;
                    bar_sync(6, 512);
                    gemm_pass<64, 2, 4, 8, 8192, 2048, 16, 1024, 1, false>(acc, bar, dA0, lane, 7);
                    if (tid == 0) TLM(0, 4);
                    uint8_t* qp = gQ + (size_t)(nb * 4) * (SEQ * 32) + (size_t)row0 * 32 + t * 8;
#pragma unroll
                    for (int h = 0; h < 4; h++) {
                        const float* v = acc + 8 * h;
                        uint8_t* o = qp + (size_t)h * (SEQ * 32);
                        *(uint2*)o = make_uint2(pk_f16(v[0] * QSCALE, v[1] * QSCALE), pk_f16(v[4] * QSCALE, v[5] * QSCALE));
                        *(uint2*)(o + 256) = make_uint2(pk_f16(v[2] * QSCALE, v[3] * QSCALE), pk_f16(v[6] * QSCALE, v[7] * QSCALE));
                    }
                    const float qm = norm_bound(acc, QSCALE * QSCALE);
                    if (lane == 0) gN[nb * 128 + T] = qm;
                    bar_arrive(10, 288);
                    if (tid == 0) TLM(0, 5);
                    mbar_wait(bar + B_G, 0);
                    load_q(q, h, qd * 512 + warp * 16 + g, t);
                }
            } else {
                if (tid < 256 + 176) {
                    const int i = tid - 256;
                    const uint32_t v = i < 112 ? *(const uint32_t*)(b1 + nb * 224 + i * 2) : *(const uint32_t*)(b2 + cb * 128 + (i - 112) * 2);
                    asm volatile("st.shared.u32 [%0], %1;" ::"r"(sb + OFF_BIAS + i * 4), "r"(v) : "memory");
                }
                bar_sync(5, 256);
                {
                    float acc[64];
                    bias_init<128>(acc, sb + OFF_BIAS + t * 4);
                    gemm_pass<128, 1, 8, 4, 8192, 2048, 4096, 1024, 1, true>(acc, bar, dA0, lane, 6);
                    if (tid == 256) TLM(0, 6);
                    gelu_store<0, 4>(acc, gH + (size_t)row0 * FF + nb * 224 + t * 8);
                }
                {
                    float acc[48];
                    bias_init<96>(acc, sb + OFF_BIAS + 256 + t * 4);
                    if (tid == 256) TLM(0, 7);
                    mbar_wait(bar + B_G2, 0);
                    bar_sync(7, 512);
                    gemm_pass<96, 3, 8, 4, 6144, 1024, 2048, 512, 2, false>(acc, bar, dA0, lane, 0);
                    if (tid == 256) TLM(0, 8);
                    gelu_store<0, 1>(acc, gH + (size_t)row0 * FF + nb * 224 + 128 + t * 8);
                    mbar_wait(bar + B_G, 0);
                    load_q(q, h, qd * 512 + warp * 16 + g, t);
                    gelu_store<1, 3>(acc, gH + (size_t)row0 * FF + nb * 224 + 128 + t * 8);
                    bar_arrive(11, 288);
                    if (tid == 256) TLM(0, 10);
                }
            }
        }
        const bool fast = lds32(sb + OFF_G + 256) != 0;
        uint4* const op = gO + ((qd * 8 + wg) * NH + h) * 128 + (tid & 127);
        const uint64_t kd0 = mkdesc(SBD, 16, 256, 3);
        const uint64_t vd0 = mkdesc(SBD + 8192, OFF_ONE - 8192, 256, 3);
        if (fast) {
#pragma unroll 1
            for (int r = 0; r < 2; r++) {
                float o[12];
#pragma unroll
                for (int i = 0; i < 12; i++) o[i] = 0.f;
                uint64_t kd = kd0, vd = vd0;
                uint32_t qn[4];
#pragma unroll 1
                for (int half = 0; half < 2; half++) {
                    float s[32];
#pragma unroll
                    for (int i = 0; i < 32; i++) s[i] = i < 2 * NMUFU ? 0.f : MAGIC;
#pragma unroll 1
                    for (int c = 0; c < 4; c++) {
                        if (r == 0) mbar_wait(bar + B_KV + 8 * (half * 4 + c), 0);
                        if ((tid & 255) == 0 && c == 0) TLM(1, (tid >> 8) * 4 + r * 2 + half);
                        if (half == 1 && c == 3) {
                            if (r == 0) load_q(qn, h, qd * 512 + 256 + warp * 16 + g, t);
                            else if (lane == 0) mbar_arrive(bar + B_DONE);
                        }
#pragma unroll 1
                        for (int j = 0; j < 4; j++) {
                            uint32_t p[16];
                            wg_fence();
                            wgmma_qk_f16_acc(s, q, kd);
                            wg_commit();
                            wg_wait<0>();
                            pin<32>(s);
#pragma unroll
                            for (int i = 0; i < 16; i++)
                                p[i] = i < NMUFU ? pk_bf16(ex2f(s[2 * i]), ex2f(s[2 * i + 1])) : exp2_pair(s[2 * i], s[2 * i + 1]);
                            pin<16>(p);
                            wg_fence();
#pragma unroll
                            for (int u = 0; u < 4; u++) wgmma_pv(o, p + 4 * u, vd + u * VSTEP);
                            wg_commit();
                            kd += 128;
                            vd += 4 * VSTEP;
                        }
                        kd += 512;
                        vd += 16 * VSTEP;
                    }
                    wg_wait<0>();
                }
                pin<12>(o);
                if ((tid & 127) == 0 && r == 1) TLM(1, 8 + wg);
                store_o(o, op + r * (4 * NH * 128), ep & 1);
#pragma unroll
                for (int i = 0; i < 4; i++) q[i] = qn[i];
            }
            if (tid == 0) { TLM(1, 12); TLC(0, 31); }
        } else {
            for (int c = 0; c < 8; c++) mbar_wait(bar + B_KV + 8 * c, 0);
            {
                float kc[8][8];
                proj16<8>(kc, x, wqkv, warp * 16, 256, DM + h * 16, g, t);
#pragma unroll
                for (int i = 0; i < 8; i++) {
                    const int T = warp + i * 16;
                    const int pos = ((T >> 6) * 16 + 2 * g) * 64 + (T & 63);
                    const uint32_t a = sb + (pos >> 8) * 16384 + (pos & 255) * 32 + t * 4, sw = ((T >> 2) & 1) << 4;
                    asm volatile("st.shared.u32 [%0], %1;" ::"r"(a + sw), "r"(pk_bf16(kc[i][0], kc[i][1])) : "memory");
                    asm volatile("st.shared.u32 [%0], %1;" ::"r"(a + (sw ^ 16)), "r"(pk_bf16(kc[i][4], kc[i][5])) : "memory");
                    asm volatile("st.shared.u32 [%0], %1;" ::"r"(a + 2048 + sw), "r"(pk_bf16(kc[i][2], kc[i][3])) : "memory");
                    asm volatile("st.shared.u32 [%0], %1;" ::"r"(a + 2048 + (sw ^ 16)), "r"(pk_bf16(kc[i][6], kc[i][7])) : "memory");
                }
                asm volatile("fence.proxy.async.shared::cta;" ::: "memory");
                bar_sync(8, 512);
            }
#pragma unroll 1
            for (int r = 0; r < 2; r++) {
                const int row = qd * 512 + r * 256 + warp * 16 + g;
                {
                    float qc[1][8];
                    proj16<1>(qc, x, wqkv, row - g, 0, h * 16, g, t);
#pragma unroll
                    for (int i = 0; i < 4; i++) q[i] = pk_bf16(qc[0][2 * i] * QSCALE, qc[0][2 * i + 1] * QSCALE);
                }
                float o[12];
#pragma unroll
                for (int i = 0; i < 12; i++) o[i] = 0.f;
                float m0 = -INFINITY, m1 = -INFINITY;
#pragma unroll 1
                for (int j = 0; j < 32; j++) {
                    const uint64_t kd = kd0 + (j >> 2) * 1024 + (j & 3) * 128, vd = vd0 + ((j >> 2) * 32 + (j & 3) * 4) * VSTEP;
                    float s[32];
                    uint32_t p[16];
                    wg_fence();
                    wgmma_qk_bf16_zero(s, q, kd);
                    wg_commit();
                    wg_wait<0>();
                    pin<32>(s);
                    pin<12>(o);
                    float n0 = m0, n1 = m1;
#pragma unroll
                    for (int i = 0; i < 8; i++) {
                        n0 = fmaxf(n0, fmaxf(s[4 * i], s[4 * i + 1]));
                        n1 = fmaxf(n1, fmaxf(s[4 * i + 2], s[4 * i + 3]));
                    }
                    n0 = fmaxf(n0, __shfl_xor_sync(0xffffffffu, n0, 1));
                    n1 = fmaxf(n1, __shfl_xor_sync(0xffffffffu, n1, 1));
                    n0 = fmaxf(n0, __shfl_xor_sync(0xffffffffu, n0, 2));
                    n1 = fmaxf(n1, __shfl_xor_sync(0xffffffffu, n1, 2));
                    const float c0 = ex2f(m0 - n0), c1 = ex2f(m1 - n1);
                    m0 = n0;
                    m1 = n1;
#pragma unroll
                    for (int i = 0; i < 3; i++) { o[4 * i] *= c0; o[4 * i + 1] *= c0; o[4 * i + 2] *= c1; o[4 * i + 3] *= c1; }
#pragma unroll
                    for (int i = 0; i < 8; i++) {
                        p[2 * i] = pk_bf16(ex2f(s[4 * i] - m0), ex2f(s[4 * i + 1] - m0));
                        p[2 * i + 1] = pk_bf16(ex2f(s[4 * i + 2] - m1), ex2f(s[4 * i + 3] - m1));
                    }
                    pin<16>(p);
                    pin<12>(o);
                    wg_fence();
#pragma unroll
                    for (int u = 0; u < 4; u++) wgmma_pv(o, p + 4 * u, vd + u * VSTEP);
                    wg_commit();
                }
                wg_wait<0>();
                pin<12>(o);
                if (r == 1 && lane == 0) mbar_arrive(bar + B_DONE);
                store_o(o, op + r * (4 * NH * 128), ep & 1);
            }
        }
        {
            const uint4* src = gO + (rb * NH + wg * 8) * 128 + (tid & 127);
            uint4 v[8];
#pragma unroll
            for (int i = 0; i < 8; i++) v[i] = load_o(src + i * 128);
            mbar_wait(bar + B_DONE, 0);
            mbar_wait(bar + B_G2, 0);
            const int lr = (warp & 3) * 16 + g;
            const uint32_t g0 = lds32(sb + OFF_G + lr * 4), g1 = lds32(sb + OFF_G + lr * 4 + 32);
            const uint32_t a0 = sb + wg * 16384 + lr * 128 + (t >> 1) * 4;
#pragma unroll
            for (int i = 0; i < 8; i++) {
                if ((i & 3) == 0) {
                    int spins = 0;
                    while (__any_sync(0xffffffffu, (((v[i].x ^ ep) | (v[i + 1].x ^ ep) | (v[i + 2].x ^ ep) | (v[i + 3].x ^ ep)) & 1) != 0)) {
                        if (++spins > (1 << 22)) __trap();
#pragma unroll
                        for (int k = i; k < 8; k++)
                            if (((v[k].x ^ ep) & 1) != 0) v[k] = load_o(src + k * 128);
                    }
                }
                const uint32_t a = a0 + (i >> 2) * 8192 + ((((i & 3) * 2 + (t & 1)) ^ g) << 4);
                sts32(a, bmul2(v[i].x, g0));
                sts32(a + 8, bmul2(v[i].y, g0));
                sts32(a + 1024, bmul2(v[i].z, g1));
                sts32(a + 1024 + 8, bmul2(v[i].w, g1));
                if ((i & 3) == 3) {
                    asm volatile("fence.proxy.async.shared::cta;" ::: "memory");
                    __syncwarp();
                    if (lane == 0) mbar_arrive(bar + B_T + 8 * (wg * 2 + (i >> 2)));
                    if ((tid & 127) == 0) TLM(1, 20 + wg * 2 + (i >> 2));
                }
            }
        }
    } else {
        if (warp == 16) {
            if (elect()) {
#pragma unroll
                for (int it = 0; it < 28; it++) {
                    const int s = it % 6, ps = strm_pass(it), i = strm_idx(it);
                    const uint32_t fb = bar + B_F1 + 8 * s, dst = sb + OFF_R + s * 16384;
                    if (it >= 6) mbar_wait(bar + B_E1 + 8 * s, ((it / 6) - 1) & 1);
                    mbar_expect(fb, ps < 3 ? 16384 : 12288);
                    if (ps == 0) tma3d_mc(dst + rank * 8192, &tm.kv, nb * 64, i * 64 + rank * 32, 1, fb);
                    if (ps == 1) tma3d_mc(dst + rank * 8192, &tm.f0, nb * 224, i * 64 + rank * 32, 0, fb);
                    if (ps == 2) tma2d_mc(dst + rank * 8192, &tm.q, nb * 64, i * 128 + rank * 64, fb);
                    if (ps == 3) tma3d_mc(dst + rank * 6144, &tm.f1, 0, i * 64 + rank * 32, nb * 7 + 4, fb);
                    if (ps == 0 && i < 7) {
                        mbar_expect(bar + B_X + 8 * (i + 1), 16384);
                        tma2d(sb + (i + 1) * 16384, &tm.x, (i + 1) * 64, mb * 128, bar + B_X + 8 * (i + 1));
                    }
                }
                const int h = cl >> 1;
                cnt_wait(gCntQ + (h >> 2) * 32, ep * 16);
                asm volatile("fence.proxy.async.global;" ::: "memory");
                TLM(0, 9);
#pragma unroll
                for (int c = 0; c < 8; c++) {
                    const int it = 20 + c;
                    if (c >= 2) mbar_wait(bar + B_E1 + 8 * (it % 6), (it / 6) & 1);
                    mbar_expect(bar + B_KV + 8 * c, 16384);
                    bulk_mc(sb + c * 16384 + rank * 8192, gKV + (size_t)h * (SEQ * 64) + c * 16384 + rank * 8192, 8192, bar + B_KV + 8 * c);
                }
#pragma unroll
                for (int s = 0; s < 4; s++) {
                    mbar_expect(bar + B_F2 + 8 * s, 24576);
                    tma5d_mc(sb + OFF_R + s * 24576 + 8192 + rank * 8192, &tm.w2, cb * 128 + rank * 64, s * 2, bar + B_F2 + 8 * s);
                }
                cnt_wait(gCntH + rb * 32, ep * 8);
                asm volatile("fence.proxy.async.global;" ::: "memory");
                TLM(1, 13);
#pragma unroll
                for (int s = 0; s < 4; s++) tma2d(sb + OFF_R + s * 24576, &tm.h, s * 64, rb * 64, bar + B_F2 + 8 * s);
            }
        } else if (warp == 17) {
            mbar_wait(bar + B_X + 8 * 7, 0);
            if (lane == 0) {
                l2_prefetch((const uint8_t*)w2 + (size_t)blockIdx.x * 14336, 14336);
                l2_prefetch((const uint8_t*)wo + (size_t)blockIdx.x * 4096, 4096);
                map_prefetch(&tm.h); map_prefetch(&tm.w2); map_prefetch(&tm.wo);
                TLM(0, 11);
            }
            const int h = cl >> 1, qd = (cl & 1) * 2 + rank;
            if (lane == 0) cnt_wait(gCntQ + (h >> 2) * 32, ep * 16);
            __syncwarp();
            const int hb = h >> 2;
            const uint4 kq = __ldcg((const uint4*)(gN + 1024 + hb * 128 + lane * 4));
            const uint4 vq = __ldcg((const uint4*)(gN + 2048 + hb * 128 + lane * 4));
            const float qq = ldcg_f(gN + hb * 128 + qd * 32 + lane);
            const float kf = __uint_as_float(__reduce_max_sync(0xffffffffu, max(max(kq.x, kq.y), max(kq.z, kq.w))));
            const float vf = __uint_as_float(__reduce_max_sync(0xffffffffu, max(max(vq.x, vq.y), max(vq.z, vq.w))));
            const float qf = __uint_as_float(__reduce_max_sync(0xffffffffu, __float_as_uint(qq)));
            if (lane == 0) {
                sts32(sb + OFF_G + 256, (kf <= 1.0e6f) && (qf <= 1.0e6f) && (kf * qf <= 3400.f) && (vf <= 1.0e12f));
                mbar_arrive(bar + B_G);
            }
        } else {
            {
                uint32_t gw[64];
#pragma unroll
                for (int i = 0; i < 64; i++) gw[i] = *(const uint32_t*)(gate + i * 8 + t * 2);
                float c[2][4] = {{0.f, 0.f, 0.f, 0.f}, {0.f, 0.f, 0.f, 0.f}};
                const int lr = (warp - 18) * 32 + (lane & 15);
                const uint32_t xa = sb + ((nb >> 2) * 64 + lr) * 128;
#pragma unroll
                for (int k = 0; k < 32; k++) {
                    if ((k & 3) == 0) mbar_wait(bar + B_X + 8 * (k >> 2), 0);
#pragma unroll
                    for (int m = 0; m < 2; m++) {
                        uint32_t a[4];
                        asm volatile("ldmatrix.sync.aligned.m8n8.x4.shared.b16 {%0, %1, %2, %3}, [%4];" : "=r"(a[0]), "=r"(a[1]), "=r"(a[2]), "=r"(a[3])
                                     : "r"(xa + (k >> 2) * 16384 + m * 2048 + ((((k & 3) * 2 + (lane >> 4)) ^ (lane & 7)) << 4)));
                        asm volatile("mma.sync.aligned.m16n8k16.row.col.f32.bf16.bf16.f32 {%0,%1,%2,%3}, {%4,%5,%6,%7}, {%8,%9}, {%0,%1,%2,%3};"
                                     : "+f"(c[m][0]), "+f"(c[m][1]), "+f"(c[m][2]), "+f"(c[m][3])
                                     : "r"(a[0]), "r"(a[1]), "r"(a[2]), "r"(a[3]), "r"(gw[2 * k]), "r"(gw[2 * k + 1]));
                    }
                }
                const float z = t == 0 ? c[0][0] : t == 1 ? c[0][2] : t == 2 ? c[1][0] : c[1][2];
                const float gv = 1.f / (1.f + __expf(-z));
                sts32(sb + OFF_G + ((warp - 18) * 32 + t * 8 + g) * 4, pk_bf16(gv, gv));
                __syncwarp();
                if (lane == 0) mbar_arrive(bar + B_G2);
                if (tid == 576) TLM(0, 12);
            }
            bar_sync(warp - 8, 288);
            if (warp == 18) { if (lane == 0) cnt_add(gCntQ + nb * 32); }
            else if (lane < 2) cnt_add(gCntH + (mb * 2 + lane) * 32);
        }
        __syncwarp();
        float acc[64];
#pragma unroll
        for (int i = 0; i < 64; i++) acc[i] = 0.f;
#pragma unroll 1
        for (int io = 0; io < 7; io++) {
#pragma unroll
            for (int s = 0; s < 4; s++) {
                const int it = io * 4 + s;
                mbar_wait(bar + B_F2 + 8 * s, io & 1);
                if (tid == 512 && s == 0 && (io == 0 || io == 4)) TLM(1, 14 + io / 4);
                const uint64_t dA = mkdesc(SBD + OFF_R + s * 24576, 16, 1024, 1);
                const uint64_t dB = mkdesc(SBD + OFF_R + s * 24576 + 8192, 8192, 1024, 1);
                wg_fence();
#pragma unroll
                for (int kk = 0; kk < EXP_FKK; kk++) wgmma_ss_n128(acc, dA + kk * 2, dB + kk * 128);
                wg_commit();
                if (warp < 18 && it >= 2 && it < 26) {
                    const int s2 = (s + 2) & 3;
                    mbar_wait(bar + B_E2 + 8 * s2, (io - (s < 2)) & 1);
                    if (elect()) {
                        if (warp == 16) {
                            mbar_expect(bar + B_F2 + 8 * s2, 24576);
                            tma5d_mc(sb + OFF_R + s2 * 24576 + 8192 + rank * 8192, &tm.w2, cb * 128 + rank * 64, it * 2 + 4, bar + B_F2 + 8 * s2);
                        } else {
                            asm volatile("fence.proxy.async.global;" ::: "memory");
                            tma2d(sb + OFF_R + s2 * 24576, &tm.h, it * 64 + 128, rb * 64, bar + B_F2 + 8 * s2);
                        }
                    }
                    __syncwarp();
                }
                wg_wait<1>();
                if (it >= 1 && lane < 2) mbar_arrive_cluster(bar + B_E2 + 8 * ((s + 3) & 3), lane);
            }
        }
        wg_wait<0>();
        if (lane < 2) mbar_arrive_cluster(bar + B_E2 + 8 * 3, lane);
        pin<64>(acc);
        if (warp == 16) {
            if (lane == 0) TLM(1, 16);
            for (int s = 0; s < 4; s++) mbar_wait(bar + B_E2 + 8 * s, 0);
            if (elect()) {
#pragma unroll
                for (int i = 0; i < 8; i++) mbar_expect(bar + B_T + 8 * i, 16384);
#pragma unroll
                for (int i = 0; i < 6; i++) tma2d_mc(sb + OFF_R + i * 16384 + rank * 8192, &tm.wo, cb * 128 + rank * 64, i * 64, bar + B_T + 8 * i);
            }
            __syncwarp();
        }
        {
            mbar_wait(bar + B_G2, 0);
            const float ga = bf_lo(lds32(sb + OFF_G + ((warp - 16) * 16 + g) * 4)), gb = bf_lo(lds32(sb + OFF_G + ((warp - 16) * 16 + g) * 4 + 32));
            const float g0 = 1.f - ga, g1 = 1.f - gb;
#pragma unroll
            for (int j = 0; j < 16; j++) {
                const uint32_t bv = lds32(sb + OFF_BIAS + 448 + j * 16 + t * 4);
                acc[4 * j] = (acc[4 * j] + bf_lo(bv)) * g0;
                acc[4 * j + 1] = (acc[4 * j + 1] + bf_hi(bv)) * g0;
                acc[4 * j + 2] = (acc[4 * j + 2] + bf_lo(bv)) * g1;
                acc[4 * j + 3] = (acc[4 * j + 3] + bf_hi(bv)) * g1;
            }
            pin<64>(acc);
        }
        if (warp == 17) {
            mbar_wait(bar + B_DONE, 0);
            if (elect()) {
#pragma unroll
                for (int i = 0; i < 4; i++)
                    tma2d(sb + 65536 + i * 8192, &tm.wo, cb * 128 + (i & 1) * 64, (6 + (i >> 1)) * 64, bar + B_T + 8 * (6 + (i >> 1)));
            }
            __syncwarp();
        }
        if (tid == 512) TLM(1, 17);
#pragma unroll
        for (int i = 0; i < 8; i++) {
            mbar_wait(bar + B_T + 8 * i, 0);
            const uint64_t dA = mkdesc(SBD + i * 8192, 16, 1024, 1);
            const uint64_t dB = mkdesc(i < 6 ? SBD + OFF_R + i * 16384 : SBD + 65536 + (i - 6) * 16384, 8192, 1024, 1);
            wg_fence();
#pragma unroll
            for (int kk = 0; kk < 4; kk++) wgmma_ss_n128(acc, dA + kk * 2, dB + kk * 128);
            wg_commit();
        }
        wg_wait<0>();
        pin<64>(acc);
        if (tid == 512) TLM(1, 18);
        {
            const uint32_t st = sb + 98304 + (warp - 16) * 4352;
            const uint32_t wa = st + (lane & 15) * 272 + (lane >> 4) * 16;
#pragma unroll
            for (int j = 0; j < 8; j++)
                asm volatile("stmatrix.sync.aligned.m8n8.x4.shared.b16 [%0], {%1, %2, %3, %4};" ::"r"(wa + j * 32),
                             "r"(pk_bf16(acc[8 * j], acc[8 * j + 1])), "r"(pk_bf16(acc[8 * j + 2], acc[8 * j + 3])),
                             "r"(pk_bf16(acc[8 * j + 4], acc[8 * j + 5])), "r"(pk_bf16(acc[8 * j + 6], acc[8 * j + 7])) : "memory");
            __syncwarp();
            __nv_bfloat16* op = out + (size_t)(rb * 64 + (warp - 16) * 16 + (lane >> 4)) * DM + cb * 128 + (lane & 15) * 8;
#pragma unroll
            for (int j = 0; j < 8; j++) {
                uint4 v;
                asm volatile("ld.shared.v4.u32 {%0, %1, %2, %3}, [%4];" : "=r"(v.x), "=r"(v.y), "=r"(v.z), "=r"(v.w)
                             : "r"(st + (2 * j + (lane >> 4)) * 272 + (lane & 15) * 16));
                *(uint4*)(op + (size_t)j * 2 * DM) = v;
            }
        }
        if (tid == 512) { gEpoch[blockIdx.x] = ep; TLM(1, 19); }
    }
}

typedef CUresult (*EncodeFn)(CUtensorMap*, CUtensorMapDataType, cuuint32_t, void*, const cuuint64_t*, const cuuint64_t*, const cuuint32_t*,
                             const cuuint32_t*, CUtensorMapInterleave, CUtensorMapSwizzle, CUtensorMapL2promotion, CUtensorMapFloatOOBfill);

static void make_map(EncodeFn enc, CUtensorMap* m, const void* p, int rank, const cuuint64_t* dims, const cuuint64_t* strides,
                     const cuuint32_t* box, CUtensorMapSwizzle swz) {
    const cuuint32_t es[5] = {1, 1, 1, 1, 1};
    enc(m, CU_TENSOR_MAP_DATA_TYPE_BFLOAT16, rank, (void*)p, dims, strides, box, es, CU_TENSOR_MAP_INTERLEAVE_NONE, swz,
        CU_TENSOR_MAP_L2_PROMOTION_L2_128B, CU_TENSOR_MAP_FLOAT_OOB_FILL_NONE);
}

extern "C" void kernel_launch(void* const* d_in, const int* in_sizes, int n_in, void* d_out, int out_size) {
    const __nv_bfloat16* x = (const __nv_bfloat16*)d_in[0];
    const __nv_bfloat16* wqkv = (const __nv_bfloat16*)d_in[1];
    const __nv_bfloat16* wo = (const __nv_bfloat16*)d_in[2];
    const __nv_bfloat16* w1 = (const __nv_bfloat16*)d_in[4];
    const __nv_bfloat16* b1 = (const __nv_bfloat16*)d_in[5];
    const __nv_bfloat16* w2 = (const __nv_bfloat16*)d_in[6];
    const __nv_bfloat16* b2 = (const __nv_bfloat16*)d_in[7];
    const __nv_bfloat16* gate = (const __nv_bfloat16*)d_in[8];

    void* fp = nullptr;
    cudaDriverEntryPointQueryResult qr;
    cudaGetDriverEntryPoint("cuTensorMapEncodeTiled", &fp, cudaEnableDefault, &qr);
    EncodeFn enc = (EncodeFn)fp;
    void* pH;
    cudaGetSymbolAddress(&pH, gH);

    Maps tm;
    const CUtensorMapSwizzle S128 = CU_TENSOR_MAP_SWIZZLE_128B, S64 = CU_TENSOR_MAP_SWIZZLE_64B;
    { cuuint64_t d[2] = {DM, SEQ}, s[1] = {DM * 2}; cuuint32_t b[2] = {64, 128}; make_map(enc, &tm.x, x, 2, d, s, b, S128); }
    { cuuint64_t d[3] = {DM, DM, 3}, s[2] = {3 * DM * 2, DM * 2}; cuuint32_t b[3] = {64, 32, 2}; make_map(enc, &tm.kv, wqkv, 3, d, s, b, S128); }
    { cuuint64_t d[2] = {3 * DM, DM}, s[1] = {3 * DM * 2}; cuuint32_t b[2] = {64, 64}; make_map(enc, &tm.q, wqkv, 2, d, s, b, S128); }
    { cuuint64_t d[3] = {FF - 64, DM, 2}, s[2] = {FF * 2, 128}; cuuint32_t b[3] = {64, 32, 2}; make_map(enc, &tm.f0, w1, 3, d, s, b, S128); }
    { cuuint64_t d[3] = {32, DM, FF / 32}, s[2] = {FF * 2, 64}; cuuint32_t b[3] = {32, 32, 3}; make_map(enc, &tm.f1, w1, 3, d, s, b, S64); }
    { cuuint64_t d[2] = {FF, SEQ}, s[1] = {FF * 2}; cuuint32_t b[2] = {64, 64}; make_map(enc, &tm.h, pH, 2, d, s, b, S128); }
    { cuuint64_t d[5] = {DM, 2, 4, 4, FF / 32}, s[4] = {1024, 8 * 1024, 2 * 1024, 32 * 1024}; cuuint32_t b[5] = {64, 2, 4, 4, 2};
      make_map(enc, &tm.w2, w2, 5, d, s, b, S128); }
    { cuuint64_t d[2] = {DM, DM}, s[1] = {DM * 2}; cuuint32_t b[2] = {64, 64}; make_map(enc, &tm.wo, wo, 2, d, s, b, S128); }

    cudaFuncSetAttribute(fused_kernel, cudaFuncAttributeMaxDynamicSharedMemorySize, SMEM_BYTES);
    fused_kernel<<<128, 640, SMEM_BYTES, cudaStreamPerThread>>>(tm, x, wqkv, wo, w1, b1, w2, b2, gate, (__nv_bfloat16*)d_out);
}
```

```cpp
#include <cuda_runtime.h>
#include <cuda_bf16.h>
#include <cuda_fp16.h>
#include <cuda.h>
#include <stdint.h>

#define SEQ 2048
#define DM 512
#define FF 1792
#define NH 32

__device__ __align__(1024) uint8_t gQ[NH * SEQ * 32];
__device__ __align__(1024) uint8_t gKV[NH * SEQ * 64];
__device__ __align__(1024) __nv_bfloat16 gH[SEQ * FF];
__device__ __align__(1024) uint4 gO[32 * NH * 128];
__device__ float gN[3 * 8 * 128];
__device__ unsigned int gCntQ[8 * 32];
__device__ unsigned int gCntH[32 * 32];
__device__ unsigned int gEpoch[128];

__device__ __forceinline__ uint32_t smem_u32(const void* p) { return (uint32_t)__cvta_generic_to_shared(p); }
__device__ __forceinline__ void mbar_init(uint32_t a, uint32_t c) { asm volatile("mbarrier.init.shared::cta.b64 [%0], %1;" ::"r"(a), "r"(c)); }
__device__ __forceinline__ void mbar_expect(uint32_t a, uint32_t b) { asm volatile("mbarrier.arrive.expect_tx.shared::cta.b64 _, [%0], %1;" ::"r"(a), "r"(b) : "memory"); }
__device__ __forceinline__ void mbar_arrive(uint32_t a) { asm volatile("mbarrier.arrive.shared::cta.b64 _, [%0];" ::"r"(a) : "memory"); }
__device__ __forceinline__ void mbar_wait(uint32_t a, uint32_t ph) {
    asm volatile("{\n.reg .pred p;\n.reg .u32 n;\nmov.u32 n, 0;\nW_%=:\nmbarrier.try_wait.parity.shared::cta.b64 p, [%0], %1;\n@p bra D_%=;\n"
                 "add.u32 n, n, 1;\nsetp.lt.u32 p, n, 0x400000;\n@p bra W_%=;\ntrap;\nD_%=:\n}" ::"r"(a), "r"(ph) : "memory");
}
__device__ __forceinline__ void mbar_arrive_cluster(uint32_t a, uint32_t cta) {
    asm volatile("{\n.reg .b32 r;\nmapa.shared::cluster.u32 r, %0, %1;\nmbarrier.arrive.shared::cluster.b64 _, [r];\n}" ::"r"(a), "r"(cta) : "memory");
}
__device__ __forceinline__ void bar_sync(int id, int n) { asm volatile("bar.sync %0, %1;" ::"r"(id), "r"(n) : "memory"); }
__device__ __forceinline__ void bar_arrive(int id, int n) { asm volatile("bar.arrive %0, %1;" ::"r"(id), "r"(n) : "memory"); }
__device__ __forceinline__ uint32_t cluster_rank() { uint32_t r; asm("mov.u32 %0, %%cluster_ctarank;" : "=r"(r)); return r; }
__device__ __forceinline__ void cnt_add(unsigned int* c) { asm volatile("red.release.gpu.global.add.u32 [%0], 1;" ::"l"(c) : "memory"); }
__device__ __forceinline__ void cnt_wait(const unsigned int* c, uint32_t target) {
    uint32_t v;
    int spins = 0;
    while (true) {
        asm volatile("ld.acquire.gpu.global.u32 %0, [%1];" : "=r"(v) : "l"(c) : "memory");
        if ((int)(v - target) >= 0) break;
        if (++spins > (1 << 22)) __trap();
        __nanosleep(40);
    }
}
__device__ __forceinline__ void tma2d(uint32_t dst, const CUtensorMap* m, int c0, int c1, uint32_t bar) {
    asm volatile("cp.async.bulk.tensor.2d.shared::cluster.global.mbarrier::complete_tx::bytes [%0], [%1, {%3, %4}], [%2];"
                 ::"r"(dst), "l"(m), "r"(bar), "r"(c0), "r"(c1) : "memory");
}
__device__ __forceinline__ void tma2d_mc(uint32_t dst, const CUtensorMap* m, int c0, int c1, uint32_t bar) {
    asm volatile("cp.async.bulk.tensor.2d.shared::cluster.global.mbarrier::complete_tx::bytes.multicast::cluster [%0], [%1, {%3, %4}], [%2], %5;"
                 ::"r"(dst), "l"(m), "r"(bar), "r"(c0), "r"(c1), "h"((uint16_t)3) : "memory");
}
__device__ __forceinline__ void tma3d_mc(uint32_t dst, const CUtensorMap* m, int c0, int c1, int c2, uint32_t bar) {
    asm volatile("cp.async.bulk.tensor.3d.shared::cluster.global.mbarrier::complete_tx::bytes.multicast::cluster [%0], [%1, {%3, %4, %5}], [%2], %6;"
                 ::"r"(dst), "l"(m), "r"(bar), "r"(c0), "r"(c1), "r"(c2), "h"((uint16_t)3) : "memory");
}
__device__ __forceinline__ void tma5d_mc(uint32_t dst, const CUtensorMap* m, int c0, int c4, uint32_t bar) {
    asm volatile("cp.async.bulk.tensor.5d.shared::cluster.global.mbarrier::complete_tx::bytes.multicast::cluster [%0], [%1, {%3, %5, %5, %5, %4}], [%2], %6;"
                 ::"r"(dst), "l"(m), "r"(bar), "r"(c0), "r"(c4), "r"(0), "h"((uint16_t)3) : "memory");
}
__device__ __forceinline__ void bulk_mc(uint32_t dst, const void* src, uint32_t bytes, uint32_t bar) {
    asm volatile("cp.async.bulk.shared::cluster.global.mbarrier::complete_tx::bytes.multicast::cluster [%0], [%1], %2, [%3], %4;"
                 ::"r"(dst), "l"(src), "r"(bytes), "r"(bar), "h"((uint16_t)3) : "memory");
}
__device__ __forceinline__ void l2_prefetch(const void* src, uint32_t bytes) {
    asm volatile("cp.async.bulk.prefetch.L2.global [%0], %1;" ::"l"(src), "r"(bytes) : "memory");
}
__device__ __forceinline__ void map_prefetch(const CUtensorMap* m) { asm volatile("prefetch.tensormap [%0];" ::"l"(m) : "memory"); }
__device__ __forceinline__ void wg_fence() { asm volatile("wgmma.fence.sync.aligned;" ::: "memory"); }
__device__ __forceinline__ void wg_commit() { asm volatile("wgmma.commit_group.sync.aligned;" ::: "memory"); }
template <int N> __device__ __forceinline__ void wg_wait() { asm volatile("wgmma.wait_group.sync.aligned %0;" ::"n"(N) : "memory"); }
template <int N> __device__ __forceinline__ void pin(float* s) {
#pragma unroll
    for (int i = 0; i < N; i++) asm volatile("" : "+f"(s[i])::"memory");
}
template <int N> __device__ __forceinline__ void pin(uint32_t* s) {
#pragma unroll
    for (int i = 0; i < N; i++) asm volatile("" : "+r"(s[i])::"memory");
}
__device__ __forceinline__ uint64_t mkdesc(uint32_t addr, uint32_t lbo, uint32_t sbo, uint32_t swz) {
    return (uint64_t)((addr & 0x3FFFF) >> 4) | ((uint64_t)(lbo >> 4) << 16) | ((uint64_t)(sbo >> 4) << 32) | ((uint64_t)swz << 62);
}
__device__ __forceinline__ float ex2f(float x) { float y; asm("ex2.approx.ftz.f32 %0, %1;" : "=f"(y) : "f"(x)); return y; }
__device__ __forceinline__ float tanhf_(float x) { float y; asm("tanh.approx.f32 %0, %1;" : "=f"(y) : "f"(x)); return y; }
__device__ __forceinline__ uint32_t pk_bf16(float lo, float hi) { uint32_t r; asm("cvt.rn.bf16x2.f32 %0, %1, %2;" : "=r"(r) : "f"(hi), "f"(lo)); return r; }
__device__ __forceinline__ uint32_t pk_f16(float lo, float hi) { uint32_t r; asm("cvt.rn.f16x2.f32 %0, %1, %2;" : "=r"(r) : "f"(hi), "f"(lo)); return r; }
__device__ __forceinline__ float bf_lo(uint32_t v) { return __uint_as_float(v << 16); }
__device__ __forceinline__ float bf_hi(uint32_t v) { return __uint_as_float(v & 0xffff0000u); }
__device__ __forceinline__ float ldcg_f(const float* p) { return __ldcg(p); }

#define TLM(k, slot) do {} while (0)
#define TLC(k, slot) do {} while (0)

__device__ __forceinline__ void wgmma_ss_n128(float* d, uint64_t da, uint64_t db) {
    asm volatile("wgmma.mma_async.sync.aligned.m64n128k16.f32.bf16.bf16 {"
        "%0, %1, %2, %3, %4, %5, %6, %7, %8, %9, %10, %11, %12, %13, %14, %15,"
        "%16, %17, %18, %19, %20, %21, %22, %23, %24, %25, %26, %27, %28, %29, %30, %31,"
        "%32, %33, %34, %35, %36, %37, %38, %39, %40, %41, %42, %43, %44, %45, %46, %47,"
        "%48, %49, %50, %51, %52, %53, %54, %55, %56, %57, %58, %59, %60, %61, %62, %63}, %64, %65, 1, 1, 1, 0, 1;\n"
        :
        "+f"(d[0]), "+f"(d[1]), "+f"(d[2]), "+f"(d[3]), "+f"(d[4]), "+f"(d[5]), "+f"(d[6]), "+f"(d[7]),
        "+f"(d[8]), "+f"(d[9]), "+f"(d[10]), "+f"(d[11]), "+f"(d[12]), "+f"(d[13]), "+f"(d[14]), "+f"(d[15]),
        "+f"(d[16]), "+f"(d[17]), "+f"(d[18]), "+f"(d[19]), "+f"(d[20]), "+f"(d[21]), "+f"(d[22]), "+f"(d[23]),
        "+f"(d[24]), "+f"(d[25]), "+f"(d[26]), "+f"(d[27]), "+f"(d[28]), "+f"(d[29]), "+f"(d[30]), "+f"(d[31]),
        "+f"(d[32]), "+f"(d[33]), "+f"(d[34]), "+f"(d[35]), "+f"(d[36]), "+f"(d[37]), "+f"(d[38]), "+f"(d[39]),
        "+f"(d[40]), "+f"(d[41]), "+f"(d[42]), "+f"(d[43]), "+f"(d[44]), "+f"(d[45]), "+f"(d[46]), "+f"(d[47]),
        "+f"(d[48]), "+f"(d[49]), "+f"(d[50]), "+f"(d[51]), "+f"(d[52]), "+f"(d[53]), "+f"(d[54]), "+f"(d[55]),
        "+f"(d[56]), "+f"(d[57]), "+f"(d[58]), "+f"(d[59]), "+f"(d[60]), "+f"(d[61]), "+f"(d[62]), "+f"(d[63])
        : "l"(da), "l"(db));
}
__device__ __forceinline__ void wgmma_ss_n96(float* d, uint64_t da, uint64_t db) {
    asm volatile("wgmma.mma_async.sync.aligned.m64n96k16.f32.bf16.bf16 {"
        "%0, %1, %2, %3, %4, %5, %6, %7, %8, %9, %10, %11, %12, %13, %14, %15,"
        "%16, %17, %18, %19, %20, %21, %22, %23, %24, %25, %26, %27, %28, %29, %30, %31,"
        "%32, %33, %34, %35, %36, %37, %38, %39, %40, %41, %42, %43, %44, %45, %46, %47}, %48, %49, 1, 1, 1, 0, 1;\n"
        :
        "+f"(d[0]), "+f"(d[1]), "+f"(d[2]), "+f"(d[3]), "+f"(d[4]), "+f"(d[5]), "+f"(d[6]), "+f"(d[7]),
        "+f"(d[8]), "+f"(d[9]), "+f"(d[10]), "+f"(d[11]), "+f"(d[12]), "+f"(d[13]), "+f"(d[14]), "+f"(d[15]),
        "+f"(d[16]), "+f"(d[17]), "+f"(d[18]), "+f"(d[19]), "+f"(d[20]), "+f"(d[21]), "+f"(d[22]), "+f"(d[23]),
        "+f"(d[24]), "+f"(d[25]), "+f"(d[26]), "+f"(d[27]), "+f"(d[28]), "+f"(d[29]), "+f"(d[30]), "+f"(d[31]),
        "+f"(d[32]), "+f"(d[33]), "+f"(d[34]), "+f"(d[35]), "+f"(d[36]), "+f"(d[37]), "+f"(d[38]), "+f"(d[39]),
        "+f"(d[40]), "+f"(d[41]), "+f"(d[42]), "+f"(d[43]), "+f"(d[44]), "+f"(d[45]), "+f"(d[46]), "+f"(d[47])
        : "l"(da), "l"(db));
}
__device__ __forceinline__ void wgmma_ss_n64(float* d, uint64_t da, uint64_t db) {
    asm volatile("wgmma.mma_async.sync.aligned.m64n64k16.f32.bf16.bf16 {"
        "%0, %1, %2, %3, %4, %5, %6, %7, %8, %9, %10, %11, %12, %13, %14, %15,"
        "%16, %17, %18, %19, %20, %21, %22, %23, %24, %25, %26, %27, %28, %29, %30, %31}, %32, %33, 1, 1, 1, 0, 1;\n"
        :
        "+f"(d[0]), "+f"(d[1]), "+f"(d[2]), "+f"(d[3]), "+f"(d[4]), "+f"(d[5]), "+f"(d[6]), "+f"(d[7]),
        "+f"(d[8]), "+f"(d[9]), "+f"(d[10]), "+f"(d[11]), "+f"(d[12]), "+f"(d[13]), "+f"(d[14]), "+f"(d[15]),
        "+f"(d[16]), "+f"(d[17]), "+f"(d[18]), "+f"(d[19]), "+f"(d[20]), "+f"(d[21]), "+f"(d[22]), "+f"(d[23]),
        "+f"(d[24]), "+f"(d[25]), "+f"(d[26]), "+f"(d[27]), "+f"(d[28]), "+f"(d[29]), "+f"(d[30]), "+f"(d[31])
        : "l"(da), "l"(db));
}
__device__ __forceinline__ void wgmma_qk_f16_acc(float* d, const uint32_t* a, uint64_t db) {
    asm volatile("wgmma.mma_async.sync.aligned.m64n64k16.f32.f16.f16 {"
        "%0, %1, %2, %3, %4, %5, %6, %7, %8, %9, %10, %11, %12, %13, %14, %15,"
        "%16, %17, %18, %19, %20, %21, %22, %23, %24, %25, %26, %27, %28, %29, %30, %31}, {%32, %33, %34, %35}, %36, 1, 1, 1, 0;\n"
        :
        "+f"(d[0]), "+f"(d[1]), "+f"(d[2]), "+f"(d[3]), "+f"(d[4]), "+f"(d[5]), "+f"(d[6]), "+f"(d[7]),
        "+f"(d[8]), "+f"(d[9]), "+f"(d[10]), "+f"(d[11]), "+f"(d[12]), "+f"(d[13]), "+f"(d[14]), "+f"(d[15]),
        "+f"(d[16]), "+f"(d[17]), "+f"(d[18]), "+f"(d[19]), "+f"(d[20]), "+f"(d[21]), "+f"(d[22]), "+f"(d[23]),
        "+f"(d[24]), "+f"(d[25]), "+f"(d[26]), "+f"(d[27]), "+f"(d[28]), "+f"(d[29]), "+f"(d[30]), "+f"(d[31])
        : "r"(a[0]), "r"(a[1]), "r"(a[2]), "r"(a[3]), "l"(db));
}
__device__ __forceinline__ void wgmma_qk_bf16_zero(float* d, const uint32_t* a, uint64_t db) {
    asm volatile("wgmma.mma_async.sync.aligned.m64n64k16.f32.bf16.bf16 {"
        "%0, %1, %2, %3, %4, %5, %6, %7, %8, %9, %10, %11, %12, %13, %14, %15,"
        "%16, %17, %18, %19, %20, %21, %22, %23, %24, %25, %26, %27, %28, %29, %30, %31}, {%32, %33, %34, %35}, %36, 0, 1, 1, 0;\n"
        :
        "=f"(d[0]), "=f"(d[1]), "=f"(d[2]), "=f"(d[3]), "=f"(d[4]), "=f"(d[5]), "=f"(d[6]), "=f"(d[7]),
        "=f"(d[8]), "=f"(d[9]), "=f"(d[10]), "=f"(d[11]), "=f"(d[12]), "=f"(d[13]), "=f"(d[14]), "=f"(d[15]),
        "=f"(d[16]), "=f"(d[17]), "=f"(d[18]), "=f"(d[19]), "=f"(d[20]), "=f"(d[21]), "=f"(d[22]), "=f"(d[23]),
        "=f"(d[24]), "=f"(d[25]), "=f"(d[26]), "=f"(d[27]), "=f"(d[28]), "=f"(d[29]), "=f"(d[30]), "=f"(d[31])
        : "r"(a[0]), "r"(a[1]), "r"(a[2]), "r"(a[3]), "l"(db));
}
__device__ __forceinline__ void wgmma_pv(float* d, const uint32_t* a, uint64_t db) {
    asm volatile("wgmma.mma_async.sync.aligned.m64n24k16.f32.bf16.bf16 {"
        "%0, %1, %2, %3, %4, %5, %6, %7, %8, %9, %10, %11}, {%12, %13, %14, %15}, %16, 1, 1, 1, 1;\n"
        :
        "+f"(d[0]), "+f"(d[1]), "+f"(d[2]), "+f"(d[3]), "+f"(d[4]), "+f"(d[5]), "+f"(d[6]), "+f"(d[7]),
        "+f"(d[8]), "+f"(d[9]), "+f"(d[10]), "+f"(d[11])
        : "r"(a[0]), "r"(a[1]), "r"(a[2]), "r"(a[3]), "l"(db));
}

template <int N> __device__ __forceinline__ void wgmma_ss(float* d, uint64_t a, uint64_t b) {
    if (N == 128) wgmma_ss_n128(d, a, b);
    if (N == 96) wgmma_ss_n96(d, a, b);
    if (N == 64) wgmma_ss_n64(d, a, b);
}

#define OFF_R 131072
#define OFF_ONE 229376
#define OFF_BAR 229888
#define OFF_BIAS (OFF_BAR + 512)
#define OFF_G (OFF_BIAS + 832)
#define SMEM_BYTES (OFF_G + 272)
#define SBD 1024u
#define B_X 0
#define B_F1 64
#define B_E1 112
#define B_KV 160
#define B_F2 224
#define B_E2 256
#define B_T 288
#define B_DONE 352
#define B_G 360
#define B_G2 368

#define PF 1
#define EXP_FKK 4
#define QSCALE 0.36067376022224085f
#define MAGIC 445.41763f
#define NMUFU 4
#define VSTEP ((uint64_t)((long long)32 - ((long long)32 << 16)))

#define KVMASK 0xEA52u
__host__ __device__ constexpr int strm_pos(int pass, int i) {
    if (pass == 1 || pass == 2) return 8 + 8 * pass + i;
    int n = 0;
    for (int p = 0; p < 16; p++)
        if ((int)((KVMASK >> p) & 1) == (pass == 3)) { if (n == i) return p; n++; }
    return 0;
}
__host__ __device__ constexpr uint32_t strm_code(int pass) {
    uint32_t c = 0;
    for (int i = 0; i < 8; i++) c |= (uint32_t)(strm_pos(pass, i) % 6 | ((strm_pos(pass, i) / 6) & 1) << 3) << (4 * i);
    return c;
}

template <int N, int SUB, int KST, int LBO, int SBO, int SWZ>
__device__ __forceinline__ void gemm_pass(float* acc, uint32_t bar, uint64_t dA, int lane, uint32_t code, int barNext) {
    uint32_t prev = 0;
#pragma unroll 1
    for (int i = 0; i < 8; i++) {
        const uint32_t slot = code & 7;
        mbar_wait(bar + B_X + 8 * i, 0);
        mbar_wait(bar + B_F1 + 8 * slot, (code >> 3) & 1);
        const uint64_t dB = mkdesc(SBD + OFF_R, LBO, SBO, SWZ) + slot * 1024;
        wg_fence();
        wgmma_ss<N>(acc, dA, dB);
        wgmma_ss<N>(acc, dA + 2, dB + KST / 16);
        wg_commit();
        wg_wait<1>();
        if (i > 0 && lane < 2) mbar_arrive_cluster(bar + B_E1 + 8 * prev, lane);
        wgmma_ss<N>(acc, dA + 4, dB + SUB / 16);
        wgmma_ss<N>(acc, dA + 6, dB + (SUB + KST) / 16);
        wg_commit();
        prev = slot;
        code >>= 4;
        dA += 1024;
    }
    if (barNext) bar_arrive(barNext, 512);
    wg_wait<0>();
    if (lane < 2) mbar_arrive_cluster(bar + B_E1 + 8 * prev, lane);
    pin<N / 2>(acc);
}

__device__ __forceinline__ uint32_t lds32(uint32_t a) { uint32_t v; asm volatile("ld.shared.u32 %0, [%1];" : "=r"(v) : "r"(a)); return v; }
__device__ __forceinline__ bool elect() {
    uint32_t p;
    asm volatile("{\n.reg .pred p;\nelect.sync _|p, 0xffffffff;\nselp.u32 %0, 1, 0, p;\n}" : "=r"(p));
    return p;
}

template <int N> __device__ __forceinline__ void bias_init(float* acc, uint32_t b) {
#pragma unroll
    for (int j = 0; j < N / 8; j++) {
        const uint32_t bv = lds32(b + j * 16);
        acc[4 * j] = acc[4 * j + 2] = bf_lo(bv);
        acc[4 * j + 1] = acc[4 * j + 3] = bf_hi(bv);
    }
    pin<N / 2>(acc);
}

template <int G0, int G1> __device__ __forceinline__ void gelu_store(const float* acc, __nv_bfloat16* hp) {
#pragma unroll
    for (int G = G0; G < G1; G++) {
        uint32_t o[8];
#pragma unroll
        for (int j = 0; j < 4; j++) {
            float y[4];
#pragma unroll
            for (int i = 0; i < 4; i++) {
                const float h = acc[16 * G + 4 * j + i];
                const float z = h * fmaf(h * h, 0.035677408136300125f, 0.7978845608028654f);
                const float hh = 0.5f * h;
                y[i] = fmaf(hh, tanhf_(z), hh);
            }
            o[j] = pk_bf16(y[0], y[1]);
            o[4 + j] = pk_bf16(y[2], y[3]);
        }
        *(uint4*)(hp + G * 32) = make_uint4(o[0], o[1], o[2], o[3]);
        *(uint4*)(hp + 8 * FF + G * 32) = make_uint4(o[4], o[5], o[6], o[7]);
    }
}

__device__ __forceinline__ float norm_bound(const float* v, float sc) {
    uint32_t m = 0;
#pragma unroll
    for (int h = 0; h < 4; h++) {
        const float* u = v + 8 * h;
        m = max(m, __float_as_uint(fmaf(u[0], u[0], fmaf(u[1], u[1], fmaf(u[4], u[4], u[5] * u[5])))));
        m = max(m, __float_as_uint(fmaf(u[2], u[2], fmaf(u[3], u[3], fmaf(u[6], u[6], u[7] * u[7])))));
    }
#pragma unroll
    for (int o = 4; o < 32; o <<= 1) m = max(m, __shfl_xor_sync(0xffffffffu, m, o));
    float f = __uint_as_float(m);
    f += __shfl_xor_sync(0xffffffffu, f, 1);
    f += __shfl_xor_sync(0xffffffffu, f, 2);
    return f * sc;
}

__device__ __forceinline__ uint32_t exp2_pair(float a, float b) {
    const uint32_t w = __byte_perm(__float_as_uint(a), __float_as_uint(b), 0x6521);
    uint32_t m, r;
    asm("lop3.b32 %0, %1, 0x007f007f, 0x9f809f80, 0xEA;" : "=r"(m) : "r"(w));
    const uint32_t e = w - m;
    asm("fma.rn.bf16x2 %0, %1, %2, %3;" : "=r"(r) : "r"(w), "r"(m), "r"(e));
    return r;
}

__device__ __forceinline__ void store_o(const float* o, uint4* dst, uint32_t par) {
    const float s0 = __fdividef(1.f, o[8]), s1 = __fdividef(1.f, o[10]);
    const uint32_t d0 = (pk_bf16(o[0] * s0, o[1] * s0) & ~1u) | par;
    asm volatile("{\n.reg .b128 t;\nmov.b128 t, {%0, %1, %2, %3};\nst.relaxed.gpu.global.b128 [%4], t;\n}" ::"r"(d0),
                 "r"(pk_bf16(o[4] * s0, o[5] * s0)), "r"(pk_bf16(o[2] * s1, o[3] * s1)), "r"(pk_bf16(o[6] * s1, o[7] * s1)), "l"(dst) : "memory");
}
__device__ __forceinline__ uint4 load_o(const uint4* src) {
    uint4 v;
    asm volatile("{\n.reg .b128 t;\nld.relaxed.gpu.global.b128 t, [%4];\nmov.b128 {%0, %1, %2, %3}, t;\n}"
                 : "=r"(v.x), "=r"(v.y), "=r"(v.z), "=r"(v.w) : "l"(src) : "memory");
    return v;
}
__device__ __forceinline__ uint32_t bmul2(uint32_t a, uint32_t b) { uint32_t r; asm("mul.rn.bf16x2 %0, %1, %2;" : "=r"(r) : "r"(a), "r"(b)); return r; }
__device__ __forceinline__ void sts32(uint32_t a, uint32_t v) { asm volatile("st.shared.u32 [%0], %1;" ::"r"(a), "r"(v) : "memory"); }
__device__ __forceinline__ void load_q(uint32_t* q, int h, int row, int t) {
    const uint8_t* p = gQ + (size_t)h * (SEQ * 32) + (size_t)row * 32 + t * 4;
    q[0] = __ldcg((const uint32_t*)p); q[1] = __ldcg((const uint32_t*)(p + 256));
    q[2] = __ldcg((const uint32_t*)(p + 16)); q[3] = __ldcg((const uint32_t*)(p + 272));
}

template <int NT>
__device__ __forceinline__ void proj16(float (*c)[8], const __nv_bfloat16* x, const __nv_bfloat16* w, int row0, int rstep, int col, int g, int t) {
#pragma unroll
    for (int i = 0; i < NT; i++)
#pragma unroll
        for (int j = 0; j < 8; j++) c[i][j] = 0.f;
    const unsigned short* wu = (const unsigned short*)w;
#pragma unroll 1
    for (int k = 0; k < DM; k += 16) {
        uint32_t b[4];
#pragma unroll
        for (int j = 0; j < 4; j++) {
            const int kr = k + 2 * t + (j & 1) * 8, cc = col + g + (j >> 1) * 8;
            b[j] = (uint32_t)wu[(size_t)kr * (3 * DM) + cc] | ((uint32_t)wu[(size_t)(kr + 1) * (3 * DM) + cc] << 16);
        }
#pragma unroll
        for (int i = 0; i < NT; i++) {
            const __nv_bfloat16* xp = x + (size_t)(row0 + i * rstep + g) * DM + k + 2 * t;
            const uint32_t a0 = *(const uint32_t*)xp, a1 = *(const uint32_t*)(xp + 8 * DM);
            const uint32_t a2 = *(const uint32_t*)(xp + 8), a3 = *(const uint32_t*)(xp + 8 * DM + 8);
#pragma unroll
            for (int j = 0; j < 2; j++)
                asm volatile("mma.sync.aligned.m16n8k16.row.col.f32.bf16.bf16.f32 {%0,%1,%2,%3}, {%4,%5,%6,%7}, {%8,%9}, {%0,%1,%2,%3};"
                             : "+f"(c[i][4 * j]), "+f"(c[i][4 * j + 1]), "+f"(c[i][4 * j + 2]), "+f"(c[i][4 * j + 3])
                             : "r"(a0), "r"(a1), "r"(a2), "r"(a3), "r"(b[2 * j]), "r"(b[2 * j + 1]));
        }
    }
}

struct Maps { CUtensorMap x, kv, q, f1, f3, h, w2, wo; };

__global__ void __cluster_dims__(2, 1, 1) __launch_bounds__(640, 1)
fused_kernel(const __grid_constant__ Maps tm, const __nv_bfloat16* __restrict__ x, const __nv_bfloat16* __restrict__ wqkv,
             const __nv_bfloat16* __restrict__ wo, const __nv_bfloat16* __restrict__ w1, const __nv_bfloat16* __restrict__ b1,
             const __nv_bfloat16* __restrict__ w2, const __nv_bfloat16* __restrict__ b2, const __nv_bfloat16* __restrict__ gate,
             __nv_bfloat16* __restrict__ out) {
    extern __shared__ __align__(1024) uint8_t smem_raw[];
    const uint32_t sb = smem_u32(smem_raw);
    const uint32_t bar = sb + OFF_BAR;
    const int tid = threadIdx.x, lane = tid & 31;
    const int warp = __shfl_sync(0xffffffffu, tid >> 5, 0);
    const uint32_t rank = cluster_rank();
    const int cl = blockIdx.x >> 1;
    const int nb = cl & 7, mb = (cl >> 3) * 2 + rank;
    const int g = lane >> 2, t = lane & 3;

    const int cb = nb & 3, rb = mb * 2 + (nb >> 2);
    if (tid == 0) TLM(0, 0);
    if (tid == 512) {
        mbar_init(bar + B_X, 1);
        asm volatile("fence.proxy.async.shared::cta;" ::: "memory");
        mbar_expect(bar + B_X, 16384);
        tma2d(sb, &tm.x, 0, mb * 128, bar + B_X);
        for (int i = 0; i < 8; i++) { if (i) mbar_init(bar + B_X + 8 * i, 1); mbar_init(bar + B_KV + 8 * i, 1); mbar_init(bar + B_T + 8 * i, 5); }
        for (int i = 0; i < 6; i++) { mbar_init(bar + B_F1 + 8 * i, 1); mbar_init(bar + B_E1 + 8 * i, 16); }
        for (int i = 0; i < 4; i++) { mbar_init(bar + B_F2 + 8 * i, 1); mbar_init(bar + B_E2 + 8 * i, 8); }
        mbar_init(bar + B_DONE, 16);
        mbar_init(bar + B_G, 1);
        mbar_init(bar + B_G2, 2);
        asm volatile("fence.mbarrier_init.release.cluster;" ::: "memory");
    } else if (tid == 544) {
        map_prefetch(&tm.q); map_prefetch(&tm.f1); map_prefetch(&tm.kv);
        l2_prefetch((const uint8_t*)wqkv + (size_t)blockIdx.x * 3072, 3072);
        map_prefetch(&tm.f3);
    } else if (tid < 128) {
        asm volatile("st.shared.u32 [%0], %1;" ::"r"(sb + OFF_ONE + tid * 4), "r"(0x3f803f80u) : "memory");
        asm volatile("fence.proxy.async.shared::cta;" ::: "memory");
    }
    uint32_t biasv = 0;
    if (tid >= 288 && tid < 256 + 208)
        biasv = tid < 400 ? *(const uint32_t*)(b1 + nb * 224 + (tid - 288) * 2) : *(const uint32_t*)(b2 + cb * 128 + (tid - 400) * 2);
    if ((sb & 0xFFFFFF) != SBD) __trap();
    __syncthreads();
    asm volatile("barrier.cluster.arrive.relaxed.aligned;\nbarrier.cluster.wait.aligned;" ::: "memory");
    const uint32_t ep = gEpoch[blockIdx.x] + 1;
    if (tid == 0) { TLM(0, 1); TLC(0, 30); }

    if (warp < 16) {
        const int wg = warp >> 2;
        const int h = cl >> 1, qd = (cl & 1) * 2 + rank;
        uint32_t q[4];
        {
            const int w8 = warp & 7;
            const int T = mb * 8 + w8, row0 = T * 16 + g;
            const uint64_t dA0 = mkdesc(SBD + (wg & 1) * 8192, 16, 1024, 1);
            if (wg < 2) {
                float acc[64];
#pragma unroll
                for (int i = 0; i < 64; i++) acc[i] = 0.f;
                gemm_pass<128, 8192, 2048, 4096, 1024, 1>(acc, bar, dA0, lane, strm_code(3), 6);
                if (tid == 0) TLM(0, 2);
                {
                    const int pos = ((T >> 6) * 16 + 2 * g) * 64 + (T & 63);
                    uint8_t* kp = gKV + (size_t)(nb * 4) * (SEQ * 64) + (pos >> 8) * 16384 + (pos & 255) * 32 + ((t * 8) ^ (((T >> 2) & 1) << 4));
                    float vm = 0.f;
#pragma unroll
                    for (int hh = 0; hh < 4; hh++) {
                        const float* v = acc + 8 * hh;
                        float p0 = __shfl_up_sync(0xffffffffu, v[2], 4), p1 = __shfl_up_sync(0xffffffffu, v[3], 4);
                        float p2 = __shfl_up_sync(0xffffffffu, v[6], 4), p3 = __shfl_up_sync(0xffffffffu, v[7], 4);
                        if (g == 0) { p0 = p1 = p2 = p3 = 0.f; }
                        uint8_t* o = kp + (size_t)hh * (SEQ * 64);
                        *(uint2*)o = make_uint2(pk_f16(v[0] - p0, v[1] - p1), pk_f16(v[4] - p2, v[5] - p3));
                        *(uint2*)(o + 2048) = make_uint2(pk_f16(v[2] - v[0], v[3] - v[1]), pk_f16(v[6] - v[4], v[7] - v[5]));
                        const float* u = acc + 32 + 8 * hh;
#pragma unroll
                        for (int i = 0; i < 8; i++) vm = fmaxf(vm, fabsf(u[i]));
                        *(uint2*)(o + 8192) = make_uint2(pk_bf16(u[0], u[1]), pk_bf16(u[4], u[5]));
                        *(uint2*)(o + 8192 + 2048) = make_uint2(pk_bf16(u[2], u[3]), pk_bf16(u[6], u[7]));
                    }
                    const float km = norm_bound(acc, 1.f);
                    vm = __uint_as_float(__reduce_max_sync(0xffffffffu, __float_as_uint(vm)));
                    if (lane == 0) { gN[1024 + nb * 128 + T] = km; gN[2048 + nb * 128 + T] = vm; }
                }
                bar_arrive(10, 544);
                if (tid == 0) TLM(0, 3);
                mbar_wait(bar + B_G2, 0);
                bar_sync(12, 512);
            } else {
                if (tid < 256 + 208) sts32(sb + OFF_BIAS + (tid - 256) * 4, biasv);
                bar_arrive(12, 512);
                bar_sync(5, 256);
            }
            const int pend = wg < 2 ? 3 : 2;
#pragma unroll 1
            for (int p = wg < 2 ? 2 : 0; p < pend; p++) {
                float acc[48];
                bias_init<96>(acc, sb + OFF_BIAS + p * 192 + t * 4);
                if (p) bar_sync(5 + p, 512);
                gemm_pass<96, 6144, 1024, 2048, 512, 2>(acc, bar, dA0, lane, p == 0 ? strm_code(0) : p == 1 ? strm_code(1) : strm_code(2), p == 1 ? 7 : 0);
                if ((tid & 255) == 0) TLM(0, 4 + 2 * p);
                __nv_bfloat16* hp = gH + (size_t)row0 * FF + nb * 224 + p * 96 - 64 + t * 8;
                if (p == 0) {
                    uint8_t* qp = gQ + (size_t)(nb * 4) * (SEQ * 32) + (size_t)row0 * 32 + t * 8;
#pragma unroll
                    for (int hh = 0; hh < 4; hh++) {
                        const float* v = acc + 8 * hh;
                        uint8_t* o = qp + (size_t)hh * (SEQ * 32);
                        *(uint2*)o = make_uint2(pk_f16(v[0] * QSCALE, v[1] * QSCALE), pk_f16(v[4] * QSCALE, v[5] * QSCALE));
                        *(uint2*)(o + 256) = make_uint2(pk_f16(v[2] * QSCALE, v[3] * QSCALE), pk_f16(v[6] * QSCALE, v[7] * QSCALE));
                    }
                    const float qm = norm_bound(acc, QSCALE * QSCALE);
                    if (lane == 0) gN[nb * 128 + T] = qm;
                    bar_arrive(10, 544);
                } else {
                    mbar_wait(bar + B_G, 0);
                    load_q(q, h, qd * 512 + warp * 16 + g, t);
                    gelu_store<0, 2>(acc, hp);
                }
                gelu_store<2, 3>(acc, hp);
                if ((tid & 255) == 0) TLM(0, 5 + 2 * p);
            }
            bar_arrive(11, 544);
        }
        const bool fast = lds32(sb + OFF_G + 256) != 0;
        uint4* const op = gO + ((qd * 8 + wg) * NH + h) * 128 + (tid & 127);
        const uint64_t kd0 = mkdesc(SBD, 16, 256, 3);
        const uint64_t vd0 = mkdesc(SBD + 8192, OFF_ONE - 8192, 256, 3);
        if (fast) {
#pragma unroll 1
            for (int r = 0; r < 2; r++) {
                float o[12];
#pragma unroll
                for (int i = 0; i < 12; i++) o[i] = 0.f;
                uint64_t kd = kd0, vd = vd0;
                uint32_t qn[4];
#pragma unroll 1
                for (int half = 0; half < 2; half++) {
                    float s[32];
#pragma unroll
                    for (int i = 0; i < 32; i++) s[i] = i < 2 * NMUFU ? 0.f : MAGIC;
#pragma unroll 1
                    for (int c = 0; c < 4; c++) {
                        if (r == 0) mbar_wait(bar + B_KV + 8 * (half * 4 + c), 0);
                        if ((tid & 255) == 0 && c == 0) TLM(1, (tid >> 8) * 4 + r * 2 + half);
                        if (half == 1 && c == 3) {
                            if (r == 0) load_q(qn, h, qd * 512 + 256 + warp * 16 + g, t);
                            else if (lane == 0) mbar_arrive(bar + B_DONE);
                        }
#pragma unroll 1
                        for (int j = 0; j < 4; j++) {
                            uint32_t p[16];
                            wg_fence();
                            wgmma_qk_f16_acc(s, q, kd);
                            wg_commit();
                            wg_wait<0>();
                            pin<32>(s);
#pragma unroll
                            for (int i = 0; i < 16; i++)
                                p[i] = i < NMUFU ? pk_bf16(ex2f(s[2 * i]), ex2f(s[2 * i + 1])) : exp2_pair(s[2 * i], s[2 * i + 1]);
                            pin<16>(p);
                            wg_fence();
#pragma unroll
                            for (int u = 0; u < 4; u++) wgmma_pv(o, p + 4 * u, vd + u * VSTEP);
                            wg_commit();
                            kd += 128;
                            vd += 4 * VSTEP;
                        }
                        kd += 512;
                        vd += 16 * VSTEP;
                    }
                    wg_wait<0>();
                }
                pin<12>(o);
                if ((tid & 127) == 0 && r == 1) TLM(1, 8 + wg);
                store_o(o, op + r * (4 * NH * 128), ep & 1);
#pragma unroll
                for (int i = 0; i < 4; i++) q[i] = qn[i];
            }
            if (tid == 0) { TLM(1, 12); TLC(0, 31); }
        } else {
            for (int c = 0; c < 8; c++) mbar_wait(bar + B_KV + 8 * c, 0);
            {
                float kc[8][8];
                proj16<8>(kc, x, wqkv, warp * 16, 256, DM + h * 16, g, t);
#pragma unroll
                for (int i = 0; i < 8; i++) {
                    const int T = warp + i * 16;
                    const int pos = ((T >> 6) * 16 + 2 * g) * 64 + (T & 63);
                    const uint32_t a = sb + (pos >> 8) * 16384 + (pos & 255) * 32 + t * 4, sw = ((T >> 2) & 1) << 4;
                    asm volatile("st.shared.u32 [%0], %1;" ::"r"(a + sw), "r"(pk_bf16(kc[i][0], kc[i][1])) : "memory");
                    asm volatile("st.shared.u32 [%0], %1;" ::"r"(a + (sw ^ 16)), "r"(pk_bf16(kc[i][4], kc[i][5])) : "memory");
                    asm volatile("st.shared.u32 [%0], %1;" ::"r"(a + 2048 + sw), "r"(pk_bf16(kc[i][2], kc[i][3])) : "memory");
                    asm volatile("st.shared.u32 [%0], %1;" ::"r"(a + 2048 + (sw ^ 16)), "r"(pk_bf16(kc[i][6], kc[i][7])) : "memory");
                }
                asm volatile("fence.proxy.async.shared::cta;" ::: "memory");
                bar_sync(8, 512);
            }
#pragma unroll 1
            for (int r = 0; r < 2; r++) {
                const int row = qd * 512 + r * 256 + warp * 16 + g;
                {
                    float qc[1][8];
                    proj16<1>(qc, x, wqkv, row - g, 0, h * 16, g, t);
#pragma unroll
                    for (int i = 0; i < 4; i++) q[i] = pk_bf16(qc[0][2 * i] * QSCALE, qc[0][2 * i + 1] * QSCALE);
                }
                float o[12];
#pragma unroll
                for (int i = 0; i < 12; i++) o[i] = 0.f;
                float m0 = -INFINITY, m1 = -INFINITY;
#pragma unroll 1
                for (int j = 0; j < 32; j++) {
                    const uint64_t kd = kd0 + (j >> 2) * 1024 + (j & 3) * 128, vd = vd0 + ((j >> 2) * 32 + (j & 3) * 4) * VSTEP;
                    float s[32];
                    uint32_t p[16];
                    wg_fence();
                    wgmma_qk_bf16_zero(s, q, kd);
                    wg_commit();
                    wg_wait<0>();
                    pin<32>(s);
                    pin<12>(o);
                    float n0 = m0, n1 = m1;
#pragma unroll
                    for (int i = 0; i < 8; i++) {
                        n0 = fmaxf(n0, fmaxf(s[4 * i], s[4 * i + 1]));
                        n1 = fmaxf(n1, fmaxf(s[4 * i + 2], s[4 * i + 3]));
                    }
                    n0 = fmaxf(n0, __shfl_xor_sync(0xffffffffu, n0, 1));
                    n1 = fmaxf(n1, __shfl_xor_sync(0xffffffffu, n1, 1));
                    n0 = fmaxf(n0, __shfl_xor_sync(0xffffffffu, n0, 2));
                    n1 = fmaxf(n1, __shfl_xor_sync(0xffffffffu, n1, 2));
                    const float c0 = ex2f(m0 - n0), c1 = ex2f(m1 - n1);
                    m0 = n0;
                    m1 = n1;
#pragma unroll
                    for (int i = 0; i < 3; i++) { o[4 * i] *= c0; o[4 * i + 1] *= c0; o[4 * i + 2] *= c1; o[4 * i + 3] *= c1; }
#pragma unroll
                    for (int i = 0; i < 8; i++) {
                        p[2 * i] = pk_bf16(ex2f(s[4 * i] - m0), ex2f(s[4 * i + 1] - m0));
                        p[2 * i + 1] = pk_bf16(ex2f(s[4 * i + 2] - m1), ex2f(s[4 * i + 3] - m1));
                    }
                    pin<16>(p);
                    pin<12>(o);
                    wg_fence();
#pragma unroll
                    for (int u = 0; u < 4; u++) wgmma_pv(o, p + 4 * u, vd + u * VSTEP);
                    wg_commit();
                }
                wg_wait<0>();
                pin<12>(o);
                if (r == 1 && lane == 0) mbar_arrive(bar + B_DONE);
                store_o(o, op + r * (4 * NH * 128), ep & 1);
            }
        }
        {
            const uint4* src = gO + (rb * NH + wg * 8) * 128 + (tid & 127);
            uint4 v[8];
#pragma unroll
            for (int i = 0; i < 8; i++) v[i] = load_o(src + i * 128);
            mbar_wait(bar + B_DONE, 0);
            mbar_wait(bar + B_G2, 0);
            const int lr = (warp & 3) * 16 + g;
            const uint32_t g0 = lds32(sb + OFF_G + lr * 4), g1 = lds32(sb + OFF_G + lr * 4 + 32);
            const uint32_t a0 = sb + wg * 16384 + lr * 128 + (t >> 1) * 4;
#pragma unroll
            for (int i = 0; i < 8; i++) {
                if ((i & 3) == 0) {
                    int spins = 0;
                    while (__any_sync(0xffffffffu, (((v[i].x ^ ep) | (v[i + 1].x ^ ep) | (v[i + 2].x ^ ep) | (v[i + 3].x ^ ep)) & 1) != 0)) {
                        if (++spins > (1 << 22)) __trap();
#pragma unroll
                        for (int k = i; k < 8; k++)
                            if (((v[k].x ^ ep) & 1) != 0) v[k] = load_o(src + k * 128);
                    }
                }
                const uint32_t a = a0 + (i >> 2) * 8192 + ((((i & 3) * 2 + (t & 1)) ^ g) << 4);
                sts32(a, bmul2(v[i].x, g0));
                sts32(a + 8, bmul2(v[i].y, g0));
                sts32(a + 1024, bmul2(v[i].z, g1));
                sts32(a + 1024 + 8, bmul2(v[i].w, g1));
                if ((i & 3) == 3) {
                    asm volatile("fence.proxy.async.shared::cta;" ::: "memory");
                    __syncwarp();
                    if (lane == 0) mbar_arrive(bar + B_T + 8 * (wg * 2 + (i >> 2)));
                    if ((tid & 127) == 0) TLM(1, 20 + wg * 2 + (i >> 2));
                }
            }
        }
    } else {
        if (warp == 16) {
            if (elect()) {
                int s = 0, par = 1, k0 = rank * 32, k3 = rank * 32;
#pragma unroll 1
                for (int it = 0; it < 32; it++) {
                    const uint32_t fb = bar + B_F1 + 8 * s, dst = sb + OFF_R + s * 16384;
                    mbar_wait(bar + B_E1 + 8 * s, par);
                    if (it < 16 && ((KVMASK >> it) & 1)) {
                        mbar_expect(fb, 16384);
                        tma3d_mc(dst + rank * 8192, &tm.kv, nb * 64, k3, 1, fb);
                        k3 += 64;
                    } else {
                        mbar_expect(fb, 12288);
                        if (it < 16) {
                            tma3d_mc(dst + rank * 6144, &tm.q, 0, k0, nb * 2, fb);
                            tma3d_mc(dst + rank * 6144 + 4096, &tm.f1, 0, k0, nb * 7, fb);
                            const int c = (k0 >> 6) + 1;
                            if (c < 8) {
                                mbar_expect(bar + B_X + 8 * c, 16384);
                                tma2d(sb + c * 16384, &tm.x, c * 64, mb * 128, bar + B_X + 8 * c);
                            }
                        } else {
                            tma3d_mc(dst + rank * 6144, &tm.f3, 0, k0 & 511, nb * 7 + (it < 24 ? 1 : 4), fb);
                        }
                        k0 += 64;
                    }
                    if (++s == 6) { s = 0; par ^= 1; }
                }
                const int h = cl >> 1;
                cnt_wait(gCntQ + (h >> 2) * 32, ep * 16);
                asm volatile("fence.proxy.async.global;" ::: "memory");
                TLM(0, 10);
#pragma unroll 1
                for (int c = 0; c < 8; c++) {
                    if (c >= 2) {
                        mbar_wait(bar + B_E1 + 8 * s, par);
                        if (++s == 6) { s = 0; par ^= 1; }
                    }
                    mbar_expect(bar + B_KV + 8 * c, 16384);
                    bulk_mc(sb + c * 16384 + rank * 8192, gKV + (size_t)h * (SEQ * 64) + c * 16384 + rank * 8192, 8192, bar + B_KV + 8 * c);
                }
#pragma unroll 1
                for (s = 0; s < 4; s++) {
                    mbar_expect(bar + B_F2 + 8 * s, 24576);
                    tma5d_mc(sb + OFF_R + s * 24576 + 8192 + rank * 8192, &tm.w2, cb * 128 + rank * 64, s * 2, bar + B_F2 + 8 * s);
                }
                cnt_wait(gCntH + rb * 32, ep * 8);
                asm volatile("fence.proxy.async.global;" ::: "memory");
                TLM(1, 13);
#pragma unroll 1
                for (s = 0; s < 4; s++) tma2d(sb + OFF_R + s * 24576, &tm.h, s * 64, rb * 64, bar + B_F2 + 8 * s);
            }
        } else if (warp == 17) {
            mbar_wait(bar + B_X + 8 * 7, 0);
            if (lane == 0) {
                l2_prefetch((const uint8_t*)w2 + (size_t)blockIdx.x * 14336, 14336);
                l2_prefetch((const uint8_t*)wo + (size_t)blockIdx.x * 4096, 4096);
                map_prefetch(&tm.h); map_prefetch(&tm.w2); map_prefetch(&tm.wo);
                TLM(0, 11);
            }
            const int h = cl >> 1, qd = (cl & 1) * 2 + rank;
            if (lane == 0) cnt_wait(gCntQ + (h >> 2) * 32, ep * 16);
            __syncwarp();
            const int hb = h >> 2;
            const uint4 kq = __ldcg((const uint4*)(gN + 1024 + hb * 128 + lane * 4));
            const uint4 vq = __ldcg((const uint4*)(gN + 2048 + hb * 128 + lane * 4));
            const float qq = ldcg_f(gN + hb * 128 + qd * 32 + lane);
            const float kf = __uint_as_float(__reduce_max_sync(0xffffffffu, max(max(kq.x, kq.y), max(kq.z, kq.w))));
            const float vf = __uint_as_float(__reduce_max_sync(0xffffffffu, max(max(vq.x, vq.y), max(vq.z, vq.w))));
            const float qf = __uint_as_float(__reduce_max_sync(0xffffffffu, __float_as_uint(qq)));
            if (lane == 0) {
                sts32(sb + OFF_G + 256, (kf <= 1.0e6f) && (qf <= 1.0e6f) && (kf * qf <= 3400.f) && (vf <= 1.0e12f));
                mbar_arrive(bar + B_G);
            }
        } else {
            {
                float c[2][4] = {{0.f, 0.f, 0.f, 0.f}, {0.f, 0.f, 0.f, 0.f}};
                const int lr = (warp - 18) * 32 + (lane & 15);
                const uint32_t xa = sb + ((nb >> 2) * 64 + lr) * 128;
#pragma unroll 1
                for (int ch = 0; ch < 8; ch++) {
                    uint32_t gw[8];
#pragma unroll
                    for (int i = 0; i < 8; i++) gw[i] = *(const uint32_t*)(gate + ch * 64 + i * 8 + t * 2);
                    mbar_wait(bar + B_X + 8 * ch, 0);
#pragma unroll
                    for (int k = 0; k < 4; k++)
#pragma unroll
                        for (int m = 0; m < 2; m++) {
                            uint32_t a[4];
                            asm volatile("ldmatrix.sync.aligned.m8n8.x4.shared.b16 {%0, %1, %2, %3}, [%4];" : "=r"(a[0]), "=r"(a[1]), "=r"(a[2]), "=r"(a[3])
                                         : "r"(xa + ch * 16384 + m * 2048 + (((k * 2 + (lane >> 4)) ^ (lane & 7)) << 4)));
                            asm volatile("mma.sync.aligned.m16n8k16.row.col.f32.bf16.bf16.f32 {%0,%1,%2,%3}, {%4,%5,%6,%7}, {%8,%9}, {%0,%1,%2,%3};"
                                         : "+f"(c[m][0]), "+f"(c[m][1]), "+f"(c[m][2]), "+f"(c[m][3])
                                         : "r"(a[0]), "r"(a[1]), "r"(a[2]), "r"(a[3]), "r"(gw[2 * k]), "r"(gw[2 * k + 1]));
                        }
                }
                const float z = t == 0 ? c[0][0] : t == 1 ? c[0][2] : t == 2 ? c[1][0] : c[1][2];
                const float gv = 1.f / (1.f + __expf(-z));
                sts32(sb + OFF_G + ((warp - 18) * 32 + t * 8 + g) * 4, pk_bf16(gv, gv));
                __syncwarp();
                if (lane == 0) mbar_arrive(bar + B_G2);
                if (tid == 576) TLM(0, 12);
            }
            bar_sync(warp - 8, 544);
            if (warp == 18) { if (lane == 0) cnt_add(gCntQ + nb * 32); }
            else if (lane < 2) cnt_add(gCntH + (mb * 2 + lane) * 32);
        }
        __syncwarp();
        float acc[64];
#pragma unroll
        for (int i = 0; i < 64; i++) acc[i] = 0.f;
#pragma unroll 1
        for (int io = 0; io < 7; io++) {
#pragma unroll
            for (int s = 0; s < 4; s++) {
                const int it = io * 4 + s;
                mbar_wait(bar + B_F2 + 8 * s, io & 1);
                if (tid == 512 && s == 0 && (io == 0 || io == 4)) TLM(1, 14 + io / 4);
                const uint64_t dA = mkdesc(SBD + OFF_R + s * 24576, 16, 1024, 1);
                const uint64_t dB = mkdesc(SBD + OFF_R + s * 24576 + 8192, 8192, 1024, 1);
                wg_fence();
#pragma unroll
                for (int kk = 0; kk < EXP_FKK; kk++) wgmma_ss_n128(acc, dA + kk * 2, dB + kk * 128);
                wg_commit();
                if (warp < 18 && it >= 2 && it < 26) {
                    const int s2 = (s + 2) & 3;
                    mbar_wait(bar + B_E2 + 8 * s2, (io - (s < 2)) & 1);
                    if (elect()) {
                        if (warp == 16) {
                            mbar_expect(bar + B_F2 + 8 * s2, 24576);
                            tma5d_mc(sb + OFF_R + s2 * 24576 + 8192 + rank * 8192, &tm.w2, cb * 128 + rank * 64, it * 2 + 4, bar + B_F2 + 8 * s2);
                        } else {
                            asm volatile("fence.proxy.async.global;" ::: "memory");
                            tma2d(sb + OFF_R + s2 * 24576, &tm.h, it * 64 + 128, rb * 64, bar + B_F2 + 8 * s2);
                        }
                    }
                    __syncwarp();
                }
                wg_wait<1>();
                if (it >= 1 && lane < 2) mbar_arrive_cluster(bar + B_E2 + 8 * ((s + 3) & 3), lane);
            }
        }
        wg_wait<0>();
        if (lane < 2) mbar_arrive_cluster(bar + B_E2 + 8 * 3, lane);
        pin<64>(acc);
        if (warp == 16) {
            if (lane == 0) TLM(1, 16);
            for (int s = 0; s < 4; s++) mbar_wait(bar + B_E2 + 8 * s, 0);
            if (elect()) {
#pragma unroll
                for (int i = 0; i < 8; i++) mbar_expect(bar + B_T + 8 * i, 16384);
#pragma unroll
                for (int i = 0; i < 6; i++) tma2d_mc(sb + OFF_R + i * 16384 + rank * 8192, &tm.wo, cb * 128 + rank * 64, i * 64, bar + B_T + 8 * i);
            }
            __syncwarp();
        }
        {
            mbar_wait(bar + B_G2, 0);
            const float ga = bf_lo(lds32(sb + OFF_G + ((warp - 16) * 16 + g) * 4)), gb = bf_lo(lds32(sb + OFF_G + ((warp - 16) * 16 + g) * 4 + 32));
            const float g0 = 1.f - ga, g1 = 1.f - gb;
#pragma unroll
            for (int j = 0; j < 16; j++) {
                const uint32_t bv = lds32(sb + OFF_BIAS + 576 + j * 16 + t * 4);
                acc[4 * j] = (acc[4 * j] + bf_lo(bv)) * g0;
                acc[4 * j + 1] = (acc[4 * j + 1] + bf_hi(bv)) * g0;
                acc[4 * j + 2] = (acc[4 * j + 2] + bf_lo(bv)) * g1;
                acc[4 * j + 3] = (acc[4 * j + 3] + bf_hi(bv)) * g1;
            }
            pin<64>(acc);
        }
        if (warp == 17) {
            mbar_wait(bar + B_DONE, 0);
            if (elect()) {
#pragma unroll
                for (int i = 0; i < 4; i++)
                    tma2d(sb + 65536 + i * 8192, &tm.wo, cb * 128 + (i & 1) * 64, (6 + (i >> 1)) * 64, bar + B_T + 8 * (6 + (i >> 1)));
            }
            __syncwarp();
        }
        if (tid == 512) TLM(1, 17);
#pragma unroll
        for (int i = 0; i < 8; i++) {
            mbar_wait(bar + B_T + 8 * i, 0);
            const uint64_t dA = mkdesc(SBD + i * 8192, 16, 1024, 1);
            const uint64_t dB = mkdesc(i < 6 ? SBD + OFF_R + i * 16384 : SBD + 65536 + (i - 6) * 16384, 8192, 1024, 1);
            wg_fence();
#pragma unroll
            for (int kk = 0; kk < 4; kk++) wgmma_ss_n128(acc, dA + kk * 2, dB + kk * 128);
            wg_commit();
        }
        wg_wait<0>();
        pin<64>(acc);
        if (tid == 512) TLM(1, 18);
        {
            const uint32_t st = sb + 98304 + (warp - 16) * 4352;
            const uint32_t wa = st + (lane & 15) * 272 + (lane >> 4) * 16;
#pragma unroll
            for (int j = 0; j < 8; j++)
                asm volatile("stmatrix.sync.aligned.m8n8.x4.shared.b16 [%0], {%1, %2, %3, %4};" ::"r"(wa + j * 32),
                             "r"(pk_bf16(acc[8 * j], acc[8 * j + 1])), "r"(pk_bf16(acc[8 * j + 2], acc[8 * j + 3])),
                             "r"(pk_bf16(acc[8 * j + 4], acc[8 * j + 5])), "r"(pk_bf16(acc[8 * j + 6], acc[8 * j + 7])) : "memory");
            __syncwarp();
            __nv_bfloat16* op = out + (size_t)(rb * 64 + (warp - 16) * 16 + (lane >> 4)) * DM + cb * 128 + (lane & 15) * 8;
#pragma unroll
            for (int j = 0; j < 8; j++) {
                uint4 v;
                asm volatile("ld.shared.v4.u32 {%0, %1, %2, %3}, [%4];" : "=r"(v.x), "=r"(v.y), "=r"(v.z), "=r"(v.w)
                             : "r"(st + (2 * j + (lane >> 4)) * 272 + (lane & 15) * 16));
                *(uint4*)(op + (size_t)j * 2 * DM) = v;
            }
        }
        if (tid == 512) { gEpoch[blockIdx.x] = ep; TLM(1, 19); }
    }
}

typedef CUresult (*EncodeFn)(CUtensorMap*, CUtensorMapDataType, cuuint32_t, void*, const cuuint64_t*, const cuuint64_t*, const cuuint32_t*,
                             const cuuint32_t*, CUtensorMapInterleave, CUtensorMapSwizzle, CUtensorMapL2promotion, CUtensorMapFloatOOBfill);

static void make_map(EncodeFn enc, CUtensorMap* m, const void* p, int rank, const cuuint64_t* dims, const cuuint64_t* strides,
                     const cuuint32_t* box, CUtensorMapSwizzle swz) {
    const cuuint32_t es[5] = {1, 1, 1, 1, 1};
    enc(m, CU_TENSOR_MAP_DATA_TYPE_BFLOAT16, rank, (void*)p, dims, strides, box, es, CU_TENSOR_MAP_INTERLEAVE_NONE, swz,
        CU_TENSOR_MAP_L2_PROMOTION_L2_128B, CU_TENSOR_MAP_FLOAT_OOB_FILL_NONE);
}

extern "C" void kernel_launch(void* const* d_in, const int* in_sizes, int n_in, void* d_out, int out_size) {
    const __nv_bfloat16* x = (const __nv_bfloat16*)d_in[0];
    const __nv_bfloat16* wqkv = (const __nv_bfloat16*)d_in[1];
    const __nv_bfloat16* wo = (const __nv_bfloat16*)d_in[2];
    const __nv_bfloat16* w1 = (const __nv_bfloat16*)d_in[4];
    const __nv_bfloat16* b1 = (const __nv_bfloat16*)d_in[5];
    const __nv_bfloat16* w2 = (const __nv_bfloat16*)d_in[6];
    const __nv_bfloat16* b2 = (const __nv_bfloat16*)d_in[7];
    const __nv_bfloat16* gate = (const __nv_bfloat16*)d_in[8];

    void* fp = nullptr;
    cudaDriverEntryPointQueryResult qr;
    cudaGetDriverEntryPoint("cuTensorMapEncodeTiled", &fp, cudaEnableDefault, &qr);
    EncodeFn enc = (EncodeFn)fp;
    void* pH;
    cudaGetSymbolAddress(&pH, gH);

    Maps tm;
    const CUtensorMapSwizzle S128 = CU_TENSOR_MAP_SWIZZLE_128B, S64 = CU_TENSOR_MAP_SWIZZLE_64B;
    { cuuint64_t d[2] = {DM, SEQ}, s[1] = {DM * 2}; cuuint32_t b[2] = {64, 128}; make_map(enc, &tm.x, x, 2, d, s, b, S128); }
    { cuuint64_t d[3] = {DM, DM, 3}, s[2] = {3 * DM * 2, DM * 2}; cuuint32_t b[3] = {64, 32, 2}; make_map(enc, &tm.kv, wqkv, 3, d, s, b, S128); }
    { cuuint64_t d[3] = {32, DM, 3 * DM / 32}, s[2] = {3 * DM * 2, 64}; cuuint32_t b[3] = {32, 32, 2}; make_map(enc, &tm.q, wqkv, 3, d, s, b, S64); }
    { cuuint64_t d[3] = {32, DM, FF / 32}, s[2] = {FF * 2, 64}; cuuint32_t b[3] = {32, 32, 1}; make_map(enc, &tm.f1, w1, 3, d, s, b, S64); }
    { cuuint64_t d[3] = {32, DM, FF / 32}, s[2] = {FF * 2, 64}; cuuint32_t b[3] = {32, 32, 3}; make_map(enc, &tm.f3, w1, 3, d, s, b, S64); }
    { cuuint64_t d[2] = {FF, SEQ}, s[1] = {FF * 2}; cuuint32_t b[2] = {64, 64}; make_map(enc, &tm.h, pH, 2, d, s, b, S128); }
    { cuuint64_t d[5] = {DM, 2, 4, 4, FF / 32}, s[4] = {1024, 8 * 1024, 2 * 1024, 32 * 1024}; cuuint32_t b[5] = {64, 2, 4, 4, 2};
      make_map(enc, &tm.w2, w2, 5, d, s, b, S128); }
    { cuuint64_t d[2] = {DM, DM}, s[1] = {DM * 2}; cuuint32_t b[2] = {64, 64}; make_map(enc, &tm.wo, wo, 2, d, s, b, S128); }

    cudaFuncSetAttribute(fused_kernel, cudaFuncAttributeMaxDynamicSharedMemorySize, SMEM_BYTES);
    fused_kernel<<<128, 640, SMEM_BYTES, cudaStreamPerThread>>>(tm, x, wqkv, wo, w1, b1, w2, b2, gate, (__nv_bfloat16*)d_out);
}
```

```cpp
#include <cuda_runtime.h>
#include <cuda_bf16.h>
#include <cuda_fp16.h>
#include <cuda.h>
#include <stdint.h>

#define SEQ 2048
#define DM 512
#define FF 1792
#define NH 32

__device__ __align__(1024) uint8_t gQ[NH * SEQ * 32];
__device__ __align__(1024) uint8_t gKV[NH * SEQ * 64];
__device__ __align__(1024) __nv_bfloat16 gH[SEQ * FF];
__device__ __align__(1024) uint4 gO[32 * NH * 128];
__device__ float gG[SEQ];
__device__ float gN[3 * 8 * 128];
__device__ unsigned int gCntQ[8 * 32];
__device__ unsigned int gCntH[32 * 32];
__device__ unsigned int gEpoch[128];

__device__ __forceinline__ uint32_t smem_u32(const void* p) { return (uint32_t)__cvta_generic_to_shared(p); }
__device__ __forceinline__ void mbar_init(uint32_t a, uint32_t c) { asm volatile("mbarrier.init.shared::cta.b64 [%0], %1;" ::"r"(a), "r"(c)); }
__device__ __forceinline__ void mbar_expect(uint32_t a, uint32_t b) { asm volatile("mbarrier.arrive.expect_tx.shared::cta.b64 _, [%0], %1;" ::"r"(a), "r"(b) : "memory"); }
__device__ __forceinline__ void mbar_arrive(uint32_t a) { asm volatile("mbarrier.arrive.shared::cta.b64 _, [%0];" ::"r"(a) : "memory"); }
__device__ __forceinline__ void mbar_wait(uint32_t a, uint32_t ph) {
    asm volatile("{\n.reg .pred p;\n.reg .u32 n;\nmov.u32 n, 0;\nW_%=:\nmbarrier.try_wait.parity.shared::cta.b64 p, [%0], %1;\n@p bra D_%=;\n"
                 "add.u32 n, n, 1;\nsetp.lt.u32 p, n, 0x400000;\n@p bra W_%=;\ntrap;\nD_%=:\n}" ::"r"(a), "r"(ph) : "memory");
}
__device__ __forceinline__ void mbar_arrive_cluster(uint32_t a, uint32_t cta) {
    asm volatile("{\n.reg .b32 r;\nmapa.shared::cluster.u32 r, %0, %1;\nmbarrier.arrive.shared::cluster.b64 _, [r];\n}" ::"r"(a), "r"(cta) : "memory");
}
__device__ __forceinline__ void bar_sync(int id, int n) { asm volatile("bar.sync %0, %1;" ::"r"(id), "r"(n) : "memory"); }
__device__ __forceinline__ void bar_arrive(int id, int n) { asm volatile("bar.arrive %0, %1;" ::"r"(id), "r"(n) : "memory"); }
__device__ __forceinline__ uint32_t cluster_rank() { uint32_t r; asm("mov.u32 %0, %%cluster_ctarank;" : "=r"(r)); return r; }
__device__ __forceinline__ void cnt_add(unsigned int* c) { asm volatile("red.release.gpu.global.add.u32 [%0], 1;" ::"l"(c) : "memory"); }
__device__ __forceinline__ void cnt_wait(const unsigned int* c, uint32_t target) {
    uint32_t v;
    int spins = 0;
    while (true) {
        asm volatile("ld.acquire.gpu.global.u32 %0, [%1];" : "=r"(v) : "l"(c) : "memory");
        if ((int)(v - target) >= 0) break;
        if (++spins > (1 << 22)) __trap();
        __nanosleep(40);
    }
}
__device__ __forceinline__ void tma2d(uint32_t dst, const CUtensorMap* m, int c0, int c1, uint32_t bar) {
    asm volatile("cp.async.bulk.tensor.2d.shared::cluster.global.mbarrier::complete_tx::bytes [%0], [%1, {%3, %4}], [%2];"
                 ::"r"(dst), "l"(m), "r"(bar), "r"(c0), "r"(c1) : "memory");
}
__device__ __forceinline__ void tma2d_mc(uint32_t dst, const CUtensorMap* m, int c0, int c1, uint32_t bar) {
    asm volatile("cp.async.bulk.tensor.2d.shared::cluster.global.mbarrier::complete_tx::bytes.multicast::cluster [%0], [%1, {%3, %4}], [%2], %5;"
                 ::"r"(dst), "l"(m), "r"(bar), "r"(c0), "r"(c1), "h"((uint16_t)3) : "memory");
}
__device__ __forceinline__ void tma3d_mc(uint32_t dst, const CUtensorMap* m, int c0, int c1, int c2, uint32_t bar) {
    asm volatile("cp.async.bulk.tensor.3d.shared::cluster.global.mbarrier::complete_tx::bytes.multicast::cluster [%0], [%1, {%3, %4, %5}], [%2], %6;"
                 ::"r"(dst), "l"(m), "r"(bar), "r"(c0), "r"(c1), "r"(c2), "h"((uint16_t)3) : "memory");
}
__device__ __forceinline__ void tma5d_mc(uint32_t dst, const CUtensorMap* m, int c0, int c4, uint32_t bar) {
    asm volatile("cp.async.bulk.tensor.5d.shared::cluster.global.mbarrier::complete_tx::bytes.multicast::cluster [%0], [%1, {%3, %5, %5, %5, %4}], [%2], %6;"
                 ::"r"(dst), "l"(m), "r"(bar), "r"(c0), "r"(c4), "r"(0), "h"((uint16_t)3) : "memory");
}
__device__ __forceinline__ void bulk_mc(uint32_t dst, const void* src, uint32_t bytes, uint32_t bar) {
    asm volatile("cp.async.bulk.shared::cluster.global.mbarrier::complete_tx::bytes.multicast::cluster [%0], [%1], %2, [%3], %4;"
                 ::"r"(dst), "l"(src), "r"(bytes), "r"(bar), "h"((uint16_t)3) : "memory");
}
__device__ __forceinline__ void l2_prefetch(const void* src, uint32_t bytes) {
    asm volatile("cp.async.bulk.prefetch.L2.global [%0], %1;" ::"l"(src), "r"(bytes) : "memory");
}
__device__ __forceinline__ void map_prefetch(const CUtensorMap* m) { asm volatile("prefetch.tensormap [%0];" ::"l"(m) : "memory"); }
__device__ __forceinline__ void wg_fence() { asm volatile("wgmma.fence.sync.aligned;" ::: "memory"); }
__device__ __forceinline__ void wg_commit() { asm volatile("wgmma.commit_group.sync.aligned;" ::: "memory"); }
template <int N> __device__ __forceinline__ void wg_wait() { asm volatile("wgmma.wait_group.sync.aligned %0;" ::"n"(N) : "memory"); }
template <int N> __device__ __forceinline__ void pin(float* s) {
#pragma unroll
    for (int i = 0; i < N; i++) asm volatile("" : "+f"(s[i])::"memory");
}
template <int N> __device__ __forceinline__ void pin(uint32_t* s) {
#pragma unroll
    for (int i = 0; i < N; i++) asm volatile("" : "+r"(s[i])::"memory");
}
__device__ __forceinline__ uint64_t mkdesc(uint32_t addr, uint32_t lbo, uint32_t sbo, uint32_t swz) {
    return (uint64_t)((addr & 0x3FFFF) >> 4) | ((uint64_t)(lbo >> 4) << 16) | ((uint64_t)(sbo >> 4) << 32) | ((uint64_t)swz << 62);
}
__device__ __forceinline__ float ex2f(float x) { float y; asm("ex2.approx.ftz.f32 %0, %1;" : "=f"(y) : "f"(x)); return y; }
__device__ __forceinline__ float tanhf_(float x) { float y; asm("tanh.approx.f32 %0, %1;" : "=f"(y) : "f"(x)); return y; }
__device__ __forceinline__ uint32_t pk_bf16(float lo, float hi) { uint32_t r; asm("cvt.rn.bf16x2.f32 %0, %1, %2;" : "=r"(r) : "f"(hi), "f"(lo)); return r; }
__device__ __forceinline__ uint32_t pk_f16(float lo, float hi) { uint32_t r; asm("cvt.rn.f16x2.f32 %0, %1, %2;" : "=r"(r) : "f"(hi), "f"(lo)); return r; }
__device__ __forceinline__ float bf_lo(uint32_t v) { return __uint_as_float(v << 16); }
__device__ __forceinline__ float bf_hi(uint32_t v) { return __uint_as_float(v & 0xffff0000u); }
__device__ __forceinline__ float dot8(const uint4& a, const uint4& b) {
    return fmaf(bf_lo(a.x), bf_lo(b.x), fmaf(bf_hi(a.x), bf_hi(b.x), fmaf(bf_lo(a.y), bf_lo(b.y), bf_hi(a.y) * bf_hi(b.y)))) +
           fmaf(bf_lo(a.z), bf_lo(b.z), fmaf(bf_hi(a.z), bf_hi(b.z), fmaf(bf_lo(a.w), bf_lo(b.w), bf_hi(a.w) * bf_hi(b.w))));
}
__device__ __forceinline__ float ldcg_f(const float* p) { return __ldcg(p); }

#define TLM(k, slot) do {} while (0)
#define TLC(k, slot) do {} while (0)

__device__ __forceinline__ void wgmma_ss_n128(float* d, uint64_t da, uint64_t db) {
    asm volatile("wgmma.mma_async.sync.aligned.m64n128k16.f32.bf16.bf16 {"
        "%0, %1, %2, %3, %4, %5, %6, %7, %8, %9, %10, %11, %12, %13, %14, %15,"
        "%16, %17, %18, %19, %20, %21, %22, %23, %24, %25, %26, %27, %28, %29, %30, %31,"
        "%32, %33, %34, %35, %36, %37, %38, %39, %40, %41, %42, %43, %44, %45, %46, %47,"
        "%48, %49, %50, %51, %52, %53, %54, %55, %56, %57, %58, %59, %60, %61, %62, %63}, %64, %65, 1, 1, 1, 0, 1;\n"
        :
        "+f"(d[0]), "+f"(d[1]), "+f"(d[2]), "+f"(d[3]), "+f"(d[4]), "+f"(d[5]), "+f"(d[6]), "+f"(d[7]),
        "+f"(d[8]), "+f"(d[9]), "+f"(d[10]), "+f"(d[11]), "+f"(d[12]), "+f"(d[13]), "+f"(d[14]), "+f"(d[15]),
        "+f"(d[16]), "+f"(d[17]), "+f"(d[18]), "+f"(d[19]), "+f"(d[20]), "+f"(d[21]), "+f"(d[22]), "+f"(d[23]),
        "+f"(d[24]), "+f"(d[25]), "+f"(d[26]), "+f"(d[27]), "+f"(d[28]), "+f"(d[29]), "+f"(d[30]), "+f"(d[31]),
        "+f"(d[32]), "+f"(d[33]), "+f"(d[34]), "+f"(d[35]), "+f"(d[36]), "+f"(d[37]), "+f"(d[38]), "+f"(d[39]),
        "+f"(d[40]), "+f"(d[41]), "+f"(d[42]), "+f"(d[43]), "+f"(d[44]), "+f"(d[45]), "+f"(d[46]), "+f"(d[47]),
        "+f"(d[48]), "+f"(d[49]), "+f"(d[50]), "+f"(d[51]), "+f"(d[52]), "+f"(d[53]), "+f"(d[54]), "+f"(d[55]),
        "+f"(d[56]), "+f"(d[57]), "+f"(d[58]), "+f"(d[59]), "+f"(d[60]), "+f"(d[61]), "+f"(d[62]), "+f"(d[63])
        : "l"(da), "l"(db));
}
__device__ __forceinline__ void wgmma_ss_n96(float* d, uint64_t da, uint64_t db) {
    asm volatile("wgmma.mma_async.sync.aligned.m64n96k16.f32.bf16.bf16 {"
        "%0, %1, %2, %3, %4, %5, %6, %7, %8, %9, %10, %11, %12, %13, %14, %15,"
        "%16, %17, %18, %19, %20, %21, %22, %23, %24, %25, %26, %27, %28, %29, %30, %31,"
        "%32, %33, %34, %35, %36, %37, %38, %39, %40, %41, %42, %43, %44, %45, %46, %47}, %48, %49, 1, 1, 1, 0, 1;\n"
        :
        "+f"(d[0]), "+f"(d[1]), "+f"(d[2]), "+f"(d[3]), "+f"(d[4]), "+f"(d[5]), "+f"(d[6]), "+f"(d[7]),
        "+f"(d[8]), "+f"(d[9]), "+f"(d[10]), "+f"(d[11]), "+f"(d[12]), "+f"(d[13]), "+f"(d[14]), "+f"(d[15]),
        "+f"(d[16]), "+f"(d[17]), "+f"(d[18]), "+f"(d[19]), "+f"(d[20]), "+f"(d[21]), "+f"(d[22]), "+f"(d[23]),
        "+f"(d[24]), "+f"(d[25]), "+f"(d[26]), "+f"(d[27]), "+f"(d[28]), "+f"(d[29]), "+f"(d[30]), "+f"(d[31]),
        "+f"(d[32]), "+f"(d[33]), "+f"(d[34]), "+f"(d[35]), "+f"(d[36]), "+f"(d[37]), "+f"(d[38]), "+f"(d[39]),
        "+f"(d[40]), "+f"(d[41]), "+f"(d[42]), "+f"(d[43]), "+f"(d[44]), "+f"(d[45]), "+f"(d[46]), "+f"(d[47])
        : "l"(da), "l"(db));
}
__device__ __forceinline__ void wgmma_ss_n64(float* d, uint64_t da, uint64_t db) {
    asm volatile("wgmma.mma_async.sync.aligned.m64n64k16.f32.bf16.bf16 {"
        "%0, %1, %2, %3, %4, %5, %6, %7, %8, %9, %10, %11, %12, %13, %14, %15,"
        "%16, %17, %18, %19, %20, %21, %22, %23, %24, %25, %26, %27, %28, %29, %30, %31}, %32, %33, 1, 1, 1, 0, 1;\n"
        :
        "+f"(d[0]), "+f"(d[1]), "+f"(d[2]), "+f"(d[3]), "+f"(d[4]), "+f"(d[5]), "+f"(d[6]), "+f"(d[7]),
        "+f"(d[8]), "+f"(d[9]), "+f"(d[10]), "+f"(d[11]), "+f"(d[12]), "+f"(d[13]), "+f"(d[14]), "+f"(d[15]),
        "+f"(d[16]), "+f"(d[17]), "+f"(d[18]), "+f"(d[19]), "+f"(d[20]), "+f"(d[21]), "+f"(d[22]), "+f"(d[23]),
        "+f"(d[24]), "+f"(d[25]), "+f"(d[26]), "+f"(d[27]), "+f"(d[28]), "+f"(d[29]), "+f"(d[30]), "+f"(d[31])
        : "l"(da), "l"(db));
}
__device__ __forceinline__ void wgmma_qk_f16_acc(float* d, const uint32_t* a, uint64_t db) {
    asm volatile("wgmma.mma_async.sync.aligned.m64n64k16.f32.f16.f16 {"
        "%0, %1, %2, %3, %4, %5, %6, %7, %8, %9, %10, %11, %12, %13, %14, %15,"
        "%16, %17, %18, %19, %20, %21, %22, %23, %24, %25, %26, %27, %28, %29, %30, %31}, {%32, %33, %34, %35}, %36, 1, 1, 1, 0;\n"
        :
        "+f"(d[0]), "+f"(d[1]), "+f"(d[2]), "+f"(d[3]), "+f"(d[4]), "+f"(d[5]), "+f"(d[6]), "+f"(d[7]),
        "+f"(d[8]), "+f"(d[9]), "+f"(d[10]), "+f"(d[11]), "+f"(d[12]), "+f"(d[13]), "+f"(d[14]), "+f"(d[15]),
        "+f"(d[16]), "+f"(d[17]), "+f"(d[18]), "+f"(d[19]), "+f"(d[20]), "+f"(d[21]), "+f"(d[22]), "+f"(d[23]),
        "+f"(d[24]), "+f"(d[25]), "+f"(d[26]), "+f"(d[27]), "+f"(d[28]), "+f"(d[29]), "+f"(d[30]), "+f"(d[31])
        : "r"(a[0]), "r"(a[1]), "r"(a[2]), "r"(a[3]), "l"(db));
}
__device__ __forceinline__ void wgmma_qk_bf16_zero(float* d, const uint32_t* a, uint64_t db) {
    asm volatile("wgmma.mma_async.sync.aligned.m64n64k16.f32.bf16.bf16 {"
        "%0, %1, %2, %3, %4, %5, %6, %7, %8, %9, %10, %11, %12, %13, %14, %15,"
        "%16, %17, %18, %19, %20, %21, %22, %23, %24, %25, %26, %27, %28, %29, %30, %31}, {%32, %33, %34, %35}, %36, 0, 1, 1, 0;\n"
        :
        "=f"(d[0]), "=f"(d[1]), "=f"(d[2]), "=f"(d[3]), "=f"(d[4]), "=f"(d[5]), "=f"(d[6]), "=f"(d[7]),
        "=f"(d[8]), "=f"(d[9]), "=f"(d[10]), "=f"(d[11]), "=f"(d[12]), "=f"(d[13]), "=f"(d[14]), "=f"(d[15]),
        "=f"(d[16]), "=f"(d[17]), "=f"(d[18]), "=f"(d[19]), "=f"(d[20]), "=f"(d[21]), "=f"(d[22]), "=f"(d[23]),
        "=f"(d[24]), "=f"(d[25]), "=f"(d[26]), "=f"(d[27]), "=f"(d[28]), "=f"(d[29]), "=f"(d[30]), "=f"(d[31])
        : "r"(a[0]), "r"(a[1]), "r"(a[2]), "r"(a[3]), "l"(db));
}
__device__ __forceinline__ void wgmma_pv(float* d, const uint32_t* a, uint64_t db) {
    asm volatile("wgmma.mma_async.sync.aligned.m64n24k16.f32.bf16.bf16 {"
        "%0, %1, %2, %3, %4, %5, %6, %7, %8, %9, %10, %11}, {%12, %13, %14, %15}, %16, 1, 1, 1, 1;\n"
        :
        "+f"(d[0]), "+f"(d[1]), "+f"(d[2]), "+f"(d[3]), "+f"(d[4]), "+f"(d[5]), "+f"(d[6]), "+f"(d[7]),
        "+f"(d[8]), "+f"(d[9]), "+f"(d[10]), "+f"(d[11])
        : "r"(a[0]), "r"(a[1]), "r"(a[2]), "r"(a[3]), "l"(db));
}

template <int N> __device__ __forceinline__ void wgmma_ss(float* d, uint64_t a, uint64_t b) {
    if (N == 128) wgmma_ss_n128(d, a, b);
    if (N == 96) wgmma_ss_n96(d, a, b);
    if (N == 64) wgmma_ss_n64(d, a, b);
}

#define OFF_R 131072
#define OFF_ONE 229376
#define OFF_BAR 229888
#define OFF_BIAS (OFF_BAR + 512)
#define OFF_G (OFF_BIAS + 832)
#define SMEM_BYTES (OFF_G + 272)
#define SBD 1024u
#define B_X 0
#define B_F1 64
#define B_E1 112
#define B_KV 160
#define B_F2 224
#define B_E2 256
#define B_T 288
#define B_DONE 352
#define B_G 360
#define B_G2 368
#define B_G3 376

#define PF 1
#define EXP_FKK 4
#define QSCALE 0.36067376022224085f
#define MAGIC 445.41763f
#define NMUFU 4
#define VSTEP ((uint64_t)((long long)32 - ((long long)32 << 16)))

#define KVMASK 0xEA52u
__host__ __device__ constexpr int strm_pos(int pass, int i) {
    if (pass == 1 || pass == 2) return 8 + 8 * pass + i;
    int n = 0;
    for (int p = 0; p < 16; p++)
        if ((int)((KVMASK >> p) & 1) == (pass == 3)) { if (n == i) return p; n++; }
    return 0;
}
__host__ __device__ constexpr uint32_t strm_code(int pass) {
    uint32_t c = 0;
    for (int i = 0; i < 8; i++) c |= (uint32_t)(strm_pos(pass, i) % 6 | ((strm_pos(pass, i) / 6) & 1) << 3) << (4 * i);
    return c;
}

template <int N, int SUB, int KST, int LBO, int SBO, int SWZ>
__device__ __forceinline__ void gemm_pass(float* acc, uint32_t bar, uint64_t dA, int lane, uint32_t code, int barNext) {
    uint32_t prev = 0;
#pragma unroll 1
    for (int i = 0; i < 8; i++) {
        const uint32_t slot = code & 7;
        mbar_wait(bar + B_X + 8 * i, 0);
        mbar_wait(bar + B_F1 + 8 * slot, (code >> 3) & 1);
        const uint64_t dB = mkdesc(SBD + OFF_R, LBO, SBO, SWZ) + slot * 1024;
        wg_fence();
        wgmma_ss<N>(acc, dA, dB);
        wgmma_ss<N>(acc, dA + 2, dB + KST / 16);
        wg_commit();
        wg_wait<1>();
        if (i > 0 && lane < 2) mbar_arrive_cluster(bar + B_E1 + 8 * prev, lane);
        wgmma_ss<N>(acc, dA + 4, dB + SUB / 16);
        wgmma_ss<N>(acc, dA + 6, dB + (SUB + KST) / 16);
        wg_commit();
        prev = slot;
        code >>= 4;
        dA += 1024;
    }
    if (barNext) bar_arrive(barNext, 512);
    wg_wait<0>();
    if (lane < 2) mbar_arrive_cluster(bar + B_E1 + 8 * prev, lane);
    pin<N / 2>(acc);
}

__device__ __forceinline__ uint32_t lds32(uint32_t a) { uint32_t v; asm volatile("ld.shared.u32 %0, [%1];" : "=r"(v) : "r"(a)); return v; }
__device__ __forceinline__ bool elect() {
    uint32_t p;
    asm volatile("{\n.reg .pred p;\nelect.sync _|p, 0xffffffff;\nselp.u32 %0, 1, 0, p;\n}" : "=r"(p));
    return p;
}

template <int N> __device__ __forceinline__ void bias_init(float* acc, uint32_t b) {
#pragma unroll
    for (int j = 0; j < N / 8; j++) {
        const uint32_t bv = lds32(b + j * 16);
        acc[4 * j] = acc[4 * j + 2] = bf_lo(bv);
        acc[4 * j + 1] = acc[4 * j + 3] = bf_hi(bv);
    }
    pin<N / 2>(acc);
}

template <int G0, int G1> __device__ __forceinline__ void gelu_store(const float* acc, __nv_bfloat16* hp) {
#pragma unroll
    for (int G = G0; G < G1; G++) {
        uint32_t o[8];
#pragma unroll
        for (int j = 0; j < 4; j++) {
            float y[4];
#pragma unroll
            for (int i = 0; i < 4; i++) {
                const float h = acc[16 * G + 4 * j + i];
                const float z = h * fmaf(h * h, 0.035677408136300125f, 0.7978845608028654f);
                const float hh = 0.5f * h;
                y[i] = fmaf(hh, tanhf_(z), hh);
            }
            o[j] = pk_bf16(y[0], y[1]);
            o[4 + j] = pk_bf16(y[2], y[3]);
        }
        *(uint4*)(hp + G * 32) = make_uint4(o[0], o[1], o[2], o[3]);
        *(uint4*)(hp + 8 * FF + G * 32) = make_uint4(o[4], o[5], o[6], o[7]);
    }
}

__device__ __forceinline__ float norm_bound(const float* v, float sc) {
    uint32_t m = 0;
#pragma unroll
    for (int h = 0; h < 4; h++) {
        const float* u = v + 8 * h;
        m = max(m, __float_as_uint(fmaf(u[0], u[0], fmaf(u[1], u[1], fmaf(u[4], u[4], u[5] * u[5])))));
        m = max(m, __float_as_uint(fmaf(u[2], u[2], fmaf(u[3], u[3], fmaf(u[6], u[6], u[7] * u[7])))));
    }
#pragma unroll
    for (int o = 4; o < 32; o <<= 1) m = max(m, __shfl_xor_sync(0xffffffffu, m, o));
    float f = __uint_as_float(m);
    f += __shfl_xor_sync(0xffffffffu, f, 1);
    f += __shfl_xor_sync(0xffffffffu, f, 2);
    return f * sc;
}

__device__ __forceinline__ uint32_t exp2_pair(float a, float b) {
    const uint32_t w = __byte_perm(__float_as_uint(a), __float_as_uint(b), 0x6521);
    uint32_t m, r;
    asm("lop3.b32 %0, %1, 0x007f007f, 0x9f809f80, 0xEA;" : "=r"(m) : "r"(w));
    const uint32_t e = w - m;
    asm("fma.rn.bf16x2 %0, %1, %2, %3;" : "=r"(r) : "r"(w), "r"(m), "r"(e));
    return r;
}

__device__ __forceinline__ void store_o(const float* o, uint4* dst, uint32_t par) {
    const float s0 = __fdividef(1.f, o[8]), s1 = __fdividef(1.f, o[10]);
    const uint32_t d0 = (pk_bf16(o[0] * s0, o[1] * s0) & ~1u) | par;
    asm volatile("{\n.reg .b128 t;\nmov.b128 t, {%0, %1, %2, %3};\nst.relaxed.gpu.global.b128 [%4], t;\n}" ::"r"(d0),
                 "r"(pk_bf16(o[4] * s0, o[5] * s0)), "r"(pk_bf16(o[2] * s1, o[3] * s1)), "r"(pk_bf16(o[6] * s1, o[7] * s1)), "l"(dst) : "memory");
}
__device__ __forceinline__ uint4 load_o(const uint4* src) {
    uint4 v;
    asm volatile("{\n.reg .b128 t;\nld.relaxed.gpu.global.b128 t, [%4];\nmov.b128 {%0, %1, %2, %3}, t;\n}"
                 : "=r"(v.x), "=r"(v.y), "=r"(v.z), "=r"(v.w) : "l"(src) : "memory");
    return v;
}
__device__ __forceinline__ uint32_t bmul2(uint32_t a, uint32_t b) { uint32_t r; asm("mul.rn.bf16x2 %0, %1, %2;" : "=r"(r) : "r"(a), "r"(b)); return r; }
__device__ __forceinline__ void sts32(uint32_t a, uint32_t v) { asm volatile("st.shared.u32 [%0], %1;" ::"r"(a), "r"(v) : "memory"); }
__device__ __forceinline__ void load_q(uint32_t* q, int h, int row, int t) {
    const uint8_t* p = gQ + (size_t)h * (SEQ * 32) + (size_t)row * 32 + t * 4;
    q[0] = __ldcg((const uint32_t*)p); q[1] = __ldcg((const uint32_t*)(p + 256));
    q[2] = __ldcg((const uint32_t*)(p + 16)); q[3] = __ldcg((const uint32_t*)(p + 272));
}

template <int NT>
__device__ __forceinline__ void proj16(float (*c)[8], const __nv_bfloat16* x, const __nv_bfloat16* w, int row0, int rstep, int col, int g, int t) {
#pragma unroll
    for (int i = 0; i < NT; i++)
#pragma unroll
        for (int j = 0; j < 8; j++) c[i][j] = 0.f;
    const unsigned short* wu = (const unsigned short*)w;
#pragma unroll 1
    for (int k = 0; k < DM; k += 16) {
        uint32_t b[4];
#pragma unroll
        for (int j = 0; j < 4; j++) {
            const int kr = k + 2 * t + (j & 1) * 8, cc = col + g + (j >> 1) * 8;
            b[j] = (uint32_t)wu[(size_t)kr * (3 * DM) + cc] | ((uint32_t)wu[(size_t)(kr + 1) * (3 * DM) + cc] << 16);
        }
#pragma unroll
        for (int i = 0; i < NT; i++) {
            const __nv_bfloat16* xp = x + (size_t)(row0 + i * rstep + g) * DM + k + 2 * t;
            const uint32_t a0 = *(const uint32_t*)xp, a1 = *(const uint32_t*)(xp + 8 * DM);
            const uint32_t a2 = *(const uint32_t*)(xp + 8), a3 = *(const uint32_t*)(xp + 8 * DM + 8);
#pragma unroll
            for (int j = 0; j < 2; j++)
                asm volatile("mma.sync.aligned.m16n8k16.row.col.f32.bf16.bf16.f32 {%0,%1,%2,%3}, {%4,%5,%6,%7}, {%8,%9}, {%0,%1,%2,%3};"
                             : "+f"(c[i][4 * j]), "+f"(c[i][4 * j + 1]), "+f"(c[i][4 * j + 2]), "+f"(c[i][4 * j + 3])
                             : "r"(a0), "r"(a1), "r"(a2), "r"(a3), "r"(b[2 * j]), "r"(b[2 * j + 1]));
        }
    }
}

struct Maps { CUtensorMap x, kv, q, f1, f3, h, w2, wo; };

__global__ void __cluster_dims__(2, 1, 1) __launch_bounds__(640, 1)
fused_kernel(const __grid_constant__ Maps tm, const __nv_bfloat16* __restrict__ x, const __nv_bfloat16* __restrict__ wqkv,
             const __nv_bfloat16* __restrict__ wo, const __nv_bfloat16* __restrict__ w1, const __nv_bfloat16* __restrict__ b1,
             const __nv_bfloat16* __restrict__ w2, const __nv_bfloat16* __restrict__ b2, const __nv_bfloat16* __restrict__ gate,
             __nv_bfloat16* __restrict__ out) {
    extern __shared__ __align__(1024) uint8_t smem_raw[];
    const uint32_t sb = smem_u32(smem_raw);
    const uint32_t bar = sb + OFF_BAR;
    const int tid = threadIdx.x, lane = tid & 31;
    const int warp = __shfl_sync(0xffffffffu, tid >> 5, 0);
    const uint32_t rank = cluster_rank();
    const int cl = blockIdx.x >> 1;
    const int nb = cl & 7, mb = (cl >> 3) * 2 + rank;
    const int g = lane >> 2, t = lane & 3;

    const int cb = nb & 3, rb = mb * 2 + (nb >> 2);
    if (tid == 0) TLM(0, 0);
    if (tid == 512) {
        mbar_init(bar + B_X, 1);
        asm volatile("fence.proxy.async.shared::cta;" ::: "memory");
        mbar_expect(bar + B_X, 16384);
        tma2d(sb, &tm.x, 0, mb * 128, bar + B_X);
        for (int i = 0; i < 8; i++) { if (i) mbar_init(bar + B_X + 8 * i, 1); mbar_init(bar + B_KV + 8 * i, 1); mbar_init(bar + B_T + 8 * i, 5); }
        for (int i = 0; i < 6; i++) { mbar_init(bar + B_F1 + 8 * i, 1); mbar_init(bar + B_E1 + 8 * i, 16); }
        for (int i = 0; i < 4; i++) { mbar_init(bar + B_F2 + 8 * i, 1); mbar_init(bar + B_E2 + 8 * i, 8); }
        mbar_init(bar + B_DONE, 16);
        mbar_init(bar + B_G, 1);
        mbar_init(bar + B_G3, 1);
        mbar_init(bar + B_G2, 4);
        asm volatile("fence.mbarrier_init.release.cluster;" ::: "memory");
    } else if (tid == 544) {
        map_prefetch(&tm.q); map_prefetch(&tm.f1); map_prefetch(&tm.kv);
        l2_prefetch((const uint8_t*)wqkv + (size_t)blockIdx.x * 3072, 3072);
        map_prefetch(&tm.f3);
    } else if (tid < 128) {
        asm volatile("st.shared.u32 [%0], %1;" ::"r"(sb + OFF_ONE + tid * 4), "r"(0x3f803f80u) : "memory");
        asm volatile("fence.proxy.async.shared::cta;" ::: "memory");
    }
    uint32_t biasv = 0;
    if (tid >= 288 && tid < 256 + 208)
        biasv = tid < 400 ? *(const uint32_t*)(b1 + nb * 224 + (tid - 288) * 2) : *(const uint32_t*)(b2 + cb * 128 + (tid - 400) * 2);
    if ((sb & 0xFFFFFF) != SBD) __trap();
    __syncthreads();
    asm volatile("barrier.cluster.arrive.relaxed.aligned;\nbarrier.cluster.wait.aligned;" ::: "memory");
    const uint32_t ep = gEpoch[blockIdx.x] + 1;
    if (tid == 0) { TLM(0, 1); TLC(0, 30); }

    if (warp < 16) {
        const int wg = warp >> 2;
        const int h = cl >> 1, qd = (cl & 1) * 2 + rank;
        uint32_t q[4];
        {
            const int w8 = warp & 7;
            const int T = mb * 8 + w8, row0 = T * 16 + g;
            const uint64_t dA0 = mkdesc(SBD + (wg & 1) * 8192, 16, 1024, 1);
            if (wg < 2) {
                float acc[64];
#pragma unroll
                for (int i = 0; i < 64; i++) acc[i] = 0.f;
                gemm_pass<128, 8192, 2048, 4096, 1024, 1>(acc, bar, dA0, lane, strm_code(3), 6);
                if (tid == 0) TLM(0, 2);
                {
                    const int pos = ((T >> 6) * 16 + 2 * g) * 64 + (T & 63);
                    uint8_t* kp = gKV + (size_t)(nb * 4) * (SEQ * 64) + (pos >> 8) * 16384 + (pos & 255) * 32 + ((t * 8) ^ (((T >> 2) & 1) << 4));
                    float vm = 0.f;
#pragma unroll
                    for (int hh = 0; hh < 4; hh++) {
                        const float* v = acc + 8 * hh;
                        float p0 = __shfl_up_sync(0xffffffffu, v[2], 4), p1 = __shfl_up_sync(0xffffffffu, v[3], 4);
                        float p2 = __shfl_up_sync(0xffffffffu, v[6], 4), p3 = __shfl_up_sync(0xffffffffu, v[7], 4);
                        if (g == 0) { p0 = p1 = p2 = p3 = 0.f; }
                        uint8_t* o = kp + (size_t)hh * (SEQ * 64);
                        *(uint2*)o = make_uint2(pk_f16(v[0] - p0, v[1] - p1), pk_f16(v[4] - p2, v[5] - p3));
                        *(uint2*)(o + 2048) = make_uint2(pk_f16(v[2] - v[0], v[3] - v[1]), pk_f16(v[6] - v[4], v[7] - v[5]));
                        const float* u = acc + 32 + 8 * hh;
#pragma unroll
                        for (int i = 0; i < 8; i++) vm = fmaxf(vm, fabsf(u[i]));
                        *(uint2*)(o + 8192) = make_uint2(pk_bf16(u[0], u[1]), pk_bf16(u[4], u[5]));
                        *(uint2*)(o + 8192 + 2048) = make_uint2(pk_bf16(u[2], u[3]), pk_bf16(u[6], u[7]));
                    }
                    const float km = norm_bound(acc, 1.f);
                    vm = __uint_as_float(__reduce_max_sync(0xffffffffu, __float_as_uint(vm)));
                    if (lane == 0) { gN[1024 + nb * 128 + T] = km; gN[2048 + nb * 128 + T] = vm; }
                }
                bar_arrive(10, 544);
                if (tid == 0) TLM(0, 3);
                bar_sync(12, 512);
            } else {
                if (tid < 256 + 208) sts32(sb + OFF_BIAS + (tid - 256) * 4, biasv);
                bar_arrive(12, 512);
                bar_sync(5, 256);
            }
            const int pend = wg < 2 ? 3 : 2;
#pragma unroll 1
            for (int p = wg < 2 ? 2 : 0; p < pend; p++) {
                float acc[48];
                bias_init<96>(acc, sb + OFF_BIAS + p * 192 + t * 4);
                if (p) bar_sync(5 + p, 512);
                gemm_pass<96, 6144, 1024, 2048, 512, 2>(acc, bar, dA0, lane, p == 0 ? strm_code(0) : p == 1 ? strm_code(1) : strm_code(2), p == 1 ? 7 : 0);
                if ((tid & 255) == 0) TLM(0, 4 + 2 * p);
                __nv_bfloat16* hp = gH + (size_t)row0 * FF + nb * 224 + p * 96 - 64 + t * 8;
                if (p == 0) {
                    uint8_t* qp = gQ + (size_t)(nb * 4) * (SEQ * 32) + (size_t)row0 * 32 + t * 8;
#pragma unroll
                    for (int hh = 0; hh < 4; hh++) {
                        const float* v = acc + 8 * hh;
                        uint8_t* o = qp + (size_t)hh * (SEQ * 32);
                        *(uint2*)o = make_uint2(pk_f16(v[0] * QSCALE, v[1] * QSCALE), pk_f16(v[4] * QSCALE, v[5] * QSCALE));
                        *(uint2*)(o + 256) = make_uint2(pk_f16(v[2] * QSCALE, v[3] * QSCALE), pk_f16(v[6] * QSCALE, v[7] * QSCALE));
                    }
                    const float qm = norm_bound(acc, QSCALE * QSCALE);
                    if (lane == 0) gN[nb * 128 + T] = qm;
                    bar_arrive(10, 544);
                } else {
                    if (p == 2) {
                        mbar_wait(bar + B_G, 0);
                        load_q(q, h, qd * 512 + warp * 16 + g, t);
                    }
                    gelu_store<0, 2>(acc, hp);
                }
                gelu_store<2, 3>(acc, hp);
                if ((tid & 255) == 0) TLM(0, 5 + 2 * p);
            }
            bar_arrive(11, 576);
            if (wg >= 2) {
                mbar_wait(bar + B_G, 0);
                load_q(q, h, qd * 512 + warp * 16 + g, t);
            }
        }
        mbar_wait(bar + B_G3, 0);
        const bool fast = lds32(sb + OFF_G + 256) != 0;
        uint4* const op = gO + ((qd * 8 + wg) * NH + h) * 128 + (tid & 127);
        const uint64_t kd0 = mkdesc(SBD, 16, 256, 3);
        const uint64_t vd0 = mkdesc(SBD + 8192, OFF_ONE - 8192, 256, 3);
        if (fast) {
#pragma unroll 1
            for (int r = 0; r < 2; r++) {
                float o[12];
#pragma unroll
                for (int i = 0; i < 12; i++) o[i] = 0.f;
                uint64_t kd = kd0, vd = vd0;
                uint32_t qn[4];
#pragma unroll 1
                for (int half = 0; half < 2; half++) {
                    float s[32];
#pragma unroll
                    for (int i = 0; i < 32; i++) s[i] = i < 2 * NMUFU ? 0.f : MAGIC;
#pragma unroll 1
                    for (int c = 0; c < 4; c++) {
                        if (r == 0) mbar_wait(bar + B_KV + 8 * (half * 4 + c), 0);
                        if ((tid & 255) == 0 && c == 0) TLM(1, (tid >> 8) * 4 + r * 2 + half);
                        if (half == 1 && c == 3) {
                            if (r == 0) load_q(qn, h, qd * 512 + 256 + warp * 16 + g, t);
                            else if (lane == 0) mbar_arrive(bar + B_DONE);
                        }
#pragma unroll 1
                        for (int j = 0; j < 4; j++) {
                            uint32_t p[16];
                            wg_fence();
                            wgmma_qk_f16_acc(s, q, kd);
                            wg_commit();
                            wg_wait<0>();
                            pin<32>(s);
#pragma unroll
                            for (int i = 0; i < 16; i++)
                                p[i] = i < NMUFU ? pk_bf16(ex2f(s[2 * i]), ex2f(s[2 * i + 1])) : exp2_pair(s[2 * i], s[2 * i + 1]);
                            pin<16>(p);
                            wg_fence();
#pragma unroll
                            for (int u = 0; u < 4; u++) wgmma_pv(o, p + 4 * u, vd + u * VSTEP);
                            wg_commit();
                            kd += 128;
                            vd += 4 * VSTEP;
                        }
                        kd += 512;
                        vd += 16 * VSTEP;
                    }
                    wg_wait<0>();
                }
                pin<12>(o);
                if ((tid & 127) == 0 && r == 1) TLM(1, 8 + wg);
                store_o(o, op + r * (4 * NH * 128), ep & 1);
#pragma unroll
                for (int i = 0; i < 4; i++) q[i] = qn[i];
            }
            if (tid == 0) { TLM(1, 12); TLC(0, 31); }
        } else {
            for (int c = 0; c < 8; c++) mbar_wait(bar + B_KV + 8 * c, 0);
            {
                float kc[8][8];
                proj16<8>(kc, x, wqkv, warp * 16, 256, DM + h * 16, g, t);
#pragma unroll
                for (int i = 0; i < 8; i++) {
                    const int T = warp + i * 16;
                    const int pos = ((T >> 6) * 16 + 2 * g) * 64 + (T & 63);
                    const uint32_t a = sb + (pos >> 8) * 16384 + (pos & 255) * 32 + t * 4, sw = ((T >> 2) & 1) << 4;
                    asm volatile("st.shared.u32 [%0], %1;" ::"r"(a + sw), "r"(pk_bf16(kc[i][0], kc[i][1])) : "memory");
                    asm volatile("st.shared.u32 [%0], %1;" ::"r"(a + (sw ^ 16)), "r"(pk_bf16(kc[i][4], kc[i][5])) : "memory");
                    asm volatile("st.shared.u32 [%0], %1;" ::"r"(a + 2048 + sw), "r"(pk_bf16(kc[i][2], kc[i][3])) : "memory");
                    asm volatile("st.shared.u32 [%0], %1;" ::"r"(a + 2048 + (sw ^ 16)), "r"(pk_bf16(kc[i][6], kc[i][7])) : "memory");
                }
                asm volatile("fence.proxy.async.shared::cta;" ::: "memory");
                bar_sync(8, 512);
            }
#pragma unroll 1
            for (int r = 0; r < 2; r++) {
                const int row = qd * 512 + r * 256 + warp * 16 + g;
                {
                    float qc[1][8];
                    proj16<1>(qc, x, wqkv, row - g, 0, h * 16, g, t);
#pragma unroll
                    for (int i = 0; i < 4; i++) q[i] = pk_bf16(qc[0][2 * i] * QSCALE, qc[0][2 * i + 1] * QSCALE);
                }
                float o[12];
#pragma unroll
                for (int i = 0; i < 12; i++) o[i] = 0.f;
                float m0 = -INFINITY, m1 = -INFINITY;
#pragma unroll 1
                for (int j = 0; j < 32; j++) {
                    const uint64_t kd = kd0 + (j >> 2) * 1024 + (j & 3) * 128, vd = vd0 + ((j >> 2) * 32 + (j & 3) * 4) * VSTEP;
                    float s[32];
                    uint32_t p[16];
                    wg_fence();
                    wgmma_qk_bf16_zero(s, q, kd);
                    wg_commit();
                    wg_wait<0>();
                    pin<32>(s);
                    pin<12>(o);
                    float n0 = m0, n1 = m1;
#pragma unroll
                    for (int i = 0; i < 8; i++) {
                        n0 = fmaxf(n0, fmaxf(s[4 * i], s[4 * i + 1]));
                        n1 = fmaxf(n1, fmaxf(s[4 * i + 2], s[4 * i + 3]));
                    }
                    n0 = fmaxf(n0, __shfl_xor_sync(0xffffffffu, n0, 1));
                    n1 = fmaxf(n1, __shfl_xor_sync(0xffffffffu, n1, 1));
                    n0 = fmaxf(n0, __shfl_xor_sync(0xffffffffu, n0, 2));
                    n1 = fmaxf(n1, __shfl_xor_sync(0xffffffffu, n1, 2));
                    const float c0 = ex2f(m0 - n0), c1 = ex2f(m1 - n1);
                    m0 = n0;
                    m1 = n1;
#pragma unroll
                    for (int i = 0; i < 3; i++) { o[4 * i] *= c0; o[4 * i + 1] *= c0; o[4 * i + 2] *= c1; o[4 * i + 3] *= c1; }
#pragma unroll
                    for (int i = 0; i < 8; i++) {
                        p[2 * i] = pk_bf16(ex2f(s[4 * i] - m0), ex2f(s[4 * i + 1] - m0));
                        p[2 * i + 1] = pk_bf16(ex2f(s[4 * i + 2] - m1), ex2f(s[4 * i + 3] - m1));
                    }
                    pin<16>(p);
                    pin<12>(o);
                    wg_fence();
#pragma unroll
                    for (int u = 0; u < 4; u++) wgmma_pv(o, p + 4 * u, vd + u * VSTEP);
                    wg_commit();
                }
                wg_wait<0>();
                pin<12>(o);
                if (r == 1 && lane == 0) mbar_arrive(bar + B_DONE);
                store_o(o, op + r * (4 * NH * 128), ep & 1);
            }
        }
        {
            const uint4* src = gO + (rb * NH + wg * 8) * 128 + (tid & 127);
            uint4 v[8];
#pragma unroll
            for (int i = 0; i < 8; i++) v[i] = load_o(src + i * 128);
            mbar_wait(bar + B_DONE, 0);
            mbar_wait(bar + B_G2, 0);
            const int lr = (warp & 3) * 16 + g;
            const uint32_t g0 = lds32(sb + OFF_G + lr * 4), g1 = lds32(sb + OFF_G + lr * 4 + 32);
            const uint32_t a0 = sb + wg * 16384 + lr * 128 + (t >> 1) * 4;
#pragma unroll
            for (int i = 0; i < 8; i++) {
                if ((i & 3) == 0) {
                    int spins = 0;
                    while (__any_sync(0xffffffffu, (((v[i].x ^ ep) | (v[i + 1].x ^ ep) | (v[i + 2].x ^ ep) | (v[i + 3].x ^ ep)) & 1) != 0)) {
                        if (++spins > (1 << 22)) __trap();
#pragma unroll
                        for (int k = i; k < 8; k++)
                            if (((v[k].x ^ ep) & 1) != 0) v[k] = load_o(src + k * 128);
                    }
                }
                const uint32_t a = a0 + (i >> 2) * 8192 + ((((i & 3) * 2 + (t & 1)) ^ g) << 4);
                sts32(a, bmul2(v[i].x, g0));
                sts32(a + 8, bmul2(v[i].y, g0));
                sts32(a + 1024, bmul2(v[i].z, g1));
                sts32(a + 1024 + 8, bmul2(v[i].w, g1));
                if ((i & 3) == 3) {
                    asm volatile("fence.proxy.async.shared::cta;" ::: "memory");
                    __syncwarp();
                    if (lane == 0) mbar_arrive(bar + B_T + 8 * (wg * 2 + (i >> 2)));
                    if ((tid & 127) == 0) TLM(1, 20 + wg * 2 + (i >> 2));
                }
            }
        }
    } else {
        if (warp == 16) {
            if (elect()) {
                int s = 0, par = 1, k0 = rank * 32, k3 = rank * 32;
#pragma unroll 1
                for (int it = 0; it < 32; it++) {
                    const uint32_t fb = bar + B_F1 + 8 * s, dst = sb + OFF_R + s * 16384;
                    mbar_wait(bar + B_E1 + 8 * s, par);
                    if (it < 16 && ((KVMASK >> it) & 1)) {
                        mbar_expect(fb, 16384);
                        tma3d_mc(dst + rank * 8192, &tm.kv, nb * 64, k3, 1, fb);
                        k3 += 64;
                    } else {
                        mbar_expect(fb, 12288);
                        if (it < 16) {
                            tma3d_mc(dst + rank * 6144, &tm.q, 0, k0, nb * 2, fb);
                            tma3d_mc(dst + rank * 6144 + 4096, &tm.f1, 0, k0, nb * 7, fb);
                            const int c = (k0 >> 6) + 1;
                            if (c < 8) {
                                mbar_expect(bar + B_X + 8 * c, 16384);
                                tma2d(sb + c * 16384, &tm.x, c * 64, mb * 128, bar + B_X + 8 * c);
                            }
                        } else {
                            tma3d_mc(dst + rank * 6144, &tm.f3, 0, k0 & 511, nb * 7 + (it < 24 ? 1 : 4), fb);
                        }
                        k0 += 64;
                    }
                    if (++s == 6) { s = 0; par ^= 1; }
                }
                const int h = cl >> 1;
                mbar_wait(bar + B_G, 0);
                asm volatile("fence.proxy.async.global;" ::: "memory");
                TLM(0, 10);
#pragma unroll 1
                for (int c = 0; c < 8; c++) {
                    if (c >= 2) {
                        mbar_wait(bar + B_E1 + 8 * s, par);
                        if (++s == 6) { s = 0; par ^= 1; }
                    }
                    mbar_expect(bar + B_KV + 8 * c, 16384);
                    bulk_mc(sb + c * 16384 + rank * 8192, gKV + (size_t)h * (SEQ * 64) + c * 16384 + rank * 8192, 8192, bar + B_KV + 8 * c);
                }
#pragma unroll 1
                for (s = 0; s < 4; s++) {
                    mbar_expect(bar + B_F2 + 8 * s, 24576);
                    tma5d_mc(sb + OFF_R + s * 24576 + 8192 + rank * 8192, &tm.w2, cb * 128 + rank * 64, s * 2, bar + B_F2 + 8 * s);
                }
                cnt_wait(gCntH + rb * 32, ep * 8);
                asm volatile("fence.proxy.async.global;" ::: "memory");
                TLM(1, 13);
#pragma unroll 1
                for (s = 0; s < 4; s++) tma2d(sb + OFF_R + s * 24576, &tm.h, s * 64, rb * 64, bar + B_F2 + 8 * s);
            }
        } else if (warp == 17) {
            mbar_wait(bar + B_X + 8 * 7, 0);
            if (lane == 0) {
                l2_prefetch((const uint8_t*)w2 + (size_t)blockIdx.x * 14336, 14336);
                l2_prefetch((const uint8_t*)wo + (size_t)blockIdx.x * 4096, 4096);
                map_prefetch(&tm.h); map_prefetch(&tm.w2); map_prefetch(&tm.wo);
                TLM(0, 11);
            }
            const int h = cl >> 1, qd = (cl & 1) * 2 + rank;
            bar_sync(10, 544);
            if (lane == 0) {
                cnt_add(gCntQ + nb * 32);
                TLM(0, 13);
                cnt_wait(gCntQ + (h >> 2) * 32, ep * 16);
                mbar_arrive(bar + B_G);
                TLM(0, 14);
            }
            __syncwarp();
            const int hb = h >> 2;
            const uint4 kq = __ldcg((const uint4*)(gN + 1024 + hb * 128 + lane * 4));
            const uint4 vq = __ldcg((const uint4*)(gN + 2048 + hb * 128 + lane * 4));
            const float qq = ldcg_f(gN + hb * 128 + qd * 32 + lane);
            const float kf = __uint_as_float(__reduce_max_sync(0xffffffffu, max(max(kq.x, kq.y), max(kq.z, kq.w))));
            const float vf = __uint_as_float(__reduce_max_sync(0xffffffffu, max(max(vq.x, vq.y), max(vq.z, vq.w))));
            const float qf = __uint_as_float(__reduce_max_sync(0xffffffffu, __float_as_uint(qq)));
            if (lane == 0) {
                sts32(sb + OFF_G + 256, (kf <= 1.0e6f) && (qf <= 1.0e6f) && (kf * qf <= 3400.f) && (vf <= 1.0e12f));
                mbar_arrive(bar + B_G3);
            }
        } else {
            {
                const int r0 = mb * 128 + nb * 16 + (warp - 18) * 8;
                uint4 xv[16];
#pragma unroll
                for (int i = 0; i < 16; i++) xv[i] = *(const uint4*)(x + (size_t)(r0 + (i >> 1)) * DM + (i & 1) * 256 + lane * 8);
                const uint4 ga = *(const uint4*)(gate + lane * 8), gb = *(const uint4*)(gate + 256 + lane * 8);
                float z[8];
#pragma unroll
                for (int r = 0; r < 8; r++) z[r] = dot8(xv[2 * r], ga) + dot8(xv[2 * r + 1], gb);
#pragma unroll
                for (int w = 4; w >= 1; w >>= 1)
#pragma unroll
                    for (int r = 0; r < w; r++) {
                        const bool up = lane & w;
                        z[r] = (up ? z[r + w] : z[r]) + __shfl_xor_sync(0xffffffffu, up ? z[r] : z[r + w], w);
                    }
                z[0] += __shfl_xor_sync(0xffffffffu, z[0], 8);
                z[0] += __shfl_xor_sync(0xffffffffu, z[0], 16);
                if (lane < 8) gG[r0 + lane] = 1.f / (1.f + __expf(-z[0]));
                if (tid == 576) TLM(0, 12);
                if (warp == 18) bar_arrive(11, 576);
            }
            if (warp == 19) {
                bar_sync(11, 576);
                if (lane < 2) cnt_add(gCntH + (mb * 2 + lane) * 32);
            }
        }
        __syncwarp();
        float acc[64];
#pragma unroll
        for (int i = 0; i < 64; i++) acc[i] = 0.f;
#pragma unroll 1
        for (int io = 0; io < 7; io++) {
#pragma unroll
            for (int s = 0; s < 4; s++) {
                const int it = io * 4 + s;
                mbar_wait(bar + B_F2 + 8 * s, io & 1);
                if (tid == 512 && s == 0 && (io == 0 || io == 4)) TLM(1, 14 + io / 4);
                const uint64_t dA = mkdesc(SBD + OFF_R + s * 24576, 16, 1024, 1);
                const uint64_t dB = mkdesc(SBD + OFF_R + s * 24576 + 8192, 8192, 1024, 1);
                wg_fence();
#pragma unroll
                for (int kk = 0; kk < EXP_FKK; kk++) wgmma_ss_n128(acc, dA + kk * 2, dB + kk * 128);
                wg_commit();
                if (warp < 18 && it >= 2 && it < 26) {
                    const int s2 = (s + 2) & 3;
                    mbar_wait(bar + B_E2 + 8 * s2, (io - (s < 2)) & 1);
                    if (elect()) {
                        if (warp == 16) {
                            mbar_expect(bar + B_F2 + 8 * s2, 24576);
                            tma5d_mc(sb + OFF_R + s2 * 24576 + 8192 + rank * 8192, &tm.w2, cb * 128 + rank * 64, it * 2 + 4, bar + B_F2 + 8 * s2);
                        } else {
                            asm volatile("fence.proxy.async.global;" ::: "memory");
                            tma2d(sb + OFF_R + s2 * 24576, &tm.h, it * 64 + 128, rb * 64, bar + B_F2 + 8 * s2);
                        }
                    }
                    __syncwarp();
                }
                wg_wait<1>();
                if (it >= 1 && lane < 2) mbar_arrive_cluster(bar + B_E2 + 8 * ((s + 3) & 3), lane);
            }
        }
        wg_wait<0>();
        if (lane < 2) mbar_arrive_cluster(bar + B_E2 + 8 * 3, lane);
        pin<64>(acc);
        if (warp == 16) {
            if (lane == 0) TLM(1, 16);
            for (int s = 0; s < 4; s++) mbar_wait(bar + B_E2 + 8 * s, 0);
            if (elect()) {
#pragma unroll
                for (int i = 0; i < 8; i++) mbar_expect(bar + B_T + 8 * i, 16384);
#pragma unroll
                for (int i = 0; i < 6; i++) tma2d_mc(sb + OFF_R + i * 16384 + rank * 8192, &tm.wo, cb * 128 + rank * 64, i * 64, bar + B_T + 8 * i);
            }
            __syncwarp();
        }
        {
            const int lr = (warp - 16) * 16 + g;
            const uint32_t pa = pk_bf16(ldcg_f(gG + rb * 64 + lr), ldcg_f(gG + rb * 64 + lr + 8));
            if (t == 0) {
                sts32(sb + OFF_G + lr * 4, __byte_perm(pa, pa, 0x1010));
                sts32(sb + OFF_G + lr * 4 + 32, __byte_perm(pa, pa, 0x3232));
            }
            __syncwarp();
            if (lane == 0) mbar_arrive(bar + B_G2);
            const float ga = bf_lo(pa), gb = bf_hi(pa);
            const float g0 = 1.f - ga, g1 = 1.f - gb;
#pragma unroll
            for (int j = 0; j < 16; j++) {
                const uint32_t bv = lds32(sb + OFF_BIAS + 576 + j * 16 + t * 4);
                acc[4 * j] = (acc[4 * j] + bf_lo(bv)) * g0;
                acc[4 * j + 1] = (acc[4 * j + 1] + bf_hi(bv)) * g0;
                acc[4 * j + 2] = (acc[4 * j + 2] + bf_lo(bv)) * g1;
                acc[4 * j + 3] = (acc[4 * j + 3] + bf_hi(bv)) * g1;
            }
            pin<64>(acc);
        }
        if (warp == 17) {
            mbar_wait(bar + B_DONE, 0);
            if (elect()) {
#pragma unroll
                for (int i = 0; i < 4; i++)
                    tma2d(sb + 65536 + i * 8192, &tm.wo, cb * 128 + (i & 1) * 64, (6 + (i >> 1)) * 64, bar + B_T + 8 * (6 + (i >> 1)));
            }
            __syncwarp();
        }
        if (tid == 512) TLM(1, 17);
#pragma unroll
        for (int i = 0; i < 8; i++) {
            mbar_wait(bar + B_T + 8 * i, 0);
            const uint64_t dA = mkdesc(SBD + i * 8192, 16, 1024, 1);
            const uint64_t dB = mkdesc(i < 6 ? SBD + OFF_R + i * 16384 : SBD + 65536 + (i - 6) * 16384, 8192, 1024, 1);
            wg_fence();
#pragma unroll
            for (int kk = 0; kk < 4; kk++) wgmma_ss_n128(acc, dA + kk * 2, dB + kk * 128);
            wg_commit();
        }
        wg_wait<0>();
        pin<64>(acc);
        if (tid == 512) TLM(1, 18);
        {
            const uint32_t st = sb + 98304 + (warp - 16) * 4352;
            const uint32_t wa = st + (lane & 15) * 272 + (lane >> 4) * 16;
#pragma unroll
            for (int j = 0; j < 8; j++)
                asm volatile("stmatrix.sync.aligned.m8n8.x4.shared.b16 [%0], {%1, %2, %3, %4};" ::"r"(wa + j * 32),
                             "r"(pk_bf16(acc[8 * j], acc[8 * j + 1])), "r"(pk_bf16(acc[8 * j + 2], acc[8 * j + 3])),
                             "r"(pk_bf16(acc[8 * j + 4], acc[8 * j + 5])), "r"(pk_bf16(acc[8 * j + 6], acc[8 * j + 7])) : "memory");
            __syncwarp();
            __nv_bfloat16* op = out + (size_t)(rb * 64 + (warp - 16) * 16 + (lane >> 4)) * DM + cb * 128 + (lane & 15) * 8;
#pragma unroll
            for (int j = 0; j < 8; j++) {
                uint4 v;
                asm volatile("ld.shared.v4.u32 {%0, %1, %2, %3}, [%4];" : "=r"(v.x), "=r"(v.y), "=r"(v.z), "=r"(v.w)
                             : "r"(st + (2 * j + (lane >> 4)) * 272 + (lane & 15) * 16));
                *(uint4*)(op + (size_t)j * 2 * DM) = v;
            }
        }
        if (tid == 512) { gEpoch[blockIdx.x] = ep; TLM(1, 19); }
    }
}

typedef CUresult (*EncodeFn)(CUtensorMap*, CUtensorMapDataType, cuuint32_t, void*, const cuuint64_t*, const cuuint64_t*, const cuuint32_t*,
                             const cuuint32_t*, CUtensorMapInterleave, CUtensorMapSwizzle, CUtensorMapL2promotion, CUtensorMapFloatOOBfill);

static void make_map(EncodeFn enc, CUtensorMap* m, const void* p, int rank, const cuuint64_t* dims, const cuuint64_t* strides,
                     const cuuint32_t* box, CUtensorMapSwizzle swz) {
    const cuuint32_t es[5] = {1, 1, 1, 1, 1};
    enc(m, CU_TENSOR_MAP_DATA_TYPE_BFLOAT16, rank, (void*)p, dims, strides, box, es, CU_TENSOR_MAP_INTERLEAVE_NONE, swz,
        CU_TENSOR_MAP_L2_PROMOTION_L2_128B, CU_TENSOR_MAP_FLOAT_OOB_FILL_NONE);
}

extern "C" void kernel_launch(void* const* d_in, const int* in_sizes, int n_in, void* d_out, int out_size) {
    const __nv_bfloat16* x = (const __nv_bfloat16*)d_in[0];
    const __nv_bfloat16* wqkv = (const __nv_bfloat16*)d_in[1];
    const __nv_bfloat16* wo = (const __nv_bfloat16*)d_in[2];
    const __nv_bfloat16* w1 = (const __nv_bfloat16*)d_in[4];
    const __nv_bfloat16* b1 = (const __nv_bfloat16*)d_in[5];
    const __nv_bfloat16* w2 = (const __nv_bfloat16*)d_in[6];
    const __nv_bfloat16* b2 = (const __nv_bfloat16*)d_in[7];
    const __nv_bfloat16* gate = (const __nv_bfloat16*)d_in[8];

    void* fp = nullptr;
    cudaDriverEntryPointQueryResult qr;
    cudaGetDriverEntryPoint("cuTensorMapEncodeTiled", &fp, cudaEnableDefault, &qr);
    EncodeFn enc = (EncodeFn)fp;
    void* pH;
    cudaGetSymbolAddress(&pH, gH);

    Maps tm;
    const CUtensorMapSwizzle S128 = CU_TENSOR_MAP_SWIZZLE_128B, S64 = CU_TENSOR_MAP_SWIZZLE_64B;
    { cuuint64_t d[2] = {DM, SEQ}, s[1] = {DM * 2}; cuuint32_t b[2] = {64, 128}; make_map(enc, &tm.x, x, 2, d, s, b, S128); }
    { cuuint64_t d[3] = {DM, DM, 3}, s[2] = {3 * DM * 2, DM * 2}; cuuint32_t b[3] = {64, 32, 2}; make_map(enc, &tm.kv, wqkv, 3, d, s, b, S128); }
    { cuuint64_t d[3] = {32, DM, 3 * DM / 32}, s[2] = {3 * DM * 2, 64}; cuuint32_t b[3] = {32, 32, 2}; make_map(enc, &tm.q, wqkv, 3, d, s, b, S64); }
    { cuuint64_t d[3] = {32, DM, FF / 32}, s[2] = {FF * 2, 64}; cuuint32_t b[3] = {32, 32, 1}; make_map(enc, &tm.f1, w1, 3, d, s, b, S64); }
    { cuuint64_t d[3] = {32, DM, FF / 32}, s[2] = {FF * 2, 64}; cuuint32_t b[3] = {32, 32, 3}; make_map(enc, &tm.f3, w1, 3, d, s, b, S64); }
    { cuuint64_t d[2] = {FF, SEQ}, s[1] = {FF * 2}; cuuint32_t b[2] = {64, 64}; make_map(enc, &tm.h, pH, 2, d, s, b, S128); }
    { cuuint64_t d[5] = {DM, 2, 4, 4, FF / 32}, s[4] = {1024, 8 * 1024, 2 * 1024, 32 * 1024}; cuuint32_t b[5] = {64, 2, 4, 4, 2};
      make_map(enc, &tm.w2, w2, 5, d, s, b, S128); }
    { cuuint64_t d[2] = {DM, DM}, s[1] = {DM * 2}; cuuint32_t b[2] = {64, 64}; make_map(enc, &tm.wo, wo, 2, d, s, b, S128); }

    cudaFuncSetAttribute(fused_kernel, cudaFuncAttributeMaxDynamicSharedMemorySize, SMEM_BYTES);
    fused_kernel<<<128, 640, SMEM_BYTES, cudaStreamPerThread>>>(tm, x, wqkv, wo, w1, b1, w2, b2, gate, (__nv_bfloat16*)d_out);
}
```

```cpp
#include <cuda_runtime.h>
#include <cuda_bf16.h>
#include <cuda_fp16.h>
#include <cuda.h>
#include <stdint.h>

#define SEQ 2048
#define DM 512
#define FF 1792
#define NH 32

__device__ __align__(1024) uint8_t gQ[NH * SEQ * 32];
__device__ __align__(1024) uint8_t gKV[NH * SEQ * 64];
__device__ __align__(1024) __nv_bfloat16 gH[SEQ * FF];
__device__ __align__(1024) uint4 gO[32 * NH * 128];
__device__ float gG[SEQ];
__device__ float gN[3 * 8 * 128];
__device__ unsigned int gCntQ[8 * 32];
__device__ unsigned int gCntH[32 * 32];
__device__ unsigned int gEpoch[128];

__device__ __forceinline__ uint32_t smem_u32(const void* p) { return (uint32_t)__cvta_generic_to_shared(p); }
__device__ __forceinline__ void mbar_init(uint32_t a, uint32_t c) { asm volatile("mbarrier.init.shared::cta.b64 [%0], %1;" ::"r"(a), "r"(c)); }
__device__ __forceinline__ void mbar_expect(uint32_t a, uint32_t b) { asm volatile("mbarrier.arrive.expect_tx.shared::cta.b64 _, [%0], %1;" ::"r"(a), "r"(b) : "memory"); }
__device__ __forceinline__ void mbar_arrive(uint32_t a) { asm volatile("mbarrier.arrive.shared::cta.b64 _, [%0];" ::"r"(a) : "memory"); }
__device__ __forceinline__ void mbar_wait(uint32_t a, uint32_t ph) {
    asm volatile("{\n.reg .pred p;\n.reg .u32 n;\nmov.u32 n, 0;\nW_%=:\nmbarrier.try_wait.parity.shared::cta.b64 p, [%0], %1;\n@p bra D_%=;\n"
                 "add.u32 n, n, 1;\nsetp.lt.u32 p, n, 0x400000;\n@p bra W_%=;\ntrap;\nD_%=:\n}" ::"r"(a), "r"(ph) : "memory");
}
__device__ __forceinline__ void mbar_arrive_cluster(uint32_t a, uint32_t cta) {
    asm volatile("{\n.reg .b32 r;\nmapa.shared::cluster.u32 r, %0, %1;\nmbarrier.arrive.shared::cluster.b64 _, [r];\n}" ::"r"(a), "r"(cta) : "memory");
}
__device__ __forceinline__ void bar_sync(int id, int n) { asm volatile("bar.sync %0, %1;" ::"r"(id), "r"(n) : "memory"); }
__device__ __forceinline__ void bar_arrive(int id, int n) { asm volatile("bar.arrive %0, %1;" ::"r"(id), "r"(n) : "memory"); }
__device__ __forceinline__ uint32_t cluster_rank() { uint32_t r; asm("mov.u32 %0, %%cluster_ctarank;" : "=r"(r)); return r; }
__device__ __forceinline__ void cnt_add(unsigned int* c) { asm volatile("red.release.gpu.global.add.u32 [%0], 1;" ::"l"(c) : "memory"); }
__device__ __forceinline__ void cnt_wait(const unsigned int* c, uint32_t target) {
    uint32_t v;
    int spins = 0;
    while (true) {
        asm volatile("ld.acquire.gpu.global.u32 %0, [%1];" : "=r"(v) : "l"(c) : "memory");
        if ((int)(v - target) >= 0) break;
        if (++spins > (1 << 22)) __trap();
        __nanosleep(40);
    }
}
__device__ __forceinline__ void tma2d(uint32_t dst, const CUtensorMap* m, int c0, int c1, uint32_t bar) {
    asm volatile("cp.async.bulk.tensor.2d.shared::cluster.global.mbarrier::complete_tx::bytes [%0], [%1, {%3, %4}], [%2];"
                 ::"r"(dst), "l"(m), "r"(bar), "r"(c0), "r"(c1) : "memory");
}
__device__ __forceinline__ void tma2d_mc(uint32_t dst, const CUtensorMap* m, int c0, int c1, uint32_t bar) {
    asm volatile("cp.async.bulk.tensor.2d.shared::cluster.global.mbarrier::complete_tx::bytes.multicast::cluster [%0], [%1, {%3, %4}], [%2], %5;"
                 ::"r"(dst), "l"(m), "r"(bar), "r"(c0), "r"(c1), "h"((uint16_t)3) : "memory");
}
__device__ __forceinline__ void tma3d_mc(uint32_t dst, const CUtensorMap* m, int c0, int c1, int c2, uint32_t bar) {
    asm volatile("cp.async.bulk.tensor.3d.shared::cluster.global.mbarrier::complete_tx::bytes.multicast::cluster [%0], [%1, {%3, %4, %5}], [%2], %6;"
                 ::"r"(dst), "l"(m), "r"(bar), "r"(c0), "r"(c1), "r"(c2), "h"((uint16_t)3) : "memory");
}
__device__ __forceinline__ void tma5d_mc(uint32_t dst, const CUtensorMap* m, int c0, int c4, uint32_t bar) {
    asm volatile("cp.async.bulk.tensor.5d.shared::cluster.global.mbarrier::complete_tx::bytes.multicast::cluster [%0], [%1, {%3, %5, %5, %5, %4}], [%2], %6;"
                 ::"r"(dst), "l"(m), "r"(bar), "r"(c0), "r"(c4), "r"(0), "h"((uint16_t)3) : "memory");
}
__device__ __forceinline__ void bulk_mc(uint32_t dst, const void* src, uint32_t bytes, uint32_t bar) {
    asm volatile("cp.async.bulk.shared::cluster.global.mbarrier::complete_tx::bytes.multicast::cluster [%0], [%1], %2, [%3], %4;"
                 ::"r"(dst), "l"(src), "r"(bytes), "r"(bar), "h"((uint16_t)3) : "memory");
}
__device__ __forceinline__ void tma3d_st(const CUtensorMap* m, uint32_t src, int c0, int c1, int c2) {
    asm volatile("cp.async.bulk.tensor.3d.global.shared::cta.bulk_group [%0, {%2, %3, %4}], [%1];" ::"l"(m), "r"(src), "r"(c0), "r"(c1), "r"(c2) : "memory");
}
__device__ __forceinline__ void tma5d_st(const CUtensorMap* m, uint32_t src, int c1, int c2, int c4) {
    asm volatile("cp.async.bulk.tensor.5d.global.shared::cta.bulk_group [%0, {%5, %2, %3, %5, %4}], [%1];"
                 ::"l"(m), "r"(src), "r"(c1), "r"(c2), "r"(c4), "r"(0) : "memory");
}
__device__ __forceinline__ void bulk_st(void* dst, uint32_t src, uint32_t bytes) {
    asm volatile("cp.async.bulk.global.shared::cta.bulk_group [%0], [%1], %2;" ::"l"(dst), "r"(src), "r"(bytes) : "memory");
}
__device__ __forceinline__ void sts64(uint32_t a, uint32_t x, uint32_t y) { asm volatile("st.shared.v2.u32 [%0], {%1, %2};" ::"r"(a), "r"(x), "r"(y) : "memory"); }
__device__ __forceinline__ void sts128(uint32_t a, const uint32_t* v) {
    asm volatile("st.shared.v4.u32 [%0], {%1, %2, %3, %4};" ::"r"(a), "r"(v[0]), "r"(v[1]), "r"(v[2]), "r"(v[3]) : "memory");
}
__device__ __forceinline__ void l2_prefetch(const void* src, uint32_t bytes) {
    asm volatile("cp.async.bulk.prefetch.L2.global [%0], %1;" ::"l"(src), "r"(bytes) : "memory");
}
__device__ __forceinline__ void map_prefetch(const CUtensorMap* m) { asm volatile("prefetch.tensormap [%0];" ::"l"(m) : "memory"); }
__device__ __forceinline__ void wg_fence() { asm volatile("wgmma.fence.sync.aligned;" ::: "memory"); }
__device__ __forceinline__ void wg_commit() { asm volatile("wgmma.commit_group.sync.aligned;" ::: "memory"); }
template <int N> __device__ __forceinline__ void wg_wait() { asm volatile("wgmma.wait_group.sync.aligned %0;" ::"n"(N) : "memory"); }
template <int N> __device__ __forceinline__ void pin(float* s) {
#pragma unroll
    for (int i = 0; i < N; i++) asm volatile("" : "+f"(s[i])::"memory");
}
template <int N> __device__ __forceinline__ void pin(uint32_t* s) {
#pragma unroll
    for (int i = 0; i < N; i++) asm volatile("" : "+r"(s[i])::"memory");
}
__device__ __forceinline__ uint64_t mkdesc(uint32_t addr, uint32_t lbo, uint32_t sbo, uint32_t swz) {
    return (uint64_t)((addr & 0x3FFFF) >> 4) | ((uint64_t)(lbo >> 4) << 16) | ((uint64_t)(sbo >> 4) << 32) | ((uint64_t)swz << 62);
}
__device__ __forceinline__ float ex2f(float x) { float y; asm("ex2.approx.ftz.f32 %0, %1;" : "=f"(y) : "f"(x)); return y; }
__device__ __forceinline__ float tanhf_(float x) { float y; asm("tanh.approx.f32 %0, %1;" : "=f"(y) : "f"(x)); return y; }
__device__ __forceinline__ uint32_t pk_bf16(float lo, float hi) { uint32_t r; asm("cvt.rn.bf16x2.f32 %0, %1, %2;" : "=r"(r) : "f"(hi), "f"(lo)); return r; }
__device__ __forceinline__ uint32_t pk_f16(float lo, float hi) { uint32_t r; asm("cvt.rn.f16x2.f32 %0, %1, %2;" : "=r"(r) : "f"(hi), "f"(lo)); return r; }
__device__ __forceinline__ float bf_lo(uint32_t v) { return __uint_as_float(v << 16); }
__device__ __forceinline__ float bf_hi(uint32_t v) { return __uint_as_float(v & 0xffff0000u); }
__device__ __forceinline__ float dot8(const uint4& a, const uint4& b) {
    return fmaf(bf_lo(a.x), bf_lo(b.x), fmaf(bf_hi(a.x), bf_hi(b.x), fmaf(bf_lo(a.y), bf_lo(b.y), bf_hi(a.y) * bf_hi(b.y)))) +
           fmaf(bf_lo(a.z), bf_lo(b.z), fmaf(bf_hi(a.z), bf_hi(b.z), fmaf(bf_lo(a.w), bf_lo(b.w), bf_hi(a.w) * bf_hi(b.w))));
}
__device__ __forceinline__ float ldcg_f(const float* p) { return __ldcg(p); }

#define TLM(k, slot) do {} while (0)
#define TLC(k, slot) do {} while (0)

__device__ __forceinline__ void wgmma_ss_n128(float* d, uint64_t da, uint64_t db) {
    asm volatile("wgmma.mma_async.sync.aligned.m64n128k16.f32.bf16.bf16 {"
        "%0, %1, %2, %3, %4, %5, %6, %7, %8, %9, %10, %11, %12, %13, %14, %15,"
        "%16, %17, %18, %19, %20, %21, %22, %23, %24, %25, %26, %27, %28, %29, %30, %31,"
        "%32, %33, %34, %35, %36, %37, %38, %39, %40, %41, %42, %43, %44, %45, %46, %47,"
        "%48, %49, %50, %51, %52, %53, %54, %55, %56, %57, %58, %59, %60, %61, %62, %63}, %64, %65, 1, 1, 1, 0, 1;\n"
        :
        "+f"(d[0]), "+f"(d[1]), "+f"(d[2]), "+f"(d[3]), "+f"(d[4]), "+f"(d[5]), "+f"(d[6]), "+f"(d[7]),
        "+f"(d[8]), "+f"(d[9]), "+f"(d[10]), "+f"(d[11]), "+f"(d[12]), "+f"(d[13]), "+f"(d[14]), "+f"(d[15]),
        "+f"(d[16]), "+f"(d[17]), "+f"(d[18]), "+f"(d[19]), "+f"(d[20]), "+f"(d[21]), "+f"(d[22]), "+f"(d[23]),
        "+f"(d[24]), "+f"(d[25]), "+f"(d[26]), "+f"(d[27]), "+f"(d[28]), "+f"(d[29]), "+f"(d[30]), "+f"(d[31]),
        "+f"(d[32]), "+f"(d[33]), "+f"(d[34]), "+f"(d[35]), "+f"(d[36]), "+f"(d[37]), "+f"(d[38]), "+f"(d[39]),
        "+f"(d[40]), "+f"(d[41]), "+f"(d[42]), "+f"(d[43]), "+f"(d[44]), "+f"(d[45]), "+f"(d[46]), "+f"(d[47]),
        "+f"(d[48]), "+f"(d[49]), "+f"(d[50]), "+f"(d[51]), "+f"(d[52]), "+f"(d[53]), "+f"(d[54]), "+f"(d[55]),
        "+f"(d[56]), "+f"(d[57]), "+f"(d[58]), "+f"(d[59]), "+f"(d[60]), "+f"(d[61]), "+f"(d[62]), "+f"(d[63])
        : "l"(da), "l"(db));
}
__device__ __forceinline__ void wgmma_ss_n96(float* d, uint64_t da, uint64_t db) {
    asm volatile("wgmma.mma_async.sync.aligned.m64n96k16.f32.bf16.bf16 {"
        "%0, %1, %2, %3, %4, %5, %6, %7, %8, %9, %10, %11, %12, %13, %14, %15,"
        "%16, %17, %18, %19, %20, %21, %22, %23, %24, %25, %26, %27, %28, %29, %30, %31,"
        "%32, %33, %34, %35, %36, %37, %38, %39, %40, %41, %42, %43, %44, %45, %46, %47}, %48, %49, 1, 1, 1, 0, 1;\n"
        :
        "+f"(d[0]), "+f"(d[1]), "+f"(d[2]), "+f"(d[3]), "+f"(d[4]), "+f"(d[5]), "+f"(d[6]), "+f"(d[7]),
        "+f"(d[8]), "+f"(d[9]), "+f"(d[10]), "+f"(d[11]), "+f"(d[12]), "+f"(d[13]), "+f"(d[14]), "+f"(d[15]),
        "+f"(d[16]), "+f"(d[17]), "+f"(d[18]), "+f"(d[19]), "+f"(d[20]), "+f"(d[21]), "+f"(d[22]), "+f"(d[23]),
        "+f"(d[24]), "+f"(d[25]), "+f"(d[26]), "+f"(d[27]), "+f"(d[28]), "+f"(d[29]), "+f"(d[30]), "+f"(d[31]),
        "+f"(d[32]), "+f"(d[33]), "+f"(d[34]), "+f"(d[35]), "+f"(d[36]), "+f"(d[37]), "+f"(d[38]), "+f"(d[39]),
        "+f"(d[40]), "+f"(d[41]), "+f"(d[42]), "+f"(d[43]), "+f"(d[44]), "+f"(d[45]), "+f"(d[46]), "+f"(d[47])
        : "l"(da), "l"(db));
}
__device__ __forceinline__ void wgmma_ss_n64(float* d, uint64_t da, uint64_t db) {
    asm volatile("wgmma.mma_async.sync.aligned.m64n64k16.f32.bf16.bf16 {"
        "%0, %1, %2, %3, %4, %5, %6, %7, %8, %9, %10, %11, %12, %13, %14, %15,"
        "%16, %17, %18, %19, %20, %21, %22, %23, %24, %25, %26, %27, %28, %29, %30, %31}, %32, %33, 1, 1, 1, 0, 1;\n"
        :
        "+f"(d[0]), "+f"(d[1]), "+f"(d[2]), "+f"(d[3]), "+f"(d[4]), "+f"(d[5]), "+f"(d[6]), "+f"(d[7]),
        "+f"(d[8]), "+f"(d[9]), "+f"(d[10]), "+f"(d[11]), "+f"(d[12]), "+f"(d[13]), "+f"(d[14]), "+f"(d[15]),
        "+f"(d[16]), "+f"(d[17]), "+f"(d[18]), "+f"(d[19]), "+f"(d[20]), "+f"(d[21]), "+f"(d[22]), "+f"(d[23]),
        "+f"(d[24]), "+f"(d[25]), "+f"(d[26]), "+f"(d[27]), "+f"(d[28]), "+f"(d[29]), "+f"(d[30]), "+f"(d[31])
        : "l"(da), "l"(db));
}
__device__ __forceinline__ void wgmma_qk_f16_acc(float* d, const uint32_t* a, uint64_t db) {
    asm volatile("wgmma.mma_async.sync.aligned.m64n64k16.f32.f16.f16 {"
        "%0, %1, %2, %3, %4, %5, %6, %7, %8, %9, %10, %11, %12, %13, %14, %15,"
        "%16, %17, %18, %19, %20, %21, %22, %23, %24, %25, %26, %27, %28, %29, %30, %31}, {%32, %33, %34, %35}, %36, 1, 1, 1, 0;\n"
        :
        "+f"(d[0]), "+f"(d[1]), "+f"(d[2]), "+f"(d[3]), "+f"(d[4]), "+f"(d[5]), "+f"(d[6]), "+f"(d[7]),
        "+f"(d[8]), "+f"(d[9]), "+f"(d[10]), "+f"(d[11]), "+f"(d[12]), "+f"(d[13]), "+f"(d[14]), "+f"(d[15]),
        "+f"(d[16]), "+f"(d[17]), "+f"(d[18]), "+f"(d[19]), "+f"(d[20]), "+f"(d[21]), "+f"(d[22]), "+f"(d[23]),
        "+f"(d[24]), "+f"(d[25]), "+f"(d[26]), "+f"(d[27]), "+f"(d[28]), "+f"(d[29]), "+f"(d[30]), "+f"(d[31])
        : "r"(a[0]), "r"(a[1]), "r"(a[2]), "r"(a[3]), "l"(db));
}
__device__ __forceinline__ void wgmma_qk_bf16_zero(float* d, const uint32_t* a, uint64_t db) {
    asm volatile("wgmma.mma_async.sync.aligned.m64n64k16.f32.bf16.bf16 {"
        "%0, %1, %2, %3, %4, %5, %6, %7, %8, %9, %10, %11, %12, %13, %14, %15,"
        "%16, %17, %18, %19, %20, %21, %22, %23, %24, %25, %26, %27, %28, %29, %30, %31}, {%32, %33, %34, %35}, %36, 0, 1, 1, 0;\n"
        :
        "=f"(d[0]), "=f"(d[1]), "=f"(d[2]), "=f"(d[3]), "=f"(d[4]), "=f"(d[5]), "=f"(d[6]), "=f"(d[7]),
        "=f"(d[8]), "=f"(d[9]), "=f"(d[10]), "=f"(d[11]), "=f"(d[12]), "=f"(d[13]), "=f"(d[14]), "=f"(d[15]),
        "=f"(d[16]), "=f"(d[17]), "=f"(d[18]), "=f"(d[19]), "=f"(d[20]), "=f"(d[21]), "=f"(d[22]), "=f"(d[23]),
        "=f"(d[24]), "=f"(d[25]), "=f"(d[26]), "=f"(d[27]), "=f"(d[28]), "=f"(d[29]), "=f"(d[30]), "=f"(d[31])
        : "r"(a[0]), "r"(a[1]), "r"(a[2]), "r"(a[3]), "l"(db));
}
__device__ __forceinline__ void wgmma_pv(float* d, const uint32_t* a, uint64_t db) {
    asm volatile("wgmma.mma_async.sync.aligned.m64n24k16.f32.bf16.bf16 {"
        "%0, %1, %2, %3, %4, %5, %6, %7, %8, %9, %10, %11}, {%12, %13, %14, %15}, %16, 1, 1, 1, 1;\n"
        :
        "+f"(d[0]), "+f"(d[1]), "+f"(d[2]), "+f"(d[3]), "+f"(d[4]), "+f"(d[5]), "+f"(d[6]), "+f"(d[7]),
        "+f"(d[8]), "+f"(d[9]), "+f"(d[10]), "+f"(d[11])
        : "r"(a[0]), "r"(a[1]), "r"(a[2]), "r"(a[3]), "l"(db));
}

template <int N> __device__ __forceinline__ void wgmma_ss(float* d, uint64_t a, uint64_t b) {
    if (N == 128) wgmma_ss_n128(d, a, b);
    if (N == 96) wgmma_ss_n96(d, a, b);
    if (N == 64) wgmma_ss_n64(d, a, b);
}

#define OFF_R 131072
#define OFF_S (OFF_R + 65536)
#define OFF_ONE 229376
#define OFF_BAR 229888
#define OFF_BIAS (OFF_BAR + 768)
#define OFF_G (OFF_BIAS + 832)
#define SMEM_BYTES (OFF_G + 272)
#define SBD 1024u
#define B_X 0
#define B_F1 512
#define B_E1 112
#define B_KV 160
#define B_F2 224
#define B_E2 256
#define B_T 288
#define B_DONE 352
#define B_G 360
#define B_G2 368
#define B_G3 376
#define B_SF 384
#define B_SF2 408
#define NR 4

#define PF 1
#define PFX 0
#define EXP_FKK 4
#define QSCALE 0.36067376022224085f
#define MAGIC 445.41763f
#define NMUFU 4
#define VSTEP ((uint64_t)((long long)32 - ((long long)32 << 16)))

#define KVMASK 0xEA52u
__host__ __device__ constexpr int strm_pos(int pass, int i) {
    if (pass == 1 || pass == 2) return 8 + 8 * pass + i;
    int n = 0;
    for (int p = 0; p < 16; p++)
        if ((int)((KVMASK >> p) & 1) == (pass == 3)) { if (n == i) return p; n++; }
    return 0;
}
__host__ __device__ constexpr uint32_t strm_code(int pass) {
    uint32_t c = 0;
    for (int i = 0; i < 7; i++) c |= (uint32_t)(strm_pos(pass, i + 1) - strm_pos(pass, i)) << (4 * i);
    return c;
}

template <int N, int SUB, int KST, int LBO, int SBO, int SWZ>
__device__ __forceinline__ void gemm_pass(float* acc, uint32_t bar, uint64_t dA, int lane, uint32_t pos, uint32_t code, int barNext, bool waitx) {
    uint32_t prev = 0;
#pragma unroll 1
    for (int i = 0; i < 8; i++) {
        const uint32_t slot = pos % NR;
        if (waitx) mbar_wait(bar + B_X + 8 * i, 0);
        mbar_wait(bar + B_F1 + 8 * pos, 0);
        const uint64_t dB = mkdesc(SBD + OFF_R, LBO, SBO, SWZ) + slot * 1024;
        wg_fence();
        wgmma_ss<N>(acc, dA, dB);
        wgmma_ss<N>(acc, dA + 2, dB + KST / 16);
        wg_commit();
        wg_wait<1>();
        if (i > 0 && lane < 2) mbar_arrive_cluster(bar + B_E1 + 8 * prev, lane);
        wgmma_ss<N>(acc, dA + 4, dB + SUB / 16);
        wgmma_ss<N>(acc, dA + 6, dB + (SUB + KST) / 16);
        wg_commit();
        prev = slot;
        pos += code & 15;
        code >>= 4;
        dA += 1024;
    }
    if (barNext) bar_arrive(barNext, 512);
    wg_wait<0>();
    if (lane < 2) mbar_arrive_cluster(bar + B_E1 + 8 * prev, lane);
    pin<N / 2>(acc);
}

__device__ __forceinline__ uint32_t lds32(uint32_t a) { uint32_t v; asm volatile("ld.shared.u32 %0, [%1];" : "=r"(v) : "r"(a)); return v; }
__device__ __forceinline__ bool elect() {
    uint32_t p;
    asm volatile("{\n.reg .pred p;\nelect.sync _|p, 0xffffffff;\nselp.u32 %0, 1, 0, p;\n}" : "=r"(p));
    return p;
}

template <int N> __device__ __forceinline__ void bias_init(float* acc, uint32_t b) {
#pragma unroll
    for (int j = 0; j < N / 8; j++) {
        const uint32_t bv = lds32(b + j * 16);
        acc[4 * j] = acc[4 * j + 2] = bf_lo(bv);
        acc[4 * j + 1] = acc[4 * j + 3] = bf_hi(bv);
    }
    pin<N / 2>(acc);
}

template <int G0, int G1> __device__ __forceinline__ void gelu_store(const float* acc, uint32_t hp) {
#pragma unroll
    for (int G = G0; G < G1; G++) {
        uint32_t o[8];
#pragma unroll
        for (int j = 0; j < 4; j++) {
            float y[4];
#pragma unroll
            for (int i = 0; i < 4; i++) {
                const float h = acc[16 * G + 4 * j + i];
                const float z = h * fmaf(h * h, 0.035677408136300125f, 0.7978845608028654f);
                const float hh = 0.5f * h;
                y[i] = fmaf(hh, tanhf_(z), hh);
            }
            o[j] = pk_bf16(y[0], y[1]);
            o[4 + j] = pk_bf16(y[2], y[3]);
        }
        sts128(hp + G * 8192, o);
        sts128(hp + G * 8192 + 512, o + 4);
    }
}

__device__ __forceinline__ float norm_bound(const float* v, float sc) {
    uint32_t m = 0;
#pragma unroll
    for (int h = 0; h < 4; h++) {
        const float* u = v + 8 * h;
        m = max(m, __float_as_uint(fmaf(u[0], u[0], fmaf(u[1], u[1], fmaf(u[4], u[4], u[5] * u[5])))));
        m = max(m, __float_as_uint(fmaf(u[2], u[2], fmaf(u[3], u[3], fmaf(u[6], u[6], u[7] * u[7])))));
    }
#pragma unroll
    for (int o = 4; o < 32; o <<= 1) m = max(m, __shfl_xor_sync(0xffffffffu, m, o));
    float f = __uint_as_float(m);
    f += __shfl_xor_sync(0xffffffffu, f, 1);
    f += __shfl_xor_sync(0xffffffffu, f, 2);
    return f * sc;
}

__device__ __forceinline__ uint32_t exp2_pair(float a, float b) {
    const uint32_t w = __byte_perm(__float_as_uint(a), __float_as_uint(b), 0x6521);
    uint32_t m, r;
    asm("lop3.b32 %0, %1, 0x007f007f, 0x9f809f80, 0xEA;" : "=r"(m) : "r"(w));
    const uint32_t e = w - m;
    asm("fma.rn.bf16x2 %0, %1, %2, %3;" : "=r"(r) : "r"(w), "r"(m), "r"(e));
    return r;
}

__device__ __forceinline__ void store_o(const float* o, uint4* dst, uint32_t par) {
    const float s0 = __fdividef(1.f, o[8]), s1 = __fdividef(1.f, o[10]);
    const uint32_t d0 = (pk_bf16(o[0] * s0, o[1] * s0) & ~1u) | par;
    asm volatile("{\n.reg .b128 t;\nmov.b128 t, {%0, %1, %2, %3};\nst.relaxed.gpu.global.b128 [%4], t;\n}" ::"r"(d0),
                 "r"(pk_bf16(o[4] * s0, o[5] * s0)), "r"(pk_bf16(o[2] * s1, o[3] * s1)), "r"(pk_bf16(o[6] * s1, o[7] * s1)), "l"(dst) : "memory");
}
__device__ __forceinline__ uint4 load_o(const uint4* src) {
    uint4 v;
    asm volatile("{\n.reg .b128 t;\nld.relaxed.gpu.global.b128 t, [%4];\nmov.b128 {%0, %1, %2, %3}, t;\n}"
                 : "=r"(v.x), "=r"(v.y), "=r"(v.z), "=r"(v.w) : "l"(src) : "memory");
    return v;
}
__device__ __forceinline__ uint32_t bmul2(uint32_t a, uint32_t b) { uint32_t r; asm("mul.rn.bf16x2 %0, %1, %2;" : "=r"(r) : "r"(a), "r"(b)); return r; }
__device__ __forceinline__ void sts32(uint32_t a, uint32_t v) { asm volatile("st.shared.u32 [%0], %1;" ::"r"(a), "r"(v) : "memory"); }
__device__ __forceinline__ void load_q(uint32_t* q, int h, int row, int t) {
    const uint8_t* p = gQ + (size_t)h * (SEQ * 32) + (size_t)row * 32 + t * 4;
    q[0] = __ldcg((const uint32_t*)p); q[1] = __ldcg((const uint32_t*)(p + 256));
    q[2] = __ldcg((const uint32_t*)(p + 16)); q[3] = __ldcg((const uint32_t*)(p + 272));
}

template <int NT>
__device__ __forceinline__ void proj16(float (*c)[8], const __nv_bfloat16* x, const __nv_bfloat16* w, int row0, int rstep, int col, int g, int t) {
#pragma unroll
    for (int i = 0; i < NT; i++)
#pragma unroll
        for (int j = 0; j < 8; j++) c[i][j] = 0.f;
    const unsigned short* wu = (const unsigned short*)w;
#pragma unroll 1
    for (int k = 0; k < DM; k += 16) {
        uint32_t b[4];
#pragma unroll
        for (int j = 0; j < 4; j++) {
            const int kr = k + 2 * t + (j & 1) * 8, cc = col + g + (j >> 1) * 8;
            b[j] = (uint32_t)wu[(size_t)kr * (3 * DM) + cc] | ((uint32_t)wu[(size_t)(kr + 1) * (3 * DM) + cc] << 16);
        }
#pragma unroll
        for (int i = 0; i < NT; i++) {
            const __nv_bfloat16* xp = x + (size_t)(row0 + i * rstep + g) * DM + k + 2 * t;
            const uint32_t a0 = *(const uint32_t*)xp, a1 = *(const uint32_t*)(xp + 8 * DM);
            const uint32_t a2 = *(const uint32_t*)(xp + 8), a3 = *(const uint32_t*)(xp + 8 * DM + 8);
#pragma unroll
            for (int j = 0; j < 2; j++)
                asm volatile("mma.sync.aligned.m16n8k16.row.col.f32.bf16.bf16.f32 {%0,%1,%2,%3}, {%4,%5,%6,%7}, {%8,%9}, {%0,%1,%2,%3};"
                             : "+f"(c[i][4 * j]), "+f"(c[i][4 * j + 1]), "+f"(c[i][4 * j + 2]), "+f"(c[i][4 * j + 3])
                             : "r"(a0), "r"(a1), "r"(a2), "r"(a3), "r"(b[2 * j]), "r"(b[2 * j + 1]));
        }
    }
}

struct Maps { CUtensorMap x, kv, q, f1, f3, h, w2, wo, hs, kvs; };

__global__ void __cluster_dims__(2, 1, 1) __launch_bounds__(640, 1)
fused_kernel(const __grid_constant__ Maps tm, const __nv_bfloat16* __restrict__ x, const __nv_bfloat16* __restrict__ wqkv,
             const __nv_bfloat16* __restrict__ wo, const __nv_bfloat16* __restrict__ w1, const __nv_bfloat16* __restrict__ b1,
             const __nv_bfloat16* __restrict__ w2, const __nv_bfloat16* __restrict__ b2, const __nv_bfloat16* __restrict__ gate,
             __nv_bfloat16* __restrict__ out) {
    extern __shared__ __align__(1024) uint8_t smem_raw[];
    const uint32_t sb = smem_u32(smem_raw);
    const uint32_t bar = sb + OFF_BAR;
    const int tid = threadIdx.x, lane = tid & 31;
    const int warp = __shfl_sync(0xffffffffu, tid >> 5, 0);
    const uint32_t rank = cluster_rank();
    const int cl = blockIdx.x >> 1;
    const int nb = cl & 7, mb = (cl >> 3) * 2 + rank;
    const int g = lane >> 2, t = lane & 3;

    const int cb = nb & 3, rb = mb * 2 + (nb >> 2);
    if (tid == 0) TLM(0, 0);
    if (tid == 512) {
        mbar_init(bar + B_X, 1);
        asm volatile("fence.proxy.async.shared::cta;" ::: "memory");
        mbar_expect(bar + B_X, 16384);
        tma2d(sb, &tm.x, 0, mb * 128, bar + B_X);
        for (int i = 0; i < 8; i++) { if (i) mbar_init(bar + B_X + 8 * i, 1); mbar_init(bar + B_KV + 8 * i, 1); mbar_init(bar + B_T + 8 * i, 5); }
        for (int i = 0; i < NR; i++) mbar_init(bar + B_E1 + 8 * i, 16);
        for (int i = 0; i < 4; i++) { mbar_init(bar + B_F2 + 8 * i, 1); mbar_init(bar + B_E2 + 8 * i, 8); }
        mbar_init(bar + B_DONE, 16);
        mbar_init(bar + B_G, 1);
        for (int i = 0; i < 3; i++) mbar_init(bar + B_SF + 8 * i, 1);
        mbar_init(bar + B_SF2, 2);
        mbar_init(bar + B_G3, 1);
        mbar_init(bar + B_G2, 4);
        asm volatile("fence.mbarrier_init.release.cluster;" ::: "memory");
    } else if (tid == 544) {
        map_prefetch(&tm.q); map_prefetch(&tm.f1); map_prefetch(&tm.kv);
        l2_prefetch((const uint8_t*)wqkv + (size_t)blockIdx.x * 3072, 3072);
        map_prefetch(&tm.f3);
    } else if (tid >= 608) {
        mbar_init(bar + B_F1 + 8 * lane, 1);
        asm volatile("fence.mbarrier_init.release.cluster;" ::: "memory");
    } else if (tid < 128) {
        asm volatile("st.shared.u32 [%0], %1;" ::"r"(sb + OFF_ONE + tid * 4), "r"(0x3f803f80u) : "memory");
        asm volatile("fence.proxy.async.shared::cta;" ::: "memory");
    }
    uint32_t biasv = 0;
    if (tid >= 288 && tid < 256 + 208)
        biasv = tid < 400 ? *(const uint32_t*)(b1 + nb * 224 + (tid - 288) * 2) : *(const uint32_t*)(b2 + cb * 128 + (tid - 400) * 2);
    if ((sb & 0xFFFFFF) != SBD) __trap();
    __syncthreads();
    asm volatile("barrier.cluster.arrive.relaxed.aligned;\nbarrier.cluster.wait.aligned;" ::: "memory");
    const uint32_t ep = gEpoch[blockIdx.x] + 1;
    if (tid == 0) { TLM(0, 1); TLC(0, 30); }

    if (warp < 16) {
        const int wg = warp >> 2;
        const int h = cl >> 1, qd = (cl & 1) * 2 + rank;
        uint32_t q[4];
        {
            const int w8 = warp & 7;
            const int T = mb * 8 + w8;
            const uint64_t dA0 = mkdesc(SBD + (wg & 1) * 8192, 16, 1024, 1);
            if (wg < 2) {
                float acc[64];
#pragma unroll
                for (int i = 0; i < 64; i++) acc[i] = 0.f;
                gemm_pass<128, 8192, 2048, 4096, 1024, 1>(acc, bar, dA0, lane, strm_pos(3, 0), strm_code(3), 6, true);
                if (tid == 0) TLM(0, 2);
                {
                    const float km = norm_bound(acc, 1.f);
                    float vm = 0.f;
#pragma unroll
                    for (int i = 32; i < 64; i++) vm = fmaxf(vm, fabsf(acc[i]));
                    vm = __uint_as_float(__reduce_max_sync(0xffffffffu, __float_as_uint(vm)));
                    if (lane == 0) { gN[1024 + nb * 128 + T] = km; gN[2048 + nb * 128 + T] = vm; }
                    const uint32_t kp = sb + OFF_S + (w8 >> 2) * 1024 + g * 128 + ((((w8 & 3) * 2 + ((t >> 1) ^ (w8 >> 2))) ^ g) << 4) + (t & 1) * 8;
                    mbar_wait(bar + B_SF, 0);
#pragma unroll
                    for (int hh = 0; hh < 4; hh++) {
                        const float* v = acc + 8 * hh;
                        float p0 = __shfl_up_sync(0xffffffffu, v[2], 4), p1 = __shfl_up_sync(0xffffffffu, v[3], 4);
                        float p2 = __shfl_up_sync(0xffffffffu, v[6], 4), p3 = __shfl_up_sync(0xffffffffu, v[7], 4);
                        if (g == 0) { p0 = p1 = p2 = p3 = 0.f; }
                        const uint32_t o = kp + hh * 8192;
                        sts64(o, pk_f16(v[0] - p0, v[1] - p1), pk_f16(v[4] - p2, v[5] - p3));
                        sts64(o + 2048, pk_f16(v[2] - v[0], v[3] - v[1]), pk_f16(v[6] - v[4], v[7] - v[5]));
                        const float* u = acc + 32 + 8 * hh;
                        sts64(o + 4096, pk_bf16(u[0], u[1]), pk_bf16(u[4], u[5]));
                        sts64(o + 6144, pk_bf16(u[2], u[3]), pk_bf16(u[6], u[7]));
                    }
                }
                asm volatile("fence.proxy.async.shared::cta;" ::: "memory");
                bar_arrive(10, 288);
                if (tid == 0) TLM(0, 3);
                bar_sync(12, 512);
            }
            const int pend = wg < 2 ? 3 : 2;
#pragma unroll 1
            for (int p = wg < 2 ? 2 : 0; p < pend; p++) {
                float acc[48];
                if (p) {
                    bias_init<96>(acc, sb + OFF_BIAS + p * 192 + t * 4);
                    bar_sync(5 + p, 512);
                } else {
#pragma unroll
                    for (int i = 0; i < 48; i++) acc[i] = 0.f;
                    pin<48>(acc);
                }
                gemm_pass<96, 6144, 1024, 2048, 512, 2>(acc, bar, dA0, lane, p == 0 ? strm_pos(0, 0) : 8 + 8 * p, p == 0 ? strm_code(0) : strm_code(1), p == 1 ? 7 : 0, p == 0);
                if ((tid & 255) == 0) TLM(0, 4 + 2 * p);
                const uint32_t hp = sb + OFF_S + (w8 * 16 + g) * 64 + t * 16;
                if (p == 0) {
                    if (tid < 256 + 208) sts32(sb + OFF_BIAS + (tid - 256) * 4, biasv);
                    bar_arrive(12, 512);
                    const float qm = norm_bound(acc, QSCALE * QSCALE);
                    if (lane == 0) gN[nb * 128 + T] = qm;
                    const uint32_t qp = sb + OFF_S + (w8 * 16 + g) * 32 + t * 8;
#pragma unroll
                    for (int hh = 0; hh < 4; hh++) {
                        const float* v = acc + 8 * hh;
                        sts64(qp + hh * 4096, pk_f16(v[0] * QSCALE, v[1] * QSCALE), pk_f16(v[4] * QSCALE, v[5] * QSCALE));
                        sts64(qp + hh * 4096 + 256, pk_f16(v[2] * QSCALE, v[3] * QSCALE), pk_f16(v[6] * QSCALE, v[7] * QSCALE));
                    }
                    bar_sync(5, 256);
#pragma unroll
                    for (int j = 8; j < 12; j++) {
                        const uint32_t bv = lds32(sb + OFF_BIAS + j * 16 + t * 4);
                        acc[4 * j] += bf_lo(bv); acc[4 * j + 1] += bf_hi(bv); acc[4 * j + 2] += bf_lo(bv); acc[4 * j + 3] += bf_hi(bv);
                    }
                } else {
                    if (p == 2) {
                        mbar_wait(bar + B_G, 0);
                        load_q(q, h, qd * 512 + warp * 16 + g, t);
                    }
                    mbar_wait(bar + B_SF + 8 * p, 0);
                    gelu_store<0, 2>(acc, hp);
                }
                gelu_store<2, 3>(acc, hp);
                asm volatile("fence.proxy.async.shared::cta;" ::: "memory");
                bar_arrive(p == 2 ? 10 : 11, 288);
                if ((tid & 255) == 0) TLM(0, 5 + 2 * p);
            }
            if (wg >= 2) {
                mbar_wait(bar + B_G, 0);
                load_q(q, h, qd * 512 + warp * 16 + g, t);
            }
        }
        mbar_wait(bar + B_G3, 0);
        const bool fast = lds32(sb + OFF_G + 256) != 0;
        uint4* const op = gO + ((qd * 8 + wg) * NH + h) * 128 + (tid & 127);
        const uint64_t kd0 = mkdesc(SBD, 16, 256, 3);
        const uint64_t vd0 = mkdesc(SBD + 8192, OFF_ONE - 8192, 256, 3);
        if (fast) {
#pragma unroll 1
            for (int r = 0; r < 2; r++) {
                float o[12];
#pragma unroll
                for (int i = 0; i < 12; i++) o[i] = 0.f;
                uint64_t kd = kd0, vd = vd0;
                uint32_t qn[4];
#pragma unroll 1
                for (int half = 0; half < 2; half++) {
                    float s[32];
#pragma unroll
                    for (int i = 0; i < 32; i++) s[i] = i < 2 * NMUFU ? 0.f : MAGIC;
#pragma unroll 1
                    for (int c = 0; c < 4; c++) {
                        if (r == 0) mbar_wait(bar + B_KV + 8 * (half * 4 + c), 0);
                        if ((tid & 255) == 0 && c == 0) TLM(1, (tid >> 8) * 4 + r * 2 + half);
                        if (half == 1 && c == 3) {
                            if (r == 0) load_q(qn, h, qd * 512 + 256 + warp * 16 + g, t);
                            else if (lane == 0) mbar_arrive(bar + B_DONE);
                        }
#pragma unroll 1
                        for (int j = 0; j < 4; j++) {
                            uint32_t p[16];
                            wg_fence();
                            wgmma_qk_f16_acc(s, q, kd);
                            wg_commit();
                            wg_wait<0>();
                            pin<32>(s);
#pragma unroll
                            for (int i = 0; i < 16; i++)
                                p[i] = i < NMUFU ? pk_bf16(ex2f(s[2 * i]), ex2f(s[2 * i + 1])) : exp2_pair(s[2 * i], s[2 * i + 1]);
                            pin<16>(p);
                            wg_fence();
#pragma unroll
                            for (int u = 0; u < 4; u++) wgmma_pv(o, p + 4 * u, vd + u * VSTEP);
                            wg_commit();
                            kd += 128;
                            vd += 4 * VSTEP;
                        }
                        kd += 512;
                        vd += 16 * VSTEP;
                    }
                    wg_wait<0>();
                }
                pin<12>(o);
                if ((tid & 127) == 0 && r == 1) TLM(1, 8 + wg);
                store_o(o, op + r * (4 * NH * 128), ep & 1);
#pragma unroll
                for (int i = 0; i < 4; i++) q[i] = qn[i];
            }
            if (tid == 0) { TLM(1, 12); TLC(0, 31); }
        } else {
            for (int c = 0; c < 8; c++) mbar_wait(bar + B_KV + 8 * c, 0);
            {
                float kc[8][8];
                proj16<8>(kc, x, wqkv, warp * 16, 256, DM + h * 16, g, t);
#pragma unroll
                for (int i = 0; i < 8; i++) {
                    const int T = warp + i * 16;
                    const int pos = ((T >> 6) * 16 + 2 * g) * 64 + (T & 63);
                    const uint32_t a = sb + (pos >> 8) * 16384 + (pos & 255) * 32 + t * 4, sw = ((T >> 2) & 1) << 4;
                    asm volatile("st.shared.u32 [%0], %1;" ::"r"(a + sw), "r"(pk_bf16(kc[i][0], kc[i][1])) : "memory");
                    asm volatile("st.shared.u32 [%0], %1;" ::"r"(a + (sw ^ 16)), "r"(pk_bf16(kc[i][4], kc[i][5])) : "memory");
                    asm volatile("st.shared.u32 [%0], %1;" ::"r"(a + 2048 + sw), "r"(pk_bf16(kc[i][2], kc[i][3])) : "memory");
                    asm volatile("st.shared.u32 [%0], %1;" ::"r"(a + 2048 + (sw ^ 16)), "r"(pk_bf16(kc[i][6], kc[i][7])) : "memory");
                }
                asm volatile("fence.proxy.async.shared::cta;" ::: "memory");
                bar_sync(8, 512);
            }
#pragma unroll 1
            for (int r = 0; r < 2; r++) {
                const int row = qd * 512 + r * 256 + warp * 16 + g;
                {
                    float qc[1][8];
                    proj16<1>(qc, x, wqkv, row - g, 0, h * 16, g, t);
#pragma unroll
                    for (int i = 0; i < 4; i++) q[i] = pk_bf16(qc[0][2 * i] * QSCALE, qc[0][2 * i + 1] * QSCALE);
                }
                float o[12];
#pragma unroll
                for (int i = 0; i < 12; i++) o[i] = 0.f;
                float m0 = -INFINITY, m1 = -INFINITY;
#pragma unroll 1
                for (int j = 0; j < 32; j++) {
                    const uint64_t kd = kd0 + (j >> 2) * 1024 + (j & 3) * 128, vd = vd0 + ((j >> 2) * 32 + (j & 3) * 4) * VSTEP;
                    float s[32];
                    uint32_t p[16];
                    wg_fence();
                    wgmma_qk_bf16_zero(s, q, kd);
                    wg_commit();
                    wg_wait<0>();
                    pin<32>(s);
                    pin<12>(o);
                    float n0 = m0, n1 = m1;
#pragma unroll
                    for (int i = 0; i < 8; i++) {
                        n0 = fmaxf(n0, fmaxf(s[4 * i], s[4 * i + 1]));
                        n1 = fmaxf(n1, fmaxf(s[4 * i + 2], s[4 * i + 3]));
                    }
                    n0 = fmaxf(n0, __shfl_xor_sync(0xffffffffu, n0, 1));
                    n1 = fmaxf(n1, __shfl_xor_sync(0xffffffffu, n1, 1));
                    n0 = fmaxf(n0, __shfl_xor_sync(0xffffffffu, n0, 2));
                    n1 = fmaxf(n1, __shfl_xor_sync(0xffffffffu, n1, 2));
                    const float c0 = ex2f(m0 - n0), c1 = ex2f(m1 - n1);
                    m0 = n0;
                    m1 = n1;
#pragma unroll
                    for (int i = 0; i < 3; i++) { o[4 * i] *= c0; o[4 * i + 1] *= c0; o[4 * i + 2] *= c1; o[4 * i + 3] *= c1; }
#pragma unroll
                    for (int i = 0; i < 8; i++) {
                        p[2 * i] = pk_bf16(ex2f(s[4 * i] - m0), ex2f(s[4 * i + 1] - m0));
                        p[2 * i + 1] = pk_bf16(ex2f(s[4 * i + 2] - m1), ex2f(s[4 * i + 3] - m1));
                    }
                    pin<16>(p);
                    pin<12>(o);
                    wg_fence();
#pragma unroll
                    for (int u = 0; u < 4; u++) wgmma_pv(o, p + 4 * u, vd + u * VSTEP);
                    wg_commit();
                }
                wg_wait<0>();
                pin<12>(o);
                if (r == 1 && lane == 0) mbar_arrive(bar + B_DONE);
                store_o(o, op + r * (4 * NH * 128), ep & 1);
            }
        }
        {
            const uint4* src = gO + (rb * NH + wg * 8) * 128 + (tid & 127);
            uint4 v[8];
#pragma unroll
            for (int i = 0; i < 8; i++) v[i] = load_o(src + i * 128);
            mbar_wait(bar + B_DONE, 0);
            mbar_wait(bar + B_G2, 0);
            const int lr = (warp & 3) * 16 + g;
            const uint32_t g0 = lds32(sb + OFF_G + lr * 4), g1 = lds32(sb + OFF_G + lr * 4 + 32);
            const uint32_t a0 = sb + wg * 16384 + lr * 128 + (t >> 1) * 4;
#pragma unroll
            for (int i = 0; i < 8; i++) {
                if ((i & 3) == 0) {
                    int spins = 0;
                    while (__any_sync(0xffffffffu, (((v[i].x ^ ep) | (v[i + 1].x ^ ep) | (v[i + 2].x ^ ep) | (v[i + 3].x ^ ep)) & 1) != 0)) {
                        if (++spins > (1 << 22)) __trap();
#pragma unroll
                        for (int k = i; k < 8; k++)
                            if (((v[k].x ^ ep) & 1) != 0) v[k] = load_o(src + k * 128);
                    }
                }
                const uint32_t a = a0 + (i >> 2) * 8192 + ((((i & 3) * 2 + (t & 1)) ^ g) << 4);
                sts32(a, bmul2(v[i].x, g0));
                sts32(a + 8, bmul2(v[i].y, g0));
                sts32(a + 1024, bmul2(v[i].z, g1));
                sts32(a + 1024 + 8, bmul2(v[i].w, g1));
                if ((i & 3) == 3) {
                    asm volatile("fence.proxy.async.shared::cta;" ::: "memory");
                    __syncwarp();
                    if (lane == 0) mbar_arrive(bar + B_T + 8 * (wg * 2 + (i >> 2)));
                    if ((tid & 127) == 0) TLM(1, 20 + wg * 2 + (i >> 2));
                }
            }
        }
    } else {
        if (warp == 16) {
            if (elect()) {
                int s = 0, par = 1, k0 = rank * 32, k3 = rank * 32;
#pragma unroll 1
                for (int it = 0; it < 32; it++) {
                    const uint32_t fb = bar + B_F1 + 8 * it, dst = sb + OFF_R + s * 16384;
                    mbar_wait(bar + B_E1 + 8 * s, par);
                    if (it < 16 && ((KVMASK >> it) & 1)) {
                        mbar_expect(fb, 16384);
                        tma3d_mc(dst + rank * 8192, &tm.kv, nb * 64, k3, 1, fb);
                        k3 += 64;
                    } else {
                        mbar_expect(fb, 12288);
                        if (it < 16) {
                            tma3d_mc(dst + rank * 6144, &tm.q, 0, k0, nb * 2, fb);
                            tma3d_mc(dst + rank * 6144 + 4096, &tm.f1, 0, k0, nb * 7, fb);
                            const int c = (k0 >> 6) + 1;
                            if (c < 8) {
                                mbar_expect(bar + B_X + 8 * c, 16384);
                                tma2d(sb + c * 16384, &tm.x, c * 64, mb * 128, bar + B_X + 8 * c);
                            }
                        } else {
                            tma3d_mc(dst + rank * 6144, &tm.f3, 0, k0 & 511, nb * 7 + (it < 24 ? 1 : 4), fb);
                        }
                        k0 += 64;
                    }
                    if (++s == NR) { s = 0; par ^= 1; }
                }
                const int h = cl >> 1;
                mbar_wait(bar + B_G, 0);
                asm volatile("fence.proxy.async.global;" ::: "memory");
                TLM(0, 10);
#pragma unroll 1
                for (int c = 0; c < 8; c++) {
                    if (c >= 8 - NR) {
                        mbar_wait(bar + B_E1 + 8 * s, par);
                        if (++s == NR) { s = 0; par ^= 1; }
                    }
                    mbar_expect(bar + B_KV + 8 * c, 16384);
                    bulk_mc(sb + c * 16384 + rank * 8192, gKV + (size_t)h * (SEQ * 64) + rank * 65536 + c * 8192, 8192, bar + B_KV + 8 * c);
                }
                mbar_wait(bar + B_SF2, 0);
#pragma unroll 1
                for (s = 0; s < 4; s++) {
                    mbar_expect(bar + B_F2 + 8 * s, 24576);
                    tma5d_mc(sb + OFF_R + s * 24576 + 8192 + rank * 8192, &tm.w2, cb * 128 + rank * 64, s * 2, bar + B_F2 + 8 * s);
                }
                cnt_wait(gCntH + mb * 32, ep * 8);
                asm volatile("fence.proxy.async.global;" ::: "memory");
                TLM(1, 13);
#pragma unroll 1
                for (s = 0; s < 4; s++) tma2d(sb + OFF_R + s * 24576, &tm.h, s * 64, rb * 64, bar + B_F2 + 8 * s);
            }
        } else if (warp == 17) {
            mbar_wait(bar + B_X + 8 * PFX, 0);
            if (lane == 0) {
                l2_prefetch((const uint8_t*)wqkv + 128 * 3072 + (size_t)blockIdx.x * 9216, 9216);
                l2_prefetch((const uint8_t*)w1 + (size_t)blockIdx.x * 14336, 14336);
            }
            mbar_wait(bar + B_X + 8 * 7, 0);
            if (lane == 0) {
                l2_prefetch((const uint8_t*)w2 + (size_t)blockIdx.x * 14336, 14336);
                l2_prefetch((const uint8_t*)wo + (size_t)blockIdx.x * 4096, 4096);
                map_prefetch(&tm.h); map_prefetch(&tm.w2); map_prefetch(&tm.wo); map_prefetch(&tm.hs); map_prefetch(&tm.kvs);
                TLM(0, 11);
            }
#pragma unroll 1
            for (int e = 0; e < 4; e++) {
                bar_sync(11 - (e & 1), 288);
                if (e == 3) bar_sync(13, 96);
                if (lane == 0) {
                    if (e == 1) {
                        tma5d_st(&tm.kvs, sb + OFF_S, (mb >> 3) * 8, (mb & 7) * 2, nb * 8);
                    } else {
                        if (e == 0) {
                            for (int hh = 0; hh < 4; hh++) bulk_st(gQ + (size_t)(nb * 4 + hh) * (SEQ * 32) + mb * 4096, sb + OFF_S + hh * 4096, 4096);
                        } else {
                            tma3d_st(&tm.hs, sb + OFF_S, 0, mb * 128, nb * 7 + e * 3 - 5);
                            tma3d_st(&tm.hs, sb + OFF_S + 8192, 0, mb * 128, nb * 7 + e * 3 - 4);
                        }
                        tma3d_st(&tm.hs, sb + OFF_S + 16384, 0, mb * 128, nb * 7 + (e == 0 ? 0 : e * 3 - 3));
                    }
                    asm volatile("cp.async.bulk.commit_group;\ncp.async.bulk.wait_group.read 0;" ::: "memory");
                    if (e < 3) mbar_arrive(bar + B_SF + 8 * e);
                    else { mbar_arrive_cluster(bar + B_SF2, 0); mbar_arrive_cluster(bar + B_SF2, 1); }
                    if (e & 1) {
                        asm volatile("cp.async.bulk.wait_group 0;\nfence.proxy.async.global;" ::: "memory");
                        if (e == 1) { cnt_add(gCntQ + nb * 32); TLM(0, 13); }
                        else { cnt_add(gCntH + mb * 32); TLM(0, 15); }
                    }
                }
                __syncwarp();
            }
        } else {
            {
                const int r0 = mb * 128 + nb * 16 + (warp - 18) * 8;
                uint4 xv[16];
#pragma unroll
                for (int i = 0; i < 16; i++) xv[i] = *(const uint4*)(x + (size_t)(r0 + (i >> 1)) * DM + (i & 1) * 256 + lane * 8);
                const uint4 ga = *(const uint4*)(gate + lane * 8), gb = *(const uint4*)(gate + 256 + lane * 8);
                float z[8];
#pragma unroll
                for (int r = 0; r < 8; r++) z[r] = dot8(xv[2 * r], ga) + dot8(xv[2 * r + 1], gb);
#pragma unroll
                for (int w = 4; w >= 1; w >>= 1)
#pragma unroll
                    for (int r = 0; r < w; r++) {
                        const bool up = lane & w;
                        z[r] = (up ? z[r + w] : z[r]) + __shfl_xor_sync(0xffffffffu, up ? z[r] : z[r + w], w);
                    }
                z[0] += __shfl_xor_sync(0xffffffffu, z[0], 8);
                z[0] += __shfl_xor_sync(0xffffffffu, z[0], 16);
                if (lane < 8) gG[r0 + lane] = 1.f / (1.f + __expf(-z[0]));
                if (tid == 576) TLM(0, 12);
                bar_arrive(13, 96);
            }
            if (warp == 18) {
                const int h = cl >> 1, qd = (cl & 1) * 2 + rank;
                if (lane == 0) {
                    cnt_wait(gCntQ + (h >> 2) * 32, ep * 16);
                    mbar_arrive(bar + B_G);
                    TLM(0, 14);
                }
                __syncwarp();
            const int hb = h >> 2;
            const uint4 kq = __ldcg((const uint4*)(gN + 1024 + hb * 128 + lane * 4));
            const uint4 vq = __ldcg((const uint4*)(gN + 2048 + hb * 128 + lane * 4));
            const float qq = ldcg_f(gN + hb * 128 + qd * 32 + lane);
            const float kf = __uint_as_float(__reduce_max_sync(0xffffffffu, max(max(kq.x, kq.y), max(kq.z, kq.w))));
            const float vf = __uint_as_float(__reduce_max_sync(0xffffffffu, max(max(vq.x, vq.y), max(vq.z, vq.w))));
            const float qf = __uint_as_float(__reduce_max_sync(0xffffffffu, __float_as_uint(qq)));
            if (lane == 0) {
                sts32(sb + OFF_G + 256, (kf <= 1.0e6f) && (qf <= 1.0e6f) && (kf * qf <= 3400.f) && (vf <= 1.0e12f));
                mbar_arrive(bar + B_G3);
            }
            }
        }
        __syncwarp();
        float acc[64];
#pragma unroll
        for (int i = 0; i < 64; i++) acc[i] = 0.f;
#pragma unroll 1
        for (int io = 0; io < 7; io++) {
#pragma unroll
            for (int s = 0; s < 4; s++) {
                const int it = io * 4 + s;
                mbar_wait(bar + B_F2 + 8 * s, io & 1);
                if (tid == 512 && s == 0 && (io == 0 || io == 4)) TLM(1, 14 + io / 4);
                const uint64_t dA = mkdesc(SBD + OFF_R + s * 24576, 16, 1024, 1);
                const uint64_t dB = mkdesc(SBD + OFF_R + s * 24576 + 8192, 8192, 1024, 1);
                wg_fence();
#pragma unroll
                for (int kk = 0; kk < EXP_FKK; kk++) wgmma_ss_n128(acc, dA + kk * 2, dB + kk * 128);
                wg_commit();
                if (warp < 18 && it >= 2 && it < 26) {
                    const int s2 = (s + 2) & 3;
                    mbar_wait(bar + B_E2 + 8 * s2, (io - (s < 2)) & 1);
                    if (elect()) {
                        if (warp == 16) {
                            mbar_expect(bar + B_F2 + 8 * s2, 24576);
                            tma5d_mc(sb + OFF_R + s2 * 24576 + 8192 + rank * 8192, &tm.w2, cb * 128 + rank * 64, it * 2 + 4, bar + B_F2 + 8 * s2);
                        } else {
                            asm volatile("fence.proxy.async.global;" ::: "memory");
                            tma2d(sb + OFF_R + s2 * 24576, &tm.h, it * 64 + 128, rb * 64, bar + B_F2 + 8 * s2);
                        }
                    }
                    __syncwarp();
                }
                wg_wait<1>();
                if (it >= 1 && lane < 2) mbar_arrive_cluster(bar + B_E2 + 8 * ((s + 3) & 3), lane);
            }
        }
        wg_wait<0>();
        if (lane < 2) mbar_arrive_cluster(bar + B_E2 + 8 * 3, lane);
        pin<64>(acc);
        if (warp == 16) {
            if (lane == 0) TLM(1, 16);
            for (int s = 0; s < 4; s++) mbar_wait(bar + B_E2 + 8 * s, 0);
            if (elect()) {
#pragma unroll
                for (int i = 0; i < 8; i++) mbar_expect(bar + B_T + 8 * i, 16384);
#pragma unroll
                for (int i = 0; i < 6; i++) tma2d_mc(sb + OFF_R + i * 16384 + rank * 8192, &tm.wo, cb * 128 + rank * 64, i * 64, bar + B_T + 8 * i);
            }
            __syncwarp();
        }
        {
            const int lr = (warp - 16) * 16 + g;
            const uint32_t pa = pk_bf16(ldcg_f(gG + rb * 64 + lr), ldcg_f(gG + rb * 64 + lr + 8));
            if (t == 0) {
                sts32(sb + OFF_G + lr * 4, __byte_perm(pa, pa, 0x1010));
                sts32(sb + OFF_G + lr * 4 + 32, __byte_perm(pa, pa, 0x3232));
            }
            __syncwarp();
            if (lane == 0) mbar_arrive(bar + B_G2);
            const float ga = bf_lo(pa), gb = bf_hi(pa);
            const float g0 = 1.f - ga, g1 = 1.f - gb;
#pragma unroll
            for (int j = 0; j < 16; j++) {
                const uint32_t bv = lds32(sb + OFF_BIAS + 576 + j * 16 + t * 4);
                acc[4 * j] = (acc[4 * j] + bf_lo(bv)) * g0;
                acc[4 * j + 1] = (acc[4 * j + 1] + bf_hi(bv)) * g0;
                acc[4 * j + 2] = (acc[4 * j + 2] + bf_lo(bv)) * g1;
                acc[4 * j + 3] = (acc[4 * j + 3] + bf_hi(bv)) * g1;
            }
            pin<64>(acc);
        }
        if (warp == 17) {
            mbar_wait(bar + B_DONE, 0);
            if (elect()) {
#pragma unroll
                for (int i = 0; i < 4; i++)
                    tma2d(sb + 65536 + i * 8192, &tm.wo, cb * 128 + (i & 1) * 64, (6 + (i >> 1)) * 64, bar + B_T + 8 * (6 + (i >> 1)));
            }
            __syncwarp();
        }
        if (tid == 512) TLM(1, 17);
#pragma unroll
        for (int i = 0; i < 8; i++) {
            mbar_wait(bar + B_T + 8 * i, 0);
            const uint64_t dA = mkdesc(SBD + i * 8192, 16, 1024, 1);
            const uint64_t dB = mkdesc(i < 6 ? SBD + OFF_R + i * 16384 : SBD + 65536 + (i - 6) * 16384, 8192, 1024, 1);
            wg_fence();
#pragma unroll
            for (int kk = 0; kk < 4; kk++) wgmma_ss_n128(acc, dA + kk * 2, dB + kk * 128);
            wg_commit();
        }
        wg_wait<0>();
        pin<64>(acc);
        if (tid == 512) TLM(1, 18);
        {
            const uint32_t st = sb + 98304 + (warp - 16) * 4352;
            const uint32_t wa = st + (lane & 15) * 272 + (lane >> 4) * 16;
#pragma unroll
            for (int j = 0; j < 8; j++)
                asm volatile("stmatrix.sync.aligned.m8n8.x4.shared.b16 [%0], {%1, %2, %3, %4};" ::"r"(wa + j * 32),
                             "r"(pk_bf16(acc[8 * j], acc[8 * j + 1])), "r"(pk_bf16(acc[8 * j + 2], acc[8 * j + 3])),
                             "r"(pk_bf16(acc[8 * j + 4], acc[8 * j + 5])), "r"(pk_bf16(acc[8 * j + 6], acc[8 * j + 7])) : "memory");
            __syncwarp();
            __nv_bfloat16* op = out + (size_t)(rb * 64 + (warp - 16) * 16 + (lane >> 4)) * DM + cb * 128 + (lane & 15) * 8;
#pragma unroll
            for (int j = 0; j < 8; j++) {
                uint4 v;
                asm volatile("ld.shared.v4.u32 {%0, %1, %2, %3}, [%4];" : "=r"(v.x), "=r"(v.y), "=r"(v.z), "=r"(v.w)
                             : "r"(st + (2 * j + (lane >> 4)) * 272 + (lane & 15) * 16));
                *(uint4*)(op + (size_t)j * 2 * DM) = v;
            }
        }
        if (tid == 512) { gEpoch[blockIdx.x] = ep; TLM(1, 19); }
    }
}

typedef CUresult (*EncodeFn)(CUtensorMap*, CUtensorMapDataType, cuuint32_t, void*, const cuuint64_t*, const cuuint64_t*, const cuuint32_t*,
                             const cuuint32_t*, CUtensorMapInterleave, CUtensorMapSwizzle, CUtensorMapL2promotion, CUtensorMapFloatOOBfill);

static void make_map(EncodeFn enc, CUtensorMap* m, const void* p, int rank, const cuuint64_t* dims, const cuuint64_t* strides,
                     const cuuint32_t* box, CUtensorMapSwizzle swz) {
    const cuuint32_t es[5] = {1, 1, 1, 1, 1};
    enc(m, CU_TENSOR_MAP_DATA_TYPE_BFLOAT16, rank, (void*)p, dims, strides, box, es, CU_TENSOR_MAP_INTERLEAVE_NONE, swz,
        CU_TENSOR_MAP_L2_PROMOTION_L2_128B, CU_TENSOR_MAP_FLOAT_OOB_FILL_NONE);
}

extern "C" void kernel_launch(void* const* d_in, const int* in_sizes, int n_in, void* d_out, int out_size) {
    const __nv_bfloat16* x = (const __nv_bfloat16*)d_in[0];
    const __nv_bfloat16* wqkv = (const __nv_bfloat16*)d_in[1];
    const __nv_bfloat16* wo = (const __nv_bfloat16*)d_in[2];
    const __nv_bfloat16* w1 = (const __nv_bfloat16*)d_in[4];
    const __nv_bfloat16* b1 = (const __nv_bfloat16*)d_in[5];
    const __nv_bfloat16* w2 = (const __nv_bfloat16*)d_in[6];
    const __nv_bfloat16* b2 = (const __nv_bfloat16*)d_in[7];
    const __nv_bfloat16* gate = (const __nv_bfloat16*)d_in[8];

    void* fp = nullptr;
    cudaDriverEntryPointQueryResult qr;
    cudaGetDriverEntryPoint("cuTensorMapEncodeTiled", &fp, cudaEnableDefault, &qr);
    EncodeFn enc = (EncodeFn)fp;
    void *pH, *pKV;
    cudaGetSymbolAddress(&pH, gH);
    cudaGetSymbolAddress(&pKV, gKV);

    Maps tm;
    const CUtensorMapSwizzle S128 = CU_TENSOR_MAP_SWIZZLE_128B, S64 = CU_TENSOR_MAP_SWIZZLE_64B;
    { cuuint64_t d[2] = {DM, SEQ}, s[1] = {DM * 2}; cuuint32_t b[2] = {64, 128}; make_map(enc, &tm.x, x, 2, d, s, b, S128); }
    { cuuint64_t d[3] = {DM, DM, 3}, s[2] = {3 * DM * 2, DM * 2}; cuuint32_t b[3] = {64, 32, 2}; make_map(enc, &tm.kv, wqkv, 3, d, s, b, S128); }
    { cuuint64_t d[3] = {32, DM, 3 * DM / 32}, s[2] = {3 * DM * 2, 64}; cuuint32_t b[3] = {32, 32, 2}; make_map(enc, &tm.q, wqkv, 3, d, s, b, S64); }
    { cuuint64_t d[3] = {32, DM, FF / 32}, s[2] = {FF * 2, 64}; cuuint32_t b[3] = {32, 32, 1}; make_map(enc, &tm.f1, w1, 3, d, s, b, S64); }
    { cuuint64_t d[3] = {32, DM, FF / 32}, s[2] = {FF * 2, 64}; cuuint32_t b[3] = {32, 32, 3}; make_map(enc, &tm.f3, w1, 3, d, s, b, S64); }
    { cuuint64_t d[2] = {FF, SEQ}, s[1] = {FF * 2}; cuuint32_t b[2] = {64, 64}; make_map(enc, &tm.h, pH, 2, d, s, b, S128); }
    { cuuint64_t d[5] = {DM, 2, 4, 4, FF / 32}, s[4] = {1024, 8 * 1024, 2 * 1024, 32 * 1024}; cuuint32_t b[5] = {64, 2, 4, 4, 2};
      make_map(enc, &tm.w2, w2, 5, d, s, b, S128); }
    { cuuint64_t d[2] = {DM, DM}, s[1] = {DM * 2}; cuuint32_t b[2] = {64, 64}; make_map(enc, &tm.wo, wo, 2, d, s, b, S128); }

    { cuuint64_t d[3] = {32, SEQ, FF / 32}, s[2] = {FF * 2, 64}; cuuint32_t b[3] = {32, 128, 1}; make_map(enc, &tm.hs, pH, 3, d, s, b, CU_TENSOR_MAP_SWIZZLE_NONE); }
    { cuuint64_t d[5] = {64, 16, 16, 2, 2 * NH}, s[4] = {4096, 128, 2048, 65536}; cuuint32_t b[5] = {64, 8, 2, 2, 8};
      make_map(enc, &tm.kvs, pKV, 5, d, s, b, S128); }
    cudaFuncSetAttribute(fused_kernel, cudaFuncAttributeMaxDynamicSharedMemorySize, SMEM_BYTES);
    fused_kernel<<<128, 640, SMEM_BYTES, cudaStreamPerThread>>>(tm, x, wqkv, wo, w1, b1, w2, b2, gate, (__nv_bfloat16*)d_out);
}
```

```cpp
#include <cuda_runtime.h>
#include <cuda_bf16.h>
#include <cuda_fp16.h>
#include <cuda.h>
#include <stdint.h>

#define SEQ 2048
#define DM 512
#define FF 1792
#define NH 32

__device__ __align__(1024) uint8_t gQ[NH * SEQ * 32];
__device__ __align__(1024) uint8_t gKV[NH * SEQ * 64];
__device__ __align__(1024) __nv_bfloat16 gH[SEQ * FF];
__device__ __align__(1024) uint4 gO[32 * NH * 128];
__device__ float gG[SEQ];
__device__ float gN[3 * 8 * 128];
__device__ unsigned int gCntQ[8 * 32];
__device__ unsigned int gCntH[32 * 32];
__device__ unsigned int gEpoch[128];

__device__ __forceinline__ uint32_t smem_u32(const void* p) { return (uint32_t)__cvta_generic_to_shared(p); }
__device__ __forceinline__ void mbar_init(uint32_t a, uint32_t c) { asm volatile("mbarrier.init.shared::cta.b64 [%0], %1;" ::"r"(a), "r"(c)); }
__device__ __forceinline__ void mbar_expect(uint32_t a, uint32_t b) { asm volatile("mbarrier.arrive.expect_tx.shared::cta.b64 _, [%0], %1;" ::"r"(a), "r"(b) : "memory"); }
__device__ __forceinline__ void mbar_arrive(uint32_t a) { asm volatile("mbarrier.arrive.shared::cta.b64 _, [%0];" ::"r"(a) : "memory"); }
__device__ __forceinline__ void mbar_wait(uint32_t a, uint32_t ph) {
    asm volatile("{\n.reg .pred p;\n.reg .u32 n;\nmov.u32 n, 0;\nW_%=:\nmbarrier.try_wait.parity.shared::cta.b64 p, [%0], %1;\n@p bra D_%=;\n"
                 "add.u32 n, n, 1;\nsetp.lt.u32 p, n, 0x400000;\n@p bra W_%=;\ntrap;\nD_%=:\n}" ::"r"(a), "r"(ph) : "memory");
}
__device__ __forceinline__ void mbar_arrive_cluster(uint32_t a, uint32_t cta) {
    asm volatile("{\n.reg .b32 r;\nmapa.shared::cluster.u32 r, %0, %1;\nmbarrier.arrive.shared::cluster.b64 _, [r];\n}" ::"r"(a), "r"(cta) : "memory");
}
__device__ __forceinline__ void bar_sync(int id, int n) { asm volatile("bar.sync %0, %1;" ::"r"(id), "r"(n) : "memory"); }
__device__ __forceinline__ void bar_arrive(int id, int n) { asm volatile("bar.arrive %0, %1;" ::"r"(id), "r"(n) : "memory"); }
__device__ __forceinline__ uint32_t cluster_rank() { uint32_t r; asm("mov.u32 %0, %%cluster_ctarank;" : "=r"(r)); return r; }
__device__ __forceinline__ void cnt_add(unsigned int* c) { asm volatile("red.release.gpu.global.add.u32 [%0], 1;" ::"l"(c) : "memory"); }
__device__ __forceinline__ void cnt_wait(const unsigned int* c, uint32_t target) {
    uint32_t v;
    int spins = 0;
    while (true) {
        asm volatile("ld.acquire.gpu.global.u32 %0, [%1];" : "=r"(v) : "l"(c) : "memory");
        if ((int)(v - target) >= 0) break;
        if (++spins > (1 << 22)) __trap();
        __nanosleep(40);
    }
}
__device__ __forceinline__ void tma2d(uint32_t dst, const CUtensorMap* m, int c0, int c1, uint32_t bar) {
    asm volatile("cp.async.bulk.tensor.2d.shared::cluster.global.mbarrier::complete_tx::bytes [%0], [%1, {%3, %4}], [%2];"
                 ::"r"(dst), "l"(m), "r"(bar), "r"(c0), "r"(c1) : "memory");
}
__device__ __forceinline__ void tma2d_mc(uint32_t dst, const CUtensorMap* m, int c0, int c1, uint32_t bar) {
    asm volatile("cp.async.bulk.tensor.2d.shared::cluster.global.mbarrier::complete_tx::bytes.multicast::cluster [%0], [%1, {%3, %4}], [%2], %5;"
                 ::"r"(dst), "l"(m), "r"(bar), "r"(c0), "r"(c1), "h"((uint16_t)3) : "memory");
}
__device__ __forceinline__ void tma3d_mc(uint32_t dst, const CUtensorMap* m, int c0, int c1, int c2, uint32_t bar) {
    asm volatile("cp.async.bulk.tensor.3d.shared::cluster.global.mbarrier::complete_tx::bytes.multicast::cluster [%0], [%1, {%3, %4, %5}], [%2], %6;"
                 ::"r"(dst), "l"(m), "r"(bar), "r"(c0), "r"(c1), "r"(c2), "h"((uint16_t)3) : "memory");
}
__device__ __forceinline__ void tma5d_mc(uint32_t dst, const CUtensorMap* m, int c0, int c4, uint32_t bar) {
    asm volatile("cp.async.bulk.tensor.5d.shared::cluster.global.mbarrier::complete_tx::bytes.multicast::cluster [%0], [%1, {%3, %5, %5, %5, %4}], [%2], %6;"
                 ::"r"(dst), "l"(m), "r"(bar), "r"(c0), "r"(c4), "r"(0), "h"((uint16_t)3) : "memory");
}
__device__ __forceinline__ void bulk_mc(uint32_t dst, const void* src, uint32_t bytes, uint32_t bar) {
    asm volatile("cp.async.bulk.shared::cluster.global.mbarrier::complete_tx::bytes.multicast::cluster [%0], [%1], %2, [%3], %4;"
                 ::"r"(dst), "l"(src), "r"(bytes), "r"(bar), "h"((uint16_t)3) : "memory");
}
__device__ __forceinline__ void tma3d_st(const CUtensorMap* m, uint32_t src, int c0, int c1, int c2) {
    asm volatile("cp.async.bulk.tensor.3d.global.shared::cta.bulk_group [%0, {%2, %3, %4}], [%1];" ::"l"(m), "r"(src), "r"(c0), "r"(c1), "r"(c2) : "memory");
}
__device__ __forceinline__ void tma5d_st(const CUtensorMap* m, uint32_t src, int c1, int c2, int c4) {
    asm volatile("cp.async.bulk.tensor.5d.global.shared::cta.bulk_group [%0, {%5, %2, %3, %5, %4}], [%1];"
                 ::"l"(m), "r"(src), "r"(c1), "r"(c2), "r"(c4), "r"(0) : "memory");
}
__device__ __forceinline__ void bulk_st(void* dst, uint32_t src, uint32_t bytes) {
    asm volatile("cp.async.bulk.global.shared::cta.bulk_group [%0], [%1], %2;" ::"l"(dst), "r"(src), "r"(bytes) : "memory");
}
__device__ __forceinline__ void sts64(uint32_t a, uint32_t x, uint32_t y) { asm volatile("st.shared.v2.u32 [%0], {%1, %2};" ::"r"(a), "r"(x), "r"(y) : "memory"); }
__device__ __forceinline__ void sts128(uint32_t a, const uint32_t* v) {
    asm volatile("st.shared.v4.u32 [%0], {%1, %2, %3, %4};" ::"r"(a), "r"(v[0]), "r"(v[1]), "r"(v[2]), "r"(v[3]) : "memory");
}
__device__ __forceinline__ void l2_prefetch(const void* src, uint32_t bytes) {
    asm volatile("cp.async.bulk.prefetch.L2.global [%0], %1;" ::"l"(src), "r"(bytes) : "memory");
}
__device__ __forceinline__ void map_prefetch(const CUtensorMap* m) { asm volatile("prefetch.tensormap [%0];" ::"l"(m) : "memory"); }
__device__ __forceinline__ void wg_fence() { asm volatile("wgmma.fence.sync.aligned;" ::: "memory"); }
__device__ __forceinline__ void wg_commit() { asm volatile("wgmma.commit_group.sync.aligned;" ::: "memory"); }
template <int N> __device__ __forceinline__ void wg_wait() { asm volatile("wgmma.wait_group.sync.aligned %0;" ::"n"(N) : "memory"); }
template <int N> __device__ __forceinline__ void pin(float* s) {
#pragma unroll
    for (int i = 0; i < N; i++) asm volatile("" : "+f"(s[i])::"memory");
}
template <int N> __device__ __forceinline__ void pin(uint32_t* s) {
#pragma unroll
    for (int i = 0; i < N; i++) asm volatile("" : "+r"(s[i])::"memory");
}
__device__ __forceinline__ uint64_t mkdesc(uint32_t addr, uint32_t lbo, uint32_t sbo, uint32_t swz) {
    return (uint64_t)((addr & 0x3FFFF) >> 4) | ((uint64_t)(lbo >> 4) << 16) | ((uint64_t)(sbo >> 4) << 32) | ((uint64_t)swz << 62);
}
__device__ __forceinline__ float ex2f(float x) { float y; asm("ex2.approx.ftz.f32 %0, %1;" : "=f"(y) : "f"(x)); return y; }
__device__ __forceinline__ float tanhf_(float x) { float y; asm("tanh.approx.f32 %0, %1;" : "=f"(y) : "f"(x)); return y; }
__device__ __forceinline__ uint32_t pk_bf16(float lo, float hi) { uint32_t r; asm("cvt.rn.bf16x2.f32 %0, %1, %2;" : "=r"(r) : "f"(hi), "f"(lo)); return r; }
__device__ __forceinline__ uint32_t pk_f16(float lo, float hi) { uint32_t r; asm("cvt.rn.f16x2.f32 %0, %1, %2;" : "=r"(r) : "f"(hi), "f"(lo)); return r; }
__device__ __forceinline__ float bf_lo(uint32_t v) { return __uint_as_float(v << 16); }
__device__ __forceinline__ float bf_hi(uint32_t v) { return __uint_as_float(v & 0xffff0000u); }
__device__ __forceinline__ float dot8(const uint4& a, const uint4& b) {
    return fmaf(bf_lo(a.x), bf_lo(b.x), fmaf(bf_hi(a.x), bf_hi(b.x), fmaf(bf_lo(a.y), bf_lo(b.y), bf_hi(a.y) * bf_hi(b.y)))) +
           fmaf(bf_lo(a.z), bf_lo(b.z), fmaf(bf_hi(a.z), bf_hi(b.z), fmaf(bf_lo(a.w), bf_lo(b.w), bf_hi(a.w) * bf_hi(b.w))));
}
__device__ __forceinline__ float ldcg_f(const float* p) { return __ldcg(p); }

#define TLM(k, slot) do {} while (0)
#define TLC(k, slot) do {} while (0)

__device__ __forceinline__ void wgmma_ss_n128(float* d, uint64_t da, uint64_t db) {
    asm volatile("wgmma.mma_async.sync.aligned.m64n128k16.f32.bf16.bf16 {"
        "%0, %1, %2, %3, %4, %5, %6, %7, %8, %9, %10, %11, %12, %13, %14, %15,"
        "%16, %17, %18, %19, %20, %21, %22, %23, %24, %25, %26, %27, %28, %29, %30, %31,"
        "%32, %33, %34, %35, %36, %37, %38, %39, %40, %41, %42, %43, %44, %45, %46, %47,"
        "%48, %49, %50, %51, %52, %53, %54, %55, %56, %57, %58, %59, %60, %61, %62, %63}, %64, %65, 1, 1, 1, 0, 1;\n"
        :
        "+f"(d[0]), "+f"(d[1]), "+f"(d[2]), "+f"(d[3]), "+f"(d[4]), "+f"(d[5]), "+f"(d[6]), "+f"(d[7]),
        "+f"(d[8]), "+f"(d[9]), "+f"(d[10]), "+f"(d[11]), "+f"(d[12]), "+f"(d[13]), "+f"(d[14]), "+f"(d[15]),
        "+f"(d[16]), "+f"(d[17]), "+f"(d[18]), "+f"(d[19]), "+f"(d[20]), "+f"(d[21]), "+f"(d[22]), "+f"(d[23]),
        "+f"(d[24]), "+f"(d[25]), "+f"(d[26]), "+f"(d[27]), "+f"(d[28]), "+f"(d[29]), "+f"(d[30]), "+f"(d[31]),
        "+f"(d[32]), "+f"(d[33]), "+f"(d[34]), "+f"(d[35]), "+f"(d[36]), "+f"(d[37]), "+f"(d[38]), "+f"(d[39]),
        "+f"(d[40]), "+f"(d[41]), "+f"(d[42]), "+f"(d[43]), "+f"(d[44]), "+f"(d[45]), "+f"(d[46]), "+f"(d[47]),
        "+f"(d[48]), "+f"(d[49]), "+f"(d[50]), "+f"(d[51]), "+f"(d[52]), "+f"(d[53]), "+f"(d[54]), "+f"(d[55]),
        "+f"(d[56]), "+f"(d[57]), "+f"(d[58]), "+f"(d[59]), "+f"(d[60]), "+f"(d[61]), "+f"(d[62]), "+f"(d[63])
        : "l"(da), "l"(db));
}
__device__ __forceinline__ void wgmma_ss_n96(float* d, uint64_t da, uint64_t db) {
    asm volatile("wgmma.mma_async.sync.aligned.m64n96k16.f32.bf16.bf16 {"
        "%0, %1, %2, %3, %4, %5, %6, %7, %8, %9, %10, %11, %12, %13, %14, %15,"
        "%16, %17, %18, %19, %20, %21, %22, %23, %24, %25, %26, %27, %28, %29, %30, %31,"
        "%32, %33, %34, %35, %36, %37, %38, %39, %40, %41, %42, %43, %44, %45, %46, %47}, %48, %49, 1, 1, 1, 0, 1;\n"
        :
        "+f"(d[0]), "+f"(d[1]), "+f"(d[2]), "+f"(d[3]), "+f"(d[4]), "+f"(d[5]), "+f"(d[6]), "+f"(d[7]),
        "+f"(d[8]), "+f"(d[9]), "+f"(d[10]), "+f"(d[11]), "+f"(d[12]), "+f"(d[13]), "+f"(d[14]), "+f"(d[15]),
        "+f"(d[16]), "+f"(d[17]), "+f"(d[18]), "+f"(d[19]), "+f"(d[20]), "+f"(d[21]), "+f"(d[22]), "+f"(d[23]),
        "+f"(d[24]), "+f"(d[25]), "+f"(d[26]), "+f"(d[27]), "+f"(d[28]), "+f"(d[29]), "+f"(d[30]), "+f"(d[31]),
        "+f"(d[32]), "+f"(d[33]), "+f"(d[34]), "+f"(d[35]), "+f"(d[36]), "+f"(d[37]), "+f"(d[38]), "+f"(d[39]),
        "+f"(d[40]), "+f"(d[41]), "+f"(d[42]), "+f"(d[43]), "+f"(d[44]), "+f"(d[45]), "+f"(d[46]), "+f"(d[47])
        : "l"(da), "l"(db));
}
__device__ __forceinline__ void wgmma_ss_n64(float* d, uint64_t da, uint64_t db) {
    asm volatile("wgmma.mma_async.sync.aligned.m64n64k16.f32.bf16.bf16 {"
        "%0, %1, %2, %3, %4, %5, %6, %7, %8, %9, %10, %11, %12, %13, %14, %15,"
        "%16, %17, %18, %19, %20, %21, %22, %23, %24, %25, %26, %27, %28, %29, %30, %31}, %32, %33, 1, 1, 1, 0, 1;\n"
        :
        "+f"(d[0]), "+f"(d[1]), "+f"(d[2]), "+f"(d[3]), "+f"(d[4]), "+f"(d[5]), "+f"(d[6]), "+f"(d[7]),
        "+f"(d[8]), "+f"(d[9]), "+f"(d[10]), "+f"(d[11]), "+f"(d[12]), "+f"(d[13]), "+f"(d[14]), "+f"(d[15]),
        "+f"(d[16]), "+f"(d[17]), "+f"(d[18]), "+f"(d[19]), "+f"(d[20]), "+f"(d[21]), "+f"(d[22]), "+f"(d[23]),
        "+f"(d[24]), "+f"(d[25]), "+f"(d[26]), "+f"(d[27]), "+f"(d[28]), "+f"(d[29]), "+f"(d[30]), "+f"(d[31])
        : "l"(da), "l"(db));
}
__device__ __forceinline__ void wgmma_qk_f16_acc(float* d, const uint32_t* a, uint64_t db) {
    asm volatile("wgmma.mma_async.sync.aligned.m64n64k16.f32.f16.f16 {"
        "%0, %1, %2, %3, %4, %5, %6, %7, %8, %9, %10, %11, %12, %13, %14, %15,"
        "%16, %17, %18, %19, %20, %21, %22, %23, %24, %25, %26, %27, %28, %29, %30, %31}, {%32, %33, %34, %35}, %36, 1, 1, 1, 0;\n"
        :
        "+f"(d[0]), "+f"(d[1]), "+f"(d[2]), "+f"(d[3]), "+f"(d[4]), "+f"(d[5]), "+f"(d[6]), "+f"(d[7]),
        "+f"(d[8]), "+f"(d[9]), "+f"(d[10]), "+f"(d[11]), "+f"(d[12]), "+f"(d[13]), "+f"(d[14]), "+f"(d[15]),
        "+f"(d[16]), "+f"(d[17]), "+f"(d[18]), "+f"(d[19]), "+f"(d[20]), "+f"(d[21]), "+f"(d[22]), "+f"(d[23]),
        "+f"(d[24]), "+f"(d[25]), "+f"(d[26]), "+f"(d[27]), "+f"(d[28]), "+f"(d[29]), "+f"(d[30]), "+f"(d[31])
        : "r"(a[0]), "r"(a[1]), "r"(a[2]), "r"(a[3]), "l"(db));
}
__device__ __forceinline__ void wgmma_qk_bf16_zero(float* d, const uint32_t* a, uint64_t db) {
    asm volatile("wgmma.mma_async.sync.aligned.m64n64k16.f32.bf16.bf16 {"
        "%0, %1, %2, %3, %4, %5, %6, %7, %8, %9, %10, %11, %12, %13, %14, %15,"
        "%16, %17, %18, %19, %20, %21, %22, %23, %24, %25, %26, %27, %28, %29, %30, %31}, {%32, %33, %34, %35}, %36, 0, 1, 1, 0;\n"
        :
        "=f"(d[0]), "=f"(d[1]), "=f"(d[2]), "=f"(d[3]), "=f"(d[4]), "=f"(d[5]), "=f"(d[6]), "=f"(d[7]),
        "=f"(d[8]), "=f"(d[9]), "=f"(d[10]), "=f"(d[11]), "=f"(d[12]), "=f"(d[13]), "=f"(d[14]), "=f"(d[15]),
        "=f"(d[16]), "=f"(d[17]), "=f"(d[18]), "=f"(d[19]), "=f"(d[20]), "=f"(d[21]), "=f"(d[22]), "=f"(d[23]),
        "=f"(d[24]), "=f"(d[25]), "=f"(d[26]), "=f"(d[27]), "=f"(d[28]), "=f"(d[29]), "=f"(d[30]), "=f"(d[31])
        : "r"(a[0]), "r"(a[1]), "r"(a[2]), "r"(a[3]), "l"(db));
}
__device__ __forceinline__ void wgmma_pv(float* d, const uint32_t* a, uint64_t db) {
    asm volatile("wgmma.mma_async.sync.aligned.m64n24k16.f32.bf16.bf16 {"
        "%0, %1, %2, %3, %4, %5, %6, %7, %8, %9, %10, %11}, {%12, %13, %14, %15}, %16, 1, 1, 1, 1;\n"
        :
        "+f"(d[0]), "+f"(d[1]), "+f"(d[2]), "+f"(d[3]), "+f"(d[4]), "+f"(d[5]), "+f"(d[6]), "+f"(d[7]),
        "+f"(d[8]), "+f"(d[9]), "+f"(d[10]), "+f"(d[11])
        : "r"(a[0]), "r"(a[1]), "r"(a[2]), "r"(a[3]), "l"(db));
}

template <int N> __device__ __forceinline__ void wgmma_ss(float* d, uint64_t a, uint64_t b) {
    if (N == 128) wgmma_ss_n128(d, a, b);
    if (N == 96) wgmma_ss_n96(d, a, b);
    if (N == 64) wgmma_ss_n64(d, a, b);
}

#define OFF_R 131072
#define OFF_ONE 229376
#define OFF_BAR 229888
#define OFF_BIAS (OFF_BAR + 768)
#define OFF_G (OFF_BIAS + 832)
#define SMEM_BYTES (OFF_G + 272)
#define SBD 1024u
#define B_X 0
#define B_F1 512
#define B_E1 112
#define B_KV 160
#define B_F2 224
#define B_E2 256
#define B_T 288
#define B_DONE 352
#define B_G 360
#define B_G2 368
#define B_G3 376
#define B_SF2 384
#define NR 6

#define PF 1
#define PFX 0
#define EXP_FKK 4
#define QSCALE 0.36067376022224085f
#define MAGIC 445.41763f
#define NMUFU 4
#define VSTEP ((uint64_t)((long long)32 - ((long long)32 << 16)))

#define KVMASK 0xEA52u
__host__ __device__ constexpr int strm_pos(int pass, int i) {
    if (pass == 1 || pass == 2) return 8 + 8 * pass + i;
    int n = 0;
    for (int p = 0; p < 16; p++)
        if ((int)((KVMASK >> p) & 1) == (pass == 3)) { if (n == i) return p; n++; }
    return 0;
}
__host__ __device__ constexpr uint32_t strm_code(int pass) {
    uint32_t c = 0;
    for (int i = 0; i < 7; i++) c |= (uint32_t)(strm_pos(pass, i + 1) - strm_pos(pass, i)) << (4 * i);
    return c;
}

template <int N, int SUB, int KST, int LBO, int SBO, int SWZ>
__device__ __forceinline__ void gemm_pass(float* acc, uint32_t bar, uint64_t dA, int lane, uint32_t pos, uint32_t code, int barNext, bool waitx) {
    uint32_t prev = 0, slot = pos % NR;
#pragma unroll 1
    for (int i = 0; i < 8; i++) {
        if (waitx) mbar_wait(bar + B_X + 8 * i, 0);
        mbar_wait(bar + B_F1 + 8 * pos, 0);
        const uint64_t dB = mkdesc(SBD + OFF_R, LBO, SBO, SWZ) + slot * 1024;
        wg_fence();
        wgmma_ss<N>(acc, dA, dB);
        wgmma_ss<N>(acc, dA + 2, dB + KST / 16);
        wg_commit();
        wg_wait<1>();
        if (i > 0 && lane < 2) mbar_arrive_cluster(bar + B_E1 + 8 * prev, lane);
        wgmma_ss<N>(acc, dA + 4, dB + SUB / 16);
        wgmma_ss<N>(acc, dA + 6, dB + (SUB + KST) / 16);
        wg_commit();
        prev = slot;
        pos += code & 15;
        slot += code & 15;
        if (slot >= NR) slot -= NR;
        code >>= 4;
        dA += 1024;
    }
    if (barNext) bar_arrive(barNext, 512);
    wg_wait<0>();
    if (lane < 2) mbar_arrive_cluster(bar + B_E1 + 8 * prev, lane);
    pin<N / 2>(acc);
}

__device__ __forceinline__ uint32_t lds32(uint32_t a) { uint32_t v; asm volatile("ld.shared.u32 %0, [%1];" : "=r"(v) : "r"(a)); return v; }
__device__ __forceinline__ bool elect() {
    uint32_t p;
    asm volatile("{\n.reg .pred p;\nelect.sync _|p, 0xffffffff;\nselp.u32 %0, 1, 0, p;\n}" : "=r"(p));
    return p;
}

template <int N> __device__ __forceinline__ void bias_init(float* acc, uint32_t b) {
#pragma unroll
    for (int j = 0; j < N / 8; j++) {
        const uint32_t bv = lds32(b + j * 16);
        acc[4 * j] = acc[4 * j + 2] = bf_lo(bv);
        acc[4 * j + 1] = acc[4 * j + 3] = bf_hi(bv);
    }
    pin<N / 2>(acc);
}

template <int G0, int G1> __device__ __forceinline__ void gelu_store(const float* acc, __nv_bfloat16* hp) {
#pragma unroll
    for (int G = G0; G < G1; G++) {
        uint32_t o[8];
#pragma unroll
        for (int j = 0; j < 4; j++) {
            float y[4];
#pragma unroll
            for (int i = 0; i < 4; i++) {
                const float h = acc[16 * G + 4 * j + i];
                const float z = h * fmaf(h * h, 0.035677408136300125f, 0.7978845608028654f);
                const float hh = 0.5f * h;
                y[i] = fmaf(hh, tanhf_(z), hh);
            }
            o[j] = pk_bf16(y[0], y[1]);
            o[4 + j] = pk_bf16(y[2], y[3]);
        }
        *(uint4*)(hp + G * 32) = make_uint4(o[0], o[1], o[2], o[3]);
        *(uint4*)(hp + 8 * FF + G * 32) = make_uint4(o[4], o[5], o[6], o[7]);
    }
}

__device__ __forceinline__ float norm_bound(const float* v, float sc) {
    uint32_t m = 0;
#pragma unroll
    for (int h = 0; h < 4; h++) {
        const float* u = v + 8 * h;
        m = max(m, __float_as_uint(fmaf(u[0], u[0], fmaf(u[1], u[1], fmaf(u[4], u[4], u[5] * u[5])))));
        m = max(m, __float_as_uint(fmaf(u[2], u[2], fmaf(u[3], u[3], fmaf(u[6], u[6], u[7] * u[7])))));
    }
#pragma unroll
    for (int o = 4; o < 32; o <<= 1) m = max(m, __shfl_xor_sync(0xffffffffu, m, o));
    float f = __uint_as_float(m);
    f += __shfl_xor_sync(0xffffffffu, f, 1);
    f += __shfl_xor_sync(0xffffffffu, f, 2);
    return f * sc;
}

__device__ __forceinline__ uint32_t exp2_pair(float a, float b) {
    const uint32_t w = __byte_perm(__float_as_uint(a), __float_as_uint(b), 0x6521);
    uint32_t m, r;
    asm("lop3.b32 %0, %1, 0x007f007f, 0x9f809f80, 0xEA;" : "=r"(m) : "r"(w));
    const uint32_t e = w - m;
    asm("fma.rn.bf16x2 %0, %1, %2, %3;" : "=r"(r) : "r"(w), "r"(m), "r"(e));
    return r;
}

__device__ __forceinline__ void store_o(const float* o, uint4* dst, uint32_t par) {
    const float s0 = __fdividef(1.f, o[8]), s1 = __fdividef(1.f, o[10]);
    const uint32_t d0 = (pk_bf16(o[0] * s0, o[1] * s0) & ~1u) | par;
    asm volatile("{\n.reg .b128 t;\nmov.b128 t, {%0, %1, %2, %3};\nst.relaxed.gpu.global.b128 [%4], t;\n}" ::"r"(d0),
                 "r"(pk_bf16(o[4] * s0, o[5] * s0)), "r"(pk_bf16(o[2] * s1, o[3] * s1)), "r"(pk_bf16(o[6] * s1, o[7] * s1)), "l"(dst) : "memory");
}
__device__ __forceinline__ uint4 load_o(const uint4* src) {
    uint4 v;
    asm volatile("{\n.reg .b128 t;\nld.relaxed.gpu.global.b128 t, [%4];\nmov.b128 {%0, %1, %2, %3}, t;\n}"
                 : "=r"(v.x), "=r"(v.y), "=r"(v.z), "=r"(v.w) : "l"(src) : "memory");
    return v;
}
__device__ __forceinline__ uint32_t bmul2(uint32_t a, uint32_t b) { uint32_t r; asm("mul.rn.bf16x2 %0, %1, %2;" : "=r"(r) : "r"(a), "r"(b)); return r; }
__device__ __forceinline__ void sts32(uint32_t a, uint32_t v) { asm volatile("st.shared.u32 [%0], %1;" ::"r"(a), "r"(v) : "memory"); }
__device__ __forceinline__ void load_q(uint32_t* q, int h, int row, int t) {
    const uint8_t* p = gQ + (size_t)h * (SEQ * 32) + (size_t)row * 32 + t * 4;
    q[0] = __ldcg((const uint32_t*)p); q[1] = __ldcg((const uint32_t*)(p + 256));
    q[2] = __ldcg((const uint32_t*)(p + 16)); q[3] = __ldcg((const uint32_t*)(p + 272));
}

template <int NT>
__device__ __forceinline__ void proj16(float (*c)[8], const __nv_bfloat16* x, const __nv_bfloat16* w, int row0, int rstep, int col, int g, int t) {
#pragma unroll
    for (int i = 0; i < NT; i++)
#pragma unroll
        for (int j = 0; j < 8; j++) c[i][j] = 0.f;
    const unsigned short* wu = (const unsigned short*)w;
#pragma unroll 1
    for (int k = 0; k < DM; k += 16) {
        uint32_t b[4];
#pragma unroll
        for (int j = 0; j < 4; j++) {
            const int kr = k + 2 * t + (j & 1) * 8, cc = col + g + (j >> 1) * 8;
            b[j] = (uint32_t)wu[(size_t)kr * (3 * DM) + cc] | ((uint32_t)wu[(size_t)(kr + 1) * (3 * DM) + cc] << 16);
        }
#pragma unroll
        for (int i = 0; i < NT; i++) {
            const __nv_bfloat16* xp = x + (size_t)(row0 + i * rstep + g) * DM + k + 2 * t;
            const uint32_t a0 = *(const uint32_t*)xp, a1 = *(const uint32_t*)(xp + 8 * DM);
            const uint32_t a2 = *(const uint32_t*)(xp + 8), a3 = *(const uint32_t*)(xp + 8 * DM + 8);
#pragma unroll
            for (int j = 0; j < 2; j++)
                asm volatile("mma.sync.aligned.m16n8k16.row.col.f32.bf16.bf16.f32 {%0,%1,%2,%3}, {%4,%5,%6,%7}, {%8,%9}, {%0,%1,%2,%3};"
                             : "+f"(c[i][4 * j]), "+f"(c[i][4 * j + 1]), "+f"(c[i][4 * j + 2]), "+f"(c[i][4 * j + 3])
                             : "r"(a0), "r"(a1), "r"(a2), "r"(a3), "r"(b[2 * j]), "r"(b[2 * j + 1]));
        }
    }
}

struct Maps { CUtensorMap x, kv, q, f1, f3, h, w2, wo, kvs; };

__global__ void __cluster_dims__(2, 1, 1) __launch_bounds__(640, 1)
fused_kernel(const __grid_constant__ Maps tm, const __nv_bfloat16* __restrict__ x, const __nv_bfloat16* __restrict__ wqkv,
             const __nv_bfloat16* __restrict__ wo, const __nv_bfloat16* __restrict__ w1, const __nv_bfloat16* __restrict__ b1,
             const __nv_bfloat16* __restrict__ w2, const __nv_bfloat16* __restrict__ b2, const __nv_bfloat16* __restrict__ gate,
             __nv_bfloat16* __restrict__ out) {
    extern __shared__ __align__(1024) uint8_t smem_raw[];
    const uint32_t sb = smem_u32(smem_raw);
    const uint32_t bar = sb + OFF_BAR;
    const int tid = threadIdx.x, lane = tid & 31;
    const int warp = __shfl_sync(0xffffffffu, tid >> 5, 0);
    const uint32_t rank = cluster_rank();
    const int cl = blockIdx.x >> 1;
    const int nb = cl & 7, mb = (cl >> 3) * 2 + rank;
    const int g = lane >> 2, t = lane & 3;

    const int cb = nb & 3, rb = mb * 2 + (nb >> 2);
    if (tid == 0) TLM(0, 0);
    if (tid == 512) {
        mbar_init(bar + B_X, 1);
        asm volatile("fence.proxy.async.shared::cta;" ::: "memory");
        mbar_expect(bar + B_X, 16384);
        tma2d(sb, &tm.x, 0, mb * 128, bar + B_X);
        for (int i = 0; i < 8; i++) { if (i) mbar_init(bar + B_X + 8 * i, 1); mbar_init(bar + B_KV + 8 * i, 1); mbar_init(bar + B_T + 8 * i, 5); }
        for (int i = 0; i < NR; i++) mbar_init(bar + B_E1 + 8 * i, 16);
        for (int i = 0; i < 4; i++) { mbar_init(bar + B_F2 + 8 * i, 1); mbar_init(bar + B_E2 + 8 * i, 8); }
        mbar_init(bar + B_DONE, 16);
        mbar_init(bar + B_G, 1);
        mbar_init(bar + B_SF2, 2);
        mbar_init(bar + B_G3, 1);
        mbar_init(bar + B_G2, 4);
        asm volatile("fence.mbarrier_init.release.cluster;" ::: "memory");
    } else if (tid == 544) {
        map_prefetch(&tm.q); map_prefetch(&tm.f1); map_prefetch(&tm.kv);
        l2_prefetch((const uint8_t*)wqkv + (size_t)blockIdx.x * 3072, 3072);
        map_prefetch(&tm.f3);
    } else if (tid == 608) {
        for (int i = 0; i < 32; i++) mbar_init(bar + B_F1 + 8 * i, 1);
        asm volatile("fence.mbarrier_init.release.cluster;" ::: "memory");
    } else if (tid < 128) {
        asm volatile("st.shared.u32 [%0], %1;" ::"r"(sb + OFF_ONE + tid * 4), "r"(0x3f803f80u) : "memory");
        asm volatile("fence.proxy.async.shared::cta;" ::: "memory");
    }
    uint32_t biasv = 0;
    if (tid >= 288 && tid < 256 + 208)
        biasv = tid < 400 ? *(const uint32_t*)(b1 + nb * 224 + (tid - 288) * 2) : *(const uint32_t*)(b2 + cb * 128 + (tid - 400) * 2);
    if ((sb & 0xFFFFFF) != SBD) __trap();
    __syncthreads();
    asm volatile("barrier.cluster.arrive.relaxed.aligned;\nbarrier.cluster.wait.aligned;" ::: "memory");
    const uint32_t ep = gEpoch[blockIdx.x] + 1;
    if (tid == 0) { TLM(0, 1); TLC(0, 30); }

    if (warp < 16) {
        const int wg = warp >> 2;
        const int h = cl >> 1, qd = (cl & 1) * 2 + rank;
        uint32_t q[4];
        {
            const int w8 = warp & 7;
            const int T = mb * 8 + w8, row0 = T * 16 + g;
            const uint64_t dA0 = mkdesc(SBD + (wg & 1) * 8192, 16, 1024, 1);
            if (wg < 2) {
                float acc[64];
#pragma unroll
                for (int i = 0; i < 64; i++) acc[i] = 0.f;
                gemm_pass<128, 8192, 2048, 4096, 1024, 1>(acc, bar, dA0, lane, strm_pos(3, 0), strm_code(3), 6, true);
                if (tid == 0) TLM(0, 2);
                {
                    const float km = norm_bound(acc, 1.f);
                    float vm = 0.f;
#pragma unroll
                    for (int i = 32; i < 64; i++) vm = fmaxf(vm, fabsf(acc[i]));
                    vm = __uint_as_float(__reduce_max_sync(0xffffffffu, __float_as_uint(vm)));
                    if (lane == 0) { gN[1024 + nb * 128 + T] = km; gN[2048 + nb * 128 + T] = vm; }
                    const uint32_t kp = sb + OFF_R + 12288 + (w8 >> 2) * 1024 + g * 128 + ((((w8 & 3) * 2 + ((t >> 1) ^ (w8 >> 2))) ^ g) << 4) + (t & 1) * 8;
                    uint8_t* vp = gKV + (size_t)(nb * 4) * (SEQ * 64) + 65536 + (((T >> 6) * 16 + 2 * g) * 64 + (T & 63)) * 32 + ((t * 8) ^ ((w8 >> 2) << 4));
                    bar_sync(9, 256);
#pragma unroll
                    for (int hh = 0; hh < 4; hh++) {
                        const float* v = acc + 8 * hh;
                        float p0 = __shfl_up_sync(0xffffffffu, v[2], 4), p1 = __shfl_up_sync(0xffffffffu, v[3], 4);
                        float p2 = __shfl_up_sync(0xffffffffu, v[6], 4), p3 = __shfl_up_sync(0xffffffffu, v[7], 4);
                        if (g == 0) { p0 = p1 = p2 = p3 = 0.f; }
                        sts64(kp + hh * 16384, pk_f16(v[0] - p0, v[1] - p1), pk_f16(v[4] - p2, v[5] - p3));
                        sts64(kp + hh * 16384 + 2048, pk_f16(v[2] - v[0], v[3] - v[1]), pk_f16(v[6] - v[4], v[7] - v[5]));
                        const float* u = acc + 32 + 8 * hh;
                        if (hh < 2) {
                            sts64(kp + (4 + hh) * 16384, pk_bf16(u[0], u[1]), pk_bf16(u[4], u[5]));
                            sts64(kp + (4 + hh) * 16384 + 2048, pk_bf16(u[2], u[3]), pk_bf16(u[6], u[7]));
                        } else {
                            *(uint2*)(vp + (size_t)hh * (SEQ * 64)) = make_uint2(pk_bf16(u[0], u[1]), pk_bf16(u[4], u[5]));
                            *(uint2*)(vp + (size_t)hh * (SEQ * 64) + 2048) = make_uint2(pk_bf16(u[2], u[3]), pk_bf16(u[6], u[7]));
                        }
                    }
                }
                asm volatile("fence.proxy.async.shared::cta;" ::: "memory");
                bar_arrive(10, 544);
                if (tid == 0) TLM(0, 3);
                bar_sync(12, 512);
            }
            const int pend = wg < 2 ? 3 : 2;
#pragma unroll 1
            for (int p = wg < 2 ? 2 : 0; p < pend; p++) {
                float acc[48];
                if (p) {
                    bias_init<96>(acc, sb + OFF_BIAS + p * 192 + t * 4);
                    bar_sync(5 + p, 512);
                } else {
#pragma unroll
                    for (int i = 0; i < 48; i++) acc[i] = 0.f;
                    pin<48>(acc);
                }
                gemm_pass<96, 6144, 1024, 2048, 512, 2>(acc, bar, dA0, lane, p == 0 ? strm_pos(0, 0) : 8 + 8 * p, p == 0 ? strm_code(0) : strm_code(1), p == 1 ? 7 : 0, p == 0);
                if ((tid & 255) == 0) TLM(0, 4 + 2 * p);
                __nv_bfloat16* hp = gH + (size_t)row0 * FF + nb * 224 + p * 96 - 64 + t * 8;
                if (p == 0) {
                    if (tid < 256 + 208) sts32(sb + OFF_BIAS + (tid - 256) * 4, biasv);
                    bar_arrive(12, 512);
                    const float qm = norm_bound(acc, QSCALE * QSCALE);
                    if (lane == 0) gN[nb * 128 + T] = qm;
                    uint8_t* qp = gQ + (size_t)(nb * 4) * (SEQ * 32) + (size_t)row0 * 32 + t * 8;
#pragma unroll
                    for (int hh = 0; hh < 4; hh++) {
                        const float* v = acc + 8 * hh;
                        *(uint2*)(qp + hh * (SEQ * 32)) = make_uint2(pk_f16(v[0] * QSCALE, v[1] * QSCALE), pk_f16(v[4] * QSCALE, v[5] * QSCALE));
                        *(uint2*)(qp + hh * (SEQ * 32) + 256) = make_uint2(pk_f16(v[2] * QSCALE, v[3] * QSCALE), pk_f16(v[6] * QSCALE, v[7] * QSCALE));
                    }
                    bar_arrive(10, 544);
                    bar_sync(5, 256);
#pragma unroll
                    for (int j = 8; j < 12; j++) {
                        const uint32_t bv = lds32(sb + OFF_BIAS + j * 16 + t * 4);
                        acc[4 * j] += bf_lo(bv); acc[4 * j + 1] += bf_hi(bv); acc[4 * j + 2] += bf_lo(bv); acc[4 * j + 3] += bf_hi(bv);
                    }
                } else {
                    if (p == 2) {
                        mbar_wait(bar + B_G, 0);
                        load_q(q, h, qd * 512 + warp * 16 + g, t);
                    }
                    gelu_store<0, 2>(acc, hp);
                }
                gelu_store<2, 3>(acc, hp);
                if ((tid & 255) == 0) TLM(0, 5 + 2 * p);
            }
            bar_arrive(11, 608);
            if (wg >= 2) {
                mbar_wait(bar + B_G, 0);
                load_q(q, h, qd * 512 + warp * 16 + g, t);
            }
        }
        mbar_wait(bar + B_G3, 0);
        const bool fast = lds32(sb + OFF_G + 256) != 0;
        uint4* const op = gO + ((qd * 8 + wg) * NH + h) * 128 + (tid & 127);
        const uint64_t kd0 = mkdesc(SBD, 16, 256, 3);
        const uint64_t vd0 = mkdesc(SBD + 8192, OFF_ONE - 8192, 256, 3);
        if (fast) {
#pragma unroll 1
            for (int r = 0; r < 2; r++) {
                float o[12];
#pragma unroll
                for (int i = 0; i < 12; i++) o[i] = 0.f;
                uint64_t kd = kd0, vd = vd0;
                uint32_t qn[4];
#pragma unroll 1
                for (int half = 0; half < 2; half++) {
                    float s[32];
#pragma unroll
                    for (int i = 0; i < 32; i++) s[i] = i < 2 * NMUFU ? 0.f : MAGIC;
#pragma unroll 1
                    for (int c = 0; c < 4; c++) {
                        if (r == 0) mbar_wait(bar + B_KV + 8 * (half * 4 + c), 0);
                        if ((tid & 255) == 0 && c == 0) TLM(1, (tid >> 8) * 4 + r * 2 + half);
                        if (half == 1 && c == 3) {
                            if (r == 0) load_q(qn, h, qd * 512 + 256 + warp * 16 + g, t);
                            else if (lane == 0) mbar_arrive(bar + B_DONE);
                        }
#pragma unroll 1
                        for (int j = 0; j < 4; j++) {
                            uint32_t p[16];
                            wg_fence();
                            wgmma_qk_f16_acc(s, q, kd);
                            wg_commit();
                            wg_wait<0>();
                            pin<32>(s);
#pragma unroll
                            for (int i = 0; i < 16; i++)
                                p[i] = i < NMUFU ? pk_bf16(ex2f(s[2 * i]), ex2f(s[2 * i + 1])) : exp2_pair(s[2 * i], s[2 * i + 1]);
                            pin<16>(p);
                            wg_fence();
#pragma unroll
                            for (int u = 0; u < 4; u++) wgmma_pv(o, p + 4 * u, vd + u * VSTEP);
                            wg_commit();
                            kd += 128;
                            vd += 4 * VSTEP;
                        }
                        kd += 512;
                        vd += 16 * VSTEP;
                    }
                    wg_wait<0>();
                }
                pin<12>(o);
                if ((tid & 127) == 0 && r == 1) TLM(1, 8 + wg);
                store_o(o, op + r * (4 * NH * 128), ep & 1);
#pragma unroll
                for (int i = 0; i < 4; i++) q[i] = qn[i];
            }
            if (tid == 0) { TLM(1, 12); TLC(0, 31); }
        } else {
            for (int c = 0; c < 8; c++) mbar_wait(bar + B_KV + 8 * c, 0);
            {
                float kc[8][8];
                proj16<8>(kc, x, wqkv, warp * 16, 256, DM + h * 16, g, t);
#pragma unroll
                for (int i = 0; i < 8; i++) {
                    const int T = warp + i * 16;
                    const int pos = ((T >> 6) * 16 + 2 * g) * 64 + (T & 63);
                    const uint32_t a = sb + (pos >> 8) * 16384 + (pos & 255) * 32 + t * 4, sw = ((T >> 2) & 1) << 4;
                    asm volatile("st.shared.u32 [%0], %1;" ::"r"(a + sw), "r"(pk_bf16(kc[i][0], kc[i][1])) : "memory");
                    asm volatile("st.shared.u32 [%0], %1;" ::"r"(a + (sw ^ 16)), "r"(pk_bf16(kc[i][4], kc[i][5])) : "memory");
                    asm volatile("st.shared.u32 [%0], %1;" ::"r"(a + 2048 + sw), "r"(pk_bf16(kc[i][2], kc[i][3])) : "memory");
                    asm volatile("st.shared.u32 [%0], %1;" ::"r"(a + 2048 + (sw ^ 16)), "r"(pk_bf16(kc[i][6], kc[i][7])) : "memory");
                }
                asm volatile("fence.proxy.async.shared::cta;" ::: "memory");
                bar_sync(8, 512);
            }
#pragma unroll 1
            for (int r = 0; r < 2; r++) {
                const int row = qd * 512 + r * 256 + warp * 16 + g;
                {
                    float qc[1][8];
                    proj16<1>(qc, x, wqkv, row - g, 0, h * 16, g, t);
#pragma unroll
                    for (int i = 0; i < 4; i++) q[i] = pk_bf16(qc[0][2 * i] * QSCALE, qc[0][2 * i + 1] * QSCALE);
                }
                float o[12];
#pragma unroll
                for (int i = 0; i < 12; i++) o[i] = 0.f;
                float m0 = -INFINITY, m1 = -INFINITY;
#pragma unroll 1
                for (int j = 0; j < 32; j++) {
                    const uint64_t kd = kd0 + (j >> 2) * 1024 + (j & 3) * 128, vd = vd0 + ((j >> 2) * 32 + (j & 3) * 4) * VSTEP;
                    float s[32];
                    uint32_t p[16];
                    wg_fence();
                    wgmma_qk_bf16_zero(s, q, kd);
                    wg_commit();
                    wg_wait<0>();
                    pin<32>(s);
                    pin<12>(o);
                    float n0 = m0, n1 = m1;
#pragma unroll
                    for (int i = 0; i < 8; i++) {
                        n0 = fmaxf(n0, fmaxf(s[4 * i], s[4 * i + 1]));
                        n1 = fmaxf(n1, fmaxf(s[4 * i + 2], s[4 * i + 3]));
                    }
                    n0 = fmaxf(n0, __shfl_xor_sync(0xffffffffu, n0, 1));
                    n1 = fmaxf(n1, __shfl_xor_sync(0xffffffffu, n1, 1));
                    n0 = fmaxf(n0, __shfl_xor_sync(0xffffffffu, n0, 2));
                    n1 = fmaxf(n1, __shfl_xor_sync(0xffffffffu, n1, 2));
                    const float c0 = ex2f(m0 - n0), c1 = ex2f(m1 - n1);
                    m0 = n0;
                    m1 = n1;
#pragma unroll
                    for (int i = 0; i < 3; i++) { o[4 * i] *= c0; o[4 * i + 1] *= c0; o[4 * i + 2] *= c1; o[4 * i + 3] *= c1; }
#pragma unroll
                    for (int i = 0; i < 8; i++) {
                        p[2 * i] = pk_bf16(ex2f(s[4 * i] - m0), ex2f(s[4 * i + 1] - m0));
                        p[2 * i + 1] = pk_bf16(ex2f(s[4 * i + 2] - m1), ex2f(s[4 * i + 3] - m1));
                    }
                    pin<16>(p);
                    pin<12>(o);
                    wg_fence();
#pragma unroll
                    for (int u = 0; u < 4; u++) wgmma_pv(o, p + 4 * u, vd + u * VSTEP);
                    wg_commit();
                }
                wg_wait<0>();
                pin<12>(o);
                if (r == 1 && lane == 0) mbar_arrive(bar + B_DONE);
                store_o(o, op + r * (4 * NH * 128), ep & 1);
            }
        }
        {
            const uint4* src = gO + (rb * NH + wg * 8) * 128 + (tid & 127);
            uint4 v[8];
#pragma unroll
            for (int i = 0; i < 8; i++) v[i] = load_o(src + i * 128);
            mbar_wait(bar + B_DONE, 0);
            mbar_wait(bar + B_G2, 0);
            const int lr = (warp & 3) * 16 + g;
            const uint32_t g0 = lds32(sb + OFF_G + lr * 4), g1 = lds32(sb + OFF_G + lr * 4 + 32);
            const uint32_t a0 = sb + wg * 16384 + lr * 128 + (t >> 1) * 4;
#pragma unroll
            for (int i = 0; i < 8; i++) {
                if ((i & 3) == 0) {
                    int spins = 0;
                    while (__any_sync(0xffffffffu, (((v[i].x ^ ep) | (v[i + 1].x ^ ep) | (v[i + 2].x ^ ep) | (v[i + 3].x ^ ep)) & 1) != 0)) {
                        if (++spins > (1 << 22)) __trap();
#pragma unroll
                        for (int k = i; k < 8; k++)
                            if (((v[k].x ^ ep) & 1) != 0) v[k] = load_o(src + k * 128);
                    }
                }
                const uint32_t a = a0 + (i >> 2) * 8192 + ((((i & 3) * 2 + (t & 1)) ^ g) << 4);
                sts32(a, bmul2(v[i].x, g0));
                sts32(a + 8, bmul2(v[i].y, g0));
                sts32(a + 1024, bmul2(v[i].z, g1));
                sts32(a + 1024 + 8, bmul2(v[i].w, g1));
                if ((i & 3) == 3) {
                    asm volatile("fence.proxy.async.shared::cta;" ::: "memory");
                    __syncwarp();
                    if (lane == 0) mbar_arrive(bar + B_T + 8 * (wg * 2 + (i >> 2)));
                    if ((tid & 127) == 0) TLM(1, 20 + wg * 2 + (i >> 2));
                }
            }
        }
    } else {
        if (warp == 16) {
            if (elect()) {
                int s = 0, par = 1, k0 = rank * 32, k3 = rank * 32;
#pragma unroll 1
                for (int it = 0; it < 32; it++) {
                    const uint32_t fb = bar + B_F1 + 8 * it, dst = sb + OFF_R + s * 16384;
                    mbar_wait(bar + B_E1 + 8 * s, par);
                    if (it < 16 && ((KVMASK >> it) & 1)) {
                        mbar_expect(fb, 16384);
                        tma3d_mc(dst + rank * 8192, &tm.kv, nb * 64, k3, 1, fb);
                        k3 += 64;
                    } else {
                        mbar_expect(fb, 12288);
                        if (it < 16) {
                            tma3d_mc(dst + rank * 6144, &tm.q, 0, k0, nb * 2, fb);
                            tma3d_mc(dst + rank * 6144 + 4096, &tm.f1, 0, k0, nb * 7, fb);
                        } else {
                            tma3d_mc(dst + rank * 6144, &tm.f3, 0, k0 & 511, nb * 7 + (it < 24 ? 1 : 4), fb);
                        }
                        k0 += 64;
                    }
                    for (int c = it; c >= 1 && c < 8 && (c == it || it == NR - 1) && it < NR; c++) {
                        mbar_expect(bar + B_X + 8 * c, 16384);
                        tma2d(sb + c * 16384, &tm.x, c * 64, mb * 128, bar + B_X + 8 * c);
                    }
                    if (++s == NR) { s = 0; par ^= 1; }
                }
                const int h = cl >> 1;
                mbar_wait(bar + B_G, 0);
                asm volatile("fence.proxy.async.global;" ::: "memory");
                TLM(0, 10);
#pragma unroll 1
                for (int c = 0; c < 8; c++) {
                    if (c >= 8 - NR) {
                        mbar_wait(bar + B_E1 + 8 * s, par);
                        if (++s == NR) { s = 0; par ^= 1; }
                    }
                    mbar_expect(bar + B_KV + 8 * c, 16384);
                    bulk_mc(sb + c * 16384 + rank * 8192, gKV + (size_t)h * (SEQ * 64) + rank * 65536 + c * 8192, 8192, bar + B_KV + 8 * c);
                }
                mbar_wait(bar + B_SF2, 0);
#pragma unroll 1
                for (s = 0; s < 4; s++) {
                    mbar_expect(bar + B_F2 + 8 * s, 24576);
                    tma5d_mc(sb + OFF_R + s * 24576 + 8192 + rank * 8192, &tm.w2, cb * 128 + rank * 64, s * 2, bar + B_F2 + 8 * s);
                }
                cnt_wait(gCntH + mb * 32, ep * 8);
                asm volatile("fence.proxy.async.global;" ::: "memory");
                TLM(1, 13);
#pragma unroll 1
                for (s = 0; s < 4; s++) tma2d(sb + OFF_R + s * 24576, &tm.h, s * 64, rb * 64, bar + B_F2 + 8 * s);
            }
        } else if (warp == 17) {
            mbar_wait(bar + B_X + 8 * PFX, 0);
            if (lane == 0) {
                l2_prefetch((const uint8_t*)wqkv + 128 * 3072 + (size_t)blockIdx.x * 9216, 9216);
                l2_prefetch((const uint8_t*)w1 + (size_t)blockIdx.x * 14336, 14336);
            }
            mbar_wait(bar + B_X + 8 * 7, 0);
            if (lane == 0) {
                l2_prefetch((const uint8_t*)w2 + (size_t)blockIdx.x * 14336, 14336);
                l2_prefetch((const uint8_t*)wo + (size_t)blockIdx.x * 4096, 4096);
                map_prefetch(&tm.h); map_prefetch(&tm.w2); map_prefetch(&tm.wo); map_prefetch(&tm.kvs);
                TLM(0, 11);
            }
            bar_sync(10, 544);
            if (lane == 0) {
#pragma unroll 1
                for (int b = 0; b < 6; b++) tma5d_st(&tm.kvs, sb + OFF_R + 12288 + b * 16384, (mb >> 3) * 8, (mb & 7) * 2, nb * 8 + (b < 4 ? 2 * b : 2 * b - 7));
                asm volatile("cp.async.bulk.commit_group;\ncp.async.bulk.wait_group 0;\nfence.proxy.async.global;" ::: "memory");
                cnt_add(gCntQ + nb * 32);
                TLM(0, 13);
                mbar_arrive_cluster(bar + B_SF2, 0);
                mbar_arrive_cluster(bar + B_SF2, 1);
            }
            __syncwarp();
            bar_sync(11, 608);
            if (lane == 0) { cnt_add(gCntH + mb * 32); TLM(0, 15); }
        } else {
            {
                const int r0 = mb * 128 + nb * 16 + (warp - 18) * 8;
                uint4 xv[16];
#pragma unroll
                for (int i = 0; i < 16; i++) xv[i] = *(const uint4*)(x + (size_t)(r0 + (i >> 1)) * DM + (i & 1) * 256 + lane * 8);
                const uint4 ga = *(const uint4*)(gate + lane * 8), gb = *(const uint4*)(gate + 256 + lane * 8);
                float z[8];
#pragma unroll
                for (int r = 0; r < 8; r++) z[r] = dot8(xv[2 * r], ga) + dot8(xv[2 * r + 1], gb);
#pragma unroll
                for (int w = 4; w >= 1; w >>= 1)
#pragma unroll
                    for (int r = 0; r < w; r++) {
                        const bool up = lane & w;
                        z[r] = (up ? z[r + w] : z[r]) + __shfl_xor_sync(0xffffffffu, up ? z[r] : z[r + w], w);
                    }
                z[0] += __shfl_xor_sync(0xffffffffu, z[0], 8);
                z[0] += __shfl_xor_sync(0xffffffffu, z[0], 16);
                if (lane < 8) gG[r0 + lane] = 1.f / (1.f + __expf(-z[0]));
                if (tid == 576) TLM(0, 12);
                bar_arrive(11, 608);
            }
            if (warp == 18) {
                const int h = cl >> 1, qd = (cl & 1) * 2 + rank;
                if (lane == 0) {
                    cnt_wait(gCntQ + (h >> 2) * 32, ep * 16);
                    mbar_arrive(bar + B_G);
                    TLM(0, 14);
                }
                __syncwarp();
            const int hb = h >> 2;
            const uint4 kq = __ldcg((const uint4*)(gN + 1024 + hb * 128 + lane * 4));
            const uint4 vq = __ldcg((const uint4*)(gN + 2048 + hb * 128 + lane * 4));
            const float qq = ldcg_f(gN + hb * 128 + qd * 32 + lane);
            const float kf = __uint_as_float(__reduce_max_sync(0xffffffffu, max(max(kq.x, kq.y), max(kq.z, kq.w))));
            const float vf = __uint_as_float(__reduce_max_sync(0xffffffffu, max(max(vq.x, vq.y), max(vq.z, vq.w))));
            const float qf = __uint_as_float(__reduce_max_sync(0xffffffffu, __float_as_uint(qq)));
            if (lane == 0) {
                sts32(sb + OFF_G + 256, (kf <= 1.0e6f) && (qf <= 1.0e6f) && (kf * qf <= 3400.f) && (vf <= 1.0e12f));
                mbar_arrive(bar + B_G3);
            }
            }
        }
        __syncwarp();
        float acc[64];
#pragma unroll
        for (int i = 0; i < 64; i++) acc[i] = 0.f;
#pragma unroll 1
        for (int io = 0; io < 7; io++) {
#pragma unroll
            for (int s = 0; s < 4; s++) {
                const int it = io * 4 + s;
                mbar_wait(bar + B_F2 + 8 * s, io & 1);
                if (tid == 512 && s == 0 && (io == 0 || io == 4)) TLM(1, 14 + io / 4);
                const uint64_t dA = mkdesc(SBD + OFF_R + s * 24576, 16, 1024, 1);
                const uint64_t dB = mkdesc(SBD + OFF_R + s * 24576 + 8192, 8192, 1024, 1);
                wg_fence();
#pragma unroll
                for (int kk = 0; kk < EXP_FKK; kk++) wgmma_ss_n128(acc, dA + kk * 2, dB + kk * 128);
                wg_commit();
                if (warp < 18 && it >= 2 && it < 26) {
                    const int s2 = (s + 2) & 3;
                    mbar_wait(bar + B_E2 + 8 * s2, (io - (s < 2)) & 1);
                    if (elect()) {
                        if (warp == 16) {
                            mbar_expect(bar + B_F2 + 8 * s2, 24576);
                            tma5d_mc(sb + OFF_R + s2 * 24576 + 8192 + rank * 8192, &tm.w2, cb * 128 + rank * 64, it * 2 + 4, bar + B_F2 + 8 * s2);
                        } else {
                            asm volatile("fence.proxy.async.global;" ::: "memory");
                            tma2d(sb + OFF_R + s2 * 24576, &tm.h, it * 64 + 128, rb * 64, bar + B_F2 + 8 * s2);
                        }
                    }
                    __syncwarp();
                }
                wg_wait<1>();
                if (it >= 1 && lane < 2) mbar_arrive_cluster(bar + B_E2 + 8 * ((s + 3) & 3), lane);
            }
        }
        wg_wait<0>();
        if (lane < 2) mbar_arrive_cluster(bar + B_E2 + 8 * 3, lane);
        pin<64>(acc);
        if (warp == 16) {
            if (lane == 0) TLM(1, 16);
            for (int s = 0; s < 4; s++) mbar_wait(bar + B_E2 + 8 * s, 0);
            if (elect()) {
#pragma unroll
                for (int i = 0; i < 8; i++) mbar_expect(bar + B_T + 8 * i, 16384);
#pragma unroll
                for (int i = 0; i < 6; i++) tma2d_mc(sb + OFF_R + i * 16384 + rank * 8192, &tm.wo, cb * 128 + rank * 64, i * 64, bar + B_T + 8 * i);
            }
            __syncwarp();
        }
        {
            const int lr = (warp - 16) * 16 + g;
            const uint32_t pa = pk_bf16(ldcg_f(gG + rb * 64 + lr), ldcg_f(gG + rb * 64 + lr + 8));
            if (t == 0) {
                sts32(sb + OFF_G + lr * 4, __byte_perm(pa, pa, 0x1010));
                sts32(sb + OFF_G + lr * 4 + 32, __byte_perm(pa, pa, 0x3232));
            }
            __syncwarp();
            if (lane == 0) mbar_arrive(bar + B_G2);
            const float ga = bf_lo(pa), gb = bf_hi(pa);
            const float g0 = 1.f - ga, g1 = 1.f - gb;
#pragma unroll
            for (int j = 0; j < 16; j++) {
                const uint32_t bv = lds32(sb + OFF_BIAS + 576 + j * 16 + t * 4);
                acc[4 * j] = (acc[4 * j] + bf_lo(bv)) * g0;
                acc[4 * j + 1] = (acc[4 * j + 1] + bf_hi(bv)) * g0;
                acc[4 * j + 2] = (acc[4 * j + 2] + bf_lo(bv)) * g1;
                acc[4 * j + 3] = (acc[4 * j + 3] + bf_hi(bv)) * g1;
            }
            pin<64>(acc);
        }
        if (warp == 17) {
            mbar_wait(bar + B_DONE, 0);
            if (elect()) {
#pragma unroll
                for (int i = 0; i < 4; i++)
                    tma2d(sb + 65536 + i * 8192, &tm.wo, cb * 128 + (i & 1) * 64, (6 + (i >> 1)) * 64, bar + B_T + 8 * (6 + (i >> 1)));
            }
            __syncwarp();
        }
        if (tid == 512) TLM(1, 17);
#pragma unroll
        for (int i = 0; i < 8; i++) {
            mbar_wait(bar + B_T + 8 * i, 0);
            const uint64_t dA = mkdesc(SBD + i * 8192, 16, 1024, 1);
            const uint64_t dB = mkdesc(i < 6 ? SBD + OFF_R + i * 16384 : SBD + 65536 + (i - 6) * 16384, 8192, 1024, 1);
            wg_fence();
#pragma unroll
            for (int kk = 0; kk < 4; kk++) wgmma_ss_n128(acc, dA + kk * 2, dB + kk * 128);
            wg_commit();
        }
        wg_wait<0>();
        pin<64>(acc);
        if (tid == 512) TLM(1, 18);
        {
            const uint32_t st = sb + 98304 + (warp - 16) * 4352;
            const uint32_t wa = st + (lane & 15) * 272 + (lane >> 4) * 16;
#pragma unroll
            for (int j = 0; j < 8; j++)
                asm volatile("stmatrix.sync.aligned.m8n8.x4.shared.b16 [%0], {%1, %2, %3, %4};" ::"r"(wa + j * 32),
                             "r"(pk_bf16(acc[8 * j], acc[8 * j + 1])), "r"(pk_bf16(acc[8 * j + 2], acc[8 * j + 3])),
                             "r"(pk_bf16(acc[8 * j + 4], acc[8 * j + 5])), "r"(pk_bf16(acc[8 * j + 6], acc[8 * j + 7])) : "memory");
            __syncwarp();
            __nv_bfloat16* op = out + (size_t)(rb * 64 + (warp - 16) * 16 + (lane >> 4)) * DM + cb * 128 + (lane & 15) * 8;
#pragma unroll
            for (int j = 0; j < 8; j++) {
                uint4 v;
                asm volatile("ld.shared.v4.u32 {%0, %1, %2, %3}, [%4];" : "=r"(v.x), "=r"(v.y), "=r"(v.z), "=r"(v.w)
                             : "r"(st + (2 * j + (lane >> 4)) * 272 + (lane & 15) * 16));
                *(uint4*)(op + (size_t)j * 2 * DM) = v;
            }
        }
        if (tid == 512) { gEpoch[blockIdx.x] = ep; TLM(1, 19); }
    }
}

typedef CUresult (*EncodeFn)(CUtensorMap*, CUtensorMapDataType, cuuint32_t, void*, const cuuint64_t*, const cuuint64_t*, const cuuint32_t*,
                             const cuuint32_t*, CUtensorMapInterleave, CUtensorMapSwizzle, CUtensorMapL2promotion, CUtensorMapFloatOOBfill);

static void make_map(EncodeFn enc, CUtensorMap* m, const void* p, int rank, const cuuint64_t* dims, const cuuint64_t* strides,
                     const cuuint32_t* box, CUtensorMapSwizzle swz) {
    const cuuint32_t es[5] = {1, 1, 1, 1, 1};
    enc(m, CU_TENSOR_MAP_DATA_TYPE_BFLOAT16, rank, (void*)p, dims, strides, box, es, CU_TENSOR_MAP_INTERLEAVE_NONE, swz,
        CU_TENSOR_MAP_L2_PROMOTION_L2_128B, CU_TENSOR_MAP_FLOAT_OOB_FILL_NONE);
}

extern "C" void kernel_launch(void* const* d_in, const int* in_sizes, int n_in, void* d_out, int out_size) {
    const __nv_bfloat16* x = (const __nv_bfloat16*)d_in[0];
    const __nv_bfloat16* wqkv = (const __nv_bfloat16*)d_in[1];
    const __nv_bfloat16* wo = (const __nv_bfloat16*)d_in[2];
    const __nv_bfloat16* w1 = (const __nv_bfloat16*)d_in[4];
    const __nv_bfloat16* b1 = (const __nv_bfloat16*)d_in[5];
    const __nv_bfloat16* w2 = (const __nv_bfloat16*)d_in[6];
    const __nv_bfloat16* b2 = (const __nv_bfloat16*)d_in[7];
    const __nv_bfloat16* gate = (const __nv_bfloat16*)d_in[8];

    void* fp = nullptr;
    cudaDriverEntryPointQueryResult qr;
    cudaGetDriverEntryPoint("cuTensorMapEncodeTiled", &fp, cudaEnableDefault, &qr);
    EncodeFn enc = (EncodeFn)fp;
    void *pH, *pKV;
    cudaGetSymbolAddress(&pH, gH);
    cudaGetSymbolAddress(&pKV, gKV);

    Maps tm;
    const CUtensorMapSwizzle S128 = CU_TENSOR_MAP_SWIZZLE_128B, S64 = CU_TENSOR_MAP_SWIZZLE_64B;
    { cuuint64_t d[2] = {DM, SEQ}, s[1] = {DM * 2}; cuuint32_t b[2] = {64, 128}; make_map(enc, &tm.x, x, 2, d, s, b, S128); }
    { cuuint64_t d[3] = {DM, DM, 3}, s[2] = {3 * DM * 2, DM * 2}; cuuint32_t b[3] = {64, 32, 2}; make_map(enc, &tm.kv, wqkv, 3, d, s, b, S128); }
    { cuuint64_t d[3] = {32, DM, 3 * DM / 32}, s[2] = {3 * DM * 2, 64}; cuuint32_t b[3] = {32, 32, 2}; make_map(enc, &tm.q, wqkv, 3, d, s, b, S64); }
    { cuuint64_t d[3] = {32, DM, FF / 32}, s[2] = {FF * 2, 64}; cuuint32_t b[3] = {32, 32, 1}; make_map(enc, &tm.f1, w1, 3, d, s, b, S64); }
    { cuuint64_t d[3] = {32, DM, FF / 32}, s[2] = {FF * 2, 64}; cuuint32_t b[3] = {32, 32, 3}; make_map(enc, &tm.f3, w1, 3, d, s, b, S64); }
    { cuuint64_t d[2] = {FF, SEQ}, s[1] = {FF * 2}; cuuint32_t b[2] = {64, 64}; make_map(enc, &tm.h, pH, 2, d, s, b, S128); }
    { cuuint64_t d[5] = {DM, 2, 4, 4, FF / 32}, s[4] = {1024, 8 * 1024, 2 * 1024, 32 * 1024}; cuuint32_t b[5] = {64, 2, 4, 4, 2};
      make_map(enc, &tm.w2, w2, 5, d, s, b, S128); }
    { cuuint64_t d[2] = {DM, DM}, s[1] = {DM * 2}; cuuint32_t b[2] = {64, 64}; make_map(enc, &tm.wo, wo, 2, d, s, b, S128); }

    { cuuint64_t d[5] = {64, 16, 16, 2, 2 * NH}, s[4] = {4096, 128, 2048, 65536}; cuuint32_t b[5] = {64, 8, 2, 2, 1};
      make_map(enc, &tm.kvs, pKV, 5, d, s, b, S128); }
    cudaFuncSetAttribute(fused_kernel, cudaFuncAttributeMaxDynamicSharedMemorySize, SMEM_BYTES);
    fused_kernel<<<128, 640, SMEM_BYTES, cudaStreamPerThread>>>(tm, x, wqkv, wo, w1, b1, w2, b2, gate, (__nv_bfloat16*)d_out);
}
```

```cpp
#include <cuda_runtime.h>
#include <cuda_bf16.h>
#include <cuda_fp16.h>
#include <cuda.h>
#include <stdint.h>

#define SEQ 2048
#define DM 512
#define FF 1792
#define NH 32

__device__ __align__(1024) uint8_t gQ[NH * SEQ * 32];
__device__ __align__(1024) uint8_t gKV[NH * SEQ * 64];
__device__ __align__(1024) __nv_bfloat16 gH[SEQ * FF];
__device__ __align__(1024) uint4 gO[32 * NH * 128];
__device__ float gG[SEQ];
__device__ float gN[3 * 8 * 128];
__device__ unsigned int gCntQ[8 * 32];
__device__ unsigned int gCntH[32 * 32];
__device__ unsigned int gEpoch[128];

__device__ __forceinline__ uint32_t smem_u32(const void* p) { return (uint32_t)__cvta_generic_to_shared(p); }
__device__ __forceinline__ void mbar_init(uint32_t a, uint32_t c) { asm volatile("mbarrier.init.shared::cta.b64 [%0], %1;" ::"r"(a), "r"(c)); }
__device__ __forceinline__ void mbar_expect(uint32_t a, uint32_t b) { asm volatile("mbarrier.arrive.expect_tx.shared::cta.b64 _, [%0], %1;" ::"r"(a), "r"(b) : "memory"); }
__device__ __forceinline__ void mbar_arrive(uint32_t a) { asm volatile("mbarrier.arrive.shared::cta.b64 _, [%0];" ::"r"(a) : "memory"); }
__device__ __forceinline__ void mbar_wait(uint32_t a, uint32_t ph) {
    asm volatile("{\n.reg .pred p;\n.reg .u32 n;\nmov.u32 n, 0;\nW_%=:\nmbarrier.try_wait.parity.shared::cta.b64 p, [%0], %1;\n@p bra D_%=;\n"
                 "add.u32 n, n, 1;\nsetp.lt.u32 p, n, 0x400000;\n@p bra W_%=;\ntrap;\nD_%=:\n}" ::"r"(a), "r"(ph) : "memory");
}
__device__ __forceinline__ void mbar_arrive_cluster(uint32_t a, uint32_t cta) {
    asm volatile("{\n.reg .b32 r;\nmapa.shared::cluster.u32 r, %0, %1;\nmbarrier.arrive.shared::cluster.b64 _, [r];\n}" ::"r"(a), "r"(cta) : "memory");
}
__device__ __forceinline__ void bar_sync(int id, int n) { asm volatile("bar.sync %0, %1;" ::"r"(id), "r"(n) : "memory"); }
__device__ __forceinline__ void bar_arrive(int id, int n) { asm volatile("bar.arrive %0, %1;" ::"r"(id), "r"(n) : "memory"); }
__device__ __forceinline__ uint32_t cluster_rank() { uint32_t r; asm("mov.u32 %0, %%cluster_ctarank;" : "=r"(r)); return r; }
__device__ __forceinline__ void cnt_add(unsigned int* c) { asm volatile("red.release.gpu.global.add.u32 [%0], 1;" ::"l"(c) : "memory"); }
__device__ __forceinline__ void cnt_wait(const unsigned int* c, uint32_t target) {
    uint32_t v;
    int spins = 0;
    while (true) {
        asm volatile("ld.acquire.gpu.global.u32 %0, [%1];" : "=r"(v) : "l"(c) : "memory");
        if ((int)(v - target) >= 0) break;
        if (++spins > (1 << 22)) __trap();
        __nanosleep(40);
    }
}
__device__ __forceinline__ void tma2d(uint32_t dst, const CUtensorMap* m, int c0, int c1, uint32_t bar) {
    asm volatile("cp.async.bulk.tensor.2d.shared::cluster.global.mbarrier::complete_tx::bytes [%0], [%1, {%3, %4}], [%2];"
                 ::"r"(dst), "l"(m), "r"(bar), "r"(c0), "r"(c1) : "memory");
}
__device__ __forceinline__ void tma2d_mc(uint32_t dst, const CUtensorMap* m, int c0, int c1, uint32_t bar) {
    asm volatile("cp.async.bulk.tensor.2d.shared::cluster.global.mbarrier::complete_tx::bytes.multicast::cluster [%0], [%1, {%3, %4}], [%2], %5;"
                 ::"r"(dst), "l"(m), "r"(bar), "r"(c0), "r"(c1), "h"((uint16_t)3) : "memory");
}
__device__ __forceinline__ void tma3d_mc(uint32_t dst, const CUtensorMap* m, int c0, int c1, int c2, uint32_t bar) {
    asm volatile("cp.async.bulk.tensor.3d.shared::cluster.global.mbarrier::complete_tx::bytes.multicast::cluster [%0], [%1, {%3, %4, %5}], [%2], %6;"
                 ::"r"(dst), "l"(m), "r"(bar), "r"(c0), "r"(c1), "r"(c2), "h"((uint16_t)3) : "memory");
}
__device__ __forceinline__ void tma5d_mc(uint32_t dst, const CUtensorMap* m, int c0, int c4, uint32_t bar) {
    asm volatile("cp.async.bulk.tensor.5d.shared::cluster.global.mbarrier::complete_tx::bytes.multicast::cluster [%0], [%1, {%3, %5, %5, %5, %4}], [%2], %6;"
                 ::"r"(dst), "l"(m), "r"(bar), "r"(c0), "r"(c4), "r"(0), "h"((uint16_t)3) : "memory");
}
__device__ __forceinline__ void bulk_mc(uint32_t dst, const void* src, uint32_t bytes, uint32_t bar) {
    asm volatile("cp.async.bulk.shared::cluster.global.mbarrier::complete_tx::bytes.multicast::cluster [%0], [%1], %2, [%3], %4;"
                 ::"r"(dst), "l"(src), "r"(bytes), "r"(bar), "h"((uint16_t)3) : "memory");
}
__device__ __forceinline__ void tma3d_st(const CUtensorMap* m, uint32_t src, int c0, int c1, int c2) {
    asm volatile("cp.async.bulk.tensor.3d.global.shared::cta.bulk_group [%0, {%2, %3, %4}], [%1];" ::"l"(m), "r"(src), "r"(c0), "r"(c1), "r"(c2) : "memory");
}
__device__ __forceinline__ void tma5d_st(const CUtensorMap* m, uint32_t src, int c1, int c2, int c4) {
    asm volatile("cp.async.bulk.tensor.5d.global.shared::cta.bulk_group [%0, {%5, %2, %3, %5, %4}], [%1];"
                 ::"l"(m), "r"(src), "r"(c1), "r"(c2), "r"(c4), "r"(0) : "memory");
}
__device__ __forceinline__ void bulk_st(void* dst, uint32_t src, uint32_t bytes) {
    asm volatile("cp.async.bulk.global.shared::cta.bulk_group [%0], [%1], %2;" ::"l"(dst), "r"(src), "r"(bytes) : "memory");
}
__device__ __forceinline__ void sts64(uint32_t a, uint32_t x, uint32_t y) { asm volatile("st.shared.v2.u32 [%0], {%1, %2};" ::"r"(a), "r"(x), "r"(y) : "memory"); }
__device__ __forceinline__ void sts128(uint32_t a, const uint32_t* v) {
    asm volatile("st.shared.v4.u32 [%0], {%1, %2, %3, %4};" ::"r"(a), "r"(v[0]), "r"(v[1]), "r"(v[2]), "r"(v[3]) : "memory");
}
__device__ __forceinline__ void l2_prefetch(const void* src, uint32_t bytes) {
    asm volatile("cp.async.bulk.prefetch.L2.global [%0], %1;" ::"l"(src), "r"(bytes) : "memory");
}
__device__ __forceinline__ void map_prefetch(const CUtensorMap* m) { asm volatile("prefetch.tensormap [%0];" ::"l"(m) : "memory"); }
__device__ __forceinline__ void wg_fence() { asm volatile("wgmma.fence.sync.aligned;" ::: "memory"); }
__device__ __forceinline__ void wg_commit() { asm volatile("wgmma.commit_group.sync.aligned;" ::: "memory"); }
template <int N> __device__ __forceinline__ void wg_wait() { asm volatile("wgmma.wait_group.sync.aligned %0;" ::"n"(N) : "memory"); }
template <int N> __device__ __forceinline__ void pin(float* s) {
#pragma unroll
    for (int i = 0; i < N; i++) asm volatile("" : "+f"(s[i])::"memory");
}
template <int N> __device__ __forceinline__ void pin(uint32_t* s) {
#pragma unroll
    for (int i = 0; i < N; i++) asm volatile("" : "+r"(s[i])::"memory");
}
__device__ __forceinline__ uint64_t mkdesc(uint32_t addr, uint32_t lbo, uint32_t sbo, uint32_t swz) {
    return (uint64_t)((addr & 0x3FFFF) >> 4) | ((uint64_t)(lbo >> 4) << 16) | ((uint64_t)(sbo >> 4) << 32) | ((uint64_t)swz << 62);
}
__device__ __forceinline__ float ex2f(float x) { float y; asm("ex2.approx.ftz.f32 %0, %1;" : "=f"(y) : "f"(x)); return y; }
__device__ __forceinline__ float tanhf_(float x) { float y; asm("tanh.approx.f32 %0, %1;" : "=f"(y) : "f"(x)); return y; }
__device__ __forceinline__ uint32_t pk_bf16(float lo, float hi) { uint32_t r; asm("cvt.rn.bf16x2.f32 %0, %1, %2;" : "=r"(r) : "f"(hi), "f"(lo)); return r; }
__device__ __forceinline__ uint32_t pk_f16(float lo, float hi) { uint32_t r; asm("cvt.rn.f16x2.f32 %0, %1, %2;" : "=r"(r) : "f"(hi), "f"(lo)); return r; }
__device__ __forceinline__ float bf_lo(uint32_t v) { return __uint_as_float(v << 16); }
__device__ __forceinline__ float bf_hi(uint32_t v) { return __uint_as_float(v & 0xffff0000u); }
__device__ __forceinline__ float dot8(const uint4& a, const uint4& b) {
    return fmaf(bf_lo(a.x), bf_lo(b.x), fmaf(bf_hi(a.x), bf_hi(b.x), fmaf(bf_lo(a.y), bf_lo(b.y), bf_hi(a.y) * bf_hi(b.y)))) +
           fmaf(bf_lo(a.z), bf_lo(b.z), fmaf(bf_hi(a.z), bf_hi(b.z), fmaf(bf_lo(a.w), bf_lo(b.w), bf_hi(a.w) * bf_hi(b.w))));
}
__device__ __forceinline__ float ldcg_f(const float* p) { return __ldcg(p); }

#define TLM(k, slot) do {} while (0)
#define TLC(k, slot) do {} while (0)

__device__ __forceinline__ void wgmma_ss_n128(float* d, uint64_t da, uint64_t db) {
    asm volatile("wgmma.mma_async.sync.aligned.m64n128k16.f32.bf16.bf16 {"
        "%0, %1, %2, %3, %4, %5, %6, %7, %8, %9, %10, %11, %12, %13, %14, %15,"
        "%16, %17, %18, %19, %20, %21, %22, %23, %24, %25, %26, %27, %28, %29, %30, %31,"
        "%32, %33, %34, %35, %36, %37, %38, %39, %40, %41, %42, %43, %44, %45, %46, %47,"
        "%48, %49, %50, %51, %52, %53, %54, %55, %56, %57, %58, %59, %60, %61, %62, %63}, %64, %65, 1, 1, 1, 0, 1;\n"
        :
        "+f"(d[0]), "+f"(d[1]), "+f"(d[2]), "+f"(d[3]), "+f"(d[4]), "+f"(d[5]), "+f"(d[6]), "+f"(d[7]),
        "+f"(d[8]), "+f"(d[9]), "+f"(d[10]), "+f"(d[11]), "+f"(d[12]), "+f"(d[13]), "+f"(d[14]), "+f"(d[15]),
        "+f"(d[16]), "+f"(d[17]), "+f"(d[18]), "+f"(d[19]), "+f"(d[20]), "+f"(d[21]), "+f"(d[22]), "+f"(d[23]),
        "+f"(d[24]), "+f"(d[25]), "+f"(d[26]), "+f"(d[27]), "+f"(d[28]), "+f"(d[29]), "+f"(d[30]), "+f"(d[31]),
        "+f"(d[32]), "+f"(d[33]), "+f"(d[34]), "+f"(d[35]), "+f"(d[36]), "+f"(d[37]), "+f"(d[38]), "+f"(d[39]),
        "+f"(d[40]), "+f"(d[41]), "+f"(d[42]), "+f"(d[43]), "+f"(d[44]), "+f"(d[45]), "+f"(d[46]), "+f"(d[47]),
        "+f"(d[48]), "+f"(d[49]), "+f"(d[50]), "+f"(d[51]), "+f"(d[52]), "+f"(d[53]), "+f"(d[54]), "+f"(d[55]),
        "+f"(d[56]), "+f"(d[57]), "+f"(d[58]), "+f"(d[59]), "+f"(d[60]), "+f"(d[61]), "+f"(d[62]), "+f"(d[63])
        : "l"(da), "l"(db));
}
__device__ __forceinline__ void wgmma_ss_n96(float* d, uint64_t da, uint64_t db) {
    asm volatile("wgmma.mma_async.sync.aligned.m64n96k16.f32.bf16.bf16 {"
        "%0, %1, %2, %3, %4, %5, %6, %7, %8, %9, %10, %11, %12, %13, %14, %15,"
        "%16, %17, %18, %19, %20, %21, %22, %23, %24, %25, %26, %27, %28, %29, %30, %31,"
        "%32, %33, %34, %35, %36, %37, %38, %39, %40, %41, %42, %43, %44, %45, %46, %47}, %48, %49, 1, 1, 1, 0, 1;\n"
        :
        "+f"(d[0]), "+f"(d[1]), "+f"(d[2]), "+f"(d[3]), "+f"(d[4]), "+f"(d[5]), "+f"(d[6]), "+f"(d[7]),
        "+f"(d[8]), "+f"(d[9]), "+f"(d[10]), "+f"(d[11]), "+f"(d[12]), "+f"(d[13]), "+f"(d[14]), "+f"(d[15]),
        "+f"(d[16]), "+f"(d[17]), "+f"(d[18]), "+f"(d[19]), "+f"(d[20]), "+f"(d[21]), "+f"(d[22]), "+f"(d[23]),
        "+f"(d[24]), "+f"(d[25]), "+f"(d[26]), "+f"(d[27]), "+f"(d[28]), "+f"(d[29]), "+f"(d[30]), "+f"(d[31]),
        "+f"(d[32]), "+f"(d[33]), "+f"(d[34]), "+f"(d[35]), "+f"(d[36]), "+f"(d[37]), "+f"(d[38]), "+f"(d[39]),
        "+f"(d[40]), "+f"(d[41]), "+f"(d[42]), "+f"(d[43]), "+f"(d[44]), "+f"(d[45]), "+f"(d[46]), "+f"(d[47])
        : "l"(da), "l"(db));
}
__device__ __forceinline__ void wgmma_ss_n64(float* d, uint64_t da, uint64_t db) {
    asm volatile("wgmma.mma_async.sync.aligned.m64n64k16.f32.bf16.bf16 {"
        "%0, %1, %2, %3, %4, %5, %6, %7, %8, %9, %10, %11, %12, %13, %14, %15,"
        "%16, %17, %18, %19, %20, %21, %22, %23, %24, %25, %26, %27, %28, %29, %30, %31}, %32, %33, 1, 1, 1, 0, 1;\n"
        :
        "+f"(d[0]), "+f"(d[1]), "+f"(d[2]), "+f"(d[3]), "+f"(d[4]), "+f"(d[5]), "+f"(d[6]), "+f"(d[7]),
        "+f"(d[8]), "+f"(d[9]), "+f"(d[10]), "+f"(d[11]), "+f"(d[12]), "+f"(d[13]), "+f"(d[14]), "+f"(d[15]),
        "+f"(d[16]), "+f"(d[17]), "+f"(d[18]), "+f"(d[19]), "+f"(d[20]), "+f"(d[21]), "+f"(d[22]), "+f"(d[23]),
        "+f"(d[24]), "+f"(d[25]), "+f"(d[26]), "+f"(d[27]), "+f"(d[28]), "+f"(d[29]), "+f"(d[30]), "+f"(d[31])
        : "l"(da), "l"(db));
}
__device__ __forceinline__ void wgmma_qk_f16_acc(float* d, const uint32_t* a, uint64_t db) {
    asm volatile("wgmma.mma_async.sync.aligned.m64n64k16.f32.f16.f16 {"
        "%0, %1, %2, %3, %4, %5, %6, %7, %8, %9, %10, %11, %12, %13, %14, %15,"
        "%16, %17, %18, %19, %20, %21, %22, %23, %24, %25, %26, %27, %28, %29, %30, %31}, {%32, %33, %34, %35}, %36, 1, 1, 1, 0;\n"
        :
        "+f"(d[0]), "+f"(d[1]), "+f"(d[2]), "+f"(d[3]), "+f"(d[4]), "+f"(d[5]), "+f"(d[6]), "+f"(d[7]),
        "+f"(d[8]), "+f"(d[9]), "+f"(d[10]), "+f"(d[11]), "+f"(d[12]), "+f"(d[13]), "+f"(d[14]), "+f"(d[15]),
        "+f"(d[16]), "+f"(d[17]), "+f"(d[18]), "+f"(d[19]), "+f"(d[20]), "+f"(d[21]), "+f"(d[22]), "+f"(d[23]),
        "+f"(d[24]), "+f"(d[25]), "+f"(d[26]), "+f"(d[27]), "+f"(d[28]), "+f"(d[29]), "+f"(d[30]), "+f"(d[31])
        : "r"(a[0]), "r"(a[1]), "r"(a[2]), "r"(a[3]), "l"(db));
}
__device__ __forceinline__ void wgmma_qk_bf16_zero(float* d, const uint32_t* a, uint64_t db) {
    asm volatile("wgmma.mma_async.sync.aligned.m64n64k16.f32.bf16.bf16 {"
        "%0, %1, %2, %3, %4, %5, %6, %7, %8, %9, %10, %11, %12, %13, %14, %15,"
        "%16, %17, %18, %19, %20, %21, %22, %23, %24, %25, %26, %27, %28, %29, %30, %31}, {%32, %33, %34, %35}, %36, 0, 1, 1, 0;\n"
        :
        "=f"(d[0]), "=f"(d[1]), "=f"(d[2]), "=f"(d[3]), "=f"(d[4]), "=f"(d[5]), "=f"(d[6]), "=f"(d[7]),
        "=f"(d[8]), "=f"(d[9]), "=f"(d[10]), "=f"(d[11]), "=f"(d[12]), "=f"(d[13]), "=f"(d[14]), "=f"(d[15]),
        "=f"(d[16]), "=f"(d[17]), "=f"(d[18]), "=f"(d[19]), "=f"(d[20]), "=f"(d[21]), "=f"(d[22]), "=f"(d[23]),
        "=f"(d[24]), "=f"(d[25]), "=f"(d[26]), "=f"(d[27]), "=f"(d[28]), "=f"(d[29]), "=f"(d[30]), "=f"(d[31])
        : "r"(a[0]), "r"(a[1]), "r"(a[2]), "r"(a[3]), "l"(db));
}
__device__ __forceinline__ void wgmma_pv(float* d, const uint32_t* a, uint64_t db) {
    asm volatile("wgmma.mma_async.sync.aligned.m64n24k16.f32.bf16.bf16 {"
        "%0, %1, %2, %3, %4, %5, %6, %7, %8, %9, %10, %11}, {%12, %13, %14, %15}, %16, 1, 1, 1, 1;\n"
        :
        "+f"(d[0]), "+f"(d[1]), "+f"(d[2]), "+f"(d[3]), "+f"(d[4]), "+f"(d[5]), "+f"(d[6]), "+f"(d[7]),
        "+f"(d[8]), "+f"(d[9]), "+f"(d[10]), "+f"(d[11])
        : "r"(a[0]), "r"(a[1]), "r"(a[2]), "r"(a[3]), "l"(db));
}

template <int N> __device__ __forceinline__ void wgmma_ss(float* d, uint64_t a, uint64_t b) {
    if (N == 128) wgmma_ss_n128(d, a, b);
    if (N == 96) wgmma_ss_n96(d, a, b);
    if (N == 64) wgmma_ss_n64(d, a, b);
}

#define OFF_R 131072
#define OFF_ONE 229376
#define OFF_BAR 229888
#define OFF_BIAS (OFF_BAR + 768)
#define OFF_G (OFF_BIAS + 832)
#define SMEM_BYTES (OFF_G + 272)
#define SBD 1024u
#define B_X 0
#define B_F1 512
#define B_E1 112
#define B_KV 160
#define B_F2 224
#define B_E2 256
#define B_T 288
#define B_DONE 352
#define B_G 360
#define B_G2 368
#define B_G3 376
#define B_SF 384
#define B_SF2 408
#define NR 6

#define PF 1
#define PFX 0
#define EXP_FKK 4
#define QSCALE 0.36067376022224085f
#define MAGIC 445.41763f
#define NMUFU 4
#define VSTEP ((uint64_t)((long long)32 - ((long long)32 << 16)))

#define KVMASK 0x15ADu
__host__ __device__ constexpr int strm_pos(int pass, int i) {
    if (pass == 1 || pass == 2) return 8 + 8 * pass + i;
    int n = 0;
    for (int p = 0; p < 16; p++)
        if ((int)((KVMASK >> p) & 1) == (pass == 3)) { if (n == i) return p; n++; }
    return 0;
}
__host__ __device__ constexpr uint32_t strm_code(int pass) {
    uint32_t c = 0;
    for (int i = 0; i < 7; i++) c |= (uint32_t)(strm_pos(pass, i + 1) - strm_pos(pass, i)) << (4 * i);
    return c;
}

template <int N, int SUB, int KST, int LBO, int SBO, int SWZ>
__device__ __forceinline__ void gemm_pass(float* acc, uint32_t bar, uint64_t dA, int lane, uint32_t pos, uint32_t code, int barNext, bool waitx) {
    uint32_t prev = 0, slot = pos % NR;
#pragma unroll 1
    for (int i = 0; i < 8; i++) {
        if (waitx) mbar_wait(bar + B_X + 8 * i, 0);
        mbar_wait(bar + B_F1 + 8 * pos, 0);
        const uint64_t dB = mkdesc(SBD + OFF_R, LBO, SBO, SWZ) + slot * 1024;
        wg_fence();
        wgmma_ss<N>(acc, dA, dB);
        wgmma_ss<N>(acc, dA + 2, dB + KST / 16);
        wg_commit();
        wg_wait<1>();
        if (i > 0 && lane < 2) mbar_arrive_cluster(bar + B_E1 + 8 * prev, lane);
        wgmma_ss<N>(acc, dA + 4, dB + SUB / 16);
        wgmma_ss<N>(acc, dA + 6, dB + (SUB + KST) / 16);
        wg_commit();
        prev = slot;
        pos += code & 15;
        slot += code & 15;
        if (slot >= NR) slot -= NR;
        code >>= 4;
        dA += 1024;
    }
    if (barNext) bar_arrive(barNext, 512);
    wg_wait<0>();
    if (lane < 2) mbar_arrive_cluster(bar + B_E1 + 8 * prev, lane);
    pin<N / 2>(acc);
}

__device__ __forceinline__ uint32_t lds32(uint32_t a) { uint32_t v; asm volatile("ld.shared.u32 %0, [%1];" : "=r"(v) : "r"(a)); return v; }
__device__ __forceinline__ bool elect() {
    uint32_t p;
    asm volatile("{\n.reg .pred p;\nelect.sync _|p, 0xffffffff;\nselp.u32 %0, 1, 0, p;\n}" : "=r"(p));
    return p;
}

template <int G0, int G1> __device__ __forceinline__ void gelu_store(const float* acc, uint32_t bias, uint32_t hp) {
#pragma unroll
    for (int G = G0; G < G1; G++) {
        uint32_t o[8];
#pragma unroll
        for (int j = 0; j < 4; j++) {
            const uint32_t bv = lds32(bias + G * 64 + j * 16);
            float y[4];
#pragma unroll
            for (int i = 0; i < 4; i++) {
                const float h = acc[16 * G + 4 * j + i] + ((i & 1) ? bf_hi(bv) : bf_lo(bv));
                const float z = h * fmaf(h * h, 0.035677408136300125f, 0.7978845608028654f);
                const float hh = 0.5f * h;
                y[i] = fmaf(hh, tanhf_(z), hh);
            }
            o[j] = pk_bf16(y[0], y[1]);
            o[4 + j] = pk_bf16(y[2], y[3]);
        }
        sts128(hp + G * 32768, o);
        sts128(hp + G * 32768 + 512, o + 4);
    }
}

__device__ __forceinline__ float norm_bound(const float* v, float sc) {
    uint32_t m = 0;
#pragma unroll
    for (int h = 0; h < 4; h++) {
        const float* u = v + 8 * h;
        m = max(m, __float_as_uint(fmaf(u[0], u[0], fmaf(u[1], u[1], fmaf(u[4], u[4], u[5] * u[5])))));
        m = max(m, __float_as_uint(fmaf(u[2], u[2], fmaf(u[3], u[3], fmaf(u[6], u[6], u[7] * u[7])))));
    }
#pragma unroll
    for (int o = 4; o < 32; o <<= 1) m = max(m, __shfl_xor_sync(0xffffffffu, m, o));
    float f = __uint_as_float(m);
    f += __shfl_xor_sync(0xffffffffu, f, 1);
    f += __shfl_xor_sync(0xffffffffu, f, 2);
    return f * sc;
}

__device__ __forceinline__ uint32_t exp2_pair(float a, float b) {
    const uint32_t w = __byte_perm(__float_as_uint(a), __float_as_uint(b), 0x6521);
    uint32_t m, r;
    asm("lop3.b32 %0, %1, 0x007f007f, 0x9f809f80, 0xEA;" : "=r"(m) : "r"(w));
    const uint32_t e = w - m;
    asm("fma.rn.bf16x2 %0, %1, %2, %3;" : "=r"(r) : "r"(w), "r"(m), "r"(e));
    return r;
}

__device__ __forceinline__ void store_o(const float* o, uint4* dst, uint32_t par) {
    const float s0 = __fdividef(1.f, o[8]), s1 = __fdividef(1.f, o[10]);
    const uint32_t d0 = (pk_bf16(o[0] * s0, o[1] * s0) & ~1u) | par;
    asm volatile("{\n.reg .b128 t;\nmov.b128 t, {%0, %1, %2, %3};\nst.relaxed.gpu.global.b128 [%4], t;\n}" ::"r"(d0),
                 "r"(pk_bf16(o[4] * s0, o[5] * s0)), "r"(pk_bf16(o[2] * s1, o[3] * s1)), "r"(pk_bf16(o[6] * s1, o[7] * s1)), "l"(dst) : "memory");
}
__device__ __forceinline__ uint4 load_o(const uint4* src) {
    uint4 v;
    asm volatile("{\n.reg .b128 t;\nld.relaxed.gpu.global.b128 t, [%4];\nmov.b128 {%0, %1, %2, %3}, t;\n}"
                 : "=r"(v.x), "=r"(v.y), "=r"(v.z), "=r"(v.w) : "l"(src) : "memory");
    return v;
}
__device__ __forceinline__ uint32_t bmul2(uint32_t a, uint32_t b) { uint32_t r; asm("mul.rn.bf16x2 %0, %1, %2;" : "=r"(r) : "r"(a), "r"(b)); return r; }
__device__ __forceinline__ void sts32(uint32_t a, uint32_t v) { asm volatile("st.shared.u32 [%0], %1;" ::"r"(a), "r"(v) : "memory"); }
__device__ __forceinline__ void load_q(uint32_t* q, int h, int row, int t) {
    const uint8_t* p = gQ + (size_t)h * (SEQ * 32) + (size_t)row * 32 + t * 4;
    q[0] = __ldcg((const uint32_t*)p); q[1] = __ldcg((const uint32_t*)(p + 256));
    q[2] = __ldcg((const uint32_t*)(p + 16)); q[3] = __ldcg((const uint32_t*)(p + 272));
}

template <int NT>
__device__ __forceinline__ void proj16(float (*c)[8], const __nv_bfloat16* x, const __nv_bfloat16* w, int row0, int rstep, int col, int g, int t) {
#pragma unroll
    for (int i = 0; i < NT; i++)
#pragma unroll
        for (int j = 0; j < 8; j++) c[i][j] = 0.f;
    const unsigned short* wu = (const unsigned short*)w;
#pragma unroll 1
    for (int k = 0; k < DM; k += 16) {
        uint32_t b[4];
#pragma unroll
        for (int j = 0; j < 4; j++) {
            const int kr = k + 2 * t + (j & 1) * 8, cc = col + g + (j >> 1) * 8;
            b[j] = (uint32_t)wu[(size_t)kr * (3 * DM) + cc] | ((uint32_t)wu[(size_t)(kr + 1) * (3 * DM) + cc] << 16);
        }
#pragma unroll
        for (int i = 0; i < NT; i++) {
            const __nv_bfloat16* xp = x + (size_t)(row0 + i * rstep + g) * DM + k + 2 * t;
            const uint32_t a0 = *(const uint32_t*)xp, a1 = *(const uint32_t*)(xp + 8 * DM);
            const uint32_t a2 = *(const uint32_t*)(xp + 8), a3 = *(const uint32_t*)(xp + 8 * DM + 8);
#pragma unroll
            for (int j = 0; j < 2; j++)
                asm volatile("mma.sync.aligned.m16n8k16.row.col.f32.bf16.bf16.f32 {%0,%1,%2,%3}, {%4,%5,%6,%7}, {%8,%9}, {%0,%1,%2,%3};"
                             : "+f"(c[i][4 * j]), "+f"(c[i][4 * j + 1]), "+f"(c[i][4 * j + 2]), "+f"(c[i][4 * j + 3])
                             : "r"(a0), "r"(a1), "r"(a2), "r"(a3), "r"(b[2 * j]), "r"(b[2 * j + 1]));
        }
    }
}

struct Maps { CUtensorMap x, kv, q, f1, f3, h, w2, wo, hs, kvs; };

__global__ void __cluster_dims__(2, 1, 1) __launch_bounds__(640, 1)
fused_kernel(const __grid_constant__ Maps tm, const __nv_bfloat16* __restrict__ x, const __nv_bfloat16* __restrict__ wqkv,
             const __nv_bfloat16* __restrict__ wo, const __nv_bfloat16* __restrict__ w1, const __nv_bfloat16* __restrict__ b1,
             const __nv_bfloat16* __restrict__ w2, const __nv_bfloat16* __restrict__ b2, const __nv_bfloat16* __restrict__ gate,
             __nv_bfloat16* __restrict__ out) {
    extern __shared__ __align__(1024) uint8_t smem_raw[];
    const uint32_t sb = smem_u32(smem_raw);
    const uint32_t bar = sb + OFF_BAR;
    const int tid = threadIdx.x, lane = tid & 31;
    const int warp = __shfl_sync(0xffffffffu, tid >> 5, 0);
    const uint32_t rank = cluster_rank();
    const int cl = blockIdx.x >> 1;
    const int nb = cl & 7, mb = (cl >> 3) * 2 + rank;
    const int g = lane >> 2, t = lane & 3;

    const int cb = nb & 3, rb = mb * 2 + (nb >> 2);
    if (tid == 0) TLM(0, 0);
    if (tid == 512) {
        mbar_init(bar + B_X, 1);
        asm volatile("fence.proxy.async.shared::cta;" ::: "memory");
        mbar_expect(bar + B_X, 16384);
        tma2d(sb, &tm.x, 0, mb * 128, bar + B_X);
        for (int i = 0; i < 8; i++) { if (i) mbar_init(bar + B_X + 8 * i, 1); mbar_init(bar + B_KV + 8 * i, 1); mbar_init(bar + B_T + 8 * i, 5); }
        for (int i = 0; i < NR; i++) mbar_init(bar + B_E1 + 8 * i, 16);
        for (int i = 0; i < 4; i++) { mbar_init(bar + B_F2 + 8 * i, 1); mbar_init(bar + B_E2 + 8 * i, 8); }
        mbar_init(bar + B_DONE, 16);
        mbar_init(bar + B_G, 1);
        for (int i = 0; i < 3; i++) mbar_init(bar + B_SF + 8 * i, 1);
        mbar_init(bar + B_SF2, 2);
        mbar_init(bar + B_G3, 1);
        mbar_init(bar + B_G2, 4);
        asm volatile("fence.mbarrier_init.release.cluster;" ::: "memory");
    } else if (tid == 544) {
        map_prefetch(&tm.kv); map_prefetch(&tm.q); map_prefetch(&tm.f1);
        l2_prefetch((const uint8_t*)wqkv + (size_t)blockIdx.x * 3072, 3072);
        l2_prefetch((const uint8_t*)w1 + (size_t)blockIdx.x * 1792, 1792);
        map_prefetch(&tm.f3);
    } else if (tid == 608) {
        for (int i = 0; i < 32; i++) mbar_init(bar + B_F1 + 8 * i, 1);
        asm volatile("fence.mbarrier_init.release.cluster;" ::: "memory");
    } else if (tid < 128) {
        asm volatile("st.shared.u32 [%0], %1;" ::"r"(sb + OFF_ONE + tid * 4), "r"(0x3f803f80u) : "memory");
        asm volatile("fence.proxy.async.shared::cta;" ::: "memory");
    }
    uint32_t biasv = 0;
    if (tid >= 288 && tid < 256 + 208)
        biasv = tid < 400 ? *(const uint32_t*)(b1 + nb * 224 + (tid - 288) * 2) : *(const uint32_t*)(b2 + cb * 128 + (tid - 400) * 2);
    if ((sb & 0xFFFFFF) != SBD) __trap();
    __syncthreads();
    asm volatile("barrier.cluster.arrive.relaxed.aligned;\nbarrier.cluster.wait.aligned;" ::: "memory");
    const uint32_t ep = gEpoch[blockIdx.x] + 1;
    if (tid == 0) { TLM(0, 1); TLC(0, 30); }

    if (warp < 16) {
        const int wg = warp >> 2;
        const int h = cl >> 1, qd = (cl & 1) * 2 + rank;
        uint32_t q[4];
        {
            const int w8 = warp & 7;
            const int T = mb * 8 + w8, row0 = T * 16 + g;
            const uint64_t dA0 = mkdesc(SBD + (wg & 1) * 8192, 16, 1024, 1);
            if (wg < 2) {
                float acc[64];
#pragma unroll
                for (int i = 0; i < 64; i++) acc[i] = 0.f;
                gemm_pass<128, 8192, 2048, 4096, 1024, 1>(acc, bar, dA0, lane, strm_pos(3, 0), strm_code(3), 0, true);
                if (tid == 0) TLM(0, 2);
                {
                    const float km = norm_bound(acc, 1.f);
                    float vm = 0.f;
#pragma unroll
                    for (int i = 32; i < 64; i++) vm = fmaxf(vm, fabsf(acc[i]));
                    vm = __uint_as_float(__reduce_max_sync(0xffffffffu, __float_as_uint(vm)));
                    if (lane == 0) { gN[1024 + nb * 128 + T] = km; gN[2048 + nb * 128 + T] = vm; }
                    const uint32_t kp = sb + OFF_R + 12288 + (w8 >> 2) * 1024 + g * 128 + ((((w8 & 3) * 2 + ((t >> 1) ^ (w8 >> 2))) ^ g) << 4) + (t & 1) * 8;
                    uint8_t* vp = gKV + (size_t)(nb * 4) * (SEQ * 64) + 65536 + (((T >> 6) * 16 + 2 * g) * 64 + (T & 63)) * 32 + ((t * 8) ^ ((w8 >> 2) << 4));
                    bar_sync(9, 256);
#pragma unroll
                    for (int hh = 0; hh < 4; hh++) {
                        const float* v = acc + 8 * hh;
                        float p0 = __shfl_up_sync(0xffffffffu, v[2], 4), p1 = __shfl_up_sync(0xffffffffu, v[3], 4);
                        float p2 = __shfl_up_sync(0xffffffffu, v[6], 4), p3 = __shfl_up_sync(0xffffffffu, v[7], 4);
                        if (g == 0) { p0 = p1 = p2 = p3 = 0.f; }
                        sts64(kp + hh * 16384, pk_f16(v[0] - p0, v[1] - p1), pk_f16(v[4] - p2, v[5] - p3));
                        sts64(kp + hh * 16384 + 2048, pk_f16(v[2] - v[0], v[3] - v[1]), pk_f16(v[6] - v[4], v[7] - v[5]));
                        const float* u = acc + 32 + 8 * hh;
                        if (hh < 2) {
                            sts64(kp + (4 + hh) * 16384, pk_bf16(u[0], u[1]), pk_bf16(u[4], u[5]));
                            sts64(kp + (4 + hh) * 16384 + 2048, pk_bf16(u[2], u[3]), pk_bf16(u[6], u[7]));
                        } else {
                            *(uint2*)(vp + (size_t)hh * (SEQ * 64)) = make_uint2(pk_bf16(u[0], u[1]), pk_bf16(u[4], u[5]));
                            *(uint2*)(vp + (size_t)hh * (SEQ * 64) + 2048) = make_uint2(pk_bf16(u[2], u[3]), pk_bf16(u[6], u[7]));
                        }
                    }
                }
                asm volatile("fence.proxy.async.shared::cta;" ::: "memory");
                bar_arrive(10, 288);
                if (tid == 0) TLM(0, 3);
            }
#pragma unroll 1
            for (int p = wg < 2 ? 1 : 0; p < 3; p += 2) {
                float acc[48];
#pragma unroll
                for (int i = 0; i < 48; i++) acc[i] = 0.f;
                pin<48>(acc);
                if (p) bar_sync(5 + p, 512);
                gemm_pass<96, 6144, 1024, 2048, 512, 2>(acc, bar, dA0, lane, p == 0 ? strm_pos(0, 0) : 8 + 8 * p, p == 0 ? strm_code(0) : strm_code(1), p < 2 ? 6 + p : 0, p == 0);
                if ((tid & 255) == 0) TLM(0, 4 + 2 * p);
                const uint32_t hp = sb + OFF_R + 12288 + (wg & 1) * 16384 + ((warp & 3) * 16 + g) * 64 + t * 16;
                const uint32_t bp = sb + OFF_BIAS + p * 192 + t * 4;
                if (p == 0) {
                    if (tid < 256 + 208) sts32(sb + OFF_BIAS + (tid - 256) * 4, biasv);
                    const float qm = norm_bound(acc, QSCALE * QSCALE);
                    if (lane == 0) gN[nb * 128 + T] = qm;
                    uint8_t* qp = gQ + (size_t)(nb * 4) * (SEQ * 32) + (size_t)row0 * 32 + t * 8;
#pragma unroll
                    for (int hh = 0; hh < 4; hh++) {
                        const float* v = acc + 8 * hh;
                        *(uint2*)(qp + hh * (SEQ * 32)) = make_uint2(pk_f16(v[0] * QSCALE, v[1] * QSCALE), pk_f16(v[4] * QSCALE, v[5] * QSCALE));
                        *(uint2*)(qp + hh * (SEQ * 32) + 256) = make_uint2(pk_f16(v[2] * QSCALE, v[3] * QSCALE), pk_f16(v[6] * QSCALE, v[7] * QSCALE));
                    }
                    bar_arrive(12, 288);
                    bar_sync(5, 256);
                    mbar_wait(bar + B_SF, 0);
                } else {
                    if (p == 2) {
                        mbar_wait(bar + B_G, 0);
                        load_q(q, h, qd * 512 + warp * 16 + g, t);
                    }
                    mbar_wait(bar + B_SF + 8 * p, 0);
                    gelu_store<0, 2>(acc, bp, hp);
                }
                gelu_store<2, 3>(acc, bp, hp);
                asm volatile("fence.proxy.async.shared::cta;" ::: "memory");
                bar_arrive(p == 1 ? 10 : 11, 288);
                if ((tid & 255) == 0) TLM(0, 5 + 2 * p);
            }
            if (wg < 2) {
                mbar_wait(bar + B_G, 0);
                load_q(q, h, qd * 512 + warp * 16 + g, t);
            }
        }
        mbar_wait(bar + B_G3, 0);
        const bool fast = lds32(sb + OFF_G + 256) != 0;
        uint4* const op = gO + ((qd * 8 + wg) * NH + h) * 128 + (tid & 127);
        const uint64_t kd0 = mkdesc(SBD, 16, 256, 3);
        const uint64_t vd0 = mkdesc(SBD + 8192, OFF_ONE - 8192, 256, 3);
        if (fast) {
#pragma unroll 1
            for (int r = 0; r < 2; r++) {
                float o[12];
#pragma unroll
                for (int i = 0; i < 12; i++) o[i] = 0.f;
                uint64_t kd = kd0, vd = vd0;
                uint32_t qn[4];
#pragma unroll 1
                for (int half = 0; half < 2; half++) {
                    float s[32];
#pragma unroll
                    for (int i = 0; i < 32; i++) s[i] = i < 2 * NMUFU ? 0.f : MAGIC;
#pragma unroll 1
                    for (int c = 0; c < 4; c++) {
                        if (r == 0) mbar_wait(bar + B_KV + 8 * (half * 4 + c), 0);
                        if ((tid & 255) == 0 && c == 0) TLM(1, (tid >> 8) * 4 + r * 2 + half);
                        if (half == 1 && c == 3) {
                            if (r == 0) load_q(qn, h, qd * 512 + 256 + warp * 16 + g, t);
                            else if (lane == 0) mbar_arrive(bar + B_DONE);
                        }
#pragma unroll
                        for (int j = 0; j < 4; j++) {
                            uint32_t p[16];
                            wg_fence();
                            wgmma_qk_f16_acc(s, q, kd);
                            wg_commit();
                            wg_wait<0>();
                            pin<32>(s);
#pragma unroll
                            for (int i = 0; i < 16; i++)
                                p[i] = i < NMUFU ? pk_bf16(ex2f(s[2 * i]), ex2f(s[2 * i + 1])) : exp2_pair(s[2 * i], s[2 * i + 1]);
                            pin<16>(p);
                            wg_fence();
#pragma unroll
                            for (int u = 0; u < 4; u++) wgmma_pv(o, p + 4 * u, vd + u * VSTEP);
                            wg_commit();
                            kd += 128;
                            vd += 4 * VSTEP;
                        }
                        kd += 512;
                        vd += 16 * VSTEP;
                    }
                    wg_wait<0>();
                }
                pin<12>(o);
                if ((tid & 127) == 0 && r == 1) TLM(1, 8 + wg);
                store_o(o, op + r * (4 * NH * 128), ep & 1);
#pragma unroll
                for (int i = 0; i < 4; i++) q[i] = qn[i];
            }
            if (tid == 0) { TLM(1, 12); TLC(0, 31); }
        } else {
            for (int c = 0; c < 8; c++) mbar_wait(bar + B_KV + 8 * c, 0);
            {
                float kc[8][8];
                proj16<8>(kc, x, wqkv, warp * 16, 256, DM + h * 16, g, t);
#pragma unroll
                for (int i = 0; i < 8; i++) {
                    const int T = warp + i * 16;
                    const int pos = ((T >> 6) * 16 + 2 * g) * 64 + (T & 63);
                    const uint32_t a = sb + (pos >> 8) * 16384 + (pos & 255) * 32 + t * 4, sw = ((T >> 2) & 1) << 4;
                    asm volatile("st.shared.u32 [%0], %1;" ::"r"(a + sw), "r"(pk_bf16(kc[i][0], kc[i][1])) : "memory");
                    asm volatile("st.shared.u32 [%0], %1;" ::"r"(a + (sw ^ 16)), "r"(pk_bf16(kc[i][4], kc[i][5])) : "memory");
                    asm volatile("st.shared.u32 [%0], %1;" ::"r"(a + 2048 + sw), "r"(pk_bf16(kc[i][2], kc[i][3])) : "memory");
                    asm volatile("st.shared.u32 [%0], %1;" ::"r"(a + 2048 + (sw ^ 16)), "r"(pk_bf16(kc[i][6], kc[i][7])) : "memory");
                }
                asm volatile("fence.proxy.async.shared::cta;" ::: "memory");
                bar_sync(8, 512);
            }
#pragma unroll 1
            for (int r = 0; r < 2; r++) {
                const int row = qd * 512 + r * 256 + warp * 16 + g;
                {
                    float qc[1][8];
                    proj16<1>(qc, x, wqkv, row - g, 0, h * 16, g, t);
#pragma unroll
                    for (int i = 0; i < 4; i++) q[i] = pk_bf16(qc[0][2 * i] * QSCALE, qc[0][2 * i + 1] * QSCALE);
                }
                float o[12];
#pragma unroll
                for (int i = 0; i < 12; i++) o[i] = 0.f;
                float m0 = -INFINITY, m1 = -INFINITY;
#pragma unroll 1
                for (int j = 0; j < 32; j++) {
                    const uint64_t kd = kd0 + (j >> 2) * 1024 + (j & 3) * 128, vd = vd0 + ((j >> 2) * 32 + (j & 3) * 4) * VSTEP;
                    float s[32];
                    uint32_t p[16];
                    wg_fence();
                    wgmma_qk_bf16_zero(s, q, kd);
                    wg_commit();
                    wg_wait<0>();
                    pin<32>(s);
                    pin<12>(o);
                    float n0 = m0, n1 = m1;
#pragma unroll
                    for (int i = 0; i < 8; i++) {
                        n0 = fmaxf(n0, fmaxf(s[4 * i], s[4 * i + 1]));
                        n1 = fmaxf(n1, fmaxf(s[4 * i + 2], s[4 * i + 3]));
                    }
                    n0 = fmaxf(n0, __shfl_xor_sync(0xffffffffu, n0, 1));
                    n1 = fmaxf(n1, __shfl_xor_sync(0xffffffffu, n1, 1));
                    n0 = fmaxf(n0, __shfl_xor_sync(0xffffffffu, n0, 2));
                    n1 = fmaxf(n1, __shfl_xor_sync(0xffffffffu, n1, 2));
                    const float c0 = ex2f(m0 - n0), c1 = ex2f(m1 - n1);
                    m0 = n0;
                    m1 = n1;
#pragma unroll
                    for (int i = 0; i < 3; i++) { o[4 * i] *= c0; o[4 * i + 1] *= c0; o[4 * i + 2] *= c1; o[4 * i + 3] *= c1; }
#pragma unroll
                    for (int i = 0; i < 8; i++) {
                        p[2 * i] = pk_bf16(ex2f(s[4 * i] - m0), ex2f(s[4 * i + 1] - m0));
                        p[2 * i + 1] = pk_bf16(ex2f(s[4 * i + 2] - m1), ex2f(s[4 * i + 3] - m1));
                    }
                    pin<16>(p);
                    pin<12>(o);
                    wg_fence();
#pragma unroll
                    for (int u = 0; u < 4; u++) wgmma_pv(o, p + 4 * u, vd + u * VSTEP);
                    wg_commit();
                }
                wg_wait<0>();
                pin<12>(o);
                if (r == 1 && lane == 0) mbar_arrive(bar + B_DONE);
                store_o(o, op + r * (4 * NH * 128), ep & 1);
            }
        }
        {
            const uint4* src = gO + (rb * NH + wg * 8) * 128 + (tid & 127);
            uint4 v[8];
#pragma unroll
            for (int i = 0; i < 8; i++) v[i] = load_o(src + i * 128);
            mbar_wait(bar + B_DONE, 0);
            mbar_wait(bar + B_G2, 0);
            const int lr = (warp & 3) * 16 + g;
            const uint32_t g0 = lds32(sb + OFF_G + lr * 4), g1 = lds32(sb + OFF_G + lr * 4 + 32);
            const uint32_t a0 = sb + wg * 16384 + lr * 128 + (t >> 1) * 4;
#pragma unroll
            for (int i = 0; i < 8; i++) {
                if ((i & 3) == 0) {
                    int spins = 0;
                    while (__any_sync(0xffffffffu, (((v[i].x ^ ep) | (v[i + 1].x ^ ep) | (v[i + 2].x ^ ep) | (v[i + 3].x ^ ep)) & 1) != 0)) {
                        if (++spins > (1 << 22)) __trap();
#pragma unroll
                        for (int k = i; k < 8; k++)
                            if (((v[k].x ^ ep) & 1) != 0) v[k] = load_o(src + k * 128);
                    }
                }
                const uint32_t a = a0 + (i >> 2) * 8192 + ((((i & 3) * 2 + (t & 1)) ^ g) << 4);
                sts32(a, bmul2(v[i].x, g0));
                sts32(a + 8, bmul2(v[i].y, g0));
                sts32(a + 1024, bmul2(v[i].z, g1));
                sts32(a + 1024 + 8, bmul2(v[i].w, g1));
                if ((i & 3) == 3) {
                    asm volatile("fence.proxy.async.shared::cta;" ::: "memory");
                    __syncwarp();
                    if (lane == 0) mbar_arrive(bar + B_T + 8 * (wg * 2 + (i >> 2)));
                    if ((tid & 127) == 0) TLM(1, 20 + wg * 2 + (i >> 2));
                }
            }
        }
    } else {
        if (warp == 16) {
            if (elect()) {
                int s = 0, par = 1, k0 = rank * 32, k3 = rank * 32;
#pragma unroll 1
                for (int it = 0; it < 32; it++) {
                    const uint32_t fb = bar + B_F1 + 8 * it, dst = sb + OFF_R + s * 16384;
                    mbar_wait(bar + B_E1 + 8 * s, par);
                    if (it < 16 && ((KVMASK >> it) & 1)) {
                        mbar_expect(fb, 16384);
                        tma3d_mc(dst + rank * 8192, &tm.kv, nb * 64, k3, 1, fb);
                        k3 += 64;
                    } else {
                        mbar_expect(fb, 12288);
                        if (it < 16) {
                            tma3d_mc(dst + rank * 6144, &tm.q, 0, k0, nb * 2, fb);
                            tma3d_mc(dst + rank * 6144 + 4096, &tm.f1, 0, k0, nb * 7, fb);
                        } else {
                            tma3d_mc(dst + rank * 6144, &tm.f3, 0, k0 & 511, nb * 7 + (it < 24 ? 1 : 4), fb);
                        }
                        k0 += 64;
                    }
                    for (int c = it; c >= 1 && c < 8 && (c == it || it == NR - 1) && it < NR; c++) {
                        mbar_expect(bar + B_X + 8 * c, 16384);
                        tma2d(sb + c * 16384, &tm.x, c * 64, mb * 128, bar + B_X + 8 * c);
                    }
                    if (++s == NR) { s = 0; par ^= 1; }
                }
                const int h = cl >> 1;
                mbar_wait(bar + B_G, 0);
                asm volatile("fence.proxy.async.global;" ::: "memory");
                TLM(0, 10);
#pragma unroll 1
                for (int c = 0; c < 8; c++) {
                    if (c >= 8 - NR) {
                        mbar_wait(bar + B_E1 + 8 * s, par);
                        if (++s == NR) { s = 0; par ^= 1; }
                    }
                    mbar_expect(bar + B_KV + 8 * c, 16384);
                    bulk_mc(sb + c * 16384 + rank * 8192, gKV + (size_t)h * (SEQ * 64) + rank * 65536 + c * 8192, 8192, bar + B_KV + 8 * c);
                }
                mbar_wait(bar + B_SF2, 0);
#pragma unroll 1
                for (s = 0; s < 4; s++) {
                    mbar_expect(bar + B_F2 + 8 * s, 24576);
                    tma5d_mc(sb + OFF_R + s * 24576 + 8192 + rank * 8192, &tm.w2, cb * 128 + rank * 64, s * 2, bar + B_F2 + 8 * s);
                }
                cnt_wait(gCntH + mb * 32, ep * 8);
                asm volatile("fence.proxy.async.global;" ::: "memory");
                TLM(1, 13);
#pragma unroll 1
                for (s = 0; s < 4; s++) tma2d(sb + OFF_R + s * 24576, &tm.h, s * 64, rb * 64, bar + B_F2 + 8 * s);
            }
        } else if (warp == 17) {
            mbar_wait(bar + B_X + 8 * PFX, 0);
            if (lane == 0) {
                l2_prefetch((const uint8_t*)wqkv + 128 * 3072 + (size_t)blockIdx.x * 9216, 9216);
                l2_prefetch((const uint8_t*)w1 + (size_t)blockIdx.x * 14336, 14336);
            }
            mbar_wait(bar + B_X + 8 * 7, 0);
            if (lane == 0) {
                l2_prefetch((const uint8_t*)w2 + (size_t)blockIdx.x * 14336, 14336);
                l2_prefetch((const uint8_t*)wo + (size_t)blockIdx.x * 4096, 4096);
                map_prefetch(&tm.h); map_prefetch(&tm.w2); map_prefetch(&tm.wo); map_prefetch(&tm.hs); map_prefetch(&tm.kvs);
                TLM(0, 11);
            }
#pragma unroll 1
            for (int e = 0; e < 4; e++) {
                bar_sync(10 + (e & 1), 288);
                if (lane == 0) {
#pragma unroll 1
                    for (int b = e == 1 ? 4 : 0; b < 6; b++) {
                        const uint32_t src = sb + OFF_R + 12288 + b * 16384;
                        if (e == 0) tma5d_st(&tm.kvs, src, (mb >> 3) * 8, (mb & 7) * 2, nb * 8 + (b < 4 ? 2 * b : 2 * b - 7));
                        else tma3d_st(&tm.hs, src, 0, mb * 128 + (b & 1) * 64, nb * 7 + e * 3 - 5 + (b >> 1));
                    }
                    asm volatile("cp.async.bulk.commit_group;\ncp.async.bulk.wait_group.read 0;" ::: "memory");
                    if (e < 3) mbar_arrive(bar + B_SF + 8 * e);
                    else { mbar_arrive_cluster(bar + B_SF2, 0); mbar_arrive_cluster(bar + B_SF2, 1); }
                }
                __syncwarp();
                if (e == 0 || e == 3) {
                    bar_sync(e == 0 ? 12 : 13, e == 0 ? 288 : 96);
                    if (lane == 0) {
                        asm volatile("cp.async.bulk.wait_group 0;\nfence.proxy.async.global;" ::: "memory");
                        cnt_add(e == 0 ? gCntQ + nb * 32 : gCntH + mb * 32);
                        TLM(0, e == 0 ? 13 : 15);
                    }
                    __syncwarp();
                }
            }
        } else {
            {
                const int r0 = mb * 128 + nb * 16 + (warp - 18) * 8;
                uint4 xv[16];
#pragma unroll
                for (int i = 0; i < 16; i++) xv[i] = *(const uint4*)(x + (size_t)(r0 + (i >> 1)) * DM + (i & 1) * 256 + lane * 8);
                const uint4 ga = *(const uint4*)(gate + lane * 8), gb = *(const uint4*)(gate + 256 + lane * 8);
                float z[8];
#pragma unroll
                for (int r = 0; r < 8; r++) z[r] = dot8(xv[2 * r], ga) + dot8(xv[2 * r + 1], gb);
#pragma unroll
                for (int w = 4; w >= 1; w >>= 1)
#pragma unroll
                    for (int r = 0; r < w; r++) {
                        const bool up = lane & w;
                        z[r] = (up ? z[r + w] : z[r]) + __shfl_xor_sync(0xffffffffu, up ? z[r] : z[r + w], w);
                    }
                z[0] += __shfl_xor_sync(0xffffffffu, z[0], 8);
                z[0] += __shfl_xor_sync(0xffffffffu, z[0], 16);
                if (lane < 8) gG[r0 + lane] = 1.f / (1.f + __expf(-z[0]));
                if (tid == 576) TLM(0, 12);
                bar_arrive(13, 96);
            }
            if (warp == 18) {
                const int h = cl >> 1, qd = (cl & 1) * 2 + rank;
                if (lane == 0) {
                    cnt_wait(gCntQ + (h >> 2) * 32, ep * 16);
                    mbar_arrive(bar + B_G);
                    TLM(0, 14);
                }
                __syncwarp();
            const int hb = h >> 2;
            const uint4 kq = __ldcg((const uint4*)(gN + 1024 + hb * 128 + lane * 4));
            const uint4 vq = __ldcg((const uint4*)(gN + 2048 + hb * 128 + lane * 4));
            const float qq = ldcg_f(gN + hb * 128 + qd * 32 + lane);
            const float kf = __uint_as_float(__reduce_max_sync(0xffffffffu, max(max(kq.x, kq.y), max(kq.z, kq.w))));
            const float vf = __uint_as_float(__reduce_max_sync(0xffffffffu, max(max(vq.x, vq.y), max(vq.z, vq.w))));
            const float qf = __uint_as_float(__reduce_max_sync(0xffffffffu, __float_as_uint(qq)));
            if (lane == 0) {
                sts32(sb + OFF_G + 256, (kf <= 1.0e6f) && (qf <= 1.0e6f) && (kf * qf <= 3400.f) && (vf <= 1.0e12f));
                mbar_arrive(bar + B_G3);
            }
            }
        }
        __syncwarp();
        float acc[64];
#pragma unroll
        for (int i = 0; i < 64; i++) acc[i] = 0.f;
#pragma unroll 1
        for (int io = 0; io < 7; io++) {
#pragma unroll
            for (int s = 0; s < 4; s++) {
                const int it = io * 4 + s;
                mbar_wait(bar + B_F2 + 8 * s, io & 1);
                if (tid == 512 && s == 0 && (io == 0 || io == 4)) TLM(1, 14 + io / 4);
                const uint64_t dA = mkdesc(SBD + OFF_R + s * 24576, 16, 1024, 1);
                const uint64_t dB = mkdesc(SBD + OFF_R + s * 24576 + 8192, 8192, 1024, 1);
                wg_fence();
#pragma unroll
                for (int kk = 0; kk < EXP_FKK; kk++) wgmma_ss_n128(acc, dA + kk * 2, dB + kk * 128);
                wg_commit();
                if (warp < 18 && it >= 2 && it < 26) {
                    const int s2 = (s + 2) & 3;
                    mbar_wait(bar + B_E2 + 8 * s2, (io - (s < 2)) & 1);
                    if (elect()) {
                        if (warp == 16) {
                            mbar_expect(bar + B_F2 + 8 * s2, 24576);
                            tma5d_mc(sb + OFF_R + s2 * 24576 + 8192 + rank * 8192, &tm.w2, cb * 128 + rank * 64, it * 2 + 4, bar + B_F2 + 8 * s2);
                        } else {
                            asm volatile("fence.proxy.async.global;" ::: "memory");
                            tma2d(sb + OFF_R + s2 * 24576, &tm.h, it * 64 + 128, rb * 64, bar + B_F2 + 8 * s2);
                        }
                    }
                    __syncwarp();
                }
                wg_wait<1>();
                if (it >= 1 && lane < 2) mbar_arrive_cluster(bar + B_E2 + 8 * ((s + 3) & 3), lane);
            }
        }
        wg_wait<0>();
        if (lane < 2) mbar_arrive_cluster(bar + B_E2 + 8 * 3, lane);
        pin<64>(acc);
        if (warp == 16) {
            if (lane == 0) TLM(1, 16);
            for (int s = 0; s < 4; s++) mbar_wait(bar + B_E2 + 8 * s, 0);
            if (elect()) {
#pragma unroll
                for (int i = 0; i < 8; i++) mbar_expect(bar + B_T + 8 * i, 16384);
#pragma unroll
                for (int i = 0; i < 6; i++) tma2d_mc(sb + OFF_R + i * 16384 + rank * 8192, &tm.wo, cb * 128 + rank * 64, i * 64, bar + B_T + 8 * i);
            }
            __syncwarp();
        }
        {
            const int lr = (warp - 16) * 16 + g;
            const uint32_t pa = pk_bf16(ldcg_f(gG + rb * 64 + lr), ldcg_f(gG + rb * 64 + lr + 8));
            if (t == 0) {
                sts32(sb + OFF_G + lr * 4, __byte_perm(pa, pa, 0x1010));
                sts32(sb + OFF_G + lr * 4 + 32, __byte_perm(pa, pa, 0x3232));
            }
            __syncwarp();
            if (lane == 0) mbar_arrive(bar + B_G2);
            const float ga = bf_lo(pa), gb = bf_hi(pa);
            const float g0 = 1.f - ga, g1 = 1.f - gb;
#pragma unroll
            for (int j = 0; j < 16; j++) {
                const uint32_t bv = lds32(sb + OFF_BIAS + 576 + j * 16 + t * 4);
                acc[4 * j] = (acc[4 * j] + bf_lo(bv)) * g0;
                acc[4 * j + 1] = (acc[4 * j + 1] + bf_hi(bv)) * g0;
                acc[4 * j + 2] = (acc[4 * j + 2] + bf_lo(bv)) * g1;
                acc[4 * j + 3] = (acc[4 * j + 3] + bf_hi(bv)) * g1;
            }
            pin<64>(acc);
        }
        if (warp == 17) {
            mbar_wait(bar + B_DONE, 0);
            if (elect()) {
#pragma unroll
                for (int i = 0; i < 4; i++)
                    tma2d(sb + 65536 + i * 8192, &tm.wo, cb * 128 + (i & 1) * 64, (6 + (i >> 1)) * 64, bar + B_T + 8 * (6 + (i >> 1)));
            }
            __syncwarp();
        }
        if (tid == 512) TLM(1, 17);
#pragma unroll
        for (int i = 0; i < 8; i++) {
            mbar_wait(bar + B_T + 8 * i, 0);
            const uint64_t dA = mkdesc(SBD + i * 8192, 16, 1024, 1);
            const uint64_t dB = mkdesc(i < 6 ? SBD + OFF_R + i * 16384 : SBD + 65536 + (i - 6) * 16384, 8192, 1024, 1);
            wg_fence();
#pragma unroll
            for (int kk = 0; kk < 4; kk++) wgmma_ss_n128(acc, dA + kk * 2, dB + kk * 128);
            wg_commit();
        }
        wg_wait<0>();
        pin<64>(acc);
        if (tid == 512) TLM(1, 18);
        {
            const uint32_t st = sb + 98304 + (warp - 16) * 4352;
            const uint32_t wa = st + (lane & 15) * 272 + (lane >> 4) * 16;
#pragma unroll
            for (int j = 0; j < 8; j++)
                asm volatile("stmatrix.sync.aligned.m8n8.x4.shared.b16 [%0], {%1, %2, %3, %4};" ::"r"(wa + j * 32),
                             "r"(pk_bf16(acc[8 * j], acc[8 * j + 1])), "r"(pk_bf16(acc[8 * j + 2], acc[8 * j + 3])),
                             "r"(pk_bf16(acc[8 * j + 4], acc[8 * j + 5])), "r"(pk_bf16(acc[8 * j + 6], acc[8 * j + 7])) : "memory");
            __syncwarp();
            __nv_bfloat16* op = out + (size_t)(rb * 64 + (warp - 16) * 16 + (lane >> 4)) * DM + cb * 128 + (lane & 15) * 8;
#pragma unroll
            for (int j = 0; j < 8; j++) {
                uint4 v;
                asm volatile("ld.shared.v4.u32 {%0, %1, %2, %3}, [%4];" : "=r"(v.x), "=r"(v.y), "=r"(v.z), "=r"(v.w)
                             : "r"(st + (2 * j + (lane >> 4)) * 272 + (lane & 15) * 16));
                *(uint4*)(op + (size_t)j * 2 * DM) = v;
            }
        }
        if (tid == 512) { gEpoch[blockIdx.x] = ep; TLM(1, 19); }
    }
}

typedef CUresult (*EncodeFn)(CUtensorMap*, CUtensorMapDataType, cuuint32_t, void*, const cuuint64_t*, const cuuint64_t*, const cuuint32_t*,
                             const cuuint32_t*, CUtensorMapInterleave, CUtensorMapSwizzle, CUtensorMapL2promotion, CUtensorMapFloatOOBfill);

static void make_map(EncodeFn enc, CUtensorMap* m, const void* p, int rank, const cuuint64_t* dims, const cuuint64_t* strides,
                     const cuuint32_t* box, CUtensorMapSwizzle swz) {
    const cuuint32_t es[5] = {1, 1, 1, 1, 1};
    enc(m, CU_TENSOR_MAP_DATA_TYPE_BFLOAT16, rank, (void*)p, dims, strides, box, es, CU_TENSOR_MAP_INTERLEAVE_NONE, swz,
        CU_TENSOR_MAP_L2_PROMOTION_L2_128B, CU_TENSOR_MAP_FLOAT_OOB_FILL_NONE);
}

extern "C" void kernel_launch(void* const* d_in, const int* in_sizes, int n_in, void* d_out, int out_size) {
    const __nv_bfloat16* x = (const __nv_bfloat16*)d_in[0];
    const __nv_bfloat16* wqkv = (const __nv_bfloat16*)d_in[1];
    const __nv_bfloat16* wo = (const __nv_bfloat16*)d_in[2];
    const __nv_bfloat16* w1 = (const __nv_bfloat16*)d_in[4];
    const __nv_bfloat16* b1 = (const __nv_bfloat16*)d_in[5];
    const __nv_bfloat16* w2 = (const __nv_bfloat16*)d_in[6];
    const __nv_bfloat16* b2 = (const __nv_bfloat16*)d_in[7];
    const __nv_bfloat16* gate = (const __nv_bfloat16*)d_in[8];

    void* fp = nullptr;
    cudaDriverEntryPointQueryResult qr;
    cudaGetDriverEntryPoint("cuTensorMapEncodeTiled", &fp, cudaEnableDefault, &qr);
    EncodeFn enc = (EncodeFn)fp;
    void *pH, *pKV;
    cudaGetSymbolAddress(&pH, gH);
    cudaGetSymbolAddress(&pKV, gKV);

    Maps tm;
    const CUtensorMapSwizzle S128 = CU_TENSOR_MAP_SWIZZLE_128B, S64 = CU_TENSOR_MAP_SWIZZLE_64B;
    { cuuint64_t d[2] = {DM, SEQ}, s[1] = {DM * 2}; cuuint32_t b[2] = {64, 128}; make_map(enc, &tm.x, x, 2, d, s, b, S128); }
    { cuuint64_t d[3] = {DM, DM, 3}, s[2] = {3 * DM * 2, DM * 2}; cuuint32_t b[3] = {64, 32, 2}; make_map(enc, &tm.kv, wqkv, 3, d, s, b, S128); }
    { cuuint64_t d[3] = {32, DM, 3 * DM / 32}, s[2] = {3 * DM * 2, 64}; cuuint32_t b[3] = {32, 32, 2}; make_map(enc, &tm.q, wqkv, 3, d, s, b, S64); }
    { cuuint64_t d[3] = {32, DM, FF / 32}, s[2] = {FF * 2, 64}; cuuint32_t b[3] = {32, 32, 1}; make_map(enc, &tm.f1, w1, 3, d, s, b, S64); }
    { cuuint64_t d[3] = {32, DM, FF / 32}, s[2] = {FF * 2, 64}; cuuint32_t b[3] = {32, 32, 3}; make_map(enc, &tm.f3, w1, 3, d, s, b, S64); }
    { cuuint64_t d[2] = {FF, SEQ}, s[1] = {FF * 2}; cuuint32_t b[2] = {64, 64}; make_map(enc, &tm.h, pH, 2, d, s, b, S128); }
    { cuuint64_t d[5] = {DM, 2, 4, 4, FF / 32}, s[4] = {1024, 8 * 1024, 2 * 1024, 32 * 1024}; cuuint32_t b[5] = {64, 2, 4, 4, 2};
      make_map(enc, &tm.w2, w2, 5, d, s, b, S128); }
    { cuuint64_t d[2] = {DM, DM}, s[1] = {DM * 2}; cuuint32_t b[2] = {64, 64}; make_map(enc, &tm.wo, wo, 2, d, s, b, S128); }

    { cuuint64_t d[3] = {32, SEQ, FF / 32}, s[2] = {FF * 2, 64}; cuuint32_t b[3] = {32, 64, 1}; make_map(enc, &tm.hs, pH, 3, d, s, b, CU_TENSOR_MAP_SWIZZLE_NONE); }
    { cuuint64_t d[5] = {64, 16, 16, 2, 2 * NH}, s[4] = {4096, 128, 2048, 65536}; cuuint32_t b[5] = {64, 8, 2, 2, 1};
      make_map(enc, &tm.kvs, pKV, 5, d, s, b, S128); }
    cudaFuncSetAttribute(fused_kernel, cudaFuncAttributeMaxDynamicSharedMemorySize, SMEM_BYTES);
    fused_kernel<<<128, 640, SMEM_BYTES, cudaStreamPerThread>>>(tm, x, wqkv, wo, w1, b1, w2, b2, gate, (__nv_bfloat16*)d_out);
}
```

```cpp
#include <cuda_runtime.h>
#include <cuda_bf16.h>
#include <cuda_fp16.h>
#include <cuda.h>
#include <stdint.h>

#define SEQ 2048
#define DM 512
#define FF 1792
#define NH 32

__device__ __align__(1024) uint8_t gQ[NH * SEQ * 32];
__device__ __align__(1024) uint8_t gKV[NH * SEQ * 64];
__device__ __align__(1024) __nv_bfloat16 gH[SEQ * FF];
__device__ __align__(1024) uint4 gO[32 * NH * 128];
__device__ float gG[SEQ];
__device__ float gN[3 * 8 * 128];
__device__ unsigned int gCntQ[8 * 32];
__device__ unsigned int gCntH[32 * 32];
__device__ unsigned int gEpoch[128];

__device__ __forceinline__ uint32_t smem_u32(const void* p) { return (uint32_t)__cvta_generic_to_shared(p); }
__device__ __forceinline__ void mbar_init(uint32_t a, uint32_t c) { asm volatile("mbarrier.init.shared::cta.b64 [%0], %1;" ::"r"(a), "r"(c)); }
__device__ __forceinline__ void mbar_expect(uint32_t a, uint32_t b) { asm volatile("mbarrier.arrive.expect_tx.shared::cta.b64 _, [%0], %1;" ::"r"(a), "r"(b) : "memory"); }
__device__ __forceinline__ void mbar_arrive(uint32_t a) { asm volatile("mbarrier.arrive.shared::cta.b64 _, [%0];" ::"r"(a) : "memory"); }
__device__ __forceinline__ void mbar_wait(uint32_t a, uint32_t ph) {
    asm volatile("{\n.reg .pred p;\n.reg .u32 n;\nmov.u32 n, 0;\nW_%=:\nmbarrier.try_wait.parity.shared::cta.b64 p, [%0], %1;\n@p bra D_%=;\n"
                 "add.u32 n, n, 1;\nsetp.lt.u32 p, n, 0x400000;\n@p bra W_%=;\ntrap;\nD_%=:\n}" ::"r"(a), "r"(ph) : "memory");
}
__device__ __forceinline__ void mbar_arrive_cluster(uint32_t a, uint32_t cta) {
    asm volatile("{\n.reg .b32 r;\nmapa.shared::cluster.u32 r, %0, %1;\nmbarrier.arrive.shared::cluster.b64 _, [r];\n}" ::"r"(a), "r"(cta) : "memory");
}
__device__ __forceinline__ void bar_sync(int id, int n) { asm volatile("bar.sync %0, %1;" ::"r"(id), "r"(n) : "memory"); }
__device__ __forceinline__ void bar_arrive(int id, int n) { asm volatile("bar.arrive %0, %1;" ::"r"(id), "r"(n) : "memory"); }
__device__ __forceinline__ uint32_t cluster_rank() { uint32_t r; asm("mov.u32 %0, %%cluster_ctarank;" : "=r"(r)); return r; }
__device__ __forceinline__ void cnt_add(unsigned int* c) { asm volatile("red.release.gpu.global.add.u32 [%0], 1;" ::"l"(c) : "memory"); }
__device__ __forceinline__ void cnt_wait(const unsigned int* c, uint32_t target) {
    uint32_t v;
    int spins = 0;
    while (true) {
        asm volatile("ld.acquire.gpu.global.u32 %0, [%1];" : "=r"(v) : "l"(c) : "memory");
        if ((int)(v - target) >= 0) break;
        if (++spins > (1 << 22)) __trap();
        __nanosleep(40);
    }
}
__device__ __forceinline__ void tma2d(uint32_t dst, const CUtensorMap* m, int c0, int c1, uint32_t bar) {
    asm volatile("cp.async.bulk.tensor.2d.shared::cluster.global.mbarrier::complete_tx::bytes [%0], [%1, {%3, %4}], [%2];"
                 ::"r"(dst), "l"(m), "r"(bar), "r"(c0), "r"(c1) : "memory");
}
__device__ __forceinline__ void tma2d_mc(uint32_t dst, const CUtensorMap* m, int c0, int c1, uint32_t bar) {
    asm volatile("cp.async.bulk.tensor.2d.shared::cluster.global.mbarrier::complete_tx::bytes.multicast::cluster [%0], [%1, {%3, %4}], [%2], %5;"
                 ::"r"(dst), "l"(m), "r"(bar), "r"(c0), "r"(c1), "h"((uint16_t)3) : "memory");
}
__device__ __forceinline__ void tma3d_mc(uint32_t dst, const CUtensorMap* m, int c0, int c1, int c2, uint32_t bar) {
    asm volatile("cp.async.bulk.tensor.3d.shared::cluster.global.mbarrier::complete_tx::bytes.multicast::cluster [%0], [%1, {%3, %4, %5}], [%2], %6;"
                 ::"r"(dst), "l"(m), "r"(bar), "r"(c0), "r"(c1), "r"(c2), "h"((uint16_t)3) : "memory");
}
__device__ __forceinline__ void tma5d_mc(uint32_t dst, const CUtensorMap* m, int c0, int c4, uint32_t bar) {
    asm volatile("cp.async.bulk.tensor.5d.shared::cluster.global.mbarrier::complete_tx::bytes.multicast::cluster [%0], [%1, {%3, %5, %5, %5, %4}], [%2], %6;"
                 ::"r"(dst), "l"(m), "r"(bar), "r"(c0), "r"(c4), "r"(0), "h"((uint16_t)3) : "memory");
}
__device__ __forceinline__ void bulk_mc(uint32_t dst, const void* src, uint32_t bytes, uint32_t bar) {
    asm volatile("cp.async.bulk.shared::cluster.global.mbarrier::complete_tx::bytes.multicast::cluster [%0], [%1], %2, [%3], %4;"
                 ::"r"(dst), "l"(src), "r"(bytes), "r"(bar), "h"((uint16_t)3) : "memory");
}
__device__ __forceinline__ void tma3d_st(const CUtensorMap* m, uint32_t src, int c0, int c1, int c2) {
    asm volatile("cp.async.bulk.tensor.3d.global.shared::cta.bulk_group [%0, {%2, %3, %4}], [%1];" ::"l"(m), "r"(src), "r"(c0), "r"(c1), "r"(c2) : "memory");
}
__device__ __forceinline__ void tma5d_st(const CUtensorMap* m, uint32_t src, int c1, int c2, int c4) {
    asm volatile("cp.async.bulk.tensor.5d.global.shared::cta.bulk_group [%0, {%5, %2, %3, %5, %4}], [%1];"
                 ::"l"(m), "r"(src), "r"(c1), "r"(c2), "r"(c4), "r"(0) : "memory");
}
__device__ __forceinline__ void bulk_st(void* dst, uint32_t src, uint32_t bytes) {
    asm volatile("cp.async.bulk.global.shared::cta.bulk_group [%0], [%1], %2;" ::"l"(dst), "r"(src), "r"(bytes) : "memory");
}
__device__ __forceinline__ void sts64(uint32_t a, uint32_t x, uint32_t y) { asm volatile("st.shared.v2.u32 [%0], {%1, %2};" ::"r"(a), "r"(x), "r"(y) : "memory"); }
__device__ __forceinline__ void sts128(uint32_t a, const uint32_t* v) {
    asm volatile("st.shared.v4.u32 [%0], {%1, %2, %3, %4};" ::"r"(a), "r"(v[0]), "r"(v[1]), "r"(v[2]), "r"(v[3]) : "memory");
}
__device__ __forceinline__ void l2_prefetch(const void* src, uint32_t bytes) {
    asm volatile("cp.async.bulk.prefetch.L2.global [%0], %1;" ::"l"(src), "r"(bytes) : "memory");
}
__device__ __forceinline__ void map_prefetch(const CUtensorMap* m) { asm volatile("prefetch.tensormap [%0];" ::"l"(m) : "memory"); }
__device__ __forceinline__ void wg_fence() { asm volatile("wgmma.fence.sync.aligned;" ::: "memory"); }
__device__ __forceinline__ void wg_commit() { asm volatile("wgmma.commit_group.sync.aligned;" ::: "memory"); }
template <int N> __device__ __forceinline__ void wg_wait() { asm volatile("wgmma.wait_group.sync.aligned %0;" ::"n"(N) : "memory"); }
template <int N> __device__ __forceinline__ void pin(float* s) {
#pragma unroll
    for (int i = 0; i < N; i++) asm volatile("" : "+f"(s[i])::"memory");
}
template <int N> __device__ __forceinline__ void pin(uint32_t* s) {
#pragma unroll
    for (int i = 0; i < N; i++) asm volatile("" : "+r"(s[i])::"memory");
}
__device__ __forceinline__ uint64_t mkdesc(uint32_t addr, uint32_t lbo, uint32_t sbo, uint32_t swz) {
    return (uint64_t)((addr & 0x3FFFF) >> 4) | ((uint64_t)(lbo >> 4) << 16) | ((uint64_t)(sbo >> 4) << 32) | ((uint64_t)swz << 62);
}
__device__ __forceinline__ float ex2f(float x) { float y; asm("ex2.approx.ftz.f32 %0, %1;" : "=f"(y) : "f"(x)); return y; }
__device__ __forceinline__ float tanhf_(float x) { float y; asm("tanh.approx.f32 %0, %1;" : "=f"(y) : "f"(x)); return y; }
__device__ __forceinline__ uint32_t pk_bf16(float lo, float hi) { uint32_t r; asm("cvt.rn.bf16x2.f32 %0, %1, %2;" : "=r"(r) : "f"(hi), "f"(lo)); return r; }
__device__ __forceinline__ uint32_t pk_f16(float lo, float hi) { uint32_t r; asm("cvt.rn.f16x2.f32 %0, %1, %2;" : "=r"(r) : "f"(hi), "f"(lo)); return r; }
__device__ __forceinline__ float bf_lo(uint32_t v) { return __uint_as_float(v << 16); }
__device__ __forceinline__ float bf_hi(uint32_t v) { return __uint_as_float(v & 0xffff0000u); }
__device__ __forceinline__ float dot8(const uint4& a, const uint4& b) {
    return fmaf(bf_lo(a.x), bf_lo(b.x), fmaf(bf_hi(a.x), bf_hi(b.x), fmaf(bf_lo(a.y), bf_lo(b.y), bf_hi(a.y) * bf_hi(b.y)))) +
           fmaf(bf_lo(a.z), bf_lo(b.z), fmaf(bf_hi(a.z), bf_hi(b.z), fmaf(bf_lo(a.w), bf_lo(b.w), bf_hi(a.w) * bf_hi(b.w))));
}
__device__ __forceinline__ float ldcg_f(const float* p) { return __ldcg(p); }

extern __shared__ __align__(1024) uint8_t smem_raw[];
#define TLM(k, slot) do {} while (0)
#define TLC(k, slot) do {} while (0)
#define TL_INIT() do {} while (0)
#define TL_DUMP() do {} while (0)
#define TL_SMEM SMEM_BYTES

__device__ __forceinline__ void wgmma_ss_n128(float* d, uint64_t da, uint64_t db) {
    asm volatile("wgmma.mma_async.sync.aligned.m64n128k16.f32.bf16.bf16 {"
        "%0, %1, %2, %3, %4, %5, %6, %7, %8, %9, %10, %11, %12, %13, %14, %15,"
        "%16, %17, %18, %19, %20, %21, %22, %23, %24, %25, %26, %27, %28, %29, %30, %31,"
        "%32, %33, %34, %35, %36, %37, %38, %39, %40, %41, %42, %43, %44, %45, %46, %47,"
        "%48, %49, %50, %51, %52, %53, %54, %55, %56, %57, %58, %59, %60, %61, %62, %63}, %64, %65, 1, 1, 1, 0, 1;\n"
        :
        "+f"(d[0]), "+f"(d[1]), "+f"(d[2]), "+f"(d[3]), "+f"(d[4]), "+f"(d[5]), "+f"(d[6]), "+f"(d[7]),
        "+f"(d[8]), "+f"(d[9]), "+f"(d[10]), "+f"(d[11]), "+f"(d[12]), "+f"(d[13]), "+f"(d[14]), "+f"(d[15]),
        "+f"(d[16]), "+f"(d[17]), "+f"(d[18]), "+f"(d[19]), "+f"(d[20]), "+f"(d[21]), "+f"(d[22]), "+f"(d[23]),
        "+f"(d[24]), "+f"(d[25]), "+f"(d[26]), "+f"(d[27]), "+f"(d[28]), "+f"(d[29]), "+f"(d[30]), "+f"(d[31]),
        "+f"(d[32]), "+f"(d[33]), "+f"(d[34]), "+f"(d[35]), "+f"(d[36]), "+f"(d[37]), "+f"(d[38]), "+f"(d[39]),
        "+f"(d[40]), "+f"(d[41]), "+f"(d[42]), "+f"(d[43]), "+f"(d[44]), "+f"(d[45]), "+f"(d[46]), "+f"(d[47]),
        "+f"(d[48]), "+f"(d[49]), "+f"(d[50]), "+f"(d[51]), "+f"(d[52]), "+f"(d[53]), "+f"(d[54]), "+f"(d[55]),
        "+f"(d[56]), "+f"(d[57]), "+f"(d[58]), "+f"(d[59]), "+f"(d[60]), "+f"(d[61]), "+f"(d[62]), "+f"(d[63])
        : "l"(da), "l"(db));
}
__device__ __forceinline__ void wgmma_ss_n96(float* d, uint64_t da, uint64_t db) {
    asm volatile("wgmma.mma_async.sync.aligned.m64n96k16.f32.bf16.bf16 {"
        "%0, %1, %2, %3, %4, %5, %6, %7, %8, %9, %10, %11, %12, %13, %14, %15,"
        "%16, %17, %18, %19, %20, %21, %22, %23, %24, %25, %26, %27, %28, %29, %30, %31,"
        "%32, %33, %34, %35, %36, %37, %38, %39, %40, %41, %42, %43, %44, %45, %46, %47}, %48, %49, 1, 1, 1, 0, 1;\n"
        :
        "+f"(d[0]), "+f"(d[1]), "+f"(d[2]), "+f"(d[3]), "+f"(d[4]), "+f"(d[5]), "+f"(d[6]), "+f"(d[7]),
        "+f"(d[8]), "+f"(d[9]), "+f"(d[10]), "+f"(d[11]), "+f"(d[12]), "+f"(d[13]), "+f"(d[14]), "+f"(d[15]),
        "+f"(d[16]), "+f"(d[17]), "+f"(d[18]), "+f"(d[19]), "+f"(d[20]), "+f"(d[21]), "+f"(d[22]), "+f"(d[23]),
        "+f"(d[24]), "+f"(d[25]), "+f"(d[26]), "+f"(d[27]), "+f"(d[28]), "+f"(d[29]), "+f"(d[30]), "+f"(d[31]),
        "+f"(d[32]), "+f"(d[33]), "+f"(d[34]), "+f"(d[35]), "+f"(d[36]), "+f"(d[37]), "+f"(d[38]), "+f"(d[39]),
        "+f"(d[40]), "+f"(d[41]), "+f"(d[42]), "+f"(d[43]), "+f"(d[44]), "+f"(d[45]), "+f"(d[46]), "+f"(d[47])
        : "l"(da), "l"(db));
}
__device__ __forceinline__ void wgmma_ss_n64(float* d, uint64_t da, uint64_t db) {
    asm volatile("wgmma.mma_async.sync.aligned.m64n64k16.f32.bf16.bf16 {"
        "%0, %1, %2, %3, %4, %5, %6, %7, %8, %9, %10, %11, %12, %13, %14, %15,"
        "%16, %17, %18, %19, %20, %21, %22, %23, %24, %25, %26, %27, %28, %29, %30, %31}, %32, %33, 1, 1, 1, 0, 1;\n"
        :
        "+f"(d[0]), "+f"(d[1]), "+f"(d[2]), "+f"(d[3]), "+f"(d[4]), "+f"(d[5]), "+f"(d[6]), "+f"(d[7]),
        "+f"(d[8]), "+f"(d[9]), "+f"(d[10]), "+f"(d[11]), "+f"(d[12]), "+f"(d[13]), "+f"(d[14]), "+f"(d[15]),
        "+f"(d[16]), "+f"(d[17]), "+f"(d[18]), "+f"(d[19]), "+f"(d[20]), "+f"(d[21]), "+f"(d[22]), "+f"(d[23]),
        "+f"(d[24]), "+f"(d[25]), "+f"(d[26]), "+f"(d[27]), "+f"(d[28]), "+f"(d[29]), "+f"(d[30]), "+f"(d[31])
        : "l"(da), "l"(db));
}
__device__ __forceinline__ void wgmma_qk_f16_acc(float* d, const uint32_t* a, uint64_t db) {
    asm volatile("wgmma.mma_async.sync.aligned.m64n64k16.f32.f16.f16 {"
        "%0, %1, %2, %3, %4, %5, %6, %7, %8, %9, %10, %11, %12, %13, %14, %15,"
        "%16, %17, %18, %19, %20, %21, %22, %23, %24, %25, %26, %27, %28, %29, %30, %31}, {%32, %33, %34, %35}, %36, 1, 1, 1, 0;\n"
        :
        "+f"(d[0]), "+f"(d[1]), "+f"(d[2]), "+f"(d[3]), "+f"(d[4]), "+f"(d[5]), "+f"(d[6]), "+f"(d[7]),
        "+f"(d[8]), "+f"(d[9]), "+f"(d[10]), "+f"(d[11]), "+f"(d[12]), "+f"(d[13]), "+f"(d[14]), "+f"(d[15]),
        "+f"(d[16]), "+f"(d[17]), "+f"(d[18]), "+f"(d[19]), "+f"(d[20]), "+f"(d[21]), "+f"(d[22]), "+f"(d[23]),
        "+f"(d[24]), "+f"(d[25]), "+f"(d[26]), "+f"(d[27]), "+f"(d[28]), "+f"(d[29]), "+f"(d[30]), "+f"(d[31])
        : "r"(a[0]), "r"(a[1]), "r"(a[2]), "r"(a[3]), "l"(db));
}
__device__ __forceinline__ void wgmma_qk_bf16_zero(float* d, const uint32_t* a, uint64_t db) {
    asm volatile("wgmma.mma_async.sync.aligned.m64n64k16.f32.bf16.bf16 {"
        "%0, %1, %2, %3, %4, %5, %6, %7, %8, %9, %10, %11, %12, %13, %14, %15,"
        "%16, %17, %18, %19, %20, %21, %22, %23, %24, %25, %26, %27, %28, %29, %30, %31}, {%32, %33, %34, %35}, %36, 0, 1, 1, 0;\n"
        :
        "=f"(d[0]), "=f"(d[1]), "=f"(d[2]), "=f"(d[3]), "=f"(d[4]), "=f"(d[5]), "=f"(d[6]), "=f"(d[7]),
        "=f"(d[8]), "=f"(d[9]), "=f"(d[10]), "=f"(d[11]), "=f"(d[12]), "=f"(d[13]), "=f"(d[14]), "=f"(d[15]),
        "=f"(d[16]), "=f"(d[17]), "=f"(d[18]), "=f"(d[19]), "=f"(d[20]), "=f"(d[21]), "=f"(d[22]), "=f"(d[23]),
        "=f"(d[24]), "=f"(d[25]), "=f"(d[26]), "=f"(d[27]), "=f"(d[28]), "=f"(d[29]), "=f"(d[30]), "=f"(d[31])
        : "r"(a[0]), "r"(a[1]), "r"(a[2]), "r"(a[3]), "l"(db));
}
__device__ __forceinline__ void wgmma_pv(float* d, const uint32_t* a, uint64_t db) {
    asm volatile("wgmma.mma_async.sync.aligned.m64n24k16.f32.bf16.bf16 {"
        "%0, %1, %2, %3, %4, %5, %6, %7, %8, %9, %10, %11}, {%12, %13, %14, %15}, %16, 1, 1, 1, 1;\n"
        :
        "+f"(d[0]), "+f"(d[1]), "+f"(d[2]), "+f"(d[3]), "+f"(d[4]), "+f"(d[5]), "+f"(d[6]), "+f"(d[7]),
        "+f"(d[8]), "+f"(d[9]), "+f"(d[10]), "+f"(d[11])
        : "r"(a[0]), "r"(a[1]), "r"(a[2]), "r"(a[3]), "l"(db));
}

template <int N> __device__ __forceinline__ void wgmma_ss(float* d, uint64_t a, uint64_t b) {
    if (N == 128) wgmma_ss_n128(d, a, b);
    if (N == 96) wgmma_ss_n96(d, a, b);
    if (N == 64) wgmma_ss_n64(d, a, b);
}

#define OFF_R 131072
#define OFF_ONE 229376
#define OFF_BAR 229888
#define OFF_BIAS (OFF_BAR + 672)
#define OFF_G (OFF_BIAS + 1152)
#define SMEM_BYTES (OFF_G + 272)
#define SBD 1024u
#define B_X 0
#define B_F1 416
#define B_E1 112
#define B_KV 160
#define B_F2 224
#define B_E2 256
#define B_T 288
#define B_DONE 352
#define B_G 360
#define B_G2 368
#define B_G3 376
#define B_SF 384
#define B_SF2 408
#define NR 6

#define PF 1
#define PFX 0
#define EXP_FKK 4
#define QSCALE 0.36067376022224085f
#define MAGIC 445.41763f
#define NMUFU 4
#define VSTEP ((uint64_t)((long long)32 - ((long long)32 << 16)))

#define KVMASK 0x15ADu
__host__ __device__ constexpr int strm_pos(int pass, int i) {
    if (pass == 1 || pass == 2) return 8 + 8 * pass + i;
    int n = 0;
    for (int p = 0; p < 16; p++)
        if ((int)((KVMASK >> p) & 1) == (pass == 3)) { if (n == i) return p; n++; }
    return 0;
}
__host__ __device__ constexpr uint32_t strm_code(int pass) {
    uint32_t c = 0;
    for (int i = 0; i < 7; i++) c |= (uint32_t)(strm_pos(pass, i + 1) - strm_pos(pass, i)) << (4 * i);
    return c;
}

template <int N, int SUB, int KST, int LBO, int SBO, int SWZ>
__device__ __forceinline__ void gemm_pass(float* acc, uint32_t bar, uint64_t dA, int lane, uint32_t pos, uint32_t code, int barNext, bool waitx) {
    uint32_t prev = 0, slot = pos % NR;
#pragma unroll 1
    for (int i = 0; i < 8; i++) {
        if (waitx) mbar_wait(bar + B_X + 8 * i, 0);
        mbar_wait(bar + B_F1 + 8 * pos, 0);
        const uint64_t dB = mkdesc(SBD + OFF_R, LBO, SBO, SWZ) + slot * 1024;
        wg_fence();
        wgmma_ss<N>(acc, dA, dB);
        wgmma_ss<N>(acc, dA + 2, dB + KST / 16);
        wg_commit();
        wg_wait<1>();
        if (i > 0 && lane < 2) mbar_arrive_cluster(bar + B_E1 + 8 * prev, lane);
        wgmma_ss<N>(acc, dA + 4, dB + SUB / 16);
        wgmma_ss<N>(acc, dA + 6, dB + (SUB + KST) / 16);
        wg_commit();
        prev = slot;
        pos += code & 15;
        slot += code & 15;
        if (slot >= NR) slot -= NR;
        code >>= 4;
        dA += 1024;
    }
    if (barNext) bar_arrive(barNext, 512);
    wg_wait<0>();
    if (lane < 2) mbar_arrive_cluster(bar + B_E1 + 8 * prev, lane);
    pin<N / 2>(acc);
}

__device__ __forceinline__ uint32_t lds32(uint32_t a) { uint32_t v; asm volatile("ld.shared.u32 %0, [%1];" : "=r"(v) : "r"(a)); return v; }
__device__ __forceinline__ bool elect() {
    uint32_t p;
    asm volatile("{\n.reg .pred p;\nelect.sync _|p, 0xffffffff;\nselp.u32 %0, 1, 0, p;\n}" : "=r"(p));
    return p;
}

template <int G0, int G1> __device__ __forceinline__ void gelu_store(const float* acc, uint32_t bias, uint32_t hp) {
#pragma unroll
    for (int G = G0; G < G1; G++) {
        uint32_t o[8];
#pragma unroll
        for (int j = 0; j < 4; j++) {
            float bv[2];
            asm volatile("ld.shared.v2.f32 {%0, %1}, [%2];" : "=f"(bv[0]), "=f"(bv[1]) : "r"(bias + G * 128 + j * 32));
            float y[4];
#pragma unroll
            for (int i = 0; i < 4; i++) {
                const float h = acc[16 * G + 4 * j + i] + bv[i & 1];
                const float z = h * fmaf(h * h, 0.035677408136300125f, 0.7978845608028654f);
                y[i] = fmaf(h, tanhf_(z), h);
            }
            o[j] = pk_bf16(y[0], y[1]);
            o[4 + j] = pk_bf16(y[2], y[3]);
        }
        sts128(hp + G * 32768, o);
        sts128(hp + G * 32768 + 512, o + 4);
    }
}

__device__ __forceinline__ float norm_bound(const float* v, float sc) {
    uint32_t m = 0;
#pragma unroll
    for (int h = 0; h < 4; h++) {
        const float* u = v + 8 * h;
        m = max(m, __float_as_uint(fmaf(u[0], u[0], fmaf(u[1], u[1], fmaf(u[4], u[4], u[5] * u[5])))));
        m = max(m, __float_as_uint(fmaf(u[2], u[2], fmaf(u[3], u[3], fmaf(u[6], u[6], u[7] * u[7])))));
    }
#pragma unroll
    for (int o = 4; o < 32; o <<= 1) m = max(m, __shfl_xor_sync(0xffffffffu, m, o));
    float f = __uint_as_float(m);
    f += __shfl_xor_sync(0xffffffffu, f, 1);
    f += __shfl_xor_sync(0xffffffffu, f, 2);
    return f * sc;
}

__device__ __forceinline__ uint32_t exp2_pair(float a, float b) {
    const uint32_t w = __byte_perm(__float_as_uint(a), __float_as_uint(b), 0x6521);
    uint32_t m, r;
    asm("lop3.b32 %0, %1, 0x007f007f, 0x9f809f80, 0xEA;" : "=r"(m) : "r"(w));
    const uint32_t e = w - m;
    asm("fma.rn.bf16x2 %0, %1, %2, %3;" : "=r"(r) : "r"(w), "r"(m), "r"(e));
    return r;
}

__device__ __forceinline__ void store_o(const float* o, uint4* dst, uint32_t par) {
    const float s0 = __fdividef(1.f, o[8]), s1 = __fdividef(1.f, o[10]);
    const uint32_t d0 = (pk_bf16(o[0] * s0, o[1] * s0) & ~1u) | par;
    asm volatile("{\n.reg .b128 t;\nmov.b128 t, {%0, %1, %2, %3};\nst.relaxed.gpu.global.b128 [%4], t;\n}" ::"r"(d0),
                 "r"(pk_bf16(o[4] * s0, o[5] * s0)), "r"(pk_bf16(o[2] * s1, o[3] * s1)), "r"(pk_bf16(o[6] * s1, o[7] * s1)), "l"(dst) : "memory");
}
__device__ __forceinline__ uint4 load_o(const uint4* src) {
    uint4 v;
    asm volatile("{\n.reg .b128 t;\nld.relaxed.gpu.global.b128 t, [%4];\nmov.b128 {%0, %1, %2, %3}, t;\n}"
                 : "=r"(v.x), "=r"(v.y), "=r"(v.z), "=r"(v.w) : "l"(src) : "memory");
    return v;
}
__device__ __forceinline__ uint32_t bmul2(uint32_t a, uint32_t b) { uint32_t r; asm("mul.rn.bf16x2 %0, %1, %2;" : "=r"(r) : "r"(a), "r"(b)); return r; }
__device__ __forceinline__ void sts32(uint32_t a, uint32_t v) { asm volatile("st.shared.u32 [%0], %1;" ::"r"(a), "r"(v) : "memory"); }
__device__ __forceinline__ void load_q(uint32_t* q, int h, int row, int t) {
    const uint8_t* p = gQ + (size_t)h * (SEQ * 32) + (size_t)row * 32 + t * 4;
    q[0] = __ldcg((const uint32_t*)p); q[1] = __ldcg((const uint32_t*)(p + 256));
    q[2] = __ldcg((const uint32_t*)(p + 16)); q[3] = __ldcg((const uint32_t*)(p + 272));
}

template <int NT>
__device__ __forceinline__ void proj16(float (*c)[8], const __nv_bfloat16* x, const __nv_bfloat16* w, int row0, int rstep, int col, int g, int t) {
#pragma unroll
    for (int i = 0; i < NT; i++)
#pragma unroll
        for (int j = 0; j < 8; j++) c[i][j] = 0.f;
    const unsigned short* wu = (const unsigned short*)w;
#pragma unroll 1
    for (int k = 0; k < DM; k += 16) {
        uint32_t b[4];
#pragma unroll
        for (int j = 0; j < 4; j++) {
            const int kr = k + 2 * t + (j & 1) * 8, cc = col + g + (j >> 1) * 8;
            b[j] = (uint32_t)wu[(size_t)kr * (3 * DM) + cc] | ((uint32_t)wu[(size_t)(kr + 1) * (3 * DM) + cc] << 16);
        }
#pragma unroll
        for (int i = 0; i < NT; i++) {
            const __nv_bfloat16* xp = x + (size_t)(row0 + i * rstep + g) * DM + k + 2 * t;
            const uint32_t a0 = *(const uint32_t*)xp, a1 = *(const uint32_t*)(xp + 8 * DM);
            const uint32_t a2 = *(const uint32_t*)(xp + 8), a3 = *(const uint32_t*)(xp + 8 * DM + 8);
#pragma unroll
            for (int j = 0; j < 2; j++)
                asm volatile("mma.sync.aligned.m16n8k16.row.col.f32.bf16.bf16.f32 {%0,%1,%2,%3}, {%4,%5,%6,%7}, {%8,%9}, {%0,%1,%2,%3};"
                             : "+f"(c[i][4 * j]), "+f"(c[i][4 * j + 1]), "+f"(c[i][4 * j + 2]), "+f"(c[i][4 * j + 3])
                             : "r"(a0), "r"(a1), "r"(a2), "r"(a3), "r"(b[2 * j]), "r"(b[2 * j + 1]));
        }
    }
}

struct Maps { CUtensorMap x, kv, q, f1, f3, h, w2, wo, hs, kvs; };

__global__ void __cluster_dims__(2, 1, 1) __launch_bounds__(640, 1)
fused_kernel(const __grid_constant__ Maps tm, const __nv_bfloat16* __restrict__ x, const __nv_bfloat16* __restrict__ wqkv,
             const __nv_bfloat16* __restrict__ wo, const __nv_bfloat16* __restrict__ w1, const __nv_bfloat16* __restrict__ b1,
             const __nv_bfloat16* __restrict__ w2, const __nv_bfloat16* __restrict__ b2, const __nv_bfloat16* __restrict__ gate,
             __nv_bfloat16* __restrict__ out) {
    const uint32_t sb = smem_u32(smem_raw);
    const uint32_t bar = sb + OFF_BAR;
    const int tid = threadIdx.x, lane = tid & 31;
    const int warp = __shfl_sync(0xffffffffu, tid >> 5, 0);
    const uint32_t rank = cluster_rank();
    const int cl = blockIdx.x >> 1;
    const int nb = cl & 7, mb = (cl >> 3) * 2 + rank;
    const int g = lane >> 2, t = lane & 3;

    const int cb = nb & 3, rb = mb * 2 + (nb >> 2);
    if (tid == 0) TLM(0, 0);
    TL_INIT();
    if (tid == 512) {
        for (int i = 0; i < 8; i++) { mbar_init(bar + B_X + 8 * i, 1); mbar_init(bar + B_KV + 8 * i, 1); mbar_init(bar + B_T + 8 * i, 5); }
        for (int i = 0; i < NR; i++) mbar_init(bar + B_E1 + 8 * i, 16);
        for (int i = 0; i < 4; i++) { mbar_init(bar + B_F2 + 8 * i, 1); mbar_init(bar + B_E2 + 8 * i, 8); }
        asm volatile("fence.mbarrier_init.release.cluster;" ::: "memory");
    } else if (tid == 608) {
        for (int i = 0; i < 32; i++) mbar_init(bar + B_F1 + 8 * i, 1);
        mbar_init(bar + B_DONE, 16);
        mbar_init(bar + B_G, 1);
        for (int i = 0; i < 3; i++) mbar_init(bar + B_SF + 8 * i, 1);
        mbar_init(bar + B_SF2, 2);
        mbar_init(bar + B_G3, 1);
        mbar_init(bar + B_G2, 4);
        asm volatile("fence.mbarrier_init.release.cluster;" ::: "memory");
    }
    __syncwarp();
    asm volatile("barrier.cluster.arrive.relaxed.aligned;" ::: "memory");
    if (tid == 512) {
        mbar_expect(bar + B_X, 16384);
        tma2d(sb, &tm.x, 0, mb * 128, bar + B_X);
    } else if (tid == 544) {
        map_prefetch(&tm.kv);
        l2_prefetch((const uint8_t*)wqkv + (size_t)blockIdx.x * 3072, 3072);
        l2_prefetch((const uint8_t*)w1 + (size_t)blockIdx.x * 1792, 1792);
        map_prefetch(&tm.q); map_prefetch(&tm.f1); map_prefetch(&tm.f3);
    }
    if ((sb & 0xFFFFFF) != SBD) __trap();
    __syncwarp();
    asm volatile("barrier.cluster.wait.aligned;" ::: "memory");
    const uint32_t ep = gEpoch[blockIdx.x] + 1;
    if (tid == 0) { TLM(0, 1); TLC(0, 30); }

    if (warp < 16) {
        const int wg = warp >> 2;
        const int h = cl >> 1, qd = (cl & 1) * 2 + rank;
        uint32_t q[4];
        {
            const int w8 = warp & 7;
            const int T = mb * 8 + w8, row0 = T * 16 + g;
            const uint64_t dA0 = mkdesc(SBD + (wg & 1) * 8192, 16, 1024, 1);
            if (wg < 2) {
                float acc[64];
#pragma unroll
                for (int i = 0; i < 64; i++) acc[i] = 0.f;
                gemm_pass<128, 8192, 2048, 4096, 1024, 1>(acc, bar, dA0, lane, strm_pos(3, 0), strm_code(3), 0, true);
                if (tid == 0) TLM(0, 2);
                {
                    const float km = norm_bound(acc, 1.f);
                    float vm = 0.f;
#pragma unroll
                    for (int i = 32; i < 64; i++) vm = fmaxf(vm, fabsf(acc[i]));
                    vm = __uint_as_float(__reduce_max_sync(0xffffffffu, __float_as_uint(vm)));
                    if (lane == 0) { gN[1024 + nb * 128 + T] = km; gN[2048 + nb * 128 + T] = vm; }
                    const uint32_t kp = sb + OFF_R + 12288 + (w8 >> 2) * 1024 + g * 128 + ((((w8 & 3) * 2 + ((t >> 1) ^ (w8 >> 2))) ^ g) << 4) + (t & 1) * 8;
                    uint8_t* vp = gKV + (size_t)(nb * 4) * (SEQ * 64) + 65536 + (((T >> 6) * 16 + 2 * g) * 64 + (T & 63)) * 32 + ((t * 8) ^ ((w8 >> 2) << 4));
                    bar_sync(9, 256);
#pragma unroll
                    for (int hh = 0; hh < 4; hh++) {
                        const float* v = acc + 8 * hh;
                        float p0 = __shfl_up_sync(0xffffffffu, v[2], 4), p1 = __shfl_up_sync(0xffffffffu, v[3], 4);
                        float p2 = __shfl_up_sync(0xffffffffu, v[6], 4), p3 = __shfl_up_sync(0xffffffffu, v[7], 4);
                        if (g == 0) { p0 = p1 = p2 = p3 = 0.f; }
                        sts64(kp + hh * 16384, pk_f16(v[0] - p0, v[1] - p1), pk_f16(v[4] - p2, v[5] - p3));
                        sts64(kp + hh * 16384 + 2048, pk_f16(v[2] - v[0], v[3] - v[1]), pk_f16(v[6] - v[4], v[7] - v[5]));
                        const float* u = acc + 32 + 8 * hh;
                        if (hh < 2) {
                            sts64(kp + (4 + hh) * 16384, pk_bf16(u[0], u[1]), pk_bf16(u[4], u[5]));
                            sts64(kp + (4 + hh) * 16384 + 2048, pk_bf16(u[2], u[3]), pk_bf16(u[6], u[7]));
                        } else {
                            *(uint2*)(vp + (size_t)hh * (SEQ * 64)) = make_uint2(pk_bf16(u[0], u[1]), pk_bf16(u[4], u[5]));
                            *(uint2*)(vp + (size_t)hh * (SEQ * 64) + 2048) = make_uint2(pk_bf16(u[2], u[3]), pk_bf16(u[6], u[7]));
                        }
                    }
                }
                asm volatile("fence.proxy.async.shared::cta;" ::: "memory");
                bar_arrive(10, 288);
                if (tid == 0) TLM(0, 3);
            }
#pragma unroll 1
            for (int p = wg < 2 ? 1 : 0; p < 3; p += 2) {
                float acc[48];
#pragma unroll
                for (int i = 0; i < 48; i++) acc[i] = 0.f;
                pin<48>(acc);
                if (p) bar_sync(5 + p, 512);
                gemm_pass<96, 6144, 1024, 2048, 512, 2>(acc, bar, dA0, lane, p == 0 ? strm_pos(0, 0) : 8 + 8 * p, p == 0 ? strm_code(0) : strm_code(1), p < 2 ? 6 + p : 0, p == 0);
                if ((tid & 255) == 0) TLM(0, 4 + 2 * p);
                const uint32_t hp = sb + OFF_R + 12288 + (wg & 1) * 16384 + ((warp & 3) * 16 + g) * 64 + t * 16;
                const uint32_t bp = sb + OFF_BIAS + p * 384 - 256 + t * 8;
                if (p == 0) {
                    const float qm = norm_bound(acc, QSCALE * QSCALE);
                    if (lane == 0) gN[nb * 128 + T] = qm;
                    uint8_t* qp = gQ + (size_t)(nb * 4) * (SEQ * 32) + (size_t)row0 * 32 + t * 8;
#pragma unroll
                    for (int hh = 0; hh < 4; hh++) {
                        const float* v = acc + 8 * hh;
                        *(uint2*)(qp + hh * (SEQ * 32)) = make_uint2(pk_f16(v[0] * QSCALE, v[1] * QSCALE), pk_f16(v[4] * QSCALE, v[5] * QSCALE));
                        *(uint2*)(qp + hh * (SEQ * 32) + 256) = make_uint2(pk_f16(v[2] * QSCALE, v[3] * QSCALE), pk_f16(v[6] * QSCALE, v[7] * QSCALE));
                    }
                    bar_arrive(12, 288);
                    mbar_wait(bar + B_SF, 0);
                } else {
                    if (p == 2) {
                        mbar_wait(bar + B_G, 0);
                        load_q(q, h, qd * 512 + warp * 16 + g, t);
                    }
                    mbar_wait(bar + B_SF + 8 * p, 0);
                    gelu_store<0, 2>(acc, bp, hp);
                }
                gelu_store<2, 3>(acc, bp, hp);
                asm volatile("fence.proxy.async.shared::cta;" ::: "memory");
                bar_arrive(p == 1 ? 10 : 11, 288);
                if ((tid & 255) == 0) TLM(0, 5 + 2 * p);
            }
            if (wg < 2) {
                mbar_wait(bar + B_G, 0);
                load_q(q, h, qd * 512 + warp * 16 + g, t);
            }
        }
        mbar_wait(bar + B_G3, 0);
        const bool fast = lds32(sb + OFF_G + 256) != 0;
        uint4* const op = gO + ((qd * 8 + wg) * NH + h) * 128 + (tid & 127);
        const uint64_t kd0 = mkdesc(SBD, 16, 256, 3);
        const uint64_t vd0 = mkdesc(SBD + 8192, OFF_ONE - 8192, 256, 3);
        if (fast) {
#pragma unroll 1
            for (int r = 0; r < 2; r++) {
                float o[12];
#pragma unroll
                for (int i = 0; i < 12; i++) o[i] = 0.f;
                uint64_t kd = kd0, vd = vd0;
                uint32_t qn[4];
#pragma unroll 1
                for (int half = 0; half < 2; half++) {
                    float s[32];
#pragma unroll
                    for (int i = 0; i < 32; i++) s[i] = i < 2 * NMUFU ? 0.f : MAGIC;
#pragma unroll 1
                    for (int c = 0; c < 4; c++) {
                        if (r == 0) mbar_wait(bar + B_KV + 8 * (half * 4 + c), 0);
                        if ((tid & 255) == 0 && c == 0) TLM(1, (tid >> 8) * 4 + r * 2 + half);
                        if (half == 1 && c == 3) {
                            if (r == 0) load_q(qn, h, qd * 512 + 256 + warp * 16 + g, t);
                            else if (lane == 0) mbar_arrive(bar + B_DONE);
                        }
#pragma unroll
                        for (int j = 0; j < 4; j++) {
                            uint32_t p[16];
                            wg_fence();
                            wgmma_qk_f16_acc(s, q, kd);
                            wg_commit();
                            wg_wait<0>();
                            pin<32>(s);
#pragma unroll
                            for (int i = 0; i < 16; i++)
                                p[i] = i < NMUFU ? pk_bf16(ex2f(s[2 * i]), ex2f(s[2 * i + 1])) : exp2_pair(s[2 * i], s[2 * i + 1]);
                            pin<16>(p);
                            wg_fence();
#pragma unroll
                            for (int u = 0; u < 4; u++) wgmma_pv(o, p + 4 * u, vd + u * VSTEP);
                            wg_commit();
                            kd += 128;
                            vd += 4 * VSTEP;
                        }
                        kd += 512;
                        vd += 16 * VSTEP;
                    }
                    wg_wait<0>();
                }
                pin<12>(o);
                if ((tid & 127) == 0 && r == 1) TLM(1, 8 + wg);
                store_o(o, op + r * (4 * NH * 128), ep & 1);
#pragma unroll
                for (int i = 0; i < 4; i++) q[i] = qn[i];
            }
            if (tid == 0) { TLM(1, 12); TLC(0, 31); }
        } else {
            for (int c = 0; c < 8; c++) mbar_wait(bar + B_KV + 8 * c, 0);
            {
                float kc[8][8];
                proj16<8>(kc, x, wqkv, warp * 16, 256, DM + h * 16, g, t);
#pragma unroll
                for (int i = 0; i < 8; i++) {
                    const int T = warp + i * 16;
                    const int pos = ((T >> 6) * 16 + 2 * g) * 64 + (T & 63);
                    const uint32_t a = sb + (pos >> 8) * 16384 + (pos & 255) * 32 + t * 4, sw = ((T >> 2) & 1) << 4;
                    asm volatile("st.shared.u32 [%0], %1;" ::"r"(a + sw), "r"(pk_bf16(kc[i][0], kc[i][1])) : "memory");
                    asm volatile("st.shared.u32 [%0], %1;" ::"r"(a + (sw ^ 16)), "r"(pk_bf16(kc[i][4], kc[i][5])) : "memory");
                    asm volatile("st.shared.u32 [%0], %1;" ::"r"(a + 2048 + sw), "r"(pk_bf16(kc[i][2], kc[i][3])) : "memory");
                    asm volatile("st.shared.u32 [%0], %1;" ::"r"(a + 2048 + (sw ^ 16)), "r"(pk_bf16(kc[i][6], kc[i][7])) : "memory");
                }
                asm volatile("fence.proxy.async.shared::cta;" ::: "memory");
                bar_sync(8, 512);
            }
#pragma unroll 1
            for (int r = 0; r < 2; r++) {
                const int row = qd * 512 + r * 256 + warp * 16 + g;
                {
                    float qc[1][8];
                    proj16<1>(qc, x, wqkv, row - g, 0, h * 16, g, t);
#pragma unroll
                    for (int i = 0; i < 4; i++) q[i] = pk_bf16(qc[0][2 * i] * QSCALE, qc[0][2 * i + 1] * QSCALE);
                }
                float o[12];
#pragma unroll
                for (int i = 0; i < 12; i++) o[i] = 0.f;
                float m0 = -INFINITY, m1 = -INFINITY;
#pragma unroll 1
                for (int j = 0; j < 32; j++) {
                    const uint64_t kd = kd0 + (j >> 2) * 1024 + (j & 3) * 128, vd = vd0 + ((j >> 2) * 32 + (j & 3) * 4) * VSTEP;
                    float s[32];
                    uint32_t p[16];
                    wg_fence();
                    wgmma_qk_bf16_zero(s, q, kd);
                    wg_commit();
                    wg_wait<0>();
                    pin<32>(s);
                    pin<12>(o);
                    float n0 = m0, n1 = m1;
#pragma unroll
                    for (int i = 0; i < 8; i++) {
                        n0 = fmaxf(n0, fmaxf(s[4 * i], s[4 * i + 1]));
                        n1 = fmaxf(n1, fmaxf(s[4 * i + 2], s[4 * i + 3]));
                    }
                    n0 = fmaxf(n0, __shfl_xor_sync(0xffffffffu, n0, 1));
                    n1 = fmaxf(n1, __shfl_xor_sync(0xffffffffu, n1, 1));
                    n0 = fmaxf(n0, __shfl_xor_sync(0xffffffffu, n0, 2));
                    n1 = fmaxf(n1, __shfl_xor_sync(0xffffffffu, n1, 2));
                    const float c0 = ex2f(m0 - n0), c1 = ex2f(m1 - n1);
                    m0 = n0;
                    m1 = n1;
#pragma unroll
                    for (int i = 0; i < 3; i++) { o[4 * i] *= c0; o[4 * i + 1] *= c0; o[4 * i + 2] *= c1; o[4 * i + 3] *= c1; }
#pragma unroll
                    for (int i = 0; i < 8; i++) {
                        p[2 * i] = pk_bf16(ex2f(s[4 * i] - m0), ex2f(s[4 * i + 1] - m0));
                        p[2 * i + 1] = pk_bf16(ex2f(s[4 * i + 2] - m1), ex2f(s[4 * i + 3] - m1));
                    }
                    pin<16>(p);
                    pin<12>(o);
                    wg_fence();
#pragma unroll
                    for (int u = 0; u < 4; u++) wgmma_pv(o, p + 4 * u, vd + u * VSTEP);
                    wg_commit();
                }
                wg_wait<0>();
                pin<12>(o);
                if (r == 1 && lane == 0) mbar_arrive(bar + B_DONE);
                store_o(o, op + r * (4 * NH * 128), ep & 1);
            }
        }
        {
            const uint4* src = gO + (rb * NH + wg * 8) * 128 + (tid & 127);
            uint4 v[8];
#pragma unroll
            for (int i = 0; i < 8; i++) v[i] = load_o(src + i * 128);
            mbar_wait(bar + B_DONE, 0);
            mbar_wait(bar + B_G2, 0);
            const int lr = (warp & 3) * 16 + g;
            const uint32_t g0 = lds32(sb + OFF_G + lr * 4), g1 = lds32(sb + OFF_G + lr * 4 + 32);
            const uint32_t a0 = sb + wg * 16384 + lr * 128 + (t >> 1) * 4;
#pragma unroll
            for (int i = 0; i < 8; i++) {
                if ((i & 3) == 0) {
                    int spins = 0;
                    while (__any_sync(0xffffffffu, (((v[i].x ^ ep) | (v[i + 1].x ^ ep) | (v[i + 2].x ^ ep) | (v[i + 3].x ^ ep)) & 1) != 0)) {
                        if (++spins > (1 << 22)) __trap();
#pragma unroll
                        for (int k = i; k < 8; k++)
                            if (((v[k].x ^ ep) & 1) != 0) v[k] = load_o(src + k * 128);
                    }
                }
                const uint32_t a = a0 + (i >> 2) * 8192 + ((((i & 3) * 2 + (t & 1)) ^ g) << 4);
                sts32(a, bmul2(v[i].x, g0));
                sts32(a + 8, bmul2(v[i].y, g0));
                sts32(a + 1024, bmul2(v[i].z, g1));
                sts32(a + 1024 + 8, bmul2(v[i].w, g1));
                if ((i & 3) == 3) {
                    asm volatile("fence.proxy.async.shared::cta;" ::: "memory");
                    __syncwarp();
                    if (lane == 0) mbar_arrive(bar + B_T + 8 * (wg * 2 + (i >> 2)));
                    if ((tid & 127) == 0) TLM(1, 20 + wg * 2 + (i >> 2));
                }
            }
        }
    } else {
        if (warp == 16) {
            if (elect()) {
                int s = 0, par = 1, k0 = rank * 32, k3 = rank * 32;
#pragma unroll 1
                for (int it = 0; it < 32; it++) {
                    const uint32_t fb = bar + B_F1 + 8 * it, dst = sb + OFF_R + s * 16384;
                    mbar_wait(bar + B_E1 + 8 * s, par);
                    if (it < 16 && ((KVMASK >> it) & 1)) {
                        mbar_expect(fb, 16384);
                        tma3d_mc(dst + rank * 8192, &tm.kv, nb * 64, k3, 1, fb);
                        k3 += 64;
                    } else {
                        mbar_expect(fb, 12288);
                        if (it < 16) {
                            tma3d_mc(dst + rank * 6144, &tm.q, 0, k0, nb * 2, fb);
                            tma3d_mc(dst + rank * 6144 + 4096, &tm.f1, 0, k0, nb * 7, fb);
                        } else {
                            tma3d_mc(dst + rank * 6144, &tm.f3, 0, k0 & 511, nb * 7 + (it < 24 ? 1 : 4), fb);
                        }
                        k0 += 64;
                    }
                    for (int c = it; c >= 1 && c < 8 && (c == it || it == NR - 1) && it < NR; c++) {
                        mbar_expect(bar + B_X + 8 * c, 16384);
                        tma2d(sb + c * 16384, &tm.x, c * 64, mb * 128, bar + B_X + 8 * c);
                    }
                    if (++s == NR) { s = 0; par ^= 1; }
                }
                const int h = cl >> 1;
                mbar_wait(bar + B_G, 0);
                asm volatile("fence.proxy.async.global;" ::: "memory");
                TLM(0, 10);
#pragma unroll 1
                for (int c = 0; c < 8; c++) {
                    if (c >= 8 - NR) {
                        mbar_wait(bar + B_E1 + 8 * s, par);
                        if (++s == NR) { s = 0; par ^= 1; }
                    }
                    mbar_expect(bar + B_KV + 8 * c, 16384);
                    bulk_mc(sb + c * 16384 + rank * 8192, gKV + (size_t)h * (SEQ * 64) + rank * 65536 + c * 8192, 8192, bar + B_KV + 8 * c);
                }
                mbar_wait(bar + B_SF2, 0);
#pragma unroll 1
                for (s = 0; s < 4; s++) {
                    mbar_expect(bar + B_F2 + 8 * s, 24576);
                    tma5d_mc(sb + OFF_R + s * 24576 + 8192 + rank * 8192, &tm.w2, cb * 128 + rank * 64, s * 2, bar + B_F2 + 8 * s);
                }
                cnt_wait(gCntH + mb * 32, ep * 8);
                asm volatile("fence.proxy.async.global;" ::: "memory");
                TLM(1, 13);
#pragma unroll 1
                for (s = 0; s < 4; s++) tma2d(sb + OFF_R + s * 24576, &tm.h, s * 64, rb * 64, bar + B_F2 + 8 * s);
            }
        } else if (warp == 17) {
            {
                uint32_t bv[4], b2v[2];
#pragma unroll
                for (int i = 0; i < 4; i++) bv[i] = lane + 32 * i < 112 ? *(const uint32_t*)(b1 + nb * 224 + (lane + 32 * i) * 2) : 0;
#pragma unroll
                for (int i = 0; i < 2; i++) b2v[i] = *(const uint32_t*)(b2 + cb * 128 + (lane + 32 * i) * 2);
#pragma unroll
                for (int i = 0; i < 4; i++) {
                    sts32(sb + OFF_ONE + (lane + 32 * i) * 4, 0x3f803f80u);
                    if (lane + 32 * i < 112) sts64(sb + OFF_BIAS + (lane + 32 * i) * 8, bv[i] << 16, bv[i] & 0xffff0000u);
                }
#pragma unroll
                for (int i = 0; i < 2; i++) sts32(sb + OFF_BIAS + 896 + (lane + 32 * i) * 4, b2v[i]);
                asm volatile("fence.proxy.async.shared::cta;" ::: "memory");
            }
            mbar_wait(bar + B_X + 8 * PFX, 0);
            if (lane == 0) {
                l2_prefetch((const uint8_t*)wqkv + 128 * 3072 + (size_t)blockIdx.x * 9216, 9216);
                l2_prefetch((const uint8_t*)w1 + (size_t)blockIdx.x * 14336, 14336);
            }
            mbar_wait(bar + B_X + 8 * 7, 0);
            if (lane == 0) {
                l2_prefetch((const uint8_t*)w2 + (size_t)blockIdx.x * 14336, 14336);
                l2_prefetch((const uint8_t*)wo + (size_t)blockIdx.x * 4096, 4096);
                map_prefetch(&tm.h); map_prefetch(&tm.w2); map_prefetch(&tm.wo); map_prefetch(&tm.hs); map_prefetch(&tm.kvs);
                TLM(0, 11);
            }
#pragma unroll 1
            for (int e = 0; e < 4; e++) {
                bar_sync(10 + (e & 1), 288);
                if (lane == 0) {
#pragma unroll 1
                    for (int b = e == 1 ? 4 : 0; b < 6; b++) {
                        const uint32_t src = sb + OFF_R + 12288 + b * 16384;
                        if (e == 0) tma5d_st(&tm.kvs, src, (mb >> 3) * 8, (mb & 7) * 2, nb * 8 + (b < 4 ? 2 * b : 2 * b - 7));
                        else tma3d_st(&tm.hs, src, 0, mb * 128 + (b & 1) * 64, nb * 7 + e * 3 - 5 + (b >> 1));
                    }
                    asm volatile("cp.async.bulk.commit_group;\ncp.async.bulk.wait_group.read 0;" ::: "memory");
                    if (e < 3) mbar_arrive(bar + B_SF + 8 * e);
                    else { mbar_arrive_cluster(bar + B_SF2, 0); mbar_arrive_cluster(bar + B_SF2, 1); }
                }
                __syncwarp();
                if (e == 0 || e == 3) {
                    bar_sync(e == 0 ? 12 : 13, e == 0 ? 288 : 96);
                    if (lane == 0) {
                        asm volatile("cp.async.bulk.wait_group 0;\nfence.proxy.async.global;" ::: "memory");
                        cnt_add(e == 0 ? gCntQ + nb * 32 : gCntH + mb * 32);
                        TLM(0, e == 0 ? 13 : 15);
                    }
                    __syncwarp();
                }
            }
        } else {
            {
                const int r0 = mb * 128 + nb * 16 + (warp - 18) * 8;
                uint4 xv[16];
#pragma unroll
                for (int i = 0; i < 16; i++) xv[i] = *(const uint4*)(x + (size_t)(r0 + (i >> 1)) * DM + (i & 1) * 256 + lane * 8);
                const uint4 ga = *(const uint4*)(gate + lane * 8), gb = *(const uint4*)(gate + 256 + lane * 8);
                float z[8];
#pragma unroll
                for (int r = 0; r < 8; r++) z[r] = dot8(xv[2 * r], ga) + dot8(xv[2 * r + 1], gb);
#pragma unroll
                for (int w = 4; w >= 1; w >>= 1)
#pragma unroll
                    for (int r = 0; r < w; r++) {
                        const bool up = lane & w;
                        z[r] = (up ? z[r + w] : z[r]) + __shfl_xor_sync(0xffffffffu, up ? z[r] : z[r + w], w);
                    }
                z[0] += __shfl_xor_sync(0xffffffffu, z[0], 8);
                z[0] += __shfl_xor_sync(0xffffffffu, z[0], 16);
                if (lane < 8) gG[r0 + lane] = 1.f / (1.f + __expf(-z[0]));
                if (tid == 576) TLM(0, 12);
                bar_arrive(13, 96);
            }
            if (warp == 18) {
                const int h = cl >> 1, qd = (cl & 1) * 2 + rank;
                if (lane == 0) {
                    cnt_wait(gCntQ + (h >> 2) * 32, ep * 16);
                    mbar_arrive(bar + B_G);
                    TLM(0, 14);
                }
                __syncwarp();
            const int hb = h >> 2;
            const uint4 kq = __ldcg((const uint4*)(gN + 1024 + hb * 128 + lane * 4));
            const uint4 vq = __ldcg((const uint4*)(gN + 2048 + hb * 128 + lane * 4));
            const float qq = ldcg_f(gN + hb * 128 + qd * 32 + lane);
            const float kf = __uint_as_float(__reduce_max_sync(0xffffffffu, max(max(kq.x, kq.y), max(kq.z, kq.w))));
            const float vf = __uint_as_float(__reduce_max_sync(0xffffffffu, max(max(vq.x, vq.y), max(vq.z, vq.w))));
            const float qf = __uint_as_float(__reduce_max_sync(0xffffffffu, __float_as_uint(qq)));
            if (lane == 0) {
                sts32(sb + OFF_G + 256, (kf <= 1.0e6f) && (qf <= 1.0e6f) && (kf * qf <= 3400.f) && (vf <= 1.0e12f));
                mbar_arrive(bar + B_G3);
            }
            }
        }
        __syncwarp();
        float acc[64];
#pragma unroll
        for (int i = 0; i < 64; i++) acc[i] = 0.f;
#pragma unroll 1
        for (int io = 0; io < 7; io++) {
#pragma unroll
            for (int s = 0; s < 4; s++) {
                const int it = io * 4 + s;
                mbar_wait(bar + B_F2 + 8 * s, io & 1);
                if (tid == 512 && s == 0 && (io == 0 || io == 4)) TLM(1, 14 + io / 4);
                const uint64_t dA = mkdesc(SBD + OFF_R + s * 24576, 16, 1024, 1);
                const uint64_t dB = mkdesc(SBD + OFF_R + s * 24576 + 8192, 8192, 1024, 1);
                wg_fence();
#pragma unroll
                for (int kk = 0; kk < EXP_FKK; kk++) wgmma_ss_n128(acc, dA + kk * 2, dB + kk * 128);
                wg_commit();
                if (warp < 18 && it >= 2 && it < 26) {
                    const int s2 = (s + 2) & 3;
                    mbar_wait(bar + B_E2 + 8 * s2, (io - (s < 2)) & 1);
                    if (elect()) {
                        if (warp == 16) {
                            mbar_expect(bar + B_F2 + 8 * s2, 24576);
                            tma5d_mc(sb + OFF_R + s2 * 24576 + 8192 + rank * 8192, &tm.w2, cb * 128 + rank * 64, it * 2 + 4, bar + B_F2 + 8 * s2);
                        } else {
                            asm volatile("fence.proxy.async.global;" ::: "memory");
                            tma2d(sb + OFF_R + s2 * 24576, &tm.h, it * 64 + 128, rb * 64, bar + B_F2 + 8 * s2);
                        }
                    }
                    __syncwarp();
                }
                wg_wait<1>();
                if (it >= 1 && lane < 2) mbar_arrive_cluster(bar + B_E2 + 8 * ((s + 3) & 3), lane);
            }
        }
        wg_wait<0>();
        if (lane < 2) mbar_arrive_cluster(bar + B_E2 + 8 * 3, lane);
        pin<64>(acc);
        if (warp == 16) {
            if (lane == 0) TLM(1, 16);
            for (int s = 0; s < 4; s++) mbar_wait(bar + B_E2 + 8 * s, 0);
            if (elect()) {
#pragma unroll
                for (int i = 0; i < 8; i++) mbar_expect(bar + B_T + 8 * i, 16384);
#pragma unroll
                for (int i = 0; i < 6; i++) tma2d_mc(sb + OFF_R + i * 16384 + rank * 8192, &tm.wo, cb * 128 + rank * 64, i * 64, bar + B_T + 8 * i);
            }
            __syncwarp();
        }
        {
            const int lr = (warp - 16) * 16 + g;
            const uint32_t pa = pk_bf16(ldcg_f(gG + rb * 64 + lr), ldcg_f(gG + rb * 64 + lr + 8));
            if (t == 0) {
                sts32(sb + OFF_G + lr * 4, __byte_perm(pa, pa, 0x1010));
                sts32(sb + OFF_G + lr * 4 + 32, __byte_perm(pa, pa, 0x3232));
            }
            __syncwarp();
            if (lane == 0) mbar_arrive(bar + B_G2);
            const float ga = bf_lo(pa), gb = bf_hi(pa);
            const float g0 = 1.f - ga, g1 = 1.f - gb;
#pragma unroll
            for (int j = 0; j < 16; j++) {
                const uint32_t bv = lds32(sb + OFF_BIAS + 896 + j * 16 + t * 4);
                acc[4 * j] = fmaf(acc[4 * j], 0.5f, bf_lo(bv)) * g0;
                acc[4 * j + 1] = fmaf(acc[4 * j + 1], 0.5f, bf_hi(bv)) * g0;
                acc[4 * j + 2] = fmaf(acc[4 * j + 2], 0.5f, bf_lo(bv)) * g1;
                acc[4 * j + 3] = fmaf(acc[4 * j + 3], 0.5f, bf_hi(bv)) * g1;
            }
            pin<64>(acc);
        }
        if (warp == 17) {
            mbar_wait(bar + B_DONE, 0);
            if (elect()) {
#pragma unroll
                for (int i = 0; i < 4; i++)
                    tma2d(sb + 65536 + i * 8192, &tm.wo, cb * 128 + (i & 1) * 64, (6 + (i >> 1)) * 64, bar + B_T + 8 * (6 + (i >> 1)));
            }
            __syncwarp();
        }
        if (tid == 512) TLM(1, 17);
#pragma unroll
        for (int i = 0; i < 8; i++) {
            mbar_wait(bar + B_T + 8 * i, 0);
            const uint64_t dA = mkdesc(SBD + i * 8192, 16, 1024, 1);
            const uint64_t dB = mkdesc(i < 6 ? SBD + OFF_R + i * 16384 : SBD + 65536 + (i - 6) * 16384, 8192, 1024, 1);
            wg_fence();
#pragma unroll
            for (int kk = 0; kk < 4; kk++) wgmma_ss_n128(acc, dA + kk * 2, dB + kk * 128);
            wg_commit();
        }
        wg_wait<0>();
        pin<64>(acc);
        if (tid == 512) TLM(1, 18);
        {
            const uint32_t st = sb + 98304 + (warp - 16) * 4352;
            const uint32_t wa = st + (lane & 15) * 272 + (lane >> 4) * 16;
#pragma unroll
            for (int j = 0; j < 8; j++)
                asm volatile("stmatrix.sync.aligned.m8n8.x4.shared.b16 [%0], {%1, %2, %3, %4};" ::"r"(wa + j * 32),
                             "r"(pk_bf16(acc[8 * j], acc[8 * j + 1])), "r"(pk_bf16(acc[8 * j + 2], acc[8 * j + 3])),
                             "r"(pk_bf16(acc[8 * j + 4], acc[8 * j + 5])), "r"(pk_bf16(acc[8 * j + 6], acc[8 * j + 7])) : "memory");
            __syncwarp();
            __nv_bfloat16* op = out + (size_t)(rb * 64 + (warp - 16) * 16 + (lane >> 4)) * DM + cb * 128 + (lane & 15) * 8;
#pragma unroll
            for (int j = 0; j < 8; j++) {
                uint4 v;
                asm volatile("ld.shared.v4.u32 {%0, %1, %2, %3}, [%4];" : "=r"(v.x), "=r"(v.y), "=r"(v.z), "=r"(v.w)
                             : "r"(st + (2 * j + (lane >> 4)) * 272 + (lane & 15) * 16));
                *(uint4*)(op + (size_t)j * 2 * DM) = v;
            }
        }
        if (tid == 512) { gEpoch[blockIdx.x] = ep; TLM(1, 19); }
        TL_DUMP();
    }
}

typedef CUresult (*EncodeFn)(CUtensorMap*, CUtensorMapDataType, cuuint32_t, void*, const cuuint64_t*, const cuuint64_t*, const cuuint32_t*,
                             const cuuint32_t*, CUtensorMapInterleave, CUtensorMapSwizzle, CUtensorMapL2promotion, CUtensorMapFloatOOBfill);

static void make_map(EncodeFn enc, CUtensorMap* m, const void* p, int rank, const cuuint64_t* dims, const cuuint64_t* strides,
                     const cuuint32_t* box, CUtensorMapSwizzle swz) {
    const cuuint32_t es[5] = {1, 1, 1, 1, 1};
    enc(m, CU_TENSOR_MAP_DATA_TYPE_BFLOAT16, rank, (void*)p, dims, strides, box, es, CU_TENSOR_MAP_INTERLEAVE_NONE, swz,
        CU_TENSOR_MAP_L2_PROMOTION_L2_128B, CU_TENSOR_MAP_FLOAT_OOB_FILL_NONE);
}

extern "C" void kernel_launch(void* const* d_in, const int* in_sizes, int n_in, void* d_out, int out_size) {
    const __nv_bfloat16* x = (const __nv_bfloat16*)d_in[0];
    const __nv_bfloat16* wqkv = (const __nv_bfloat16*)d_in[1];
    const __nv_bfloat16* wo = (const __nv_bfloat16*)d_in[2];
    const __nv_bfloat16* w1 = (const __nv_bfloat16*)d_in[4];
    const __nv_bfloat16* b1 = (const __nv_bfloat16*)d_in[5];
    const __nv_bfloat16* w2 = (const __nv_bfloat16*)d_in[6];
    const __nv_bfloat16* b2 = (const __nv_bfloat16*)d_in[7];
    const __nv_bfloat16* gate = (const __nv_bfloat16*)d_in[8];

    void* fp = nullptr;
    cudaDriverEntryPointQueryResult qr;
    cudaGetDriverEntryPoint("cuTensorMapEncodeTiled", &fp, cudaEnableDefault, &qr);
    EncodeFn enc = (EncodeFn)fp;
    void *pH, *pKV;
    cudaGetSymbolAddress(&pH, gH);
    cudaGetSymbolAddress(&pKV, gKV);

    Maps tm;
    const CUtensorMapSwizzle S128 = CU_TENSOR_MAP_SWIZZLE_128B, S64 = CU_TENSOR_MAP_SWIZZLE_64B;
    { cuuint64_t d[2] = {DM, SEQ}, s[1] = {DM * 2}; cuuint32_t b[2] = {64, 128}; make_map(enc, &tm.x, x, 2, d, s, b, S128); }
    { cuuint64_t d[3] = {DM, DM, 3}, s[2] = {3 * DM * 2, DM * 2}; cuuint32_t b[3] = {64, 32, 2}; make_map(enc, &tm.kv, wqkv, 3, d, s, b, S128); }
    { cuuint64_t d[3] = {32, DM, 3 * DM / 32}, s[2] = {3 * DM * 2, 64}; cuuint32_t b[3] = {32, 32, 2}; make_map(enc, &tm.q, wqkv, 3, d, s, b, S64); }
    { cuuint64_t d[3] = {32, DM, FF / 32}, s[2] = {FF * 2, 64}; cuuint32_t b[3] = {32, 32, 1}; make_map(enc, &tm.f1, w1, 3, d, s, b, S64); }
    { cuuint64_t d[3] = {32, DM, FF / 32}, s[2] = {FF * 2, 64}; cuuint32_t b[3] = {32, 32, 3}; make_map(enc, &tm.f3, w1, 3, d, s, b, S64); }
    { cuuint64_t d[2] = {FF, SEQ}, s[1] = {FF * 2}; cuuint32_t b[2] = {64, 64}; make_map(enc, &tm.h, pH, 2, d, s, b, S128); }
    { cuuint64_t d[5] = {DM, 2, 4, 4, FF / 32}, s[4] = {1024, 8 * 1024, 2 * 1024, 32 * 1024}; cuuint32_t b[5] = {64, 2, 4, 4, 2};
      make_map(enc, &tm.w2, w2, 5, d, s, b, S128); }
    { cuuint64_t d[2] = {DM, DM}, s[1] = {DM * 2}; cuuint32_t b[2] = {64, 64}; make_map(enc, &tm.wo, wo, 2, d, s, b, S128); }

    { cuuint64_t d[3] = {32, SEQ, FF / 32}, s[2] = {FF * 2, 64}; cuuint32_t b[3] = {32, 64, 1}; make_map(enc, &tm.hs, pH, 3, d, s, b, CU_TENSOR_MAP_SWIZZLE_NONE); }
    { cuuint64_t d[5] = {64, 16, 16, 2, 2 * NH}, s[4] = {4096, 128, 2048, 65536}; cuuint32_t b[5] = {64, 8, 2, 2, 1};
      make_map(enc, &tm.kvs, pKV, 5, d, s, b, S128); }
    cudaFuncSetAttribute(fused_kernel, cudaFuncAttributeMaxDynamicSharedMemorySize, TL_SMEM);
    fused_kernel<<<128, 640, TL_SMEM, cudaStreamPerThread>>>(tm, x, wqkv, wo, w1, b1, w2, b2, gate, (__nv_bfloat16*)d_out);
}
```

```cpp
#include <cuda_runtime.h>
#include <cuda_bf16.h>
#include <cuda_fp16.h>
#include <cuda.h>
#include <stdint.h>

#define SEQ 2048
#define DM 512
#define FF 1792
#define NH 32

__device__ __align__(1024) uint8_t gQ[NH * SEQ * 32];
__device__ __align__(1024) uint8_t gKV[NH * SEQ * 64];
__device__ __align__(1024) __nv_bfloat16 gH[SEQ * FF];
__device__ __align__(1024) uint4 gO[32 * NH * 128];
__device__ float gG[SEQ];
__device__ float gN[3 * 8 * 128];
__device__ unsigned int gCntQ[8 * 32];
__device__ unsigned int gCntH[32 * 32];
__device__ unsigned int gEpoch[128];

__device__ __forceinline__ uint32_t smem_u32(const void* p) { return (uint32_t)__cvta_generic_to_shared(p); }
__device__ __forceinline__ void mbar_init(uint32_t a, uint32_t c) { asm volatile("mbarrier.init.shared::cta.b64 [%0], %1;" ::"r"(a), "r"(c)); }
__device__ __forceinline__ void mbar_expect(uint32_t a, uint32_t b) { asm volatile("mbarrier.arrive.expect_tx.shared::cta.b64 _, [%0], %1;" ::"r"(a), "r"(b) : "memory"); }
__device__ __forceinline__ void mbar_arrive(uint32_t a) { asm volatile("mbarrier.arrive.shared::cta.b64 _, [%0];" ::"r"(a) : "memory"); }
__device__ __forceinline__ void mbar_wait(uint32_t a, uint32_t ph) {
    asm volatile("{\n.reg .pred p;\n.reg .u32 n;\nmov.u32 n, 0;\nW_%=:\nmbarrier.try_wait.parity.shared::cta.b64 p, [%0], %1;\n@p bra D_%=;\n"
                 "add.u32 n, n, 1;\nsetp.lt.u32 p, n, 0x400000;\n@p bra W_%=;\ntrap;\nD_%=:\n}" ::"r"(a), "r"(ph) : "memory");
}
__device__ __forceinline__ void mbar_arrive_cluster(uint32_t a, uint32_t cta) {
    asm volatile("{\n.reg .b32 r;\nmapa.shared::cluster.u32 r, %0, %1;\nmbarrier.arrive.shared::cluster.b64 _, [r];\n}" ::"r"(a), "r"(cta) : "memory");
}
__device__ __forceinline__ void bar_sync(int id, int n) { asm volatile("bar.sync %0, %1;" ::"r"(id), "r"(n) : "memory"); }
__device__ __forceinline__ void bar_arrive(int id, int n) { asm volatile("bar.arrive %0, %1;" ::"r"(id), "r"(n) : "memory"); }
__device__ __forceinline__ uint32_t cluster_rank() { uint32_t r; asm("mov.u32 %0, %%cluster_ctarank;" : "=r"(r)); return r; }
__device__ __forceinline__ void cnt_add(unsigned int* c) { asm volatile("red.release.gpu.global.add.u32 [%0], 1;" ::"l"(c) : "memory"); }
__device__ __forceinline__ void cnt_wait(const unsigned int* c, uint32_t target) {
    uint32_t v;
    int spins = 0;
    while (true) {
        asm volatile("ld.acquire.gpu.global.u32 %0, [%1];" : "=r"(v) : "l"(c) : "memory");
        if ((int)(v - target) >= 0) break;
        if (++spins > (1 << 22)) __trap();
        __nanosleep(40);
    }
}
__device__ __forceinline__ void tma2d(uint32_t dst, const CUtensorMap* m, int c0, int c1, uint32_t bar) {
    asm volatile("cp.async.bulk.tensor.2d.shared::cluster.global.mbarrier::complete_tx::bytes [%0], [%1, {%3, %4}], [%2];"
                 ::"r"(dst), "l"(m), "r"(bar), "r"(c0), "r"(c1) : "memory");
}
__device__ __forceinline__ void tma2d_mc(uint32_t dst, const CUtensorMap* m, int c0, int c1, uint32_t bar) {
    asm volatile("cp.async.bulk.tensor.2d.shared::cluster.global.mbarrier::complete_tx::bytes.multicast::cluster [%0], [%1, {%3, %4}], [%2], %5;"
                 ::"r"(dst), "l"(m), "r"(bar), "r"(c0), "r"(c1), "h"((uint16_t)3) : "memory");
}
__device__ __forceinline__ void tma3d_mc(uint32_t dst, const CUtensorMap* m, int c0, int c1, int c2, uint32_t bar) {
    asm volatile("cp.async.bulk.tensor.3d.shared::cluster.global.mbarrier::complete_tx::bytes.multicast::cluster [%0], [%1, {%3, %4, %5}], [%2], %6;"
                 ::"r"(dst), "l"(m), "r"(bar), "r"(c0), "r"(c1), "r"(c2), "h"((uint16_t)3) : "memory");
}
__device__ __forceinline__ void tma5d_mc(uint32_t dst, const CUtensorMap* m, int c0, int c4, uint32_t bar) {
    asm volatile("cp.async.bulk.tensor.5d.shared::cluster.global.mbarrier::complete_tx::bytes.multicast::cluster [%0], [%1, {%3, %5, %5, %5, %4}], [%2], %6;"
                 ::"r"(dst), "l"(m), "r"(bar), "r"(c0), "r"(c4), "r"(0), "h"((uint16_t)3) : "memory");
}
__device__ __forceinline__ void bulk_mc(uint32_t dst, const void* src, uint32_t bytes, uint32_t bar) {
    asm volatile("cp.async.bulk.shared::cluster.global.mbarrier::complete_tx::bytes.multicast::cluster [%0], [%1], %2, [%3], %4;"
                 ::"r"(dst), "l"(src), "r"(bytes), "r"(bar), "h"((uint16_t)3) : "memory");
}
__device__ __forceinline__ void tma3d_st(const CUtensorMap* m, uint32_t src, int c0, int c1, int c2) {
    asm volatile("cp.async.bulk.tensor.3d.global.shared::cta.bulk_group [%0, {%2, %3, %4}], [%1];" ::"l"(m), "r"(src), "r"(c0), "r"(c1), "r"(c2) : "memory");
}
__device__ __forceinline__ void tma5d_st(const CUtensorMap* m, uint32_t src, int c1, int c2, int c4) {
    asm volatile("cp.async.bulk.tensor.5d.global.shared::cta.bulk_group [%0, {%5, %2, %3, %5, %4}], [%1];"
                 ::"l"(m), "r"(src), "r"(c1), "r"(c2), "r"(c4), "r"(0) : "memory");
}
__device__ __forceinline__ void bulk_st(void* dst, uint32_t src, uint32_t bytes) {
    asm volatile("cp.async.bulk.global.shared::cta.bulk_group [%0], [%1], %2;" ::"l"(dst), "r"(src), "r"(bytes) : "memory");
}
__device__ __forceinline__ void sts64(uint32_t a, uint32_t x, uint32_t y) { asm volatile("st.shared.v2.u32 [%0], {%1, %2};" ::"r"(a), "r"(x), "r"(y) : "memory"); }
__device__ __forceinline__ void sts128(uint32_t a, const uint32_t* v) {
    asm volatile("st.shared.v4.u32 [%0], {%1, %2, %3, %4};" ::"r"(a), "r"(v[0]), "r"(v[1]), "r"(v[2]), "r"(v[3]) : "memory");
}
__device__ __forceinline__ void l2_prefetch(const void* src, uint32_t bytes) {
    asm volatile("cp.async.bulk.prefetch.L2.global [%0], %1;" ::"l"(src), "r"(bytes) : "memory");
}
__device__ __forceinline__ void map_prefetch(const CUtensorMap* m) { asm volatile("prefetch.tensormap [%0];" ::"l"(m) : "memory"); }
__device__ __forceinline__ void wg_fence() { asm volatile("wgmma.fence.sync.aligned;" ::: "memory"); }
__device__ __forceinline__ void wg_commit() { asm volatile("wgmma.commit_group.sync.aligned;" ::: "memory"); }
template <int N> __device__ __forceinline__ void wg_wait() { asm volatile("wgmma.wait_group.sync.aligned %0;" ::"n"(N) : "memory"); }
template <int N> __device__ __forceinline__ void pin(float* s) {
#pragma unroll
    for (int i = 0; i < N; i++) asm volatile("" : "+f"(s[i])::"memory");
}
template <int N> __device__ __forceinline__ void pin(uint32_t* s) {
#pragma unroll
    for (int i = 0; i < N; i++) asm volatile("" : "+r"(s[i])::"memory");
}
__device__ __forceinline__ uint64_t mkdesc(uint32_t addr, uint32_t lbo, uint32_t sbo, uint32_t swz) {
    return (uint64_t)((addr & 0x3FFFF) >> 4) | ((uint64_t)(lbo >> 4) << 16) | ((uint64_t)(sbo >> 4) << 32) | ((uint64_t)swz << 62);
}
__device__ __forceinline__ float ex2f(float x) { float y; asm("ex2.approx.ftz.f32 %0, %1;" : "=f"(y) : "f"(x)); return y; }
__device__ __forceinline__ float tanhf_(float x) { float y; asm("tanh.approx.f32 %0, %1;" : "=f"(y) : "f"(x)); return y; }
__device__ __forceinline__ uint32_t pk_bf16(float lo, float hi) { uint32_t r; asm("cvt.rn.bf16x2.f32 %0, %1, %2;" : "=r"(r) : "f"(hi), "f"(lo)); return r; }
__device__ __forceinline__ uint32_t pk_f16(float lo, float hi) { uint32_t r; asm("cvt.rn.f16x2.f32 %0, %1, %2;" : "=r"(r) : "f"(hi), "f"(lo)); return r; }
__device__ __forceinline__ float bf_lo(uint32_t v) { return __uint_as_float(v << 16); }
__device__ __forceinline__ float bf_hi(uint32_t v) { return __uint_as_float(v & 0xffff0000u); }
__device__ __forceinline__ float dot8(const uint4& a, const uint4& b) {
    return fmaf(bf_lo(a.x), bf_lo(b.x), fmaf(bf_hi(a.x), bf_hi(b.x), fmaf(bf_lo(a.y), bf_lo(b.y), bf_hi(a.y) * bf_hi(b.y)))) +
           fmaf(bf_lo(a.z), bf_lo(b.z), fmaf(bf_hi(a.z), bf_hi(b.z), fmaf(bf_lo(a.w), bf_lo(b.w), bf_hi(a.w) * bf_hi(b.w))));
}
__device__ __forceinline__ float ldcg_f(const float* p) { return __ldcg(p); }

extern __shared__ __align__(1024) uint8_t smem_raw[];
#define TLM(k, slot) do {} while (0)
#define TLC(k, slot) do {} while (0)
#define TL_INIT() do {} while (0)
#define TL_DUMP() do {} while (0)
#define TL_SMEM SMEM_BYTES

__device__ __forceinline__ void wgmma_ss_n128(float* d, uint64_t da, uint64_t db) {
    asm volatile("wgmma.mma_async.sync.aligned.m64n128k16.f32.bf16.bf16 {"
        "%0, %1, %2, %3, %4, %5, %6, %7, %8, %9, %10, %11, %12, %13, %14, %15,"
        "%16, %17, %18, %19, %20, %21, %22, %23, %24, %25, %26, %27, %28, %29, %30, %31,"
        "%32, %33, %34, %35, %36, %37, %38, %39, %40, %41, %42, %43, %44, %45, %46, %47,"
        "%48, %49, %50, %51, %52, %53, %54, %55, %56, %57, %58, %59, %60, %61, %62, %63}, %64, %65, 1, 1, 1, 0, 1;\n"
        :
        "+f"(d[0]), "+f"(d[1]), "+f"(d[2]), "+f"(d[3]), "+f"(d[4]), "+f"(d[5]), "+f"(d[6]), "+f"(d[7]),
        "+f"(d[8]), "+f"(d[9]), "+f"(d[10]), "+f"(d[11]), "+f"(d[12]), "+f"(d[13]), "+f"(d[14]), "+f"(d[15]),
        "+f"(d[16]), "+f"(d[17]), "+f"(d[18]), "+f"(d[19]), "+f"(d[20]), "+f"(d[21]), "+f"(d[22]), "+f"(d[23]),
        "+f"(d[24]), "+f"(d[25]), "+f"(d[26]), "+f"(d[27]), "+f"(d[28]), "+f"(d[29]), "+f"(d[30]), "+f"(d[31]),
        "+f"(d[32]), "+f"(d[33]), "+f"(d[34]), "+f"(d[35]), "+f"(d[36]), "+f"(d[37]), "+f"(d[38]), "+f"(d[39]),
        "+f"(d[40]), "+f"(d[41]), "+f"(d[42]), "+f"(d[43]), "+f"(d[44]), "+f"(d[45]), "+f"(d[46]), "+f"(d[47]),
        "+f"(d[48]), "+f"(d[49]), "+f"(d[50]), "+f"(d[51]), "+f"(d[52]), "+f"(d[53]), "+f"(d[54]), "+f"(d[55]),
        "+f"(d[56]), "+f"(d[57]), "+f"(d[58]), "+f"(d[59]), "+f"(d[60]), "+f"(d[61]), "+f"(d[62]), "+f"(d[63])
        : "l"(da), "l"(db));
}
__device__ __forceinline__ void wgmma_ss_n96(float* d, uint64_t da, uint64_t db) {
    asm volatile("wgmma.mma_async.sync.aligned.m64n96k16.f32.bf16.bf16 {"
        "%0, %1, %2, %3, %4, %5, %6, %7, %8, %9, %10, %11, %12, %13, %14, %15,"
        "%16, %17, %18, %19, %20, %21, %22, %23, %24, %25, %26, %27, %28, %29, %30, %31,"
        "%32, %33, %34, %35, %36, %37, %38, %39, %40, %41, %42, %43, %44, %45, %46, %47}, %48, %49, 1, 1, 1, 0, 1;\n"
        :
        "+f"(d[0]), "+f"(d[1]), "+f"(d[2]), "+f"(d[3]), "+f"(d[4]), "+f"(d[5]), "+f"(d[6]), "+f"(d[7]),
        "+f"(d[8]), "+f"(d[9]), "+f"(d[10]), "+f"(d[11]), "+f"(d[12]), "+f"(d[13]), "+f"(d[14]), "+f"(d[15]),
        "+f"(d[16]), "+f"(d[17]), "+f"(d[18]), "+f"(d[19]), "+f"(d[20]), "+f"(d[21]), "+f"(d[22]), "+f"(d[23]),
        "+f"(d[24]), "+f"(d[25]), "+f"(d[26]), "+f"(d[27]), "+f"(d[28]), "+f"(d[29]), "+f"(d[30]), "+f"(d[31]),
        "+f"(d[32]), "+f"(d[33]), "+f"(d[34]), "+f"(d[35]), "+f"(d[36]), "+f"(d[37]), "+f"(d[38]), "+f"(d[39]),
        "+f"(d[40]), "+f"(d[41]), "+f"(d[42]), "+f"(d[43]), "+f"(d[44]), "+f"(d[45]), "+f"(d[46]), "+f"(d[47])
        : "l"(da), "l"(db));
}
__device__ __forceinline__ void wgmma_ss_n64(float* d, uint64_t da, uint64_t db) {
    asm volatile("wgmma.mma_async.sync.aligned.m64n64k16.f32.bf16.bf16 {"
        "%0, %1, %2, %3, %4, %5, %6, %7, %8, %9, %10, %11, %12, %13, %14, %15,"
        "%16, %17, %18, %19, %20, %21, %22, %23, %24, %25, %26, %27, %28, %29, %30, %31}, %32, %33, 1, 1, 1, 0, 1;\n"
        :
        "+f"(d[0]), "+f"(d[1]), "+f"(d[2]), "+f"(d[3]), "+f"(d[4]), "+f"(d[5]), "+f"(d[6]), "+f"(d[7]),
        "+f"(d[8]), "+f"(d[9]), "+f"(d[10]), "+f"(d[11]), "+f"(d[12]), "+f"(d[13]), "+f"(d[14]), "+f"(d[15]),
        "+f"(d[16]), "+f"(d[17]), "+f"(d[18]), "+f"(d[19]), "+f"(d[20]), "+f"(d[21]), "+f"(d[22]), "+f"(d[23]),
        "+f"(d[24]), "+f"(d[25]), "+f"(d[26]), "+f"(d[27]), "+f"(d[28]), "+f"(d[29]), "+f"(d[30]), "+f"(d[31])
        : "l"(da), "l"(db));
}
__device__ __forceinline__ void wgmma_qk_f16_acc(float* d, const uint32_t* a, uint64_t db) {
    asm volatile("wgmma.mma_async.sync.aligned.m64n64k16.f32.f16.f16 {"
        "%0, %1, %2, %3, %4, %5, %6, %7, %8, %9, %10, %11, %12, %13, %14, %15,"
        "%16, %17, %18, %19, %20, %21, %22, %23, %24, %25, %26, %27, %28, %29, %30, %31}, {%32, %33, %34, %35}, %36, 1, 1, 1, 0;\n"
        :
        "+f"(d[0]), "+f"(d[1]), "+f"(d[2]), "+f"(d[3]), "+f"(d[4]), "+f"(d[5]), "+f"(d[6]), "+f"(d[7]),
        "+f"(d[8]), "+f"(d[9]), "+f"(d[10]), "+f"(d[11]), "+f"(d[12]), "+f"(d[13]), "+f"(d[14]), "+f"(d[15]),
        "+f"(d[16]), "+f"(d[17]), "+f"(d[18]), "+f"(d[19]), "+f"(d[20]), "+f"(d[21]), "+f"(d[22]), "+f"(d[23]),
        "+f"(d[24]), "+f"(d[25]), "+f"(d[26]), "+f"(d[27]), "+f"(d[28]), "+f"(d[29]), "+f"(d[30]), "+f"(d[31])
        : "r"(a[0]), "r"(a[1]), "r"(a[2]), "r"(a[3]), "l"(db));
}
__device__ __forceinline__ void wgmma_qk_bf16_zero(float* d, const uint32_t* a, uint64_t db) {
    asm volatile("wgmma.mma_async.sync.aligned.m64n64k16.f32.bf16.bf16 {"
        "%0, %1, %2, %3, %4, %5, %6, %7, %8, %9, %10, %11, %12, %13, %14, %15,"
        "%16, %17, %18, %19, %20, %21, %22, %23, %24, %25, %26, %27, %28, %29, %30, %31}, {%32, %33, %34, %35}, %36, 0, 1, 1, 0;\n"
        :
        "=f"(d[0]), "=f"(d[1]), "=f"(d[2]), "=f"(d[3]), "=f"(d[4]), "=f"(d[5]), "=f"(d[6]), "=f"(d[7]),
        "=f"(d[8]), "=f"(d[9]), "=f"(d[10]), "=f"(d[11]), "=f"(d[12]), "=f"(d[13]), "=f"(d[14]), "=f"(d[15]),
        "=f"(d[16]), "=f"(d[17]), "=f"(d[18]), "=f"(d[19]), "=f"(d[20]), "=f"(d[21]), "=f"(d[22]), "=f"(d[23]),
        "=f"(d[24]), "=f"(d[25]), "=f"(d[26]), "=f"(d[27]), "=f"(d[28]), "=f"(d[29]), "=f"(d[30]), "=f"(d[31])
        : "r"(a[0]), "r"(a[1]), "r"(a[2]), "r"(a[3]), "l"(db));
}
__device__ __forceinline__ void wgmma_pv(float* d, const uint32_t* a, uint64_t db) {
    asm volatile("wgmma.mma_async.sync.aligned.m64n24k16.f32.bf16.bf16 {"
        "%0, %1, %2, %3, %4, %5, %6, %7, %8, %9, %10, %11}, {%12, %13, %14, %15}, %16, 1, 1, 1, 1;\n"
        :
        "+f"(d[0]), "+f"(d[1]), "+f"(d[2]), "+f"(d[3]), "+f"(d[4]), "+f"(d[5]), "+f"(d[6]), "+f"(d[7]),
        "+f"(d[8]), "+f"(d[9]), "+f"(d[10]), "+f"(d[11])
        : "r"(a[0]), "r"(a[1]), "r"(a[2]), "r"(a[3]), "l"(db));
}

template <int N> __device__ __forceinline__ void wgmma_ss(float* d, uint64_t a, uint64_t b) {
    if (N == 128) wgmma_ss_n128(d, a, b);
    if (N == 96) wgmma_ss_n96(d, a, b);
    if (N == 64) wgmma_ss_n64(d, a, b);
}

#define OFF_R 131072
#define OFF_ONE 229376
#define OFF_BAR 229888
#define OFF_BIAS (OFF_BAR + 672)
#define OFF_G (OFF_BIAS + 1152)
#define SMEM_BYTES (OFF_G + 272)
#define SBD 1024u
#define B_X 0
#define B_F1 416
#define B_E1 112
#define B_KV 160
#define B_F2 224
#define B_E2 256
#define B_T 288
#define B_DONE 352
#define B_G 360
#define B_G2 368
#define B_G3 376
#define B_SF 384
#define B_SF2 408
#define NR 6

#define PF 1
#define PFX 0
#define PACE 0
#define EXP_FKK 4
#define QSCALE 0.36067376022224085f
#define MAGIC 445.41763f
#define NMUFU 4
#define VSTEP ((uint64_t)((long long)32 - ((long long)32 << 16)))

#define KVMASK 0x15ADu
__host__ __device__ constexpr int strm_pos(int pass, int i) {
    if (pass == 1 || pass == 2) return 8 + 8 * pass + i;
    int n = 0;
    for (int p = 0; p < 16; p++)
        if ((int)((KVMASK >> p) & 1) == (pass == 3)) { if (n == i) return p; n++; }
    return 0;
}
__host__ __device__ constexpr uint32_t strm_code(int pass) {
    uint32_t c = 0;
    for (int i = 0; i < 7; i++) c |= (uint32_t)(strm_pos(pass, i + 1) - strm_pos(pass, i)) << (4 * i);
    return c;
}

template <int N, int SUB, int KST, int LBO, int SBO, int SWZ>
__device__ __forceinline__ void gemm_pass(float* acc, uint32_t bar, uint64_t dA, int lane, uint32_t pos, uint32_t code, int barNext, bool waitx) {
    uint32_t prev = 0, slot = pos % NR;
#pragma unroll 1
    for (int i = 0; i < 8; i++) {
        if (waitx) mbar_wait(bar + B_X + 8 * i, 0);
        mbar_wait(bar + B_F1 + 8 * pos, 0);
        const uint64_t dB = mkdesc(SBD + OFF_R, LBO, SBO, SWZ) + slot * 1024;
        wg_fence();
        wgmma_ss<N>(acc, dA, dB);
        wgmma_ss<N>(acc, dA + 2, dB + KST / 16);
        wg_commit();
        wg_wait<1>();
        if (i > 0 && lane < 2) mbar_arrive_cluster(bar + B_E1 + 8 * prev, lane);
        wgmma_ss<N>(acc, dA + 4, dB + SUB / 16);
        wgmma_ss<N>(acc, dA + 6, dB + (SUB + KST) / 16);
        wg_commit();
        prev = slot;
        pos += code & 15;
        slot += code & 15;
        if (slot >= NR) slot -= NR;
        code >>= 4;
        dA += 1024;
    }
    if (barNext) bar_arrive(barNext, 512);
    wg_wait<0>();
    if (lane < 2) mbar_arrive_cluster(bar + B_E1 + 8 * prev, lane);
    pin<N / 2>(acc);
}

__device__ __forceinline__ uint32_t lds32(uint32_t a) { uint32_t v; asm volatile("ld.shared.u32 %0, [%1];" : "=r"(v) : "r"(a)); return v; }
__device__ __forceinline__ bool elect() {
    uint32_t p;
    asm volatile("{\n.reg .pred p;\nelect.sync _|p, 0xffffffff;\nselp.u32 %0, 1, 0, p;\n}" : "=r"(p));
    return p;
}

template <int G0, int G1> __device__ __forceinline__ void gelu_store(const float* acc, uint32_t bias, uint32_t hp) {
#pragma unroll
    for (int G = G0; G < G1; G++) {
        uint32_t o[8];
#pragma unroll
        for (int j = 0; j < 4; j++) {
            float bv[2];
            asm volatile("ld.shared.v2.f32 {%0, %1}, [%2];" : "=f"(bv[0]), "=f"(bv[1]) : "r"(bias + G * 128 + j * 32));
            float y[4];
#pragma unroll
            for (int i = 0; i < 4; i++) {
                const float h = acc[16 * G + 4 * j + i] + bv[i & 1];
                const float z = h * fmaf(h * h, 0.035677408136300125f, 0.7978845608028654f);
                y[i] = fmaf(h, tanhf_(z), h);
            }
            o[j] = pk_bf16(y[0], y[1]);
            o[4 + j] = pk_bf16(y[2], y[3]);
        }
        sts128(hp + G * 32768, o);
        sts128(hp + G * 32768 + 512, o + 4);
    }
}

__device__ __forceinline__ float norm_bound(const float* v, float sc) {
    uint32_t m = 0;
#pragma unroll
    for (int h = 0; h < 4; h++) {
        const float* u = v + 8 * h;
        m = max(m, __float_as_uint(fmaf(u[0], u[0], fmaf(u[1], u[1], fmaf(u[4], u[4], u[5] * u[5])))));
        m = max(m, __float_as_uint(fmaf(u[2], u[2], fmaf(u[3], u[3], fmaf(u[6], u[6], u[7] * u[7])))));
    }
#pragma unroll
    for (int o = 4; o < 32; o <<= 1) m = max(m, __shfl_xor_sync(0xffffffffu, m, o));
    float f = __uint_as_float(m);
    f += __shfl_xor_sync(0xffffffffu, f, 1);
    f += __shfl_xor_sync(0xffffffffu, f, 2);
    return f * sc;
}

__device__ __forceinline__ uint32_t exp2_pair(float a, float b) {
    const uint32_t w = __byte_perm(__float_as_uint(a), __float_as_uint(b), 0x6521);
    uint32_t m, r;
    asm("lop3.b32 %0, %1, 0x007f007f, 0x9f809f80, 0xEA;" : "=r"(m) : "r"(w));
    const uint32_t e = w - m;
    asm("fma.rn.bf16x2 %0, %1, %2, %3;" : "=r"(r) : "r"(w), "r"(m), "r"(e));
    return r;
}

__device__ __forceinline__ void store_o(const float* o, uint4* dst, uint32_t par) {
    const float s0 = __fdividef(1.f, o[8]), s1 = __fdividef(1.f, o[10]);
    const uint32_t d0 = (pk_bf16(o[0] * s0, o[1] * s0) & ~1u) | par;
    asm volatile("{\n.reg .b128 t;\nmov.b128 t, {%0, %1, %2, %3};\nst.relaxed.gpu.global.b128 [%4], t;\n}" ::"r"(d0),
                 "r"(pk_bf16(o[4] * s0, o[5] * s0)), "r"(pk_bf16(o[2] * s1, o[3] * s1)), "r"(pk_bf16(o[6] * s1, o[7] * s1)), "l"(dst) : "memory");
}
__device__ __forceinline__ uint4 load_o(const uint4* src) {
    uint4 v;
    asm volatile("{\n.reg .b128 t;\nld.relaxed.gpu.global.b128 t, [%4];\nmov.b128 {%0, %1, %2, %3}, t;\n}"
                 : "=r"(v.x), "=r"(v.y), "=r"(v.z), "=r"(v.w) : "l"(src) : "memory");
    return v;
}
__device__ __forceinline__ uint32_t bmul2(uint32_t a, uint32_t b) { uint32_t r; asm("mul.rn.bf16x2 %0, %1, %2;" : "=r"(r) : "r"(a), "r"(b)); return r; }
__device__ __forceinline__ void sts32(uint32_t a, uint32_t v) { asm volatile("st.shared.u32 [%0], %1;" ::"r"(a), "r"(v) : "memory"); }
__device__ __forceinline__ void load_q(uint32_t* q, int h, int row, int t) {
    const uint8_t* p = gQ + (size_t)h * (SEQ * 32) + (size_t)row * 32 + t * 4;
    q[0] = __ldcg((const uint32_t*)p); q[1] = __ldcg((const uint32_t*)(p + 256));
    q[2] = __ldcg((const uint32_t*)(p + 16)); q[3] = __ldcg((const uint32_t*)(p + 272));
}

template <int NT>
__device__ __forceinline__ void proj16(float (*c)[8], const __nv_bfloat16* x, const __nv_bfloat16* w, int row0, int rstep, int col, int g, int t) {
#pragma unroll
    for (int i = 0; i < NT; i++)
#pragma unroll
        for (int j = 0; j < 8; j++) c[i][j] = 0.f;
    const unsigned short* wu = (const unsigned short*)w;
#pragma unroll 1
    for (int k = 0; k < DM; k += 16) {
        uint32_t b[4];
#pragma unroll
        for (int j = 0; j < 4; j++) {
            const int kr = k + 2 * t + (j & 1) * 8, cc = col + g + (j >> 1) * 8;
            b[j] = (uint32_t)wu[(size_t)kr * (3 * DM) + cc] | ((uint32_t)wu[(size_t)(kr + 1) * (3 * DM) + cc] << 16);
        }
#pragma unroll
        for (int i = 0; i < NT; i++) {
            const __nv_bfloat16* xp = x + (size_t)(row0 + i * rstep + g) * DM + k + 2 * t;
            const uint32_t a0 = *(const uint32_t*)xp, a1 = *(const uint32_t*)(xp + 8 * DM);
            const uint32_t a2 = *(const uint32_t*)(xp + 8), a3 = *(const uint32_t*)(xp + 8 * DM + 8);
#pragma unroll
            for (int j = 0; j < 2; j++)
                asm volatile("mma.sync.aligned.m16n8k16.row.col.f32.bf16.bf16.f32 {%0,%1,%2,%3}, {%4,%5,%6,%7}, {%8,%9}, {%0,%1,%2,%3};"
                             : "+f"(c[i][4 * j]), "+f"(c[i][4 * j + 1]), "+f"(c[i][4 * j + 2]), "+f"(c[i][4 * j + 3])
                             : "r"(a0), "r"(a1), "r"(a2), "r"(a3), "r"(b[2 * j]), "r"(b[2 * j + 1]));
        }
    }
}

struct Maps { CUtensorMap x, kv, q, f1, f3, h, w2, wo, hs, kvs; };

__global__ void __cluster_dims__(2, 1, 1) __launch_bounds__(640, 1)
fused_kernel(const __grid_constant__ Maps tm, const __nv_bfloat16* __restrict__ x, const __nv_bfloat16* __restrict__ wqkv,
             const __nv_bfloat16* __restrict__ wo, const __nv_bfloat16* __restrict__ w1, const __nv_bfloat16* __restrict__ b1,
             const __nv_bfloat16* __restrict__ w2, const __nv_bfloat16* __restrict__ b2, const __nv_bfloat16* __restrict__ gate,
             __nv_bfloat16* __restrict__ out) {
    const uint32_t sb = smem_u32(smem_raw);
    const uint32_t bar = sb + OFF_BAR;
    const int tid = threadIdx.x, lane = tid & 31;
    const int warp = __shfl_sync(0xffffffffu, tid >> 5, 0);
    const uint32_t rank = cluster_rank();
    const int cl = blockIdx.x >> 1;
    const int nb = cl & 7, mb = (cl >> 3) * 2 + rank;
    const int g = lane >> 2, t = lane & 3;

    const int cb = nb & 3, rb = mb * 2 + (nb >> 2);
    if (tid == 0) TLM(0, 0);
    TL_INIT();
    if (tid == 512) {
        for (int i = 0; i < 8; i++) { mbar_init(bar + B_X + 8 * i, 1); mbar_init(bar + B_KV + 8 * i, 1); mbar_init(bar + B_T + 8 * i, 5); }
        for (int i = 0; i < NR; i++) mbar_init(bar + B_E1 + 8 * i, 16);
        for (int i = 0; i < 4; i++) { mbar_init(bar + B_F2 + 8 * i, 1); mbar_init(bar + B_E2 + 8 * i, 8); }
        asm volatile("fence.mbarrier_init.release.cluster;" ::: "memory");
    } else if (tid == 608) {
        for (int i = 0; i < 32; i++) mbar_init(bar + B_F1 + 8 * i, 1);
        mbar_init(bar + B_DONE, 16);
        mbar_init(bar + B_G, 1);
        for (int i = 0; i < 3; i++) mbar_init(bar + B_SF + 8 * i, i == 1 ? 2 : 1);
        mbar_init(bar + B_SF2, 2);
        mbar_init(bar + B_G3, 1);
        mbar_init(bar + B_G2, 4);
        asm volatile("fence.mbarrier_init.release.cluster;" ::: "memory");
    }
    __syncwarp();
    asm volatile("barrier.cluster.arrive.relaxed.aligned;" ::: "memory");
    if (tid == 512) {
        mbar_expect(bar + B_X, 16384);
        tma2d(sb, &tm.x, 0, mb * 128, bar + B_X);
    } else if (tid == 544) {
        map_prefetch(&tm.kv);
        l2_prefetch((const uint8_t*)wqkv + (size_t)blockIdx.x * 3072, 3072);
        l2_prefetch((const uint8_t*)w1 + (size_t)blockIdx.x * 1792, 1792);
        map_prefetch(&tm.q); map_prefetch(&tm.f1); map_prefetch(&tm.f3);
    }
    if ((sb & 0xFFFFFF) != SBD) __trap();
    __syncwarp();
    asm volatile("barrier.cluster.wait.aligned;" ::: "memory");
    const uint32_t ep = gEpoch[blockIdx.x] + 1;
    if (tid == 0) { TLM(0, 1); TLC(0, 30); }

    if (warp < 16) {
        const int wg = warp >> 2;
        const int h = cl >> 1, qd = (cl & 1) * 2 + rank;
        uint32_t q[4];
        {
            const int w8 = warp & 7;
            const int T = mb * 8 + w8, row0 = T * 16 + g;
            const uint64_t dA0 = mkdesc(SBD + (wg & 1) * 8192, 16, 1024, 1);
            if (wg < 2) {
                float acc[64];
#pragma unroll
                for (int i = 0; i < 64; i++) acc[i] = 0.f;
                gemm_pass<128, 8192, 2048, 4096, 1024, 1>(acc, bar, dA0, lane, strm_pos(3, 0), strm_code(3), 0, true);
                if (tid == 0) TLM(0, 2);
                {
                    const float km = norm_bound(acc, 1.f);
                    float vm = 0.f;
#pragma unroll
                    for (int i = 32; i < 64; i++) vm = fmaxf(vm, fabsf(acc[i]));
                    vm = __uint_as_float(__reduce_max_sync(0xffffffffu, __float_as_uint(vm)));
                    if (lane == 0) { gN[1024 + nb * 128 + T] = km; gN[2048 + nb * 128 + T] = vm; }
                    const uint32_t kp = sb + OFF_R + 12288 + (w8 >> 2) * 1024 + g * 128 + ((((w8 & 3) * 2 + ((t >> 1) ^ (w8 >> 2))) ^ g) << 4) + (t & 1) * 8;
                    uint8_t* vp = gKV + (size_t)(nb * 4) * (SEQ * 64) + 65536 + (((T >> 6) * 16 + 2 * g) * 64 + (T & 63)) * 32 + ((t * 8) ^ ((w8 >> 2) << 4));
                    bar_sync(9, 256);
#pragma unroll
                    for (int hh = 0; hh < 4; hh++) {
                        const float* v = acc + 8 * hh;
                        float p0 = __shfl_up_sync(0xffffffffu, v[2], 4), p1 = __shfl_up_sync(0xffffffffu, v[3], 4);
                        float p2 = __shfl_up_sync(0xffffffffu, v[6], 4), p3 = __shfl_up_sync(0xffffffffu, v[7], 4);
                        if (g == 0) { p0 = p1 = p2 = p3 = 0.f; }
                        sts64(kp + hh * 16384, pk_f16(v[0] - p0, v[1] - p1), pk_f16(v[4] - p2, v[5] - p3));
                        sts64(kp + hh * 16384 + 2048, pk_f16(v[2] - v[0], v[3] - v[1]), pk_f16(v[6] - v[4], v[7] - v[5]));
                        const float* u = acc + 32 + 8 * hh;
                        if (hh < 2) {
                            sts64(kp + (4 + hh) * 16384, pk_bf16(u[0], u[1]), pk_bf16(u[4], u[5]));
                            sts64(kp + (4 + hh) * 16384 + 2048, pk_bf16(u[2], u[3]), pk_bf16(u[6], u[7]));
                        } else {
                            *(uint2*)(vp + (size_t)hh * (SEQ * 64)) = make_uint2(pk_bf16(u[0], u[1]), pk_bf16(u[4], u[5]));
                            *(uint2*)(vp + (size_t)hh * (SEQ * 64) + 2048) = make_uint2(pk_bf16(u[2], u[3]), pk_bf16(u[6], u[7]));
                        }
                    }
                }
                asm volatile("fence.proxy.async.shared::cta;" ::: "memory");
                bar_arrive(10, 288);
                if (tid == 0) TLM(0, 3);
            }
#pragma unroll 1
            for (int p = wg < 2 ? 1 : 0; p < 3; p += 2) {
                float acc[48];
#pragma unroll
                for (int i = 0; i < 48; i++) acc[i] = 0.f;
                pin<48>(acc);
                if (p) bar_sync(5 + p, 512);
                gemm_pass<96, 6144, 1024, 2048, 512, 2>(acc, bar, dA0, lane, p == 0 ? strm_pos(0, 0) : 8 + 8 * p, p == 0 ? strm_code(0) : strm_code(1), p < 2 ? 6 + p : 0, p == 0);
                if ((tid & 255) == 0) TLM(0, 4 + 2 * p);
                const uint32_t hp = sb + OFF_R + 12288 + (wg & 1) * 16384 + ((warp & 3) * 16 + g) * 64 + t * 16;
                const uint32_t bp = sb + OFF_BIAS + p * 384 - 256 + t * 8;
                if (p == 0) {
                    const float qm = norm_bound(acc, QSCALE * QSCALE);
                    if (lane == 0) gN[nb * 128 + T] = qm;
                    uint8_t* qp = gQ + (size_t)(nb * 4) * (SEQ * 32) + (size_t)row0 * 32 + t * 8;
#pragma unroll
                    for (int hh = 0; hh < 4; hh++) {
                        const float* v = acc + 8 * hh;
                        *(uint2*)(qp + hh * (SEQ * 32)) = make_uint2(pk_f16(v[0] * QSCALE, v[1] * QSCALE), pk_f16(v[4] * QSCALE, v[5] * QSCALE));
                        *(uint2*)(qp + hh * (SEQ * 32) + 256) = make_uint2(pk_f16(v[2] * QSCALE, v[3] * QSCALE), pk_f16(v[6] * QSCALE, v[7] * QSCALE));
                    }
                    bar_arrive(12, 288);
                    mbar_wait(bar + B_SF, 0);
                } else {
                    if (p == 2) {
                        mbar_wait(bar + B_G, 0);
                        load_q(q, h, qd * 512 + warp * 16 + g, t);
                    }
                    mbar_wait(bar + B_SF + 8 * p, 0);
                    gelu_store<0, 2>(acc, bp, hp);
                }
                gelu_store<2, 3>(acc, bp, hp);
                asm volatile("fence.proxy.async.shared::cta;" ::: "memory");
                bar_arrive(p == 1 ? 14 : 11, 288);
                if ((tid & 255) == 0) TLM(0, 5 + 2 * p);
            }
            if (wg < 2) {
                mbar_wait(bar + B_G, 0);
                load_q(q, h, qd * 512 + warp * 16 + g, t);
            }
        }
        mbar_wait(bar + B_G3, 0);
        const bool fast = lds32(sb + OFF_G + 256) != 0;
        uint4* const op = gO + ((qd * 8 + wg) * NH + h) * 128 + (tid & 127);
        const uint64_t kd0 = mkdesc(SBD, 16, 256, 3);
        const uint64_t vd0 = mkdesc(SBD + 8192, OFF_ONE - 8192, 256, 3);
        if (fast) {
#pragma unroll 1
            for (int r = 0; r < 2; r++) {
                float o[12];
#pragma unroll
                for (int i = 0; i < 12; i++) o[i] = 0.f;
                uint64_t kd = kd0, vd = vd0;
                uint32_t qn[4];
#pragma unroll 1
                for (int half = 0; half < 2; half++) {
                    float s[32];
#pragma unroll
                    for (int i = 0; i < 32; i++) s[i] = i < 2 * NMUFU ? 0.f : MAGIC;
#pragma unroll 1
                    for (int c = 0; c < 4; c++) {
                        if (r == 0) mbar_wait(bar + B_KV + 8 * (half * 4 + c), 0);
                        if ((tid & 255) == 0 && c == 0) TLM(1, (tid >> 8) * 4 + r * 2 + half);
                        if (half == 1 && c == 3) {
                            if (r == 0) load_q(qn, h, qd * 512 + 256 + warp * 16 + g, t);
                            else if (lane == 0) mbar_arrive(bar + B_DONE);
                        }
#pragma unroll
                        for (int j = 0; j < 4; j++) {
                            uint32_t p[16];
                            wg_fence();
                            wgmma_qk_f16_acc(s, q, kd);
                            wg_commit();
                            wg_wait<0>();
                            pin<32>(s);
#pragma unroll
                            for (int i = 0; i < 16; i++)
                                p[i] = i < NMUFU ? pk_bf16(ex2f(s[2 * i]), ex2f(s[2 * i + 1])) : exp2_pair(s[2 * i], s[2 * i + 1]);
                            pin<16>(p);
                            wg_fence();
#pragma unroll
                            for (int u = 0; u < 4; u++) wgmma_pv(o, p + 4 * u, vd + u * VSTEP);
                            wg_commit();
                            kd += 128;
                            vd += 4 * VSTEP;
                        }
                        kd += 512;
                        vd += 16 * VSTEP;
                    }
                    wg_wait<0>();
                }
                pin<12>(o);
                if ((tid & 127) == 0 && r == 1) TLM(1, 8 + wg);
                store_o(o, op + r * (4 * NH * 128), ep & 1);
#pragma unroll
                for (int i = 0; i < 4; i++) q[i] = qn[i];
            }
            if (tid == 0) { TLM(1, 12); TLC(0, 31); }
        } else {
            for (int c = 0; c < 8; c++) mbar_wait(bar + B_KV + 8 * c, 0);
            {
                float kc[8][8];
                proj16<8>(kc, x, wqkv, warp * 16, 256, DM + h * 16, g, t);
#pragma unroll
                for (int i = 0; i < 8; i++) {
                    const int T = warp + i * 16;
                    const int pos = ((T >> 6) * 16 + 2 * g) * 64 + (T & 63);
                    const uint32_t a = sb + (pos >> 8) * 16384 + (pos & 255) * 32 + t * 4, sw = ((T >> 2) & 1) << 4;
                    asm volatile("st.shared.u32 [%0], %1;" ::"r"(a + sw), "r"(pk_bf16(kc[i][0], kc[i][1])) : "memory");
                    asm volatile("st.shared.u32 [%0], %1;" ::"r"(a + (sw ^ 16)), "r"(pk_bf16(kc[i][4], kc[i][5])) : "memory");
                    asm volatile("st.shared.u32 [%0], %1;" ::"r"(a + 2048 + sw), "r"(pk_bf16(kc[i][2], kc[i][3])) : "memory");
                    asm volatile("st.shared.u32 [%0], %1;" ::"r"(a + 2048 + (sw ^ 16)), "r"(pk_bf16(kc[i][6], kc[i][7])) : "memory");
                }
                asm volatile("fence.proxy.async.shared::cta;" ::: "memory");
                bar_sync(8, 512);
            }
#pragma unroll 1
            for (int r = 0; r < 2; r++) {
                const int row = qd * 512 + r * 256 + warp * 16 + g;
                {
                    float qc[1][8];
                    proj16<1>(qc, x, wqkv, row - g, 0, h * 16, g, t);
#pragma unroll
                    for (int i = 0; i < 4; i++) q[i] = pk_bf16(qc[0][2 * i] * QSCALE, qc[0][2 * i + 1] * QSCALE);
                }
                float o[12];
#pragma unroll
                for (int i = 0; i < 12; i++) o[i] = 0.f;
                float m0 = -INFINITY, m1 = -INFINITY;
#pragma unroll 1
                for (int j = 0; j < 32; j++) {
                    const uint64_t kd = kd0 + (j >> 2) * 1024 + (j & 3) * 128, vd = vd0 + ((j >> 2) * 32 + (j & 3) * 4) * VSTEP;
                    float s[32];
                    uint32_t p[16];
                    wg_fence();
                    wgmma_qk_bf16_zero(s, q, kd);
                    wg_commit();
                    wg_wait<0>();
                    pin<32>(s);
                    pin<12>(o);
                    float n0 = m0, n1 = m1;
#pragma unroll
                    for (int i = 0; i < 8; i++) {
                        n0 = fmaxf(n0, fmaxf(s[4 * i], s[4 * i + 1]));
                        n1 = fmaxf(n1, fmaxf(s[4 * i + 2], s[4 * i + 3]));
                    }
                    n0 = fmaxf(n0, __shfl_xor_sync(0xffffffffu, n0, 1));
                    n1 = fmaxf(n1, __shfl_xor_sync(0xffffffffu, n1, 1));
                    n0 = fmaxf(n0, __shfl_xor_sync(0xffffffffu, n0, 2));
                    n1 = fmaxf(n1, __shfl_xor_sync(0xffffffffu, n1, 2));
                    const float c0 = ex2f(m0 - n0), c1 = ex2f(m1 - n1);
                    m0 = n0;
                    m1 = n1;
#pragma unroll
                    for (int i = 0; i < 3; i++) { o[4 * i] *= c0; o[4 * i + 1] *= c0; o[4 * i + 2] *= c1; o[4 * i + 3] *= c1; }
#pragma unroll
                    for (int i = 0; i < 8; i++) {
                        p[2 * i] = pk_bf16(ex2f(s[4 * i] - m0), ex2f(s[4 * i + 1] - m0));
                        p[2 * i + 1] = pk_bf16(ex2f(s[4 * i + 2] - m1), ex2f(s[4 * i + 3] - m1));
                    }
                    pin<16>(p);
                    pin<12>(o);
                    wg_fence();
#pragma unroll
                    for (int u = 0; u < 4; u++) wgmma_pv(o, p + 4 * u, vd + u * VSTEP);
                    wg_commit();
                }
                wg_wait<0>();
                pin<12>(o);
                if (r == 1 && lane == 0) mbar_arrive(bar + B_DONE);
                store_o(o, op + r * (4 * NH * 128), ep & 1);
            }
        }
        {
            const uint4* src = gO + (rb * NH + wg * 8) * 128 + (tid & 127);
            uint4 v[8];
#pragma unroll
            for (int i = 0; i < 8; i++) v[i] = load_o(src + i * 128);
            mbar_wait(bar + B_DONE, 0);
            mbar_wait(bar + B_G2, 0);
            const int lr = (warp & 3) * 16 + g;
            const uint32_t g0 = lds32(sb + OFF_G + lr * 4), g1 = lds32(sb + OFF_G + lr * 4 + 32);
            const uint32_t a0 = sb + wg * 16384 + lr * 128 + (t >> 1) * 4;
#pragma unroll
            for (int i = 0; i < 8; i++) {
                if ((i & 3) == 0) {
                    int spins = 0;
                    while (__any_sync(0xffffffffu, (((v[i].x ^ ep) | (v[i + 1].x ^ ep) | (v[i + 2].x ^ ep) | (v[i + 3].x ^ ep)) & 1) != 0)) {
                        if (++spins > (1 << 22)) __trap();
#pragma unroll
                        for (int k = i; k < 8; k++)
                            if (((v[k].x ^ ep) & 1) != 0) v[k] = load_o(src + k * 128);
                    }
                }
                const uint32_t a = a0 + (i >> 2) * 8192 + ((((i & 3) * 2 + (t & 1)) ^ g) << 4);
                sts32(a, bmul2(v[i].x, g0));
                sts32(a + 8, bmul2(v[i].y, g0));
                sts32(a + 1024, bmul2(v[i].z, g1));
                sts32(a + 1024 + 8, bmul2(v[i].w, g1));
                if ((i & 3) == 3) {
                    asm volatile("fence.proxy.async.shared::cta;" ::: "memory");
                    __syncwarp();
                    if (lane == 0) mbar_arrive(bar + B_T + 8 * (wg * 2 + (i >> 2)));
                    if ((tid & 127) == 0) TLM(1, 20 + wg * 2 + (i >> 2));
                }
            }
        }
    } else {
        if (warp == 16) {
            if (elect()) {
                int s = 0, par = 1, k0 = rank * 32, k3 = rank * 32;
#pragma unroll 1
                for (int it = 0; it < 32; it++) {
                    const uint32_t fb = bar + B_F1 + 8 * it, dst = sb + OFF_R + s * 16384;
                    mbar_wait(bar + B_E1 + 8 * s, par);
                    if (it < 16 && ((KVMASK >> it) & 1)) {
                        mbar_expect(fb, 16384);
                        tma3d_mc(dst + rank * 8192, &tm.kv, nb * 64, k3, 1, fb);
                        k3 += 64;
                    } else {
                        mbar_expect(fb, 12288);
                        if (it < 16) {
                            tma3d_mc(dst + rank * 6144, &tm.q, 0, k0, nb * 2, fb);
                            tma3d_mc(dst + rank * 6144 + 4096, &tm.f1, 0, k0, nb * 7, fb);
                        } else {
                            tma3d_mc(dst + rank * 6144, &tm.f3, 0, k0 & 511, nb * 7 + (it < 24 ? 1 : 4), fb);
                        }
                        k0 += 64;
                    }
                    for (int c = it; c >= 1 && c < 8 && (c == it || it == NR - 1) && it < NR; c++) {
                        mbar_expect(bar + B_X + 8 * c, 16384);
                        tma2d(sb + c * 16384, &tm.x, c * 64, mb * 128, bar + B_X + 8 * c);
                    }
                    if (++s == NR) { s = 0; par ^= 1; }
                }
                const int h = cl >> 1;
                mbar_wait(bar + B_G, 0);
                asm volatile("fence.proxy.async.global;" ::: "memory");
                TLM(0, 10);
#pragma unroll 1
                for (int c = 0; c < 8; c++) {
                    if (c >= 8 - NR) {
                        mbar_wait(bar + B_E1 + 8 * s, par);
                        if (++s == NR) { s = 0; par ^= 1; }
                    }
                    mbar_expect(bar + B_KV + 8 * c, 16384);
                    bulk_mc(sb + c * 16384 + rank * 8192, gKV + (size_t)h * (SEQ * 64) + rank * 65536 + c * 8192, 8192, bar + B_KV + 8 * c);
                }
                mbar_wait(bar + B_SF2, 0);
#pragma unroll 1
                for (s = 0; s < 4; s++) {
                    mbar_expect(bar + B_F2 + 8 * s, 24576);
                    tma5d_mc(sb + OFF_R + s * 24576 + 8192 + rank * 8192, &tm.w2, cb * 128 + rank * 64, s * 2, bar + B_F2 + 8 * s);
                }
                cnt_wait(gCntH + mb * 32, ep * 8);
                asm volatile("fence.proxy.async.global;" ::: "memory");
                TLM(1, 13);
#pragma unroll 1
                for (s = 0; s < 4; s++) tma2d(sb + OFF_R + s * 24576, &tm.h, s * 64, rb * 64, bar + B_F2 + 8 * s);
            }
        } else if (warp == 17) {
            {
                uint32_t bv[4], b2v[2];
#pragma unroll
                for (int i = 0; i < 4; i++) bv[i] = lane + 32 * i < 112 ? *(const uint32_t*)(b1 + nb * 224 + (lane + 32 * i) * 2) : 0;
#pragma unroll
                for (int i = 0; i < 2; i++) b2v[i] = *(const uint32_t*)(b2 + cb * 128 + (lane + 32 * i) * 2);
#pragma unroll
                for (int i = 0; i < 4; i++) {
                    sts32(sb + OFF_ONE + (lane + 32 * i) * 4, 0x3f803f80u);
                    if (lane + 32 * i < 112) sts64(sb + OFF_BIAS + (lane + 32 * i) * 8, bv[i] << 16, bv[i] & 0xffff0000u);
                }
#pragma unroll
                for (int i = 0; i < 2; i++) sts32(sb + OFF_BIAS + 896 + (lane + 32 * i) * 4, b2v[i]);
                asm volatile("fence.proxy.async.shared::cta;" ::: "memory");
            }
            mbar_wait(bar + B_X + 8 * PFX, 0);
            if (lane == 0) {
                l2_prefetch((const uint8_t*)wqkv + 128 * 3072 + (size_t)blockIdx.x * 9216, 9216);
                l2_prefetch((const uint8_t*)w1 + (size_t)blockIdx.x * 14336, 14336);
            }
            mbar_wait(bar + B_X + 8 * 7, 0);
            if (lane == 0) {
                l2_prefetch((const uint8_t*)w2 + (size_t)blockIdx.x * 14336, 14336);
                l2_prefetch((const uint8_t*)wo + (size_t)blockIdx.x * 4096, 4096);
                map_prefetch(&tm.h); map_prefetch(&tm.w2); map_prefetch(&tm.wo); map_prefetch(&tm.hs); map_prefetch(&tm.kvs);
                TLM(0, 11);
            }
            bar_sync(10, 288);
            if (lane == 0) {
#pragma unroll 1
                for (int b = 5; b >= 0; b--) {
                    tma5d_st(&tm.kvs, sb + OFF_R + 12288 + b * 16384, (mb >> 3) * 8, (mb & 7) * 2, nb * 8 + (b < 4 ? 2 * b : 2 * b - 7));
                    asm volatile("cp.async.bulk.commit_group;\ncp.async.bulk.wait_group.read %0;" ::"n"(PACE) : "memory");
                    if (b == 4 - PACE) mbar_arrive(bar + B_SF);
                }
                asm volatile("cp.async.bulk.wait_group.read 0;" ::: "memory");
                mbar_arrive(bar + B_SF + 8);
            }
            __syncwarp();
            bar_sync(12, 288);
            if (lane == 0) {
                asm volatile("cp.async.bulk.wait_group 0;\nfence.proxy.async.global;" ::: "memory");
                cnt_add(gCntQ + nb * 32);
                TLM(0, 13);
            }
        } else {
            {
                const int r0 = mb * 128 + nb * 16 + (warp - 18) * 8;
                uint4 xv[16];
#pragma unroll
                for (int i = 0; i < 16; i++) xv[i] = *(const uint4*)(x + (size_t)(r0 + (i >> 1)) * DM + (i & 1) * 256 + lane * 8);
                const uint4 ga = *(const uint4*)(gate + lane * 8), gb = *(const uint4*)(gate + 256 + lane * 8);
                float z[8];
#pragma unroll
                for (int r = 0; r < 8; r++) z[r] = dot8(xv[2 * r], ga) + dot8(xv[2 * r + 1], gb);
#pragma unroll
                for (int w = 4; w >= 1; w >>= 1)
#pragma unroll
                    for (int r = 0; r < w; r++) {
                        const bool up = lane & w;
                        z[r] = (up ? z[r + w] : z[r]) + __shfl_xor_sync(0xffffffffu, up ? z[r] : z[r + w], w);
                    }
                z[0] += __shfl_xor_sync(0xffffffffu, z[0], 8);
                z[0] += __shfl_xor_sync(0xffffffffu, z[0], 16);
                if (lane < 8) gG[r0 + lane] = 1.f / (1.f + __expf(-z[0]));
                if (tid == 576) TLM(0, 12);
            }
            if (warp == 19) {
#pragma unroll 1
                for (int e = 0; e < 3; e++) {
                    bar_sync(e == 1 ? 14 : 11, 288);
                    if (lane == 0) {
#pragma unroll 1
                        for (int b = e == 0 ? 4 : 0; b < 6; b++) {
                            tma3d_st(&tm.hs, sb + OFF_R + 12288 + b * 16384, 0, mb * 128 + (b & 1) * 64, nb * 7 + e * 3 - 2 + (b >> 1));
                            asm volatile("cp.async.bulk.commit_group;\ncp.async.bulk.wait_group.read %0;" ::"n"(PACE) : "memory");
                        }
                        asm volatile("cp.async.bulk.wait_group.read 0;" ::: "memory");
                        if (e < 2) mbar_arrive(bar + B_SF + 8 + 8 * e);
                        else { mbar_arrive_cluster(bar + B_SF2, 0); mbar_arrive_cluster(bar + B_SF2, 1); }
                    }
                    __syncwarp();
                }
                bar_sync(13, 64);
                if (lane == 0) {
                    asm volatile("cp.async.bulk.wait_group 0;\nfence.proxy.async.global;" ::: "memory");
                    cnt_add(gCntH + mb * 32);
                    TLM(0, 15);
                }
            } else {
                bar_arrive(13, 64);
                const int h = cl >> 1, qd = (cl & 1) * 2 + rank;
                if (lane == 0) {
                    cnt_wait(gCntQ + (h >> 2) * 32, ep * 16);
                    mbar_arrive(bar + B_G);
                    TLM(0, 14);
                }
                __syncwarp();
            const int hb = h >> 2;
            const uint4 kq = __ldcg((const uint4*)(gN + 1024 + hb * 128 + lane * 4));
            const uint4 vq = __ldcg((const uint4*)(gN + 2048 + hb * 128 + lane * 4));
            const float qq = ldcg_f(gN + hb * 128 + qd * 32 + lane);
            const float kf = __uint_as_float(__reduce_max_sync(0xffffffffu, max(max(kq.x, kq.y), max(kq.z, kq.w))));
            const float vf = __uint_as_float(__reduce_max_sync(0xffffffffu, max(max(vq.x, vq.y), max(vq.z, vq.w))));
            const float qf = __uint_as_float(__reduce_max_sync(0xffffffffu, __float_as_uint(qq)));
            if (lane == 0) {
                sts32(sb + OFF_G + 256, (kf <= 1.0e6f) && (qf <= 1.0e6f) && (kf * qf <= 3400.f) && (vf <= 1.0e12f));
                mbar_arrive(bar + B_G3);
            }
            }
        }
        __syncwarp();
        float acc[64];
#pragma unroll
        for (int i = 0; i < 64; i++) acc[i] = 0.f;
#pragma unroll 1
        for (int io = 0; io < 7; io++) {
#pragma unroll
            for (int s = 0; s < 4; s++) {
                const int it = io * 4 + s;
                mbar_wait(bar + B_F2 + 8 * s, io & 1);
                if (tid == 512 && s == 0 && (io == 0 || io == 4)) TLM(1, 14 + io / 4);
                const uint64_t dA = mkdesc(SBD + OFF_R + s * 24576, 16, 1024, 1);
                const uint64_t dB = mkdesc(SBD + OFF_R + s * 24576 + 8192, 8192, 1024, 1);
                wg_fence();
#pragma unroll
                for (int kk = 0; kk < EXP_FKK; kk++) wgmma_ss_n128(acc, dA + kk * 2, dB + kk * 128);
                wg_commit();
                if (warp < 18 && it >= 2 && it < 26) {
                    const int s2 = (s + 2) & 3;
                    mbar_wait(bar + B_E2 + 8 * s2, (io - (s < 2)) & 1);
                    if (elect()) {
                        if (warp == 16) {
                            mbar_expect(bar + B_F2 + 8 * s2, 24576);
                            tma5d_mc(sb + OFF_R + s2 * 24576 + 8192 + rank * 8192, &tm.w2, cb * 128 + rank * 64, it * 2 + 4, bar + B_F2 + 8 * s2);
                        } else {
                            asm volatile("fence.proxy.async.global;" ::: "memory");
                            tma2d(sb + OFF_R + s2 * 24576, &tm.h, it * 64 + 128, rb * 64, bar + B_F2 + 8 * s2);
                        }
                    }
                    __syncwarp();
                }
                wg_wait<1>();
                if (it >= 1 && lane < 2) mbar_arrive_cluster(bar + B_E2 + 8 * ((s + 3) & 3), lane);
            }
        }
        wg_wait<0>();
        if (lane < 2) mbar_arrive_cluster(bar + B_E2 + 8 * 3, lane);
        pin<64>(acc);
        if (warp == 16) {
            if (lane == 0) TLM(1, 16);
            for (int s = 0; s < 4; s++) mbar_wait(bar + B_E2 + 8 * s, 0);
            if (elect()) {
#pragma unroll
                for (int i = 0; i < 8; i++) mbar_expect(bar + B_T + 8 * i, 16384);
#pragma unroll
                for (int i = 0; i < 6; i++) tma2d_mc(sb + OFF_R + i * 16384 + rank * 8192, &tm.wo, cb * 128 + rank * 64, i * 64, bar + B_T + 8 * i);
            }
            __syncwarp();
        }
        {
            const int lr = (warp - 16) * 16 + g;
            const uint32_t pa = pk_bf16(ldcg_f(gG + rb * 64 + lr), ldcg_f(gG + rb * 64 + lr + 8));
            if (t == 0) {
                sts32(sb + OFF_G + lr * 4, __byte_perm(pa, pa, 0x1010));
                sts32(sb + OFF_G + lr * 4 + 32, __byte_perm(pa, pa, 0x3232));
            }
            __syncwarp();
            if (lane == 0) mbar_arrive(bar + B_G2);
            const float ga = bf_lo(pa), gb = bf_hi(pa);
            const float g0 = 1.f - ga, g1 = 1.f - gb;
#pragma unroll
            for (int j = 0; j < 16; j++) {
                const uint32_t bv = lds32(sb + OFF_BIAS + 896 + j * 16 + t * 4);
                acc[4 * j] = fmaf(acc[4 * j], 0.5f, bf_lo(bv)) * g0;
                acc[4 * j + 1] = fmaf(acc[4 * j + 1], 0.5f, bf_hi(bv)) * g0;
                acc[4 * j + 2] = fmaf(acc[4 * j + 2], 0.5f, bf_lo(bv)) * g1;
                acc[4 * j + 3] = fmaf(acc[4 * j + 3], 0.5f, bf_hi(bv)) * g1;
            }
            pin<64>(acc);
        }
        if (warp == 17) {
            mbar_wait(bar + B_DONE, 0);
            if (elect()) {
#pragma unroll
                for (int i = 0; i < 4; i++)
                    tma2d(sb + 65536 + i * 8192, &tm.wo, cb * 128 + (i & 1) * 64, (6 + (i >> 1)) * 64, bar + B_T + 8 * (6 + (i >> 1)));
            }
            __syncwarp();
        }
        if (tid == 512) TLM(1, 17);
#pragma unroll
        for (int i = 0; i < 8; i++) {
            mbar_wait(bar + B_T + 8 * i, 0);
            const uint64_t dA = mkdesc(SBD + i * 8192, 16, 1024, 1);
            const uint64_t dB = mkdesc(i < 6 ? SBD + OFF_R + i * 16384 : SBD + 65536 + (i - 6) * 16384, 8192, 1024, 1);
            wg_fence();
#pragma unroll
            for (int kk = 0; kk < 4; kk++) wgmma_ss_n128(acc, dA + kk * 2, dB + kk * 128);
            wg_commit();
        }
        wg_wait<0>();
        pin<64>(acc);
        if (tid == 512) TLM(1, 18);
        {
            const uint32_t st = sb + 98304 + (warp - 16) * 4352;
            const uint32_t wa = st + (lane & 15) * 272 + (lane >> 4) * 16;
#pragma unroll
            for (int j = 0; j < 8; j++)
                asm volatile("stmatrix.sync.aligned.m8n8.x4.shared.b16 [%0], {%1, %2, %3, %4};" ::"r"(wa + j * 32),
                             "r"(pk_bf16(acc[8 * j], acc[8 * j + 1])), "r"(pk_bf16(acc[8 * j + 2], acc[8 * j + 3])),
                             "r"(pk_bf16(acc[8 * j + 4], acc[8 * j + 5])), "r"(pk_bf16(acc[8 * j + 6], acc[8 * j + 7])) : "memory");
            __syncwarp();
            __nv_bfloat16* op = out + (size_t)(rb * 64 + (warp - 16) * 16 + (lane >> 4)) * DM + cb * 128 + (lane & 15) * 8;
#pragma unroll
            for (int j = 0; j < 8; j++) {
                uint4 v;
                asm volatile("ld.shared.v4.u32 {%0, %1, %2, %3}, [%4];" : "=r"(v.x), "=r"(v.y), "=r"(v.z), "=r"(v.w)
                             : "r"(st + (2 * j + (lane >> 4)) * 272 + (lane & 15) * 16));
                *(uint4*)(op + (size_t)j * 2 * DM) = v;
            }
        }
        if (tid == 512) { gEpoch[blockIdx.x] = ep; TLM(1, 19); }
        TL_DUMP();
    }
}

typedef CUresult (*EncodeFn)(CUtensorMap*, CUtensorMapDataType, cuuint32_t, void*, const cuuint64_t*, const cuuint64_t*, const cuuint32_t*,
                             const cuuint32_t*, CUtensorMapInterleave, CUtensorMapSwizzle, CUtensorMapL2promotion, CUtensorMapFloatOOBfill);

static void make_map(EncodeFn enc, CUtensorMap* m, const void* p, int rank, const cuuint64_t* dims, const cuuint64_t* strides,
                     const cuuint32_t* box, CUtensorMapSwizzle swz) {
    const cuuint32_t es[5] = {1, 1, 1, 1, 1};
    enc(m, CU_TENSOR_MAP_DATA_TYPE_BFLOAT16, rank, (void*)p, dims, strides, box, es, CU_TENSOR_MAP_INTERLEAVE_NONE, swz,
        CU_TENSOR_MAP_L2_PROMOTION_L2_128B, CU_TENSOR_MAP_FLOAT_OOB_FILL_NONE);
}

extern "C" void kernel_launch(void* const* d_in, const int* in_sizes, int n_in, void* d_out, int out_size) {
    const __nv_bfloat16* x = (const __nv_bfloat16*)d_in[0];
    const __nv_bfloat16* wqkv = (const __nv_bfloat16*)d_in[1];
    const __nv_bfloat16* wo = (const __nv_bfloat16*)d_in[2];
    const __nv_bfloat16* w1 = (const __nv_bfloat16*)d_in[4];
    const __nv_bfloat16* b1 = (const __nv_bfloat16*)d_in[5];
    const __nv_bfloat16* w2 = (const __nv_bfloat16*)d_in[6];
    const __nv_bfloat16* b2 = (const __nv_bfloat16*)d_in[7];
    const __nv_bfloat16* gate = (const __nv_bfloat16*)d_in[8];

    void* fp = nullptr;
    cudaDriverEntryPointQueryResult qr;
    cudaGetDriverEntryPoint("cuTensorMapEncodeTiled", &fp, cudaEnableDefault, &qr);
    EncodeFn enc = (EncodeFn)fp;
    void *pH, *pKV;
    cudaGetSymbolAddress(&pH, gH);
    cudaGetSymbolAddress(&pKV, gKV);

    Maps tm;
    const CUtensorMapSwizzle S128 = CU_TENSOR_MAP_SWIZZLE_128B, S64 = CU_TENSOR_MAP_SWIZZLE_64B;
    { cuuint64_t d[2] = {DM, SEQ}, s[1] = {DM * 2}; cuuint32_t b[2] = {64, 128}; make_map(enc, &tm.x, x, 2, d, s, b, S128); }
    { cuuint64_t d[3] = {DM, DM, 3}, s[2] = {3 * DM * 2, DM * 2}; cuuint32_t b[3] = {64, 32, 2}; make_map(enc, &tm.kv, wqkv, 3, d, s, b, S128); }
    { cuuint64_t d[3] = {32, DM, 3 * DM / 32}, s[2] = {3 * DM * 2, 64}; cuuint32_t b[3] = {32, 32, 2}; make_map(enc, &tm.q, wqkv, 3, d, s, b, S64); }
    { cuuint64_t d[3] = {32, DM, FF / 32}, s[2] = {FF * 2, 64}; cuuint32_t b[3] = {32, 32, 1}; make_map(enc, &tm.f1, w1, 3, d, s, b, S64); }
    { cuuint64_t d[3] = {32, DM, FF / 32}, s[2] = {FF * 2, 64}; cuuint32_t b[3] = {32, 32, 3}; make_map(enc, &tm.f3, w1, 3, d, s, b, S64); }
    { cuuint64_t d[2] = {FF, SEQ}, s[1] = {FF * 2}; cuuint32_t b[2] = {64, 64}; make_map(enc, &tm.h, pH, 2, d, s, b, S128); }
    { cuuint64_t d[5] = {DM, 2, 4, 4, FF / 32}, s[4] = {1024, 8 * 1024, 2 * 1024, 32 * 1024}; cuuint32_t b[5] = {64, 2, 4, 4, 2};
      make_map(enc, &tm.w2, w2, 5, d, s, b, S128); }
    { cuuint64_t d[2] = {DM, DM}, s[1] = {DM * 2}; cuuint32_t b[2] = {64, 64}; make_map(enc, &tm.wo, wo, 2, d, s, b, S128); }

    { cuuint64_t d[3] = {32, SEQ, FF / 32}, s[2] = {FF * 2, 64}; cuuint32_t b[3] = {32, 64, 1}; make_map(enc, &tm.hs, pH, 3, d, s, b, CU_TENSOR_MAP_SWIZZLE_NONE); }
    { cuuint64_t d[5] = {64, 16, 16, 2, 2 * NH}, s[4] = {4096, 128, 2048, 65536}; cuuint32_t b[5] = {64, 8, 2, 2, 1};
      make_map(enc, &tm.kvs, pKV, 5, d, s, b, S128); }
    cudaFuncSetAttribute(fused_kernel, cudaFuncAttributeMaxDynamicSharedMemorySize, TL_SMEM);
    fused_kernel<<<128, 640, TL_SMEM, cudaStreamPerThread>>>(tm, x, wqkv, wo, w1, b1, w2, b2, gate, (__nv_bfloat16*)d_out);
}
```

```cpp
#include <cuda_runtime.h>
#include <cuda_bf16.h>
#include <cuda_fp16.h>
#include <cuda.h>
#include <stdint.h>

#define SEQ 2048
#define DM 512
#define FF 1792
#define NH 32

__device__ __align__(1024) uint8_t gQ[NH * SEQ * 32];
__device__ __align__(1024) uint8_t gKV[NH * SEQ * 64];
__device__ __align__(1024) __nv_bfloat16 gH[SEQ * FF];
__device__ __align__(1024) uint4 gO[32 * NH * 128];
__device__ float gG[SEQ];
__device__ float gN[3 * 8 * 128];
__device__ unsigned int gCntQ[8 * 32];
__device__ unsigned int gCntH[32 * 32];
__device__ unsigned int gEpoch[128];

__device__ __forceinline__ uint32_t smem_u32(const void* p) { return (uint32_t)__cvta_generic_to_shared(p); }
__device__ __forceinline__ void mbar_init(uint32_t a, uint32_t c) { asm volatile("mbarrier.init.shared::cta.b64 [%0], %1;" ::"r"(a), "r"(c)); }
__device__ __forceinline__ void mbar_expect(uint32_t a, uint32_t b) { asm volatile("mbarrier.arrive.expect_tx.shared::cta.b64 _, [%0], %1;" ::"r"(a), "r"(b) : "memory"); }
__device__ __forceinline__ void mbar_arrive(uint32_t a) { asm volatile("mbarrier.arrive.shared::cta.b64 _, [%0];" ::"r"(a) : "memory"); }
__device__ __forceinline__ void mbar_wait(uint32_t a, uint32_t ph) {
    asm volatile("{\n.reg .pred p;\n.reg .u32 n;\nmov.u32 n, 0;\nW_%=:\nmbarrier.try_wait.parity.shared::cta.b64 p, [%0], %1;\n@p bra D_%=;\n"
                 "add.u32 n, n, 1;\nsetp.lt.u32 p, n, 0x400000;\n@p bra W_%=;\ntrap;\nD_%=:\n}" ::"r"(a), "r"(ph) : "memory");
}
__device__ __forceinline__ void mbar_arrive_cluster(uint32_t a, uint32_t cta) {
    asm volatile("{\n.reg .b32 r;\nmapa.shared::cluster.u32 r, %0, %1;\nmbarrier.arrive.shared::cluster.b64 _, [r];\n}" ::"r"(a), "r"(cta) : "memory");
}
__device__ __forceinline__ void bar_sync(int id, int n) { asm volatile("bar.sync %0, %1;" ::"r"(id), "r"(n) : "memory"); }
__device__ __forceinline__ void bar_arrive(int id, int n) { asm volatile("bar.arrive %0, %1;" ::"r"(id), "r"(n) : "memory"); }
__device__ __forceinline__ uint32_t cluster_rank() { uint32_t r; asm("mov.u32 %0, %%cluster_ctarank;" : "=r"(r)); return r; }
__device__ __forceinline__ void cnt_add(unsigned int* c) { asm volatile("red.release.gpu.global.add.u32 [%0], 1;" ::"l"(c) : "memory"); }
__device__ __forceinline__ void cnt_wait(const unsigned int* c, uint32_t target) {
    uint32_t v;
    int spins = 0;
    while (true) {
        asm volatile("ld.acquire.gpu.global.u32 %0, [%1];" : "=r"(v) : "l"(c) : "memory");
        if ((int)(v - target) >= 0) break;
        if (++spins > (1 << 22)) __trap();
        __nanosleep(40);
    }
}
__device__ __forceinline__ void tma2d(uint32_t dst, const CUtensorMap* m, int c0, int c1, uint32_t bar) {
    asm volatile("cp.async.bulk.tensor.2d.shared::cluster.global.mbarrier::complete_tx::bytes [%0], [%1, {%3, %4}], [%2];"
                 ::"r"(dst), "l"(m), "r"(bar), "r"(c0), "r"(c1) : "memory");
}
__device__ __forceinline__ void tma2d_mc(uint32_t dst, const CUtensorMap* m, int c0, int c1, uint32_t bar) {
    asm volatile("cp.async.bulk.tensor.2d.shared::cluster.global.mbarrier::complete_tx::bytes.multicast::cluster [%0], [%1, {%3, %4}], [%2], %5;"
                 ::"r"(dst), "l"(m), "r"(bar), "r"(c0), "r"(c1), "h"((uint16_t)3) : "memory");
}
__device__ __forceinline__ void tma3d_mc(uint32_t dst, const CUtensorMap* m, int c0, int c1, int c2, uint32_t bar) {
    asm volatile("cp.async.bulk.tensor.3d.shared::cluster.global.mbarrier::complete_tx::bytes.multicast::cluster [%0], [%1, {%3, %4, %5}], [%2], %6;"
                 ::"r"(dst), "l"(m), "r"(bar), "r"(c0), "r"(c1), "r"(c2), "h"((uint16_t)3) : "memory");
}
__device__ __forceinline__ void tma5d_mc(uint32_t dst, const CUtensorMap* m, int c0, int c4, uint32_t bar) {
    asm volatile("cp.async.bulk.tensor.5d.shared::cluster.global.mbarrier::complete_tx::bytes.multicast::cluster [%0], [%1, {%3, %5, %5, %5, %4}], [%2], %6;"
                 ::"r"(dst), "l"(m), "r"(bar), "r"(c0), "r"(c4), "r"(0), "h"((uint16_t)3) : "memory");
}
__device__ __forceinline__ void bulk_mc(uint32_t dst, const void* src, uint32_t bytes, uint32_t bar) {
    asm volatile("cp.async.bulk.shared::cluster.global.mbarrier::complete_tx::bytes.multicast::cluster [%0], [%1], %2, [%3], %4;"
                 ::"r"(dst), "l"(src), "r"(bytes), "r"(bar), "h"((uint16_t)3) : "memory");
}
__device__ __forceinline__ void tma3d_st(const CUtensorMap* m, uint32_t src, int c0, int c1, int c2) {
    asm volatile("cp.async.bulk.tensor.3d.global.shared::cta.bulk_group [%0, {%2, %3, %4}], [%1];" ::"l"(m), "r"(src), "r"(c0), "r"(c1), "r"(c2) : "memory");
}
__device__ __forceinline__ void tma5d_st(const CUtensorMap* m, uint32_t src, int c1, int c2, int c4) {
    asm volatile("cp.async.bulk.tensor.5d.global.shared::cta.bulk_group [%0, {%5, %2, %3, %5, %4}], [%1];"
                 ::"l"(m), "r"(src), "r"(c1), "r"(c2), "r"(c4), "r"(0) : "memory");
}
__device__ __forceinline__ void bulk_st(void* dst, uint32_t src, uint32_t bytes) {
    asm volatile("cp.async.bulk.global.shared::cta.bulk_group [%0], [%1], %2;" ::"l"(dst), "r"(src), "r"(bytes) : "memory");
}
__device__ __forceinline__ void sts64(uint32_t a, uint32_t x, uint32_t y) { asm volatile("st.shared.v2.u32 [%0], {%1, %2};" ::"r"(a), "r"(x), "r"(y) : "memory"); }
__device__ __forceinline__ void sts128(uint32_t a, const uint32_t* v) {
    asm volatile("st.shared.v4.u32 [%0], {%1, %2, %3, %4};" ::"r"(a), "r"(v[0]), "r"(v[1]), "r"(v[2]), "r"(v[3]) : "memory");
}
__device__ __forceinline__ void l2_prefetch(const void* src, uint32_t bytes) {
    asm volatile("cp.async.bulk.prefetch.L2.global [%0], %1;" ::"l"(src), "r"(bytes) : "memory");
}
__device__ __forceinline__ void map_prefetch(const CUtensorMap* m) { asm volatile("prefetch.tensormap [%0];" ::"l"(m) : "memory"); }
__device__ __forceinline__ void wg_fence() { asm volatile("wgmma.fence.sync.aligned;" ::: "memory"); }
__device__ __forceinline__ void wg_commit() { asm volatile("wgmma.commit_group.sync.aligned;" ::: "memory"); }
template <int N> __device__ __forceinline__ void wg_wait() { asm volatile("wgmma.wait_group.sync.aligned %0;" ::"n"(N) : "memory"); }
template <int N> __device__ __forceinline__ void pin(float* s) {
#pragma unroll
    for (int i = 0; i < N; i++) asm volatile("" : "+f"(s[i])::"memory");
}
template <int N> __device__ __forceinline__ void pin(uint32_t* s) {
#pragma unroll
    for (int i = 0; i < N; i++) asm volatile("" : "+r"(s[i])::"memory");
}
__device__ __forceinline__ uint64_t mkdesc(uint32_t addr, uint32_t lbo, uint32_t sbo, uint32_t swz) {
    return (uint64_t)((addr & 0x3FFFF) >> 4) | ((uint64_t)(lbo >> 4) << 16) | ((uint64_t)(sbo >> 4) << 32) | ((uint64_t)swz << 62);
}
__device__ __forceinline__ float ex2f(float x) { float y; asm("ex2.approx.ftz.f32 %0, %1;" : "=f"(y) : "f"(x)); return y; }
__device__ __forceinline__ float tanhf_(float x) { float y; asm("tanh.approx.f32 %0, %1;" : "=f"(y) : "f"(x)); return y; }
__device__ __forceinline__ uint32_t pk_bf16(float lo, float hi) { uint32_t r; asm("cvt.rn.bf16x2.f32 %0, %1, %2;" : "=r"(r) : "f"(hi), "f"(lo)); return r; }
__device__ __forceinline__ uint32_t pk_f16(float lo, float hi) { uint32_t r; asm("cvt.rn.f16x2.f32 %0, %1, %2;" : "=r"(r) : "f"(hi), "f"(lo)); return r; }
__device__ __forceinline__ float bf_lo(uint32_t v) { return __uint_as_float(v << 16); }
__device__ __forceinline__ float bf_hi(uint32_t v) { return __uint_as_float(v & 0xffff0000u); }
__device__ __forceinline__ float dot8(const uint4& a, const uint4& b) {
    return fmaf(bf_lo(a.x), bf_lo(b.x), fmaf(bf_hi(a.x), bf_hi(b.x), fmaf(bf_lo(a.y), bf_lo(b.y), bf_hi(a.y) * bf_hi(b.y)))) +
           fmaf(bf_lo(a.z), bf_lo(b.z), fmaf(bf_hi(a.z), bf_hi(b.z), fmaf(bf_lo(a.w), bf_lo(b.w), bf_hi(a.w) * bf_hi(b.w))));
}
__device__ __forceinline__ float ldcg_f(const float* p) { return __ldcg(p); }

extern __shared__ __align__(1024) uint8_t smem_raw[];
#define TLM(k, slot) do {} while (0)
#define TLC(k, slot) do {} while (0)
#define TL_INIT() do {} while (0)
#define TL_DUMP() do {} while (0)
#define TL_SMEM SMEM_BYTES

__device__ __forceinline__ void wgmma_ss_n128(float* d, uint64_t da, uint64_t db) {
    asm volatile("wgmma.mma_async.sync.aligned.m64n128k16.f32.bf16.bf16 {"
        "%0, %1, %2, %3, %4, %5, %6, %7, %8, %9, %10, %11, %12, %13, %14, %15,"
        "%16, %17, %18, %19, %20, %21, %22, %23, %24, %25, %26, %27, %28, %29, %30, %31,"
        "%32, %33, %34, %35, %36, %37, %38, %39, %40, %41, %42, %43, %44, %45, %46, %47,"
        "%48, %49, %50, %51, %52, %53, %54, %55, %56, %57, %58, %59, %60, %61, %62, %63}, %64, %65, 1, 1, 1, 0, 1;\n"
        :
        "+f"(d[0]), "+f"(d[1]), "+f"(d[2]), "+f"(d[3]), "+f"(d[4]), "+f"(d[5]), "+f"(d[6]), "+f"(d[7]),
        "+f"(d[8]), "+f"(d[9]), "+f"(d[10]), "+f"(d[11]), "+f"(d[12]), "+f"(d[13]), "+f"(d[14]), "+f"(d[15]),
        "+f"(d[16]), "+f"(d[17]), "+f"(d[18]), "+f"(d[19]), "+f"(d[20]), "+f"(d[21]), "+f"(d[22]), "+f"(d[23]),
        "+f"(d[24]), "+f"(d[25]), "+f"(d[26]), "+f"(d[27]), "+f"(d[28]), "+f"(d[29]), "+f"(d[30]), "+f"(d[31]),
        "+f"(d[32]), "+f"(d[33]), "+f"(d[34]), "+f"(d[35]), "+f"(d[36]), "+f"(d[37]), "+f"(d[38]), "+f"(d[39]),
        "+f"(d[40]), "+f"(d[41]), "+f"(d[42]), "+f"(d[43]), "+f"(d[44]), "+f"(d[45]), "+f"(d[46]), "+f"(d[47]),
        "+f"(d[48]), "+f"(d[49]), "+f"(d[50]), "+f"(d[51]), "+f"(d[52]), "+f"(d[53]), "+f"(d[54]), "+f"(d[55]),
        "+f"(d[56]), "+f"(d[57]), "+f"(d[58]), "+f"(d[59]), "+f"(d[60]), "+f"(d[61]), "+f"(d[62]), "+f"(d[63])
        : "l"(da), "l"(db));
}
__device__ __forceinline__ void wgmma_ss_n96(float* d, uint64_t da, uint64_t db) {
    asm volatile("wgmma.mma_async.sync.aligned.m64n96k16.f32.bf16.bf16 {"
        "%0, %1, %2, %3, %4, %5, %6, %7, %8, %9, %10, %11, %12, %13, %14, %15,"
        "%16, %17, %18, %19, %20, %21, %22, %23, %24, %25, %26, %27, %28, %29, %30, %31,"
        "%32, %33, %34, %35, %36, %37, %38, %39, %40, %41, %42, %43, %44, %45, %46, %47}, %48, %49, 1, 1, 1, 0, 1;\n"
        :
        "+f"(d[0]), "+f"(d[1]), "+f"(d[2]), "+f"(d[3]), "+f"(d[4]), "+f"(d[5]), "+f"(d[6]), "+f"(d[7]),
        "+f"(d[8]), "+f"(d[9]), "+f"(d[10]), "+f"(d[11]), "+f"(d[12]), "+f"(d[13]), "+f"(d[14]), "+f"(d[15]),
        "+f"(d[16]), "+f"(d[17]), "+f"(d[18]), "+f"(d[19]), "+f"(d[20]), "+f"(d[21]), "+f"(d[22]), "+f"(d[23]),
        "+f"(d[24]), "+f"(d[25]), "+f"(d[26]), "+f"(d[27]), "+f"(d[28]), "+f"(d[29]), "+f"(d[30]), "+f"(d[31]),
        "+f"(d[32]), "+f"(d[33]), "+f"(d[34]), "+f"(d[35]), "+f"(d[36]), "+f"(d[37]), "+f"(d[38]), "+f"(d[39]),
        "+f"(d[40]), "+f"(d[41]), "+f"(d[42]), "+f"(d[43]), "+f"(d[44]), "+f"(d[45]), "+f"(d[46]), "+f"(d[47])
        : "l"(da), "l"(db));
}
__device__ __forceinline__ void wgmma_ss_n64(float* d, uint64_t da, uint64_t db) {
    asm volatile("wgmma.mma_async.sync.aligned.m64n64k16.f32.bf16.bf16 {"
        "%0, %1, %2, %3, %4, %5, %6, %7, %8, %9, %10, %11, %12, %13, %14, %15,"
        "%16, %17, %18, %19, %20, %21, %22, %23, %24, %25, %26, %27, %28, %29, %30, %31}, %32, %33, 1, 1, 1, 0, 1;\n"
        :
        "+f"(d[0]), "+f"(d[1]), "+f"(d[2]), "+f"(d[3]), "+f"(d[4]), "+f"(d[5]), "+f"(d[6]), "+f"(d[7]),
        "+f"(d[8]), "+f"(d[9]), "+f"(d[10]), "+f"(d[11]), "+f"(d[12]), "+f"(d[13]), "+f"(d[14]), "+f"(d[15]),
        "+f"(d[16]), "+f"(d[17]), "+f"(d[18]), "+f"(d[19]), "+f"(d[20]), "+f"(d[21]), "+f"(d[22]), "+f"(d[23]),
        "+f"(d[24]), "+f"(d[25]), "+f"(d[26]), "+f"(d[27]), "+f"(d[28]), "+f"(d[29]), "+f"(d[30]), "+f"(d[31])
        : "l"(da), "l"(db));
}
__device__ __forceinline__ void wgmma_qk_f16_acc(float* d, const uint32_t* a, uint64_t db) {
    asm volatile("wgmma.mma_async.sync.aligned.m64n64k16.f32.f16.f16 {"
        "%0, %1, %2, %3, %4, %5, %6, %7, %8, %9, %10, %11, %12, %13, %14, %15,"
        "%16, %17, %18, %19, %20, %21, %22, %23, %24, %25, %26, %27, %28, %29, %30, %31}, {%32, %33, %34, %35}, %36, 1, 1, 1, 0;\n"
        :
        "+f"(d[0]), "+f"(d[1]), "+f"(d[2]), "+f"(d[3]), "+f"(d[4]), "+f"(d[5]), "+f"(d[6]), "+f"(d[7]),
        "+f"(d[8]), "+f"(d[9]), "+f"(d[10]), "+f"(d[11]), "+f"(d[12]), "+f"(d[13]), "+f"(d[14]), "+f"(d[15]),
        "+f"(d[16]), "+f"(d[17]), "+f"(d[18]), "+f"(d[19]), "+f"(d[20]), "+f"(d[21]), "+f"(d[22]), "+f"(d[23]),
        "+f"(d[24]), "+f"(d[25]), "+f"(d[26]), "+f"(d[27]), "+f"(d[28]), "+f"(d[29]), "+f"(d[30]), "+f"(d[31])
        : "r"(a[0]), "r"(a[1]), "r"(a[2]), "r"(a[3]), "l"(db));
}
__device__ __forceinline__ void wgmma_qk_bf16_zero(float* d, const uint32_t* a, uint64_t db) {
    asm volatile("wgmma.mma_async.sync.aligned.m64n64k16.f32.bf16.bf16 {"
        "%0, %1, %2, %3, %4, %5, %6, %7, %8, %9, %10, %11, %12, %13, %14, %15,"
        "%16, %17, %18, %19, %20, %21, %22, %23, %24, %25, %26, %27, %28, %29, %30, %31}, {%32, %33, %34, %35}, %36, 0, 1, 1, 0;\n"
        :
        "=f"(d[0]), "=f"(d[1]), "=f"(d[2]), "=f"(d[3]), "=f"(d[4]), "=f"(d[5]), "=f"(d[6]), "=f"(d[7]),
        "=f"(d[8]), "=f"(d[9]), "=f"(d[10]), "=f"(d[11]), "=f"(d[12]), "=f"(d[13]), "=f"(d[14]), "=f"(d[15]),
        "=f"(d[16]), "=f"(d[17]), "=f"(d[18]), "=f"(d[19]), "=f"(d[20]), "=f"(d[21]), "=f"(d[22]), "=f"(d[23]),
        "=f"(d[24]), "=f"(d[25]), "=f"(d[26]), "=f"(d[27]), "=f"(d[28]), "=f"(d[29]), "=f"(d[30]), "=f"(d[31])
        : "r"(a[0]), "r"(a[1]), "r"(a[2]), "r"(a[3]), "l"(db));
}
__device__ __forceinline__ void wgmma_pv(float* d, const uint32_t* a, uint64_t db) {
    asm volatile("wgmma.mma_async.sync.aligned.m64n24k16.f32.bf16.bf16 {"
        "%0, %1, %2, %3, %4, %5, %6, %7, %8, %9, %10, %11}, {%12, %13, %14, %15}, %16, 1, 1, 1, 1;\n"
        :
        "+f"(d[0]), "+f"(d[1]), "+f"(d[2]), "+f"(d[3]), "+f"(d[4]), "+f"(d[5]), "+f"(d[6]), "+f"(d[7]),
        "+f"(d[8]), "+f"(d[9]), "+f"(d[10]), "+f"(d[11])
        : "r"(a[0]), "r"(a[1]), "r"(a[2]), "r"(a[3]), "l"(db));
}

template <int N> __device__ __forceinline__ void wgmma_ss(float* d, uint64_t a, uint64_t b) {
    if (N == 128) wgmma_ss_n128(d, a, b);
    if (N == 96) wgmma_ss_n96(d, a, b);
    if (N == 64) wgmma_ss_n64(d, a, b);
}

#define OFF_R 131072
#define OFF_ONE 229376
#define OFF_BAR 229888
#define OFF_BIAS (OFF_BAR + 672)
#define OFF_G (OFF_BIAS + 1152)
#define SMEM_BYTES (OFF_G + 272)
#define SBD 1024u
#define B_X 0
#define B_F1 416
#define B_E1 112
#define B_KV 160
#define B_F2 224
#define B_E2 256
#define B_T 288
#define B_DONE 352
#define B_G 360
#define B_G2 368
#define B_G3 376
#define B_SF 384
#define B_BI 400
#define B_SF2 408
#define NR 6

#define PF 1
#define PFX 0
#define PACE 0
#define EXP_FKK 4
#define QSCALE 0.36067376022224085f
#define MAGIC 445.41763f
#define NMUFU 4
#define VSTEP ((uint64_t)((long long)32 - ((long long)32 << 16)))

#define KVMASK 0x15ADu
__host__ __device__ constexpr int strm_pos(int pass, int i) {
    if (pass == 1 || pass == 2) return 8 + 8 * pass + i;
    int n = 0;
    for (int p = 0; p < 16; p++)
        if ((int)((KVMASK >> p) & 1) == (pass == 3)) { if (n == i) return p; n++; }
    return 0;
}
__host__ __device__ constexpr uint32_t strm_code(int pass) {
    uint32_t c = 0;
    for (int i = 0; i < 7; i++) c |= (uint32_t)(strm_pos(pass, i + 1) - strm_pos(pass, i)) << (4 * i);
    return c;
}

template <int N, int SUB, int KST, int LBO, int SBO, int SWZ>
__device__ __forceinline__ void gemm_pass(float* acc, uint32_t bar, uint64_t dA, int lane, uint32_t pos, uint32_t code, int barNext, bool waitx) {
    uint32_t prev = 0, slot = pos % NR;
#pragma unroll 1
    for (int i = 0; i < 8; i++) {
        if (waitx) mbar_wait(bar + B_X + 8 * i, 0);
        mbar_wait(bar + B_F1 + 8 * pos, 0);
        const uint64_t dB = mkdesc(SBD + OFF_R, LBO, SBO, SWZ) + slot * 1024;
        wg_fence();
        wgmma_ss<N>(acc, dA, dB);
        wgmma_ss<N>(acc, dA + 2, dB + KST / 16);
        wg_commit();
        wg_wait<1>();
        if (i > 0 && lane < 2) mbar_arrive_cluster(bar + B_E1 + 8 * prev, lane);
        wgmma_ss<N>(acc, dA + 4, dB + SUB / 16);
        wgmma_ss<N>(acc, dA + 6, dB + (SUB + KST) / 16);
        wg_commit();
        prev = slot;
        pos += code & 15;
        slot += code & 15;
        if (slot >= NR) slot -= NR;
        code >>= 4;
        dA += 1024;
    }
    if (barNext) bar_arrive(barNext, 512);
    wg_wait<0>();
    if (lane < 2) mbar_arrive_cluster(bar + B_E1 + 8 * prev, lane);
    pin<N / 2>(acc);
}

__device__ __forceinline__ uint32_t lds32(uint32_t a) { uint32_t v; asm volatile("ld.shared.u32 %0, [%1];" : "=r"(v) : "r"(a)); return v; }
__device__ __forceinline__ bool elect() {
    uint32_t p;
    asm volatile("{\n.reg .pred p;\nelect.sync _|p, 0xffffffff;\nselp.u32 %0, 1, 0, p;\n}" : "=r"(p));
    return p;
}

template <int G0, int G1> __device__ __forceinline__ void gelu_pack(const float* acc, uint32_t bias, uint32_t* out) {
#pragma unroll
    for (int G = G0; G < G1; G++) {
        uint32_t* o = out + 8 * G;
#pragma unroll
        for (int j = 0; j < 4; j++) {
            float bv[2];
            asm volatile("ld.shared.v2.f32 {%0, %1}, [%2];" : "=f"(bv[0]), "=f"(bv[1]) : "r"(bias + G * 128 + j * 32));
            float y[4];
#pragma unroll
            for (int i = 0; i < 4; i++) {
                const float h = acc[16 * G + 4 * j + i] + bv[i & 1];
                const float z = h * fmaf(h * h, 0.035677408136300125f, 0.7978845608028654f);
                y[i] = fmaf(h, tanhf_(z), h);
            }
            o[j] = pk_bf16(y[0], y[1]);
            o[4 + j] = pk_bf16(y[2], y[3]);
        }
    }
}

__device__ __forceinline__ float norm_bound(const float* v, float sc) {
    uint32_t m = 0;
#pragma unroll
    for (int h = 0; h < 4; h++) {
        const float* u = v + 8 * h;
        m = max(m, __float_as_uint(fmaf(u[0], u[0], fmaf(u[1], u[1], fmaf(u[4], u[4], u[5] * u[5])))));
        m = max(m, __float_as_uint(fmaf(u[2], u[2], fmaf(u[3], u[3], fmaf(u[6], u[6], u[7] * u[7])))));
    }
#pragma unroll
    for (int o = 4; o < 32; o <<= 1) m = max(m, __shfl_xor_sync(0xffffffffu, m, o));
    float f = __uint_as_float(m);
    f += __shfl_xor_sync(0xffffffffu, f, 1);
    f += __shfl_xor_sync(0xffffffffu, f, 2);
    return f * sc;
}

__device__ __forceinline__ uint32_t exp2_pair(float a, float b) {
    const uint32_t w = __byte_perm(__float_as_uint(a), __float_as_uint(b), 0x6521);
    uint32_t m, r;
    asm("lop3.b32 %0, %1, 0x007f007f, 0x9f809f80, 0xEA;" : "=r"(m) : "r"(w));
    const uint32_t e = w - m;
    asm("fma.rn.bf16x2 %0, %1, %2, %3;" : "=r"(r) : "r"(w), "r"(m), "r"(e));
    return r;
}

__device__ __forceinline__ void store_o(const float* o, uint4* dst, uint32_t par) {
    const float s0 = __fdividef(1.f, o[8]), s1 = __fdividef(1.f, o[10]);
    const uint32_t d0 = (pk_bf16(o[0] * s0, o[1] * s0) & ~1u) | par;
    asm volatile("{\n.reg .b128 t;\nmov.b128 t, {%0, %1, %2, %3};\nst.relaxed.gpu.global.b128 [%4], t;\n}" ::"r"(d0),
                 "r"(pk_bf16(o[4] * s0, o[5] * s0)), "r"(pk_bf16(o[2] * s1, o[3] * s1)), "r"(pk_bf16(o[6] * s1, o[7] * s1)), "l"(dst) : "memory");
}
__device__ __forceinline__ uint4 load_o(const uint4* src) {
    uint4 v;
    asm volatile("{\n.reg .b128 t;\nld.relaxed.gpu.global.b128 t, [%4];\nmov.b128 {%0, %1, %2, %3}, t;\n}"
                 : "=r"(v.x), "=r"(v.y), "=r"(v.z), "=r"(v.w) : "l"(src) : "memory");
    return v;
}
__device__ __forceinline__ uint32_t bmul2(uint32_t a, uint32_t b) { uint32_t r; asm("mul.rn.bf16x2 %0, %1, %2;" : "=r"(r) : "r"(a), "r"(b)); return r; }
__device__ __forceinline__ void sts32(uint32_t a, uint32_t v) { asm volatile("st.shared.u32 [%0], %1;" ::"r"(a), "r"(v) : "memory"); }
__device__ __forceinline__ void load_q(uint32_t* q, int h, int row, int t) {
    const uint8_t* p = gQ + (size_t)h * (SEQ * 32) + (size_t)row * 32 + t * 4;
    q[0] = __ldcg((const uint32_t*)p); q[1] = __ldcg((const uint32_t*)(p + 256));
    q[2] = __ldcg((const uint32_t*)(p + 16)); q[3] = __ldcg((const uint32_t*)(p + 272));
}

template <int NT>
__device__ __forceinline__ void proj16(float (*c)[8], const __nv_bfloat16* x, const __nv_bfloat16* w, int row0, int rstep, int col, int g, int t) {
#pragma unroll
    for (int i = 0; i < NT; i++)
#pragma unroll
        for (int j = 0; j < 8; j++) c[i][j] = 0.f;
    const unsigned short* wu = (const unsigned short*)w;
#pragma unroll 1
    for (int k = 0; k < DM; k += 16) {
        uint32_t b[4];
#pragma unroll
        for (int j = 0; j < 4; j++) {
            const int kr = k + 2 * t + (j & 1) * 8, cc = col + g + (j >> 1) * 8;
            b[j] = (uint32_t)wu[(size_t)kr * (3 * DM) + cc] | ((uint32_t)wu[(size_t)(kr + 1) * (3 * DM) + cc] << 16);
        }
#pragma unroll
        for (int i = 0; i < NT; i++) {
            const __nv_bfloat16* xp = x + (size_t)(row0 + i * rstep + g) * DM + k + 2 * t;
            const uint32_t a0 = *(const uint32_t*)xp, a1 = *(const uint32_t*)(xp + 8 * DM);
            const uint32_t a2 = *(const uint32_t*)(xp + 8), a3 = *(const uint32_t*)(xp + 8 * DM + 8);
#pragma unroll
            for (int j = 0; j < 2; j++)
                asm volatile("mma.sync.aligned.m16n8k16.row.col.f32.bf16.bf16.f32 {%0,%1,%2,%3}, {%4,%5,%6,%7}, {%8,%9}, {%0,%1,%2,%3};"
                             : "+f"(c[i][4 * j]), "+f"(c[i][4 * j + 1]), "+f"(c[i][4 * j + 2]), "+f"(c[i][4 * j + 3])
                             : "r"(a0), "r"(a1), "r"(a2), "r"(a3), "r"(b[2 * j]), "r"(b[2 * j + 1]));
        }
    }
}

struct Maps { CUtensorMap x, kv, q, f1, f3, h, w2, wo, hs, kvs; };

__global__ void __cluster_dims__(2, 1, 1) __launch_bounds__(640, 1)
fused_kernel(const __grid_constant__ Maps tm, const __nv_bfloat16* __restrict__ x, const __nv_bfloat16* __restrict__ wqkv,
             const __nv_bfloat16* __restrict__ wo, const __nv_bfloat16* __restrict__ w1, const __nv_bfloat16* __restrict__ b1,
             const __nv_bfloat16* __restrict__ w2, const __nv_bfloat16* __restrict__ b2, const __nv_bfloat16* __restrict__ gate,
             __nv_bfloat16* __restrict__ out) {
    const uint32_t sb = smem_u32(smem_raw);
    const uint32_t bar = sb + OFF_BAR;
    const int tid = threadIdx.x, lane = tid & 31;
    const int warp = __shfl_sync(0xffffffffu, tid >> 5, 0);
    const uint32_t rank = cluster_rank();
    const int cl = blockIdx.x >> 1;
    const int nb = cl & 7, mb = (cl >> 3) * 2 + rank;
    const int g = lane >> 2, t = lane & 3;

    const int cb = nb & 3, rb = mb * 2 + (nb >> 2);
    if (tid == 0) TLM(0, 0);
    TL_INIT();
    if (tid == 512) {
        for (int i = 0; i < 8; i++) { mbar_init(bar + B_X + 8 * i, 1); mbar_init(bar + B_KV + 8 * i, 1); mbar_init(bar + B_T + 8 * i, 5); }
        for (int i = 0; i < NR; i++) mbar_init(bar + B_E1 + 8 * i, 16);
        for (int i = 0; i < 4; i++) { mbar_init(bar + B_F2 + 8 * i, 1); mbar_init(bar + B_E2 + 8 * i, 8); }
        asm volatile("fence.mbarrier_init.release.cluster;" ::: "memory");
    } else if (tid == 608) {
        for (int i = 0; i < 32; i++) mbar_init(bar + B_F1 + 8 * i, 1);
        mbar_init(bar + B_DONE, 16);
        mbar_init(bar + B_G, 1);
        for (int i = 0; i < 3; i++) mbar_init(bar + B_SF + 8 * i, i == 1 ? 2 : 1);
        mbar_init(bar + B_SF2, 2);
        mbar_init(bar + B_G3, 1);
        mbar_init(bar + B_G2, 4);
        asm volatile("fence.mbarrier_init.release.cluster;" ::: "memory");
    }
    __syncwarp();
    asm volatile("barrier.cluster.arrive.relaxed.aligned;" ::: "memory");
    if (tid == 512) {
        mbar_expect(bar + B_X, 16384);
        tma2d(sb, &tm.x, 0, mb * 128, bar + B_X);
    } else if (tid == 544) {
        map_prefetch(&tm.kv);
        l2_prefetch((const uint8_t*)wqkv + (size_t)blockIdx.x * 3072, 3072);
        l2_prefetch((const uint8_t*)w1 + (size_t)blockIdx.x * 1792, 1792);
        map_prefetch(&tm.q); map_prefetch(&tm.f1); map_prefetch(&tm.f3);
    }
    if ((sb & 0xFFFFFF) != SBD) __trap();
    __syncwarp();
    asm volatile("barrier.cluster.wait.aligned;" ::: "memory");
    const uint32_t ep = gEpoch[blockIdx.x] + 1;
    if (tid == 0) { TLM(0, 1); TLC(0, 30); }

    if (warp < 16) {
        const int wg = warp >> 2;
        const int h = cl >> 1, qd = (cl & 1) * 2 + rank;
        uint32_t q[4];
        {
            const int w8 = warp & 7;
            const int T = mb * 8 + w8, row0 = T * 16 + g;
            const uint64_t dA0 = mkdesc(SBD + (wg & 1) * 8192, 16, 1024, 1);
            if (wg < 2) {
                float acc[64];
#pragma unroll
                for (int i = 0; i < 64; i++) acc[i] = 0.f;
                gemm_pass<128, 8192, 2048, 4096, 1024, 1>(acc, bar, dA0, lane, strm_pos(3, 0), strm_code(3), 0, true);
                if (tid == 0) TLM(0, 2);
                {
                    const float km = norm_bound(acc, 1.f);
                    float vm = 0.f;
#pragma unroll
                    for (int i = 32; i < 64; i++) vm = fmaxf(vm, fabsf(acc[i]));
                    vm = __uint_as_float(__reduce_max_sync(0xffffffffu, __float_as_uint(vm)));
                    if (lane == 0) { gN[1024 + nb * 128 + T] = km; gN[2048 + nb * 128 + T] = vm; }
                    const uint32_t kp = sb + OFF_R + 12288 + (w8 >> 2) * 1024 + g * 128 + ((((w8 & 3) * 2 + ((t >> 1) ^ (w8 >> 2))) ^ g) << 4) + (t & 1) * 8;
                    uint8_t* vp = gKV + (size_t)(nb * 4) * (SEQ * 64) + 65536 + (((T >> 6) * 16 + 2 * g) * 64 + (T & 63)) * 32 + ((t * 8) ^ ((w8 >> 2) << 4));
                    bar_sync(9, 256);
#pragma unroll
                    for (int hh = 0; hh < 4; hh++) {
                        const float* v = acc + 8 * hh;
                        float p0 = __shfl_up_sync(0xffffffffu, v[2], 4), p1 = __shfl_up_sync(0xffffffffu, v[3], 4);
                        float p2 = __shfl_up_sync(0xffffffffu, v[6], 4), p3 = __shfl_up_sync(0xffffffffu, v[7], 4);
                        if (g == 0) { p0 = p1 = p2 = p3 = 0.f; }
                        sts64(kp + hh * 16384, pk_f16(v[0] - p0, v[1] - p1), pk_f16(v[4] - p2, v[5] - p3));
                        sts64(kp + hh * 16384 + 2048, pk_f16(v[2] - v[0], v[3] - v[1]), pk_f16(v[6] - v[4], v[7] - v[5]));
                        const float* u = acc + 32 + 8 * hh;
                        if (hh < 2) {
                            sts64(kp + (4 + hh) * 16384, pk_bf16(u[0], u[1]), pk_bf16(u[4], u[5]));
                            sts64(kp + (4 + hh) * 16384 + 2048, pk_bf16(u[2], u[3]), pk_bf16(u[6], u[7]));
                        } else {
                            *(uint2*)(vp + (size_t)hh * (SEQ * 64)) = make_uint2(pk_bf16(u[0], u[1]), pk_bf16(u[4], u[5]));
                            *(uint2*)(vp + (size_t)hh * (SEQ * 64) + 2048) = make_uint2(pk_bf16(u[2], u[3]), pk_bf16(u[6], u[7]));
                        }
                    }
                }
                asm volatile("fence.proxy.async.shared::cta;" ::: "memory");
                bar_arrive(10, 288);
                if (tid == 0) TLM(0, 3);
            }
#pragma unroll 1
            for (int p = wg < 2 ? 1 : 0; p < 3; p += 2) {
                float acc[48];
#pragma unroll
                for (int i = 0; i < 48; i++) acc[i] = 0.f;
                pin<48>(acc);
                if (p) bar_sync(5 + p, 512);
                gemm_pass<96, 6144, 1024, 2048, 512, 2>(acc, bar, dA0, lane, p == 0 ? strm_pos(0, 0) : 8 + 8 * p, p == 0 ? strm_code(0) : strm_code(1), p < 2 ? 6 + p : 0, p == 0);
                if ((tid & 255) == 0) TLM(0, 4 + 2 * p);
                const uint32_t hp = sb + OFF_R + (p == 2 ? 0 : 12288) + (wg & 1) * 16384 + ((warp & 3) * 16 + g) * 64 + t * 16;
                const uint32_t bp = sb + OFF_BIAS + p * 384 - 256 + t * 8;
                uint32_t ho[24];
                mbar_wait(bar + B_BI, 0);
                if (p == 0) {
                    const float qm = norm_bound(acc, QSCALE * QSCALE);
                    if (lane == 0) gN[nb * 128 + T] = qm;
                    uint8_t* qp = gQ + (size_t)(nb * 4) * (SEQ * 32) + (size_t)row0 * 32 + t * 8;
#pragma unroll
                    for (int hh = 0; hh < 4; hh++) {
                        const float* v = acc + 8 * hh;
                        *(uint2*)(qp + hh * (SEQ * 32)) = make_uint2(pk_f16(v[0] * QSCALE, v[1] * QSCALE), pk_f16(v[4] * QSCALE, v[5] * QSCALE));
                        *(uint2*)(qp + hh * (SEQ * 32) + 256) = make_uint2(pk_f16(v[2] * QSCALE, v[3] * QSCALE), pk_f16(v[6] * QSCALE, v[7] * QSCALE));
                    }
                    bar_arrive(12, 288);
                } else {
                    if (p == 2) {
                        mbar_wait(bar + B_G, 0);
                        load_q(q, h, qd * 512 + warp * 16 + g, t);
                    }
                    gelu_pack<0, 2>(acc, bp, ho);
                }
                gelu_pack<2, 3>(acc, bp, ho);
                pin<8>(ho + 16);
                if (p == 2) bar_sync(9, 256);
                else mbar_wait(bar + B_SF + 8 * p, 0);
                if (p) {
#pragma unroll
                    for (int i = 0; i < 4; i++) sts128(hp + (i >> 1) * 32768 + (i & 1) * 512, ho + 4 * i);
                }
                sts128(hp + 65536, ho + 16);
                sts128(hp + 65536 + 512, ho + 20);
                asm volatile("fence.proxy.async.shared::cta;" ::: "memory");
                bar_arrive(p == 1 ? 14 : 11, 288);
                if ((tid & 255) == 0) TLM(0, 5 + 2 * p);
            }
            if (wg < 2) {
                mbar_wait(bar + B_G, 0);
                load_q(q, h, qd * 512 + warp * 16 + g, t);
            }
        }
        mbar_wait(bar + B_G3, 0);
        const bool fast = lds32(sb + OFF_G + 256) != 0;
        uint4* const op = gO + ((qd * 8 + wg) * NH + h) * 128 + (tid & 127);
        const uint64_t kd0 = mkdesc(SBD, 16, 256, 3);
        const uint64_t vd0 = mkdesc(SBD + 8192, OFF_ONE - 8192, 256, 3);
        if (fast) {
#pragma unroll 1
            for (int r = 0; r < 2; r++) {
                float o[12];
#pragma unroll
                for (int i = 0; i < 12; i++) o[i] = 0.f;
                uint64_t kd = kd0, vd = vd0;
                uint32_t qn[4];
#pragma unroll 1
                for (int half = 0; half < 2; half++) {
                    float s[32];
#pragma unroll
                    for (int i = 0; i < 32; i++) s[i] = i < 2 * NMUFU ? 0.f : MAGIC;
#pragma unroll 1
                    for (int c = 0; c < 4; c++) {
                        if (r == 0) mbar_wait(bar + B_KV + 8 * (half * 4 + c), 0);
                        if ((tid & 255) == 0 && c == 0) TLM(1, (tid >> 8) * 4 + r * 2 + half);
                        if (half == 1 && c == 3) {
                            if (r == 0) load_q(qn, h, qd * 512 + 256 + warp * 16 + g, t);
                            else if (lane == 0) mbar_arrive(bar + B_DONE);
                        }
#pragma unroll
                        for (int j = 0; j < 4; j++) {
                            uint32_t p[16];
                            wg_fence();
                            wgmma_qk_f16_acc(s, q, kd);
                            wg_commit();
                            wg_wait<0>();
                            pin<32>(s);
#pragma unroll
                            for (int i = 0; i < 16; i++)
                                p[i] = i < NMUFU ? pk_bf16(ex2f(s[2 * i]), ex2f(s[2 * i + 1])) : exp2_pair(s[2 * i], s[2 * i + 1]);
                            pin<16>(p);
                            wg_fence();
#pragma unroll
                            for (int u = 0; u < 4; u++) wgmma_pv(o, p + 4 * u, vd + u * VSTEP);
                            wg_commit();
                            kd += 128;
                            vd += 4 * VSTEP;
                        }
                        kd += 512;
                        vd += 16 * VSTEP;
                    }
                    wg_wait<0>();
                }
                pin<12>(o);
                if ((tid & 127) == 0 && r == 1) TLM(1, 8 + wg);
                store_o(o, op + r * (4 * NH * 128), ep & 1);
#pragma unroll
                for (int i = 0; i < 4; i++) q[i] = qn[i];
            }
            if (tid == 0) { TLM(1, 12); TLC(0, 31); }
        } else {
            for (int c = 0; c < 8; c++) mbar_wait(bar + B_KV + 8 * c, 0);
            {
                float kc[8][8];
                proj16<8>(kc, x, wqkv, warp * 16, 256, DM + h * 16, g, t);
#pragma unroll
                for (int i = 0; i < 8; i++) {
                    const int T = warp + i * 16;
                    const int pos = ((T >> 6) * 16 + 2 * g) * 64 + (T & 63);
                    const uint32_t a = sb + (pos >> 8) * 16384 + (pos & 255) * 32 + t * 4, sw = ((T >> 2) & 1) << 4;
                    asm volatile("st.shared.u32 [%0], %1;" ::"r"(a + sw), "r"(pk_bf16(kc[i][0], kc[i][1])) : "memory");
                    asm volatile("st.shared.u32 [%0], %1;" ::"r"(a + (sw ^ 16)), "r"(pk_bf16(kc[i][4], kc[i][5])) : "memory");
                    asm volatile("st.shared.u32 [%0], %1;" ::"r"(a + 2048 + sw), "r"(pk_bf16(kc[i][2], kc[i][3])) : "memory");
                    asm volatile("st.shared.u32 [%0], %1;" ::"r"(a + 2048 + (sw ^ 16)), "r"(pk_bf16(kc[i][6], kc[i][7])) : "memory");
                }
                asm volatile("fence.proxy.async.shared::cta;" ::: "memory");
                bar_sync(8, 512);
            }
#pragma unroll 1
            for (int r = 0; r < 2; r++) {
                const int row = qd * 512 + r * 256 + warp * 16 + g;
                {
                    float qc[1][8];
                    proj16<1>(qc, x, wqkv, row - g, 0, h * 16, g, t);
#pragma unroll
                    for (int i = 0; i < 4; i++) q[i] = pk_bf16(qc[0][2 * i] * QSCALE, qc[0][2 * i + 1] * QSCALE);
                }
                float o[12];
#pragma unroll
                for (int i = 0; i < 12; i++) o[i] = 0.f;
                float m0 = -INFINITY, m1 = -INFINITY;
#pragma unroll 1
                for (int j = 0; j < 32; j++) {
                    const uint64_t kd = kd0 + (j >> 2) * 1024 + (j & 3) * 128, vd = vd0 + ((j >> 2) * 32 + (j & 3) * 4) * VSTEP;
                    float s[32];
                    uint32_t p[16];
                    wg_fence();
                    wgmma_qk_bf16_zero(s, q, kd);
                    wg_commit();
                    wg_wait<0>();
                    pin<32>(s);
                    pin<12>(o);
                    float n0 = m0, n1 = m1;
#pragma unroll
                    for (int i = 0; i < 8; i++) {
                        n0 = fmaxf(n0, fmaxf(s[4 * i], s[4 * i + 1]));
                        n1 = fmaxf(n1, fmaxf(s[4 * i + 2], s[4 * i + 3]));
                    }
                    n0 = fmaxf(n0, __shfl_xor_sync(0xffffffffu, n0, 1));
                    n1 = fmaxf(n1, __shfl_xor_sync(0xffffffffu, n1, 1));
                    n0 = fmaxf(n0, __shfl_xor_sync(0xffffffffu, n0, 2));
                    n1 = fmaxf(n1, __shfl_xor_sync(0xffffffffu, n1, 2));
                    const float c0 = ex2f(m0 - n0), c1 = ex2f(m1 - n1);
                    m0 = n0;
                    m1 = n1;
#pragma unroll
                    for (int i = 0; i < 3; i++) { o[4 * i] *= c0; o[4 * i + 1] *= c0; o[4 * i + 2] *= c1; o[4 * i + 3] *= c1; }
#pragma unroll
                    for (int i = 0; i < 8; i++) {
                        p[2 * i] = pk_bf16(ex2f(s[4 * i] - m0), ex2f(s[4 * i + 1] - m0));
                        p[2 * i + 1] = pk_bf16(ex2f(s[4 * i + 2] - m1), ex2f(s[4 * i + 3] - m1));
                    }
                    pin<16>(p);
                    pin<12>(o);
                    wg_fence();
#pragma unroll
                    for (int u = 0; u < 4; u++) wgmma_pv(o, p + 4 * u, vd + u * VSTEP);
                    wg_commit();
                }
                wg_wait<0>();
                pin<12>(o);
                if (r == 1 && lane == 0) mbar_arrive(bar + B_DONE);
                store_o(o, op + r * (4 * NH * 128), ep & 1);
            }
        }
        {
            const uint4* src = gO + (rb * NH + wg * 8) * 128 + (tid & 127);
            uint4 v[8];
#pragma unroll
            for (int i = 0; i < 8; i++) v[i] = load_o(src + i * 128);
            mbar_wait(bar + B_DONE, 0);
            mbar_wait(bar + B_G2, 0);
            const int lr = (warp & 3) * 16 + g;
            const uint32_t g0 = lds32(sb + OFF_G + lr * 4), g1 = lds32(sb + OFF_G + lr * 4 + 32);
            const uint32_t a0 = sb + wg * 16384 + lr * 128 + (t >> 1) * 4;
#pragma unroll
            for (int i = 0; i < 8; i++) {
                if ((i & 3) == 0) {
                    int spins = 0;
                    while (__any_sync(0xffffffffu, (((v[i].x ^ ep) | (v[i + 1].x ^ ep) | (v[i + 2].x ^ ep) | (v[i + 3].x ^ ep)) & 1) != 0)) {
                        if (++spins > (1 << 22)) __trap();
#pragma unroll
                        for (int k = i; k < 8; k++)
                            if (((v[k].x ^ ep) & 1) != 0) v[k] = load_o(src + k * 128);
                    }
                }
                const uint32_t a = a0 + (i >> 2) * 8192 + ((((i & 3) * 2 + (t & 1)) ^ g) << 4);
                sts32(a, bmul2(v[i].x, g0));
                sts32(a + 8, bmul2(v[i].y, g0));
                sts32(a + 1024, bmul2(v[i].z, g1));
                sts32(a + 1024 + 8, bmul2(v[i].w, g1));
                if ((i & 3) == 3) {
                    asm volatile("fence.proxy.async.shared::cta;" ::: "memory");
                    __syncwarp();
                    if (lane == 0) mbar_arrive(bar + B_T + 8 * (wg * 2 + (i >> 2)));
                    if ((tid & 127) == 0) TLM(1, 20 + wg * 2 + (i >> 2));
                }
            }
        }
    } else {
        if (warp == 16) {
            if (elect()) {
                int s = 0, par = 1, k0 = rank * 32, k3 = rank * 32;
#pragma unroll 1
                for (int it = 0; it < 32; it++) {
                    const uint32_t fb = bar + B_F1 + 8 * it, dst = sb + OFF_R + s * 16384;
                    mbar_wait(bar + B_E1 + 8 * s, par);
                    if (it < 16 && ((KVMASK >> it) & 1)) {
                        mbar_expect(fb, 16384);
                        tma3d_mc(dst + rank * 8192, &tm.kv, nb * 64, k3, 1, fb);
                        k3 += 64;
                    } else {
                        mbar_expect(fb, 12288);
                        if (it < 16) {
                            tma3d_mc(dst + rank * 6144, &tm.q, 0, k0, nb * 2, fb);
                            tma3d_mc(dst + rank * 6144 + 4096, &tm.f1, 0, k0, nb * 7, fb);
                        } else {
                            tma3d_mc(dst + rank * 6144, &tm.f3, 0, k0 & 511, nb * 7 + (it < 24 ? 1 : 4), fb);
                        }
                        k0 += 64;
                    }
                    for (int c = it; c >= 1 && c < 8 && (c == it || it == NR - 1) && it < NR; c++) {
                        mbar_expect(bar + B_X + 8 * c, 16384);
                        tma2d(sb + c * 16384, &tm.x, c * 64, mb * 128, bar + B_X + 8 * c);
                    }
                    if (++s == NR) { s = 0; par ^= 1; }
                }
                const int h = cl >> 1;
                mbar_wait(bar + B_G, 0);
                asm volatile("fence.proxy.async.global;" ::: "memory");
                TLM(0, 10);
#pragma unroll 1
                for (int c = 0; c < 8; c++) {
                    if (c >= 8 - NR) {
                        mbar_wait(bar + B_E1 + 8 * s, par);
                        if (++s == NR) { s = 0; par ^= 1; }
                    }
                    mbar_expect(bar + B_KV + 8 * c, 16384);
                    bulk_mc(sb + c * 16384 + rank * 8192, gKV + (size_t)h * (SEQ * 64) + rank * 65536 + c * 8192, 8192, bar + B_KV + 8 * c);
                }
                mbar_wait(bar + B_SF2, 0);
#pragma unroll 1
                for (s = 0; s < 4; s++) {
                    mbar_expect(bar + B_F2 + 8 * s, 24576);
                    tma5d_mc(sb + OFF_R + s * 24576 + 8192 + rank * 8192, &tm.w2, cb * 128 + rank * 64, s * 2, bar + B_F2 + 8 * s);
                }
                cnt_wait(gCntH + mb * 32, ep * 8);
                asm volatile("fence.proxy.async.global;" ::: "memory");
                TLM(1, 13);
#pragma unroll 1
                for (s = 0; s < 4; s++) tma2d(sb + OFF_R + s * 24576, &tm.h, s * 64, rb * 64, bar + B_F2 + 8 * s);
            }
        } else if (warp == 17) {
            {
                uint32_t bv[4], b2v[2];
#pragma unroll
                for (int i = 0; i < 4; i++) bv[i] = lane + 32 * i < 112 ? *(const uint32_t*)(b1 + nb * 224 + (lane + 32 * i) * 2) : 0;
#pragma unroll
                for (int i = 0; i < 2; i++) b2v[i] = *(const uint32_t*)(b2 + cb * 128 + (lane + 32 * i) * 2);
#pragma unroll
                for (int i = 0; i < 4; i++) {
                    sts32(sb + OFF_ONE + (lane + 32 * i) * 4, 0x3f803f80u);
                    if (lane + 32 * i < 112) sts64(sb + OFF_BIAS + (lane + 32 * i) * 8, bv[i] << 16, bv[i] & 0xffff0000u);
                }
#pragma unroll
                for (int i = 0; i < 2; i++) sts32(sb + OFF_BIAS + 896 + (lane + 32 * i) * 4, b2v[i]);
                asm volatile("fence.proxy.async.shared::cta;" ::: "memory");
                __syncwarp();
                if (lane == 0) mbar_arrive(bar + B_BI);
            }
            mbar_wait(bar + B_X + 8 * PFX, 0);
            if (lane == 0) {
                l2_prefetch((const uint8_t*)wqkv + 128 * 3072 + (size_t)blockIdx.x * 9216, 9216);
                l2_prefetch((const uint8_t*)w1 + (size_t)blockIdx.x * 14336, 14336);
            }
            mbar_wait(bar + B_X + 8 * 7, 0);
            if (lane == 0) {
                l2_prefetch((const uint8_t*)w2 + (size_t)blockIdx.x * 14336, 14336);
                l2_prefetch((const uint8_t*)wo + (size_t)blockIdx.x * 4096, 4096);
                map_prefetch(&tm.h); map_prefetch(&tm.w2); map_prefetch(&tm.wo); map_prefetch(&tm.hs); map_prefetch(&tm.kvs);
                TLM(0, 11);
            }
            bar_sync(10, 288);
            if (lane == 0) {
#pragma unroll 1
                for (int b = 5; b >= 0; b--) {
                    tma5d_st(&tm.kvs, sb + OFF_R + 12288 + b * 16384, (mb >> 3) * 8, (mb & 7) * 2, nb * 8 + (b < 4 ? 2 * b : 2 * b - 7));
                    asm volatile("cp.async.bulk.commit_group;\ncp.async.bulk.wait_group.read %0;" ::"n"(PACE) : "memory");
                    if (b == 4 - PACE) mbar_arrive(bar + B_SF);
                }
                asm volatile("cp.async.bulk.wait_group.read 0;" ::: "memory");
                mbar_arrive(bar + B_SF + 8);
            }
            __syncwarp();
            bar_sync(12, 288);
            if (lane == 0) {
                asm volatile("cp.async.bulk.wait_group 0;\nfence.proxy.async.global;" ::: "memory");
                cnt_add(gCntQ + nb * 32);
                TLM(0, 13);
            }
        } else {
            {
                const int r0 = mb * 128 + nb * 16 + (warp - 18) * 8;
                uint4 xv[16];
#pragma unroll
                for (int i = 0; i < 16; i++) xv[i] = *(const uint4*)(x + (size_t)(r0 + (i >> 1)) * DM + (i & 1) * 256 + lane * 8);
                const uint4 ga = *(const uint4*)(gate + lane * 8), gb = *(const uint4*)(gate + 256 + lane * 8);
                float z[8];
#pragma unroll
                for (int r = 0; r < 8; r++) z[r] = dot8(xv[2 * r], ga) + dot8(xv[2 * r + 1], gb);
#pragma unroll
                for (int w = 4; w >= 1; w >>= 1)
#pragma unroll
                    for (int r = 0; r < w; r++) {
                        const bool up = lane & w;
                        z[r] = (up ? z[r + w] : z[r]) + __shfl_xor_sync(0xffffffffu, up ? z[r] : z[r + w], w);
                    }
                z[0] += __shfl_xor_sync(0xffffffffu, z[0], 8);
                z[0] += __shfl_xor_sync(0xffffffffu, z[0], 16);
                if (lane < 8) gG[r0 + lane] = 1.f / (1.f + __expf(-z[0]));
                if (tid == 576) TLM(0, 12);
            }
            if (warp == 19) {
#pragma unroll 1
                for (int e = 0; e < 3; e++) {
                    bar_sync(e == 1 ? 14 : 11, 288);
                    if (lane == 0) {
#pragma unroll 1
                        for (int b = e == 0 ? 4 : 0; b < 6; b++) {
                            tma3d_st(&tm.hs, sb + OFF_R + (e == 2 ? 0 : 12288) + b * 16384, 0, mb * 128 + (b & 1) * 64, nb * 7 + e * 3 - 2 + (b >> 1));
                            asm volatile("cp.async.bulk.commit_group;\ncp.async.bulk.wait_group.read %0;" ::"n"(PACE) : "memory");
                        }
                        asm volatile("cp.async.bulk.wait_group.read 0;" ::: "memory");
                        if (e == 0) mbar_arrive(bar + B_SF + 8);
                        if (e == 2) { mbar_arrive_cluster(bar + B_SF2, 0); mbar_arrive_cluster(bar + B_SF2, 1); }
                    }
                    __syncwarp();
                }
                bar_sync(13, 64);
                if (lane == 0) {
                    asm volatile("cp.async.bulk.wait_group 0;\nfence.proxy.async.global;" ::: "memory");
                    cnt_add(gCntH + mb * 32);
                    TLM(0, 15);
                }
            } else {
                bar_arrive(13, 64);
                const int h = cl >> 1, qd = (cl & 1) * 2 + rank;
                if (lane == 0) {
                    cnt_wait(gCntQ + (h >> 2) * 32, ep * 16);
                    mbar_arrive(bar + B_G);
                    TLM(0, 14);
                }
                __syncwarp();
            const int hb = h >> 2;
            const uint4 kq = __ldcg((const uint4*)(gN + 1024 + hb * 128 + lane * 4));
            const uint4 vq = __ldcg((const uint4*)(gN + 2048 + hb * 128 + lane * 4));
            const float qq = ldcg_f(gN + hb * 128 + qd * 32 + lane);
            const float kf = __uint_as_float(__reduce_max_sync(0xffffffffu, max(max(kq.x, kq.y), max(kq.z, kq.w))));
            const float vf = __uint_as_float(__reduce_max_sync(0xffffffffu, max(max(vq.x, vq.y), max(vq.z, vq.w))));
            const float qf = __uint_as_float(__reduce_max_sync(0xffffffffu, __float_as_uint(qq)));
            if (lane == 0) {
                sts32(sb + OFF_G + 256, (kf <= 1.0e6f) && (qf <= 1.0e6f) && (kf * qf <= 3400.f) && (vf <= 1.0e12f));
                mbar_arrive(bar + B_G3);
            }
            }
        }
        __syncwarp();
        float acc[64];
#pragma unroll
        for (int i = 0; i < 64; i++) acc[i] = 0.f;
#pragma unroll 1
        for (int io = 0; io < 7; io++) {
#pragma unroll
            for (int s = 0; s < 4; s++) {
                const int it = io * 4 + s;
                mbar_wait(bar + B_F2 + 8 * s, io & 1);
                if (tid == 512 && s == 0 && (io == 0 || io == 4)) TLM(1, 14 + io / 4);
                const uint64_t dA = mkdesc(SBD + OFF_R + s * 24576, 16, 1024, 1);
                const uint64_t dB = mkdesc(SBD + OFF_R + s * 24576 + 8192, 8192, 1024, 1);
                wg_fence();
#pragma unroll
                for (int kk = 0; kk < EXP_FKK; kk++) wgmma_ss_n128(acc, dA + kk * 2, dB + kk * 128);
                wg_commit();
                if (warp < 18 && it >= 2 && it < 26) {
                    const int s2 = (s + 2) & 3;
                    mbar_wait(bar + B_E2 + 8 * s2, (io - (s < 2)) & 1);
                    if (elect()) {
                        if (warp == 16) {
                            mbar_expect(bar + B_F2 + 8 * s2, 24576);
                            tma5d_mc(sb + OFF_R + s2 * 24576 + 8192 + rank * 8192, &tm.w2, cb * 128 + rank * 64, it * 2 + 4, bar + B_F2 + 8 * s2);
                        } else {
                            asm volatile("fence.proxy.async.global;" ::: "memory");
                            tma2d(sb + OFF_R + s2 * 24576, &tm.h, it * 64 + 128, rb * 64, bar + B_F2 + 8 * s2);
                        }
                    }
                    __syncwarp();
                }
                wg_wait<1>();
                if (it >= 1 && lane < 2) mbar_arrive_cluster(bar + B_E2 + 8 * ((s + 3) & 3), lane);
            }
        }
        wg_wait<0>();
        if (lane < 2) mbar_arrive_cluster(bar + B_E2 + 8 * 3, lane);
        pin<64>(acc);
        if (warp == 16) {
            if (lane == 0) TLM(1, 16);
            for (int s = 0; s < 4; s++) mbar_wait(bar + B_E2 + 8 * s, 0);
            if (elect()) {
#pragma unroll
                for (int i = 0; i < 8; i++) mbar_expect(bar + B_T + 8 * i, 16384);
#pragma unroll
                for (int i = 0; i < 6; i++) tma2d_mc(sb + OFF_R + i * 16384 + rank * 8192, &tm.wo, cb * 128 + rank * 64, i * 64, bar + B_T + 8 * i);
            }
            __syncwarp();
        }
        {
            const int lr = (warp - 16) * 16 + g;
            const uint32_t pa = pk_bf16(ldcg_f(gG + rb * 64 + lr), ldcg_f(gG + rb * 64 + lr + 8));
            if (t == 0) {
                sts32(sb + OFF_G + lr * 4, __byte_perm(pa, pa, 0x1010));
                sts32(sb + OFF_G + lr * 4 + 32, __byte_perm(pa, pa, 0x3232));
            }
            __syncwarp();
            if (lane == 0) mbar_arrive(bar + B_G2);
            const float ga = bf_lo(pa), gb = bf_hi(pa);
            const float g0 = 1.f - ga, g1 = 1.f - gb;
#pragma unroll
            for (int j = 0; j < 16; j++) {
                const uint32_t bv = lds32(sb + OFF_BIAS + 896 + j * 16 + t * 4);
                acc[4 * j] = fmaf(acc[4 * j], 0.5f, bf_lo(bv)) * g0;
                acc[4 * j + 1] = fmaf(acc[4 * j + 1], 0.5f, bf_hi(bv)) * g0;
                acc[4 * j + 2] = fmaf(acc[4 * j + 2], 0.5f, bf_lo(bv)) * g1;
                acc[4 * j + 3] = fmaf(acc[4 * j + 3], 0.5f, bf_hi(bv)) * g1;
            }
            pin<64>(acc);
        }
        if (warp == 17) {
            mbar_wait(bar + B_DONE, 0);
            if (elect()) {
#pragma unroll
                for (int i = 0; i < 4; i++)
                    tma2d(sb + 65536 + i * 8192, &tm.wo, cb * 128 + (i & 1) * 64, (6 + (i >> 1)) * 64, bar + B_T + 8 * (6 + (i >> 1)));
            }
            __syncwarp();
        }
        if (tid == 512) TLM(1, 17);
#pragma unroll
        for (int i = 0; i < 8; i++) {
            mbar_wait(bar + B_T + 8 * i, 0);
            const uint64_t dA = mkdesc(SBD + i * 8192, 16, 1024, 1);
            const uint64_t dB = mkdesc(i < 6 ? SBD + OFF_R + i * 16384 : SBD + 65536 + (i - 6) * 16384, 8192, 1024, 1);
            wg_fence();
#pragma unroll
            for (int kk = 0; kk < 4; kk++) wgmma_ss_n128(acc, dA + kk * 2, dB + kk * 128);
            wg_commit();
        }
        wg_wait<0>();
        pin<64>(acc);
        if (tid == 512) TLM(1, 18);
        {
            const uint32_t st = sb + 98304 + (warp - 16) * 4352;
            const uint32_t wa = st + (lane & 15) * 272 + (lane >> 4) * 16;
#pragma unroll
            for (int j = 0; j < 8; j++)
                asm volatile("stmatrix.sync.aligned.m8n8.x4.shared.b16 [%0], {%1, %2, %3, %4};" ::"r"(wa + j * 32),
                             "r"(pk_bf16(acc[8 * j], acc[8 * j + 1])), "r"(pk_bf16(acc[8 * j + 2], acc[8 * j + 3])),
                             "r"(pk_bf16(acc[8 * j + 4], acc[8 * j + 5])), "r"(pk_bf16(acc[8 * j + 6], acc[8 * j + 7])) : "memory");
            __syncwarp();
            __nv_bfloat16* op = out + (size_t)(rb * 64 + (warp - 16) * 16 + (lane >> 4)) * DM + cb * 128 + (lane & 15) * 8;
#pragma unroll
            for (int j = 0; j < 8; j++) {
                uint4 v;
                asm volatile("ld.shared.v4.u32 {%0, %1, %2, %3}, [%4];" : "=r"(v.x), "=r"(v.y), "=r"(v.z), "=r"(v.w)
                             : "r"(st + (2 * j + (lane >> 4)) * 272 + (lane & 15) * 16));
                *(uint4*)(op + (size_t)j * 2 * DM) = v;
            }
        }
        if (tid == 512) { gEpoch[blockIdx.x] = ep; TLM(1, 19); }
        TL_DUMP();
    }
}

typedef CUresult (*EncodeFn)(CUtensorMap*, CUtensorMapDataType, cuuint32_t, void*, const cuuint64_t*, const cuuint64_t*, const cuuint32_t*,
                             const cuuint32_t*, CUtensorMapInterleave, CUtensorMapSwizzle, CUtensorMapL2promotion, CUtensorMapFloatOOBfill);

static void make_map(EncodeFn enc, CUtensorMap* m, const void* p, int rank, const cuuint64_t* dims, const cuuint64_t* strides,
                     const cuuint32_t* box, CUtensorMapSwizzle swz) {
    const cuuint32_t es[5] = {1, 1, 1, 1, 1};
    enc(m, CU_TENSOR_MAP_DATA_TYPE_BFLOAT16, rank, (void*)p, dims, strides, box, es, CU_TENSOR_MAP_INTERLEAVE_NONE, swz,
        CU_TENSOR_MAP_L2_PROMOTION_L2_128B, CU_TENSOR_MAP_FLOAT_OOB_FILL_NONE);
}

extern "C" void kernel_launch(void* const* d_in, const int* in_sizes, int n_in, void* d_out, int out_size) {
    const __nv_bfloat16* x = (const __nv_bfloat16*)d_in[0];
    const __nv_bfloat16* wqkv = (const __nv_bfloat16*)d_in[1];
    const __nv_bfloat16* wo = (const __nv_bfloat16*)d_in[2];
    const __nv_bfloat16* w1 = (const __nv_bfloat16*)d_in[4];
    const __nv_bfloat16* b1 = (const __nv_bfloat16*)d_in[5];
    const __nv_bfloat16* w2 = (const __nv_bfloat16*)d_in[6];
    const __nv_bfloat16* b2 = (const __nv_bfloat16*)d_in[7];
    const __nv_bfloat16* gate = (const __nv_bfloat16*)d_in[8];

    void* fp = nullptr;
    cudaDriverEntryPointQueryResult qr;
    cudaGetDriverEntryPoint("cuTensorMapEncodeTiled", &fp, cudaEnableDefault, &qr);
    EncodeFn enc = (EncodeFn)fp;
    void *pH, *pKV;
    cudaGetSymbolAddress(&pH, gH);
    cudaGetSymbolAddress(&pKV, gKV);

    Maps tm;
    const CUtensorMapSwizzle S128 = CU_TENSOR_MAP_SWIZZLE_128B, S64 = CU_TENSOR_MAP_SWIZZLE_64B;
    { cuuint64_t d[2] = {DM, SEQ}, s[1] = {DM * 2}; cuuint32_t b[2] = {64, 128}; make_map(enc, &tm.x, x, 2, d, s, b, S128); }
    { cuuint64_t d[3] = {DM, DM, 3}, s[2] = {3 * DM * 2, DM * 2}; cuuint32_t b[3] = {64, 32, 2}; make_map(enc, &tm.kv, wqkv, 3, d, s, b, S128); }
    { cuuint64_t d[3] = {32, DM, 3 * DM / 32}, s[2] = {3 * DM * 2, 64}; cuuint32_t b[3] = {32, 32, 2}; make_map(enc, &tm.q, wqkv, 3, d, s, b, S64); }
    { cuuint64_t d[3] = {32, DM, FF / 32}, s[2] = {FF * 2, 64}; cuuint32_t b[3] = {32, 32, 1}; make_map(enc, &tm.f1, w1, 3, d, s, b, S64); }
    { cuuint64_t d[3] = {32, DM, FF / 32}, s[2] = {FF * 2, 64}; cuuint32_t b[3] = {32, 32, 3}; make_map(enc, &tm.f3, w1, 3, d, s, b, S64); }
    { cuuint64_t d[2] = {FF, SEQ}, s[1] = {FF * 2}; cuuint32_t b[2] = {64, 64}; make_map(enc, &tm.h, pH, 2, d, s, b, S128); }
    { cuuint64_t d[5] = {DM, 2, 4, 4, FF / 32}, s[4] = {1024, 8 * 1024, 2 * 1024, 32 * 1024}; cuuint32_t b[5] = {64, 2, 4, 4, 2};
      make_map(enc, &tm.w2, w2, 5, d, s, b, S128); }
    { cuuint64_t d[2] = {DM, DM}, s[1] = {DM * 2}; cuuint32_t b[2] = {64, 64}; make_map(enc, &tm.wo, wo, 2, d, s, b, S128); }

    { cuuint64_t d[3] = {32, SEQ, FF / 32}, s[2] = {FF * 2, 64}; cuuint32_t b[3] = {32, 64, 1}; make_map(enc, &tm.hs, pH, 3, d, s, b, CU_TENSOR_MAP_SWIZZLE_NONE); }
    { cuuint64_t d[5] = {64, 16, 16, 2, 2 * NH}, s[4] = {4096, 128, 2048, 65536}; cuuint32_t b[5] = {64, 8, 2, 2, 1};
      make_map(enc, &tm.kvs, pKV, 5, d, s, b, S128); }
    cudaFuncSetAttribute(fused_kernel, cudaFuncAttributeMaxDynamicSharedMemorySize, TL_SMEM);
    fused_kernel<<<128, 640, TL_SMEM, cudaStreamPerThread>>>(tm, x, wqkv, wo, w1, b1, w2, b2, gate, (__nv_bfloat16*)d_out);
}
```

```cpp
#include <cuda_runtime.h>
#include <cuda_bf16.h>
#include <cuda_fp16.h>
#include <cuda.h>
#include <stdint.h>

#define SEQ 2048
#define DM 512
#define FF 1792
#define NH 32

__device__ __align__(1024) uint8_t gQ[NH * SEQ * 32];
__device__ __align__(1024) uint8_t gKV[NH * SEQ * 64];
__device__ __align__(1024) __nv_bfloat16 gH[SEQ * FF];
__device__ __align__(1024) uint4 gO[32 * NH * 128];
__device__ float gG[SEQ];
__device__ float gN[3 * 8 * 128];
__device__ unsigned int gCntQ[8 * 32];
__device__ unsigned int gCntH[32 * 32];
__device__ unsigned int gEpoch[128];

__device__ __forceinline__ uint32_t smem_u32(const void* p) { return (uint32_t)__cvta_generic_to_shared(p); }
__device__ __forceinline__ void mbar_init(uint32_t a, uint32_t c) { asm volatile("mbarrier.init.shared::cta.b64 [%0], %1;" ::"r"(a), "r"(c)); }
__device__ __forceinline__ void mbar_expect(uint32_t a, uint32_t b) { asm volatile("mbarrier.arrive.expect_tx.shared::cta.b64 _, [%0], %1;" ::"r"(a), "r"(b) : "memory"); }
__device__ __forceinline__ void mbar_arrive(uint32_t a) { asm volatile("mbarrier.arrive.shared::cta.b64 _, [%0];" ::"r"(a) : "memory"); }
__device__ __forceinline__ void mbar_wait(uint32_t a, uint32_t ph) {
    asm volatile("{\n.reg .pred p;\n.reg .u32 n;\nmov.u32 n, 0;\nW_%=:\nmbarrier.try_wait.parity.shared::cta.b64 p, [%0], %1;\n@p bra D_%=;\n"
                 "add.u32 n, n, 1;\nsetp.lt.u32 p, n, 0x400000;\n@p bra W_%=;\ntrap;\nD_%=:\n}" ::"r"(a), "r"(ph) : "memory");
}
__device__ __forceinline__ void mbar_arrive_cluster(uint32_t a, uint32_t cta) {
    asm volatile("{\n.reg .b32 r;\nmapa.shared::cluster.u32 r, %0, %1;\nmbarrier.arrive.shared::cluster.b64 _, [r];\n}" ::"r"(a), "r"(cta) : "memory");
}
__device__ __forceinline__ void bar_sync(int id, int n) { asm volatile("bar.sync %0, %1;" ::"r"(id), "r"(n) : "memory"); }
__device__ __forceinline__ void bar_arrive(int id, int n) { asm volatile("bar.arrive %0, %1;" ::"r"(id), "r"(n) : "memory"); }
__device__ __forceinline__ uint32_t cluster_rank() { uint32_t r; asm("mov.u32 %0, %%cluster_ctarank;" : "=r"(r)); return r; }
__device__ __forceinline__ void cnt_add(unsigned int* c) { asm volatile("red.release.gpu.global.add.u32 [%0], 1;" ::"l"(c) : "memory"); }
__device__ __forceinline__ void cnt_wait(const unsigned int* c, uint32_t target) {
    uint32_t v;
    int spins = 0;
    while (true) {
        asm volatile("ld.acquire.gpu.global.u32 %0, [%1];" : "=r"(v) : "l"(c) : "memory");
        if ((int)(v - target) >= 0) break;
        if (++spins > (1 << 22)) __trap();
        __nanosleep(40);
    }
}
__device__ __forceinline__ void tma2d(uint32_t dst, const CUtensorMap* m, int c0, int c1, uint32_t bar) {
    asm volatile("cp.async.bulk.tensor.2d.shared::cluster.global.mbarrier::complete_tx::bytes [%0], [%1, {%3, %4}], [%2];"
                 ::"r"(dst), "l"(m), "r"(bar), "r"(c0), "r"(c1) : "memory");
}
__device__ __forceinline__ void tma2d_mc(uint32_t dst, const CUtensorMap* m, int c0, int c1, uint32_t bar) {
    asm volatile("cp.async.bulk.tensor.2d.shared::cluster.global.mbarrier::complete_tx::bytes.multicast::cluster [%0], [%1, {%3, %4}], [%2], %5;"
                 ::"r"(dst), "l"(m), "r"(bar), "r"(c0), "r"(c1), "h"((uint16_t)3) : "memory");
}
__device__ __forceinline__ void tma3d_mc(uint32_t dst, const CUtensorMap* m, int c0, int c1, int c2, uint32_t bar) {
    asm volatile("cp.async.bulk.tensor.3d.shared::cluster.global.mbarrier::complete_tx::bytes.multicast::cluster [%0], [%1, {%3, %4, %5}], [%2], %6;"
                 ::"r"(dst), "l"(m), "r"(bar), "r"(c0), "r"(c1), "r"(c2), "h"((uint16_t)3) : "memory");
}
__device__ __forceinline__ void tma5d_mc(uint32_t dst, const CUtensorMap* m, int c0, int c4, uint32_t bar) {
    asm volatile("cp.async.bulk.tensor.5d.shared::cluster.global.mbarrier::complete_tx::bytes.multicast::cluster [%0], [%1, {%3, %5, %5, %5, %4}], [%2], %6;"
                 ::"r"(dst), "l"(m), "r"(bar), "r"(c0), "r"(c4), "r"(0), "h"((uint16_t)3) : "memory");
}
__device__ __forceinline__ void bulk_mc(uint32_t dst, const void* src, uint32_t bytes, uint32_t bar) {
    asm volatile("cp.async.bulk.shared::cluster.global.mbarrier::complete_tx::bytes.multicast::cluster [%0], [%1], %2, [%3], %4;"
                 ::"r"(dst), "l"(src), "r"(bytes), "r"(bar), "h"((uint16_t)3) : "memory");
}
__device__ __forceinline__ void tma3d_st(const CUtensorMap* m, uint32_t src, int c0, int c1, int c2) {
    asm volatile("cp.async.bulk.tensor.3d.global.shared::cta.bulk_group [%0, {%2, %3, %4}], [%1];" ::"l"(m), "r"(src), "r"(c0), "r"(c1), "r"(c2) : "memory");
}
__device__ __forceinline__ void tma5d_st(const CUtensorMap* m, uint32_t src, int c1, int c2, int c4) {
    asm volatile("cp.async.bulk.tensor.5d.global.shared::cta.bulk_group [%0, {%5, %2, %3, %5, %4}], [%1];"
                 ::"l"(m), "r"(src), "r"(c1), "r"(c2), "r"(c4), "r"(0) : "memory");
}
__device__ __forceinline__ void bulk_st(void* dst, uint32_t src, uint32_t bytes) {
    asm volatile("cp.async.bulk.global.shared::cta.bulk_group [%0], [%1], %2;" ::"l"(dst), "r"(src), "r"(bytes) : "memory");
}
__device__ __forceinline__ void sts64(uint32_t a, uint32_t x, uint32_t y) { asm volatile("st.shared.v2.u32 [%0], {%1, %2};" ::"r"(a), "r"(x), "r"(y) : "memory"); }
__device__ __forceinline__ void sts128(uint32_t a, const uint32_t* v) {
    asm volatile("st.shared.v4.u32 [%0], {%1, %2, %3, %4};" ::"r"(a), "r"(v[0]), "r"(v[1]), "r"(v[2]), "r"(v[3]) : "memory");
}
__device__ __forceinline__ void l2_prefetch(const void* src, uint32_t bytes) {
    asm volatile("cp.async.bulk.prefetch.L2.global [%0], %1;" ::"l"(src), "r"(bytes) : "memory");
}
__device__ __forceinline__ void map_prefetch(const CUtensorMap* m) { asm volatile("prefetch.tensormap [%0];" ::"l"(m) : "memory"); }
__device__ __forceinline__ void wg_fence() { asm volatile("wgmma.fence.sync.aligned;" ::: "memory"); }
__device__ __forceinline__ void wg_commit() { asm volatile("wgmma.commit_group.sync.aligned;" ::: "memory"); }
template <int N> __device__ __forceinline__ void wg_wait() { asm volatile("wgmma.wait_group.sync.aligned %0;" ::"n"(N) : "memory"); }
template <int N> __device__ __forceinline__ void pin(float* s) {
#pragma unroll
    for (int i = 0; i < N; i++) asm volatile("" : "+f"(s[i])::"memory");
}
template <int N> __device__ __forceinline__ void pin(uint32_t* s) {
#pragma unroll
    for (int i = 0; i < N; i++) asm volatile("" : "+r"(s[i])::"memory");
}
__device__ __forceinline__ uint64_t mkdesc(uint32_t addr, uint32_t lbo, uint32_t sbo, uint32_t swz) {
    return (uint64_t)((addr & 0x3FFFF) >> 4) | ((uint64_t)(lbo >> 4) << 16) | ((uint64_t)(sbo >> 4) << 32) | ((uint64_t)swz << 62);
}
__device__ __forceinline__ float ex2f(float x) { float y; asm("ex2.approx.ftz.f32 %0, %1;" : "=f"(y) : "f"(x)); return y; }
__device__ __forceinline__ float tanhf_(float x) { float y; asm("tanh.approx.f32 %0, %1;" : "=f"(y) : "f"(x)); return y; }
__device__ __forceinline__ uint32_t pk_bf16(float lo, float hi) { uint32_t r; asm("cvt.rn.bf16x2.f32 %0, %1, %2;" : "=r"(r) : "f"(hi), "f"(lo)); return r; }
__device__ __forceinline__ uint32_t pk_f16(float lo, float hi) { uint32_t r; asm("cvt.rn.f16x2.f32 %0, %1, %2;" : "=r"(r) : "f"(hi), "f"(lo)); return r; }
__device__ __forceinline__ float bf_lo(uint32_t v) { return __uint_as_float(v << 16); }
__device__ __forceinline__ float bf_hi(uint32_t v) { return __uint_as_float(v & 0xffff0000u); }
__device__ __forceinline__ float dot8(const uint4& a, const uint4& b) {
    return fmaf(bf_lo(a.x), bf_lo(b.x), fmaf(bf_hi(a.x), bf_hi(b.x), fmaf(bf_lo(a.y), bf_lo(b.y), bf_hi(a.y) * bf_hi(b.y)))) +
           fmaf(bf_lo(a.z), bf_lo(b.z), fmaf(bf_hi(a.z), bf_hi(b.z), fmaf(bf_lo(a.w), bf_lo(b.w), bf_hi(a.w) * bf_hi(b.w))));
}
__device__ __forceinline__ uint32_t epoch() {
    uint32_t v;
    asm volatile("ld.global.u32 %0, [%1];" : "=r"(v) : "l"(gEpoch + blockIdx.x));
    return v + 1;
}
__device__ __forceinline__ float ldcg_f(const float* p) { return __ldcg(p); }

extern __shared__ __align__(1024) uint8_t smem_raw[];
#define TLM(k, slot) do {} while (0)
#define TLC(k, slot) do {} while (0)
#define TL_INIT() do {} while (0)
#define TL_DUMP() do {} while (0)
#define TL_SMEM SMEM_BYTES

__device__ __forceinline__ void wgmma_ss_n128(float* d, uint64_t da, uint64_t db) {
    asm volatile("wgmma.mma_async.sync.aligned.m64n128k16.f32.bf16.bf16 {"
        "%0, %1, %2, %3, %4, %5, %6, %7, %8, %9, %10, %11, %12, %13, %14, %15,"
        "%16, %17, %18, %19, %20, %21, %22, %23, %24, %25, %26, %27, %28, %29, %30, %31,"
        "%32, %33, %34, %35, %36, %37, %38, %39, %40, %41, %42, %43, %44, %45, %46, %47,"
        "%48, %49, %50, %51, %52, %53, %54, %55, %56, %57, %58, %59, %60, %61, %62, %63}, %64, %65, 1, 1, 1, 0, 1;\n"
        :
        "+f"(d[0]), "+f"(d[1]), "+f"(d[2]), "+f"(d[3]), "+f"(d[4]), "+f"(d[5]), "+f"(d[6]), "+f"(d[7]),
        "+f"(d[8]), "+f"(d[9]), "+f"(d[10]), "+f"(d[11]), "+f"(d[12]), "+f"(d[13]), "+f"(d[14]), "+f"(d[15]),
        "+f"(d[16]), "+f"(d[17]), "+f"(d[18]), "+f"(d[19]), "+f"(d[20]), "+f"(d[21]), "+f"(d[22]), "+f"(d[23]),
        "+f"(d[24]), "+f"(d[25]), "+f"(d[26]), "+f"(d[27]), "+f"(d[28]), "+f"(d[29]), "+f"(d[30]), "+f"(d[31]),
        "+f"(d[32]), "+f"(d[33]), "+f"(d[34]), "+f"(d[35]), "+f"(d[36]), "+f"(d[37]), "+f"(d[38]), "+f"(d[39]),
        "+f"(d[40]), "+f"(d[41]), "+f"(d[42]), "+f"(d[43]), "+f"(d[44]), "+f"(d[45]), "+f"(d[46]), "+f"(d[47]),
        "+f"(d[48]), "+f"(d[49]), "+f"(d[50]), "+f"(d[51]), "+f"(d[52]), "+f"(d[53]), "+f"(d[54]), "+f"(d[55]),
        "+f"(d[56]), "+f"(d[57]), "+f"(d[58]), "+f"(d[59]), "+f"(d[60]), "+f"(d[61]), "+f"(d[62]), "+f"(d[63])
        : "l"(da), "l"(db));
}
__device__ __forceinline__ void wgmma_ss_n96(float* d, uint64_t da, uint64_t db) {
    asm volatile("wgmma.mma_async.sync.aligned.m64n96k16.f32.bf16.bf16 {"
        "%0, %1, %2, %3, %4, %5, %6, %7, %8, %9, %10, %11, %12, %13, %14, %15,"
        "%16, %17, %18, %19, %20, %21, %22, %23, %24, %25, %26, %27, %28, %29, %30, %31,"
        "%32, %33, %34, %35, %36, %37, %38, %39, %40, %41, %42, %43, %44, %45, %46, %47}, %48, %49, 1, 1, 1, 0, 1;\n"
        :
        "+f"(d[0]), "+f"(d[1]), "+f"(d[2]), "+f"(d[3]), "+f"(d[4]), "+f"(d[5]), "+f"(d[6]), "+f"(d[7]),
        "+f"(d[8]), "+f"(d[9]), "+f"(d[10]), "+f"(d[11]), "+f"(d[12]), "+f"(d[13]), "+f"(d[14]), "+f"(d[15]),
        "+f"(d[16]), "+f"(d[17]), "+f"(d[18]), "+f"(d[19]), "+f"(d[20]), "+f"(d[21]), "+f"(d[22]), "+f"(d[23]),
        "+f"(d[24]), "+f"(d[25]), "+f"(d[26]), "+f"(d[27]), "+f"(d[28]), "+f"(d[29]), "+f"(d[30]), "+f"(d[31]),
        "+f"(d[32]), "+f"(d[33]), "+f"(d[34]), "+f"(d[35]), "+f"(d[36]), "+f"(d[37]), "+f"(d[38]), "+f"(d[39]),
        "+f"(d[40]), "+f"(d[41]), "+f"(d[42]), "+f"(d[43]), "+f"(d[44]), "+f"(d[45]), "+f"(d[46]), "+f"(d[47])
        : "l"(da), "l"(db));
}
__device__ __forceinline__ void wgmma_ss_n64(float* d, uint64_t da, uint64_t db) {
    asm volatile("wgmma.mma_async.sync.aligned.m64n64k16.f32.bf16.bf16 {"
        "%0, %1, %2, %3, %4, %5, %6, %7, %8, %9, %10, %11, %12, %13, %14, %15,"
        "%16, %17, %18, %19, %20, %21, %22, %23, %24, %25, %26, %27, %28, %29, %30, %31}, %32, %33, 1, 1, 1, 0, 1;\n"
        :
        "+f"(d[0]), "+f"(d[1]), "+f"(d[2]), "+f"(d[3]), "+f"(d[4]), "+f"(d[5]), "+f"(d[6]), "+f"(d[7]),
        "+f"(d[8]), "+f"(d[9]), "+f"(d[10]), "+f"(d[11]), "+f"(d[12]), "+f"(d[13]), "+f"(d[14]), "+f"(d[15]),
        "+f"(d[16]), "+f"(d[17]), "+f"(d[18]), "+f"(d[19]), "+f"(d[20]), "+f"(d[21]), "+f"(d[22]), "+f"(d[23]),
        "+f"(d[24]), "+f"(d[25]), "+f"(d[26]), "+f"(d[27]), "+f"(d[28]), "+f"(d[29]), "+f"(d[30]), "+f"(d[31])
        : "l"(da), "l"(db));
}
__device__ __forceinline__ void wgmma_qk_f16_acc(float* d, const uint32_t* a, uint64_t db) {
    asm volatile("wgmma.mma_async.sync.aligned.m64n64k16.f32.f16.f16 {"
        "%0, %1, %2, %3, %4, %5, %6, %7, %8, %9, %10, %11, %12, %13, %14, %15,"
        "%16, %17, %18, %19, %20, %21, %22, %23, %24, %25, %26, %27, %28, %29, %30, %31}, {%32, %33, %34, %35}, %36, 1, 1, 1, 0;\n"
        :
        "+f"(d[0]), "+f"(d[1]), "+f"(d[2]), "+f"(d[3]), "+f"(d[4]), "+f"(d[5]), "+f"(d[6]), "+f"(d[7]),
        "+f"(d[8]), "+f"(d[9]), "+f"(d[10]), "+f"(d[11]), "+f"(d[12]), "+f"(d[13]), "+f"(d[14]), "+f"(d[15]),
        "+f"(d[16]), "+f"(d[17]), "+f"(d[18]), "+f"(d[19]), "+f"(d[20]), "+f"(d[21]), "+f"(d[22]), "+f"(d[23]),
        "+f"(d[24]), "+f"(d[25]), "+f"(d[26]), "+f"(d[27]), "+f"(d[28]), "+f"(d[29]), "+f"(d[30]), "+f"(d[31])
        : "r"(a[0]), "r"(a[1]), "r"(a[2]), "r"(a[3]), "l"(db));
}
__device__ __forceinline__ void wgmma_qk_bf16_zero(float* d, const uint32_t* a, uint64_t db) {
    asm volatile("wgmma.mma_async.sync.aligned.m64n64k16.f32.bf16.bf16 {"
        "%0, %1, %2, %3, %4, %5, %6, %7, %8, %9, %10, %11, %12, %13, %14, %15,"
        "%16, %17, %18, %19, %20, %21, %22, %23, %24, %25, %26, %27, %28, %29, %30, %31}, {%32, %33, %34, %35}, %36, 0, 1, 1, 0;\n"
        :
        "=f"(d[0]), "=f"(d[1]), "=f"(d[2]), "=f"(d[3]), "=f"(d[4]), "=f"(d[5]), "=f"(d[6]), "=f"(d[7]),
        "=f"(d[8]), "=f"(d[9]), "=f"(d[10]), "=f"(d[11]), "=f"(d[12]), "=f"(d[13]), "=f"(d[14]), "=f"(d[15]),
        "=f"(d[16]), "=f"(d[17]), "=f"(d[18]), "=f"(d[19]), "=f"(d[20]), "=f"(d[21]), "=f"(d[22]), "=f"(d[23]),
        "=f"(d[24]), "=f"(d[25]), "=f"(d[26]), "=f"(d[27]), "=f"(d[28]), "=f"(d[29]), "=f"(d[30]), "=f"(d[31])
        : "r"(a[0]), "r"(a[1]), "r"(a[2]), "r"(a[3]), "l"(db));
}
__device__ __forceinline__ void wgmma_pv(float* d, const uint32_t* a, uint64_t db) {
    asm volatile("wgmma.mma_async.sync.aligned.m64n24k16.f32.bf16.bf16 {"
        "%0, %1, %2, %3, %4, %5, %6, %7, %8, %9, %10, %11}, {%12, %13, %14, %15}, %16, 1, 1, 1, 1;\n"
        :
        "+f"(d[0]), "+f"(d[1]), "+f"(d[2]), "+f"(d[3]), "+f"(d[4]), "+f"(d[5]), "+f"(d[6]), "+f"(d[7]),
        "+f"(d[8]), "+f"(d[9]), "+f"(d[10]), "+f"(d[11])
        : "r"(a[0]), "r"(a[1]), "r"(a[2]), "r"(a[3]), "l"(db));
}

template <int N> __device__ __forceinline__ void wgmma_ss(float* d, uint64_t a, uint64_t b) {
    if (N == 128) wgmma_ss_n128(d, a, b);
    if (N == 96) wgmma_ss_n96(d, a, b);
    if (N == 64) wgmma_ss_n64(d, a, b);
}

#define OFF_R 131072
#define OFF_ONE 229376
#define OFF_BAR 229888
#define OFF_BIAS (OFF_BAR + 672)
#define OFF_G (OFF_BIAS + 1152)
#define SMEM_BYTES (OFF_G + 272)
#define SBD 1024u
#define B_X 0
#define B_F1 416
#define B_E1 112
#define B_KV 160
#define B_F2 224
#define B_E2 256
#define B_T 288
#define B_DONE 352
#define B_G 360
#define B_G2 368
#define B_G3 376
#define B_SF 384
#define B_SF2 408
#define NR 6

#define PF 1
#define PFX 0
#define PACE 0
#define EXP_FKK 4
#define QSCALE 0.36067376022224085f
#define MAGIC 445.41763f
#define NMUFU 4
#define VSTEP ((uint64_t)((long long)32 - ((long long)32 << 16)))

#define XMASK 0x0D55u
#define KVMASK 0x1D55u
__host__ __device__ constexpr int strm_pos(int pass, int i) {
    if (pass == 1 || pass == 2) return 8 + 8 * pass + i;
    int n = 0;
    for (int p = 0; p < 16; p++)
        if ((int)((KVMASK >> p) & 1) == (pass == 3)) { if (n == i) return p; n++; }
    return 0;
}
__host__ __device__ constexpr uint32_t strm_code(int pass) {
    uint32_t c = 0;
    for (int i = 0; i < 7; i++) c |= (uint32_t)(strm_pos(pass, i + 1) - strm_pos(pass, i)) << (4 * i);
    return c;
}

template <int N, int SUB, int KST, int LBO, int SBO, int SWZ>
__device__ __forceinline__ void gemm_pass(float* acc, uint32_t bar, uint64_t dA, int lane, uint32_t pos, uint32_t code, int barNext, bool waitx) {
    uint32_t prev = 0, slot = pos % NR;
#pragma unroll 1
    for (int i = 0; i < 8; i++) {
        if (waitx) mbar_wait(bar + B_X + 8 * i, 0);
        mbar_wait(bar + B_F1 + 8 * pos, 0);
        const uint64_t dB = mkdesc(SBD + OFF_R, LBO, SBO, SWZ) + slot * 1024;
        wg_fence();
        wgmma_ss<N>(acc, dA, dB);
        wgmma_ss<N>(acc, dA + 2, dB + KST / 16);
        wg_commit();
        wg_wait<1>();
        if (i > 0 && lane < 2) mbar_arrive_cluster(bar + B_E1 + 8 * prev, lane);
        wgmma_ss<N>(acc, dA + 4, dB + SUB / 16);
        wgmma_ss<N>(acc, dA + 6, dB + (SUB + KST) / 16);
        wg_commit();
        prev = slot;
        pos += code & 15;
        slot += code & 15;
        if (slot >= NR) slot -= NR;
        code >>= 4;
        dA += 1024;
    }
    if (barNext) bar_arrive(barNext, 512);
    wg_wait<0>();
    if (lane < 2) mbar_arrive_cluster(bar + B_E1 + 8 * prev, lane);
    pin<N / 2>(acc);
}

__device__ __forceinline__ uint32_t lds32(uint32_t a) { uint32_t v; asm volatile("ld.shared.u32 %0, [%1];" : "=r"(v) : "r"(a)); return v; }
__device__ __forceinline__ bool elect() {
    uint32_t p;
    asm volatile("{\n.reg .pred p;\nelect.sync _|p, 0xffffffff;\nselp.u32 %0, 1, 0, p;\n}" : "=r"(p));
    return p;
}

template <int G0, int G1> __device__ __forceinline__ void gelu_store(const float* acc, uint32_t bias, uint32_t hp) {
#pragma unroll
    for (int G = G0; G < G1; G++) {
        uint32_t o[8];
#pragma unroll
        for (int j = 0; j < 4; j++) {
            float bv[2];
            asm volatile("ld.shared.v2.f32 {%0, %1}, [%2];" : "=f"(bv[0]), "=f"(bv[1]) : "r"(bias + G * 128 + j * 32));
            float y[4];
#pragma unroll
            for (int i = 0; i < 4; i++) {
                const float h = acc[16 * G + 4 * j + i] + bv[i & 1];
                const float z = h * fmaf(h * h, 0.035677408136300125f, 0.7978845608028654f);
                y[i] = fmaf(h, tanhf_(z), h);
            }
            o[j] = pk_bf16(y[0], y[1]);
            o[4 + j] = pk_bf16(y[2], y[3]);
        }
        sts128(hp + G * 32768, o);
        sts128(hp + G * 32768 + 512, o + 4);
    }
}

__device__ __forceinline__ float norm_bound(const float* v, float sc) {
    uint32_t m = 0;
#pragma unroll
    for (int h = 0; h < 4; h++) {
        const float* u = v + 8 * h;
        m = max(m, __float_as_uint(fmaf(u[0], u[0], fmaf(u[1], u[1], fmaf(u[4], u[4], u[5] * u[5])))));
        m = max(m, __float_as_uint(fmaf(u[2], u[2], fmaf(u[3], u[3], fmaf(u[6], u[6], u[7] * u[7])))));
    }
#pragma unroll
    for (int o = 4; o < 32; o <<= 1) m = max(m, __shfl_xor_sync(0xffffffffu, m, o));
    float f = __uint_as_float(m);
    f += __shfl_xor_sync(0xffffffffu, f, 1);
    f += __shfl_xor_sync(0xffffffffu, f, 2);
    return f * sc;
}

__device__ __forceinline__ uint32_t exp2_pair(float a, float b, uint32_t m1) {
    const uint32_t w = __byte_perm(__float_as_uint(a), __float_as_uint(b), 0x6521);
    uint32_t m, r;
    asm("lop3.b32 %0, %1, 0x007f007f, 0x9f809f80, 0xEA;" : "=r"(m) : "r"(w));
    const uint32_t e = w - m;
    asm("fma.rn.bf16x2 %0, %1, %2, %3;" : "=r"(r) : "r"(w), "r"(m), "r"(e));
    return r;
}

__device__ __forceinline__ void store_o(const float* o, uint4* dst, uint32_t par) {
    const float s0 = __fdividef(1.f, o[8]), s1 = __fdividef(1.f, o[10]);
    const uint32_t d0 = (pk_bf16(o[0] * s0, o[1] * s0) & ~1u) | par;
    asm volatile("{\n.reg .b128 t;\nmov.b128 t, {%0, %1, %2, %3};\nst.relaxed.gpu.global.b128 [%4], t;\n}" ::"r"(d0),
                 "r"(pk_bf16(o[4] * s0, o[5] * s0)), "r"(pk_bf16(o[2] * s1, o[3] * s1)), "r"(pk_bf16(o[6] * s1, o[7] * s1)), "l"(dst) : "memory");
}
__device__ __forceinline__ uint4 load_o(const uint4* src) {
    uint4 v;
    asm volatile("{\n.reg .b128 t;\nld.relaxed.gpu.global.b128 t, [%4];\nmov.b128 {%0, %1, %2, %3}, t;\n}"
                 : "=r"(v.x), "=r"(v.y), "=r"(v.z), "=r"(v.w) : "l"(src) : "memory");
    return v;
}
__device__ __forceinline__ uint32_t bmul2(uint32_t a, uint32_t b) { uint32_t r; asm("mul.rn.bf16x2 %0, %1, %2;" : "=r"(r) : "r"(a), "r"(b)); return r; }
__device__ __forceinline__ void sts32(uint32_t a, uint32_t v) { asm volatile("st.shared.u32 [%0], %1;" ::"r"(a), "r"(v) : "memory"); }
__device__ __forceinline__ void load_q(uint32_t* q, int h, int row, int t) {
    const uint8_t* p = gQ + (size_t)h * (SEQ * 32) + (size_t)row * 32 + t * 4;
    q[0] = __ldcg((const uint32_t*)p); q[1] = __ldcg((const uint32_t*)(p + 256));
    q[2] = __ldcg((const uint32_t*)(p + 16)); q[3] = __ldcg((const uint32_t*)(p + 272));
}

template <int NT>
__device__ __forceinline__ void proj16(float (*c)[8], const __nv_bfloat16* x, const __nv_bfloat16* w, int row0, int rstep, int col, int g, int t) {
#pragma unroll
    for (int i = 0; i < NT; i++)
#pragma unroll
        for (int j = 0; j < 8; j++) c[i][j] = 0.f;
    const unsigned short* wu = (const unsigned short*)w;
#pragma unroll 1
    for (int k = 0; k < DM; k += 16) {
        uint32_t b[4];
#pragma unroll
        for (int j = 0; j < 4; j++) {
            const int kr = k + 2 * t + (j & 1) * 8, cc = col + g + (j >> 1) * 8;
            b[j] = (uint32_t)wu[(size_t)kr * (3 * DM) + cc] | ((uint32_t)wu[(size_t)(kr + 1) * (3 * DM) + cc] << 16);
        }
#pragma unroll
        for (int i = 0; i < NT; i++) {
            const __nv_bfloat16* xp = x + (size_t)(row0 + i * rstep + g) * DM + k + 2 * t;
            const uint32_t a0 = *(const uint32_t*)xp, a1 = *(const uint32_t*)(xp + 8 * DM);
            const uint32_t a2 = *(const uint32_t*)(xp + 8), a3 = *(const uint32_t*)(xp + 8 * DM + 8);
#pragma unroll
            for (int j = 0; j < 2; j++)
                asm volatile("mma.sync.aligned.m16n8k16.row.col.f32.bf16.bf16.f32 {%0,%1,%2,%3}, {%4,%5,%6,%7}, {%8,%9}, {%0,%1,%2,%3};"
                             : "+f"(c[i][4 * j]), "+f"(c[i][4 * j + 1]), "+f"(c[i][4 * j + 2]), "+f"(c[i][4 * j + 3])
                             : "r"(a0), "r"(a1), "r"(a2), "r"(a3), "r"(b[2 * j]), "r"(b[2 * j + 1]));
        }
    }
}

struct Maps { CUtensorMap x, kv, q, f1, f3, h, w2, wo, hs, kvs; };

__global__ void __cluster_dims__(2, 1, 1) __launch_bounds__(640, 1)
fused_kernel(const __grid_constant__ Maps tm, const __nv_bfloat16* __restrict__ x, const __nv_bfloat16* __restrict__ wqkv,
             const __nv_bfloat16* __restrict__ wo, const __nv_bfloat16* __restrict__ w1, const __nv_bfloat16* __restrict__ b1,
             const __nv_bfloat16* __restrict__ w2, const __nv_bfloat16* __restrict__ b2, const __nv_bfloat16* __restrict__ gate,
             __nv_bfloat16* __restrict__ out, const uint32_t m1) {
    const uint32_t sb = smem_u32(smem_raw);
    const uint32_t bar = sb + OFF_BAR;
    const int tid = threadIdx.x, lane = tid & 31;
    const int warp = __shfl_sync(0xffffffffu, tid >> 5, 0);
    const uint32_t rank = cluster_rank();
    const int cl = blockIdx.x >> 1;
    const int nb = cl & 7, mb = (cl >> 3) * 2 + rank;
    const int g = lane >> 2, t = lane & 3;

    const int cb = nb & 3, rb = mb * 2 + (nb >> 2);
    if (tid == 0) TLM(0, 0);
    TL_INIT();
    if (tid == 512) {
        for (int i = 0; i < 8; i++) { mbar_init(bar + B_X + 8 * i, 1); mbar_init(bar + B_KV + 8 * i, 1); mbar_init(bar + B_T + 8 * i, 5); }
        for (int i = 0; i < NR; i++) mbar_init(bar + B_E1 + 8 * i, 16);
        for (int i = 0; i < 4; i++) { mbar_init(bar + B_F2 + 8 * i, 1); mbar_init(bar + B_E2 + 8 * i, 8); }
        asm volatile("fence.mbarrier_init.release.cluster;" ::: "memory");
    } else if (tid == 608) {
        for (int i = 0; i < 32; i++) mbar_init(bar + B_F1 + 8 * i, 1);
        mbar_init(bar + B_DONE, 16);
        mbar_init(bar + B_G, 1);
        for (int i = 0; i < 3; i++) mbar_init(bar + B_SF + 8 * i, i == 1 ? 2 : 1);
        mbar_init(bar + B_SF2, 2);
        mbar_init(bar + B_G3, 1);
        mbar_init(bar + B_G2, 4);
        asm volatile("fence.mbarrier_init.release.cluster;" ::: "memory");
    }
    __syncwarp();
    asm volatile("barrier.cluster.arrive.relaxed.aligned;" ::: "memory");
    if (warp == 19) mbar_expect(bar + B_F1 + 8 * lane, ((KVMASK >> lane) & 1) ? 16384 : 12288);
    if (warp == 16 && lane < 24) mbar_expect(bar + (lane < 8 ? B_X : lane < 16 ? B_KV - 64 : B_T - 128) + 8 * lane, 16384);
    if (tid == 512) {
        tma2d(sb, &tm.x, 0, mb * 128, bar + B_X);
    } else if (tid == 544) {
        map_prefetch(&tm.kv);
        l2_prefetch((const uint8_t*)wqkv + (size_t)blockIdx.x * 3072, 3072);
        l2_prefetch((const uint8_t*)w1 + (size_t)blockIdx.x * 1792, 1792);
        map_prefetch(&tm.q); map_prefetch(&tm.f1); map_prefetch(&tm.f3);
    }
    if ((sb & 0xFFFFFF) != SBD) __trap();
    __syncwarp();
    asm volatile("barrier.cluster.wait.aligned;" ::: "memory");
    if (tid == 0) { TLM(0, 1); TLC(0, 30); }

    if (warp < 16) {
        const int wg = warp >> 2;
        const int h = cl >> 1, qd = (cl & 1) * 2 + rank;
        uint32_t q[4];
        {
            const int w8 = warp & 7;
            const int T = mb * 8 + w8, row0 = T * 16 + g;
            const uint64_t dA0 = mkdesc(SBD + (wg & 1) * 8192, 16, 1024, 1);
            if (wg < 2) {
                float acc[64];
#pragma unroll
                for (int i = 0; i < 64; i++) acc[i] = 0.f;
                gemm_pass<128, 8192, 2048, 4096, 1024, 1>(acc, bar, dA0, lane, strm_pos(3, 0), strm_code(3), 0, true);
                if (tid == 0) TLM(0, 2);
                {
                    const float km = norm_bound(acc, 1.f);
                    float vm = 0.f;
#pragma unroll
                    for (int i = 32; i < 64; i++) vm = fmaxf(vm, fabsf(acc[i]));
                    vm = __uint_as_float(__reduce_max_sync(0xffffffffu, __float_as_uint(vm)));
                    if (lane == 0) { gN[1024 + nb * 128 + T] = km; gN[2048 + nb * 128 + T] = vm; }
                    const uint32_t kp = sb + OFF_R + 12288 + (w8 >> 2) * 1024 + g * 128 + ((((w8 & 3) * 2 + ((t >> 1) ^ (w8 >> 2))) ^ g) << 4) + (t & 1) * 8;
                    uint8_t* vp = gKV + (size_t)(nb * 4) * (SEQ * 64) + 65536 + (((T >> 6) * 16 + 2 * g) * 64 + (T & 63)) * 32 + ((t * 8) ^ ((w8 >> 2) << 4));
                    bar_sync(9, 256);
#pragma unroll
                    for (int hh = 0; hh < 4; hh++) {
                        const float* v = acc + 8 * hh;
                        float p0 = __shfl_up_sync(0xffffffffu, v[2], 4), p1 = __shfl_up_sync(0xffffffffu, v[3], 4);
                        float p2 = __shfl_up_sync(0xffffffffu, v[6], 4), p3 = __shfl_up_sync(0xffffffffu, v[7], 4);
                        if (g == 0) { p0 = p1 = p2 = p3 = 0.f; }
                        sts64(kp + hh * 16384, pk_f16(v[0] - p0, v[1] - p1), pk_f16(v[4] - p2, v[5] - p3));
                        sts64(kp + hh * 16384 + 2048, pk_f16(v[2] - v[0], v[3] - v[1]), pk_f16(v[6] - v[4], v[7] - v[5]));
                        const float* u = acc + 32 + 8 * hh;
                        if (hh < 2) {
                            sts64(kp + (4 + hh) * 16384, pk_bf16(u[0], u[1]), pk_bf16(u[4], u[5]));
                            sts64(kp + (4 + hh) * 16384 + 2048, pk_bf16(u[2], u[3]), pk_bf16(u[6], u[7]));
                        } else {
                            *(uint2*)(vp + (size_t)hh * (SEQ * 64)) = make_uint2(pk_bf16(u[0], u[1]), pk_bf16(u[4], u[5]));
                            *(uint2*)(vp + (size_t)hh * (SEQ * 64) + 2048) = make_uint2(pk_bf16(u[2], u[3]), pk_bf16(u[6], u[7]));
                        }
                    }
                }
                asm volatile("fence.proxy.async.shared::cta;" ::: "memory");
                bar_arrive(10, 288);
                if (tid == 0) TLM(0, 3);
            }
#pragma unroll 1
            for (int p = wg < 2 ? 1 : 0; p < 3; p += 2) {
                float acc[48];
#pragma unroll
                for (int i = 0; i < 48; i++) acc[i] = 0.f;
                pin<48>(acc);
                if (p) bar_sync(5 + p, 512);
                gemm_pass<96, 6144, 1024, 2048, 512, 2>(acc, bar, dA0, lane, p == 0 ? strm_pos(0, 0) : 8 + 8 * p, p == 0 ? strm_code(0) : strm_code(1), p < 2 ? 6 + p : 0, p == 0);
                if ((tid & 255) == 0) TLM(0, 4 + 2 * p);
                const uint32_t hp = sb + OFF_R + 12288 + (wg & 1) * 16384 + ((warp & 3) * 16 + g) * 64 + t * 16;
                const uint32_t bp = sb + OFF_BIAS + p * 384 - 256 + t * 8;
                if (p == 0) {
                    const float qm = norm_bound(acc, QSCALE * QSCALE);
                    if (lane == 0) gN[nb * 128 + T] = qm;
                    uint8_t* qp = gQ + (size_t)(nb * 4) * (SEQ * 32) + (size_t)row0 * 32 + t * 8;
#pragma unroll
                    for (int hh = 0; hh < 4; hh++) {
                        const float* v = acc + 8 * hh;
                        *(uint2*)(qp + hh * (SEQ * 32)) = make_uint2(pk_f16(v[0] * QSCALE, v[1] * QSCALE), pk_f16(v[4] * QSCALE, v[5] * QSCALE));
                        *(uint2*)(qp + hh * (SEQ * 32) + 256) = make_uint2(pk_f16(v[2] * QSCALE, v[3] * QSCALE), pk_f16(v[6] * QSCALE, v[7] * QSCALE));
                    }
                    bar_arrive(12, 288);
                    mbar_wait(bar + B_SF, 0);
                } else {
                    if (p == 2) {
                        mbar_wait(bar + B_G, 0);
                        load_q(q, h, qd * 512 + warp * 16 + g, t);
                    }
                    mbar_wait(bar + B_SF + 8 * p, 0);
                    gelu_store<0, 2>(acc, bp, hp);
                }
                gelu_store<2, 3>(acc, bp, hp);
                asm volatile("fence.proxy.async.shared::cta;" ::: "memory");
                bar_arrive(p == 1 ? 14 : 11, 288);
                if ((tid & 255) == 0) TLM(0, 5 + 2 * p);
            }
            if (wg < 2) {
                mbar_wait(bar + B_G, 0);
                load_q(q, h, qd * 512 + warp * 16 + g, t);
            }
        }
        mbar_wait(bar + B_G3, 0);
        const uint32_t ep = lds32(sb + OFF_G + 256);
        const bool fast = (ep & 2) != 0;
        uint4* const op = gO + ((qd * 8 + wg) * NH + h) * 128 + (tid & 127);
        const uint64_t kd0 = mkdesc(SBD, 16, 256, 3);
        const uint64_t vd0 = mkdesc(SBD + 8192, OFF_ONE - 8192, 256, 3);
        if (fast) {
#pragma unroll 1
            for (int r = 0; r < 2; r++) {
                float o[12];
#pragma unroll
                for (int i = 0; i < 12; i++) o[i] = 0.f;
                uint64_t kd = kd0, vd = vd0;
                uint32_t qn[4];
#pragma unroll 1
                for (int half = 0; half < 2; half++) {
                    float s[32];
#pragma unroll
                    for (int i = 0; i < 32; i++) s[i] = i < 2 * NMUFU ? 0.f : MAGIC;
#pragma unroll 1
                    for (int c = 0; c < 4; c++) {
                        if (r == 0) mbar_wait(bar + B_KV + 8 * (half * 4 + c), 0);
                        if ((tid & 255) == 0 && c == 0) TLM(1, (tid >> 8) * 4 + r * 2 + half);
                        if (half == 1 && c == 3) {
                            if (r == 0) load_q(qn, h, qd * 512 + 256 + warp * 16 + g, t);
                            else if (lane == 0) mbar_arrive(bar + B_DONE);
                        }
#pragma unroll
                        for (int j = 0; j < 4; j++) {
                            uint32_t p[16];
                            wg_fence();
                            wgmma_qk_f16_acc(s, q, kd);
                            wg_commit();
                            wg_wait<0>();
                            pin<32>(s);
#pragma unroll
                            for (int i = 0; i < 16; i++)
                                p[i] = i < NMUFU ? pk_bf16(ex2f(s[2 * i]), ex2f(s[2 * i + 1])) : exp2_pair(s[2 * i], s[2 * i + 1], m1);
                            pin<16>(p);
                            wg_fence();
#pragma unroll
                            for (int u = 0; u < 4; u++) wgmma_pv(o, p + 4 * u, vd + u * VSTEP);
                            wg_commit();
                            kd += 128;
                            vd += 4 * VSTEP;
                        }
                        kd += 512;
                        vd += 16 * VSTEP;
                    }
                    wg_wait<0>();
                }
                pin<12>(o);
                if ((tid & 127) == 0 && r == 1) TLM(1, 8 + wg);
                store_o(o, op + r * (4 * NH * 128), ep & 1);
#pragma unroll
                for (int i = 0; i < 4; i++) q[i] = qn[i];
            }
            if (tid == 0) { TLM(1, 12); TLC(0, 31); }
        } else {
            for (int c = 0; c < 8; c++) mbar_wait(bar + B_KV + 8 * c, 0);
            {
                float kc[8][8];
                proj16<8>(kc, x, wqkv, warp * 16, 256, DM + h * 16, g, t);
#pragma unroll
                for (int i = 0; i < 8; i++) {
                    const int T = warp + i * 16;
                    const int pos = ((T >> 6) * 16 + 2 * g) * 64 + (T & 63);
                    const uint32_t a = sb + (pos >> 8) * 16384 + (pos & 255) * 32 + t * 4, sw = ((T >> 2) & 1) << 4;
                    asm volatile("st.shared.u32 [%0], %1;" ::"r"(a + sw), "r"(pk_bf16(kc[i][0], kc[i][1])) : "memory");
                    asm volatile("st.shared.u32 [%0], %1;" ::"r"(a + (sw ^ 16)), "r"(pk_bf16(kc[i][4], kc[i][5])) : "memory");
                    asm volatile("st.shared.u32 [%0], %1;" ::"r"(a + 2048 + sw), "r"(pk_bf16(kc[i][2], kc[i][3])) : "memory");
                    asm volatile("st.shared.u32 [%0], %1;" ::"r"(a + 2048 + (sw ^ 16)), "r"(pk_bf16(kc[i][6], kc[i][7])) : "memory");
                }
                asm volatile("fence.proxy.async.shared::cta;" ::: "memory");
                bar_sync(8, 512);
            }
#pragma unroll 1
            for (int r = 0; r < 2; r++) {
                const int row = qd * 512 + r * 256 + warp * 16 + g;
                {
                    float qc[1][8];
                    proj16<1>(qc, x, wqkv, row - g, 0, h * 16, g, t);
#pragma unroll
                    for (int i = 0; i < 4; i++) q[i] = pk_bf16(qc[0][2 * i] * QSCALE, qc[0][2 * i + 1] * QSCALE);
                }
                float o[12];
#pragma unroll
                for (int i = 0; i < 12; i++) o[i] = 0.f;
                float m0 = -INFINITY, m1 = -INFINITY;
#pragma unroll 1
                for (int j = 0; j < 32; j++) {
                    const uint64_t kd = kd0 + (j >> 2) * 1024 + (j & 3) * 128, vd = vd0 + ((j >> 2) * 32 + (j & 3) * 4) * VSTEP;
                    float s[32];
                    uint32_t p[16];
                    wg_fence();
                    wgmma_qk_bf16_zero(s, q, kd);
                    wg_commit();
                    wg_wait<0>();
                    pin<32>(s);
                    pin<12>(o);
                    float n0 = m0, n1 = m1;
#pragma unroll
                    for (int i = 0; i < 8; i++) {
                        n0 = fmaxf(n0, fmaxf(s[4 * i], s[4 * i + 1]));
                        n1 = fmaxf(n1, fmaxf(s[4 * i + 2], s[4 * i + 3]));
                    }
                    n0 = fmaxf(n0, __shfl_xor_sync(0xffffffffu, n0, 1));
                    n1 = fmaxf(n1, __shfl_xor_sync(0xffffffffu, n1, 1));
                    n0 = fmaxf(n0, __shfl_xor_sync(0xffffffffu, n0, 2));
                    n1 = fmaxf(n1, __shfl_xor_sync(0xffffffffu, n1, 2));
                    const float c0 = ex2f(m0 - n0), c1 = ex2f(m1 - n1);
                    m0 = n0;
                    m1 = n1;
#pragma unroll
                    for (int i = 0; i < 3; i++) { o[4 * i] *= c0; o[4 * i + 1] *= c0; o[4 * i + 2] *= c1; o[4 * i + 3] *= c1; }
#pragma unroll
                    for (int i = 0; i < 8; i++) {
                        p[2 * i] = pk_bf16(ex2f(s[4 * i] - m0), ex2f(s[4 * i + 1] - m0));
                        p[2 * i + 1] = pk_bf16(ex2f(s[4 * i + 2] - m1), ex2f(s[4 * i + 3] - m1));
                    }
                    pin<16>(p);
                    pin<12>(o);
                    wg_fence();
#pragma unroll
                    for (int u = 0; u < 4; u++) wgmma_pv(o, p + 4 * u, vd + u * VSTEP);
                    wg_commit();
                }
                wg_wait<0>();
                pin<12>(o);
                if (r == 1 && lane == 0) mbar_arrive(bar + B_DONE);
                store_o(o, op + r * (4 * NH * 128), ep & 1);
            }
        }
        {
            const uint4* src = gO + (rb * NH + wg * 8) * 128 + (tid & 127);
            uint4 v[8];
#pragma unroll
            for (int i = 0; i < 8; i++) v[i] = load_o(src + i * 128);
            mbar_wait(bar + B_DONE, 0);
            mbar_wait(bar + B_G2, 0);
            const int lr = (warp & 3) * 16 + g;
            const uint32_t g0 = lds32(sb + OFF_G + lr * 4), g1 = lds32(sb + OFF_G + lr * 4 + 32);
            const uint32_t a0 = sb + wg * 16384 + lr * 128 + (t >> 1) * 4;
#pragma unroll
            for (int i = 0; i < 8; i++) {
                if ((i & 3) == 0) {
                    int spins = 0;
                    while (__any_sync(0xffffffffu, (((v[i].x ^ ep) | (v[i + 1].x ^ ep) | (v[i + 2].x ^ ep) | (v[i + 3].x ^ ep)) & 1) != 0)) {
                        if (++spins > (1 << 22)) __trap();
#pragma unroll
                        for (int k = i; k < 8; k++)
                            if (((v[k].x ^ ep) & 1) != 0) v[k] = load_o(src + k * 128);
                    }
                }
                const uint32_t a = a0 + (i >> 2) * 8192 + ((((i & 3) * 2 + (t & 1)) ^ g) << 4);
                sts32(a, bmul2(v[i].x, g0));
                sts32(a + 8, bmul2(v[i].y, g0));
                sts32(a + 1024, bmul2(v[i].z, g1));
                sts32(a + 1024 + 8, bmul2(v[i].w, g1));
                if ((i & 3) == 3) {
                    asm volatile("fence.proxy.async.shared::cta;" ::: "memory");
                    __syncwarp();
                    if (lane == 0) mbar_arrive(bar + B_T + 8 * (wg * 2 + (i >> 2)));
                    if ((tid & 127) == 0) TLM(1, 20 + wg * 2 + (i >> 2));
                }
            }
        }
    } else {
        if (warp == 16) {
            if (elect()) {
                const uint32_t dst = sb + OFF_R;
                const int kr = rank * 32;
#pragma unroll
                for (int it = 0; it < 32; it++) {
                    const int s = it % NR;
                    const uint32_t fb = bar + B_F1 + 8 * it;
                    if (it >= NR) mbar_wait(bar + B_E1 + 8 * s, ((it / NR) - 1) & 1);
                    const int nkv = __builtin_popcount(KVMASK & ((1u << it) - 1));
                    if (it < 16 && ((KVMASK >> it) & 1)) {
                        tma3d_mc(dst + s * 16384 + rank * 8192, &tm.kv, nb * 64, nkv * 64 + kr, 1, fb);
                    } else if (it < 16) {
                        tma3d_mc(dst + s * 16384 + rank * 6144, &tm.q, 0, (it - nkv) * 64 + kr, nb * 2, fb);
                        tma3d_mc(dst + s * 16384 + rank * 6144 + 4096, &tm.f1, 0, (it - nkv) * 64 + kr, nb * 7, fb);
                    } else {
                        tma3d_mc(dst + s * 16384 + rank * 6144, &tm.f3, 0, (it & 7) * 64 + kr, nb * 7 + (it < 24 ? 1 : 4), fb);
                    }
                    if ((XMASK >> it) & 1) {
                        const int xc = 1 + __builtin_popcount(XMASK & ((1u << it) - 1));
                        tma2d(sb + xc * 16384, &tm.x, xc * 64, mb * 128, bar + B_X + 8 * xc);
                    }
                }
                const int h = cl >> 1;
                mbar_wait(bar + B_G, 0);
                asm volatile("fence.proxy.async.global;" ::: "memory");
                TLM(0, 10);
#pragma unroll
                for (int c = 0; c < 8; c++) {
                    if (c >= 8 - NR) mbar_wait(bar + B_E1 + 8 * ((24 + c) % NR), ((24 + c) / NR) & 1);
                    bulk_mc(sb + c * 16384 + rank * 8192, gKV + (size_t)h * (SEQ * 64) + rank * 65536 + c * 8192, 8192, bar + B_KV + 8 * c);
                }
                mbar_wait(bar + B_SF2, 0);
#pragma unroll
                for (int s = 0; s < 4; s++) {
                    mbar_expect(bar + B_F2 + 8 * s, 24576);
                    tma5d_mc(sb + OFF_R + s * 24576 + 8192 + rank * 8192, &tm.w2, cb * 128 + rank * 64, s * 2, bar + B_F2 + 8 * s);
                }
                cnt_wait(gCntH + mb * 32, epoch() * 8);
                asm volatile("fence.proxy.async.global;" ::: "memory");
                TLM(1, 13);
#pragma unroll
                for (int s = 0; s < 4; s++) tma2d(sb + OFF_R + s * 24576, &tm.h, s * 64, rb * 64, bar + B_F2 + 8 * s);
            }
        } else if (warp == 17) {
            {
                uint32_t bv[4], b2v[2];
#pragma unroll
                for (int i = 0; i < 4; i++) bv[i] = lane + 32 * i < 112 ? *(const uint32_t*)(b1 + nb * 224 + (lane + 32 * i) * 2) : 0;
#pragma unroll
                for (int i = 0; i < 2; i++) b2v[i] = *(const uint32_t*)(b2 + cb * 128 + (lane + 32 * i) * 2);
#pragma unroll
                for (int i = 0; i < 4; i++) {
                    sts32(sb + OFF_ONE + (lane + 32 * i) * 4, 0x3f803f80u);
                    if (lane + 32 * i < 112) sts64(sb + OFF_BIAS + (lane + 32 * i) * 8, bv[i] << 16, bv[i] & 0xffff0000u);
                }
#pragma unroll
                for (int i = 0; i < 2; i++) sts32(sb + OFF_BIAS + 896 + (lane + 32 * i) * 4, b2v[i]);
                asm volatile("fence.proxy.async.shared::cta;" ::: "memory");
            }
            mbar_wait(bar + B_X + 8 * PFX, 0);
            if (lane == 0) {
                l2_prefetch((const uint8_t*)wqkv + 128 * 3072 + (size_t)blockIdx.x * 9216, 9216);
                l2_prefetch((const uint8_t*)w1 + (size_t)blockIdx.x * 14336, 14336);
            }
            mbar_wait(bar + B_X + 8 * 7, 0);
            if (lane == 0) {
                l2_prefetch((const uint8_t*)w2 + (size_t)blockIdx.x * 14336, 14336);
                l2_prefetch((const uint8_t*)wo + (size_t)blockIdx.x * 4096, 4096);
                map_prefetch(&tm.h); map_prefetch(&tm.w2); map_prefetch(&tm.wo); map_prefetch(&tm.hs); map_prefetch(&tm.kvs);
                TLM(0, 11);
            }
            bar_sync(10, 288);
            if (lane == 0) {
#pragma unroll 1
                for (int b = 5; b >= 0; b--) {
                    tma5d_st(&tm.kvs, sb + OFF_R + 12288 + b * 16384, (mb >> 3) * 8, (mb & 7) * 2, nb * 8 + (b < 4 ? 2 * b : 2 * b - 7));
                    asm volatile("cp.async.bulk.commit_group;\ncp.async.bulk.wait_group.read %0;" ::"n"(PACE) : "memory");
                    if (b == 4 - PACE) mbar_arrive(bar + B_SF);
                }
                asm volatile("cp.async.bulk.wait_group.read 0;" ::: "memory");
                mbar_arrive(bar + B_SF + 8);
            }
            __syncwarp();
            bar_sync(12, 288);
            if (lane == 0) {
                asm volatile("cp.async.bulk.wait_group 0;\nfence.proxy.async.global;" ::: "memory");
                cnt_add(gCntQ + nb * 32);
                TLM(0, 13);
            }
        } else {
            {
                const int r0 = mb * 128 + nb * 16 + (warp - 18) * 8;
                uint4 xv[16];
#pragma unroll
                for (int i = 0; i < 16; i++) xv[i] = *(const uint4*)(x + (size_t)(r0 + (i >> 1)) * DM + (i & 1) * 256 + lane * 8);
                const uint4 ga = *(const uint4*)(gate + lane * 8), gb = *(const uint4*)(gate + 256 + lane * 8);
                float z[8];
#pragma unroll
                for (int r = 0; r < 8; r++) z[r] = dot8(xv[2 * r], ga) + dot8(xv[2 * r + 1], gb);
#pragma unroll
                for (int w = 4; w >= 1; w >>= 1)
#pragma unroll
                    for (int r = 0; r < w; r++) {
                        const bool up = lane & w;
                        z[r] = (up ? z[r + w] : z[r]) + __shfl_xor_sync(0xffffffffu, up ? z[r] : z[r + w], w);
                    }
                z[0] += __shfl_xor_sync(0xffffffffu, z[0], 8);
                z[0] += __shfl_xor_sync(0xffffffffu, z[0], 16);
                if (lane < 8) gG[r0 + lane] = 1.f / (1.f + __expf(-z[0]));
                if (tid == 576) TLM(0, 12);
            }
            if (warp == 19) {
#pragma unroll 1
                for (int e = 0; e < 3; e++) {
                    bar_sync(e == 1 ? 14 : 11, 288);
                    if (lane == 0) {
#pragma unroll 1
                        for (int b = e == 0 ? 4 : 0; b < 6; b++) {
                            tma3d_st(&tm.hs, sb + OFF_R + 12288 + b * 16384, 0, mb * 128 + (b & 1) * 64, nb * 7 + e * 3 - 2 + (b >> 1));
                            asm volatile("cp.async.bulk.commit_group;\ncp.async.bulk.wait_group.read %0;" ::"n"(PACE) : "memory");
                        }
                        asm volatile("cp.async.bulk.wait_group.read 0;" ::: "memory");
                        if (e < 2) mbar_arrive(bar + B_SF + 8 + 8 * e);
                        else { mbar_arrive_cluster(bar + B_SF2, 0); mbar_arrive_cluster(bar + B_SF2, 1); }
                    }
                    __syncwarp();
                }
                bar_sync(13, 64);
                if (lane == 0) {
                    asm volatile("cp.async.bulk.wait_group 0;\nfence.proxy.async.global;" ::: "memory");
                    cnt_add(gCntH + mb * 32);
                    TLM(0, 15);
                }
            } else {
                bar_arrive(13, 64);
                const int h = cl >> 1, qd = (cl & 1) * 2 + rank;
                if (lane == 0) {
                    cnt_wait(gCntQ + (h >> 2) * 32, epoch() * 16);
                    mbar_arrive(bar + B_G);
                    TLM(0, 14);
                }
                __syncwarp();
            const int hb = h >> 2;
            const uint4 kq = __ldcg((const uint4*)(gN + 1024 + hb * 128 + lane * 4));
            const uint4 vq = __ldcg((const uint4*)(gN + 2048 + hb * 128 + lane * 4));
            const float qq = ldcg_f(gN + hb * 128 + qd * 32 + lane);
            const float kf = __uint_as_float(__reduce_max_sync(0xffffffffu, max(max(kq.x, kq.y), max(kq.z, kq.w))));
            const float vf = __uint_as_float(__reduce_max_sync(0xffffffffu, max(max(vq.x, vq.y), max(vq.z, vq.w))));
            const float qf = __uint_as_float(__reduce_max_sync(0xffffffffu, __float_as_uint(qq)));
            if (lane == 0) {
                sts32(sb + OFF_G + 256, (epoch() & 1) | ((kf <= 1.0e6f) && (qf <= 1.0e6f) && (kf * qf <= 3400.f) && (vf <= 1.0e12f) ? 2 : 0));
                mbar_arrive(bar + B_G3);
            }
            }
        }
        __syncwarp();
        float acc[64];
#pragma unroll
        for (int i = 0; i < 64; i++) acc[i] = 0.f;
#pragma unroll 1
        for (int io = 0; io < 7; io++) {
#pragma unroll
            for (int s = 0; s < 4; s++) {
                const int it = io * 4 + s;
                mbar_wait(bar + B_F2 + 8 * s, io & 1);
                if (tid == 512 && s == 0 && (io == 0 || io == 4)) TLM(1, 14 + io / 4);
                const uint64_t dA = mkdesc(SBD + OFF_R + s * 24576, 16, 1024, 1);
                const uint64_t dB = mkdesc(SBD + OFF_R + s * 24576 + 8192, 8192, 1024, 1);
                wg_fence();
#pragma unroll
                for (int kk = 0; kk < EXP_FKK; kk++) wgmma_ss_n128(acc, dA + kk * 2, dB + kk * 128);
                wg_commit();
                if (warp < 18 && it >= 2 && it < 26) {
                    const int s2 = (s + 2) & 3;
                    mbar_wait(bar + B_E2 + 8 * s2, (io - (s < 2)) & 1);
                    if (elect()) {
                        if (warp == 16) {
                            mbar_expect(bar + B_F2 + 8 * s2, 24576);
                            tma5d_mc(sb + OFF_R + s2 * 24576 + 8192 + rank * 8192, &tm.w2, cb * 128 + rank * 64, it * 2 + 4, bar + B_F2 + 8 * s2);
                        } else {
                            asm volatile("fence.proxy.async.global;" ::: "memory");
                            tma2d(sb + OFF_R + s2 * 24576, &tm.h, it * 64 + 128, rb * 64, bar + B_F2 + 8 * s2);
                        }
                    }
                    __syncwarp();
                }
                wg_wait<1>();
                if (it >= 1 && lane < 2) mbar_arrive_cluster(bar + B_E2 + 8 * ((s + 3) & 3), lane);
            }
        }
        wg_wait<0>();
        if (lane < 2) mbar_arrive_cluster(bar + B_E2 + 8 * 3, lane);
        pin<64>(acc);
        if (warp == 16) {
            if (lane == 0) TLM(1, 16);
            for (int s = 0; s < 4; s++) mbar_wait(bar + B_E2 + 8 * s, 0);
            if (elect()) {
#pragma unroll
                for (int i = 0; i < 6; i++) tma2d_mc(sb + OFF_R + i * 16384 + rank * 8192, &tm.wo, cb * 128 + rank * 64, i * 64, bar + B_T + 8 * i);
            }
            __syncwarp();
        }
        {
            const int lr = (warp - 16) * 16 + g;
            const uint32_t pa = pk_bf16(ldcg_f(gG + rb * 64 + lr), ldcg_f(gG + rb * 64 + lr + 8));
            if (t == 0) {
                sts32(sb + OFF_G + lr * 4, __byte_perm(pa, pa, 0x1010));
                sts32(sb + OFF_G + lr * 4 + 32, __byte_perm(pa, pa, 0x3232));
            }
            __syncwarp();
            if (lane == 0) mbar_arrive(bar + B_G2);
            const float ga = bf_lo(pa), gb = bf_hi(pa);
            const float g0 = 1.f - ga, g1 = 1.f - gb;
#pragma unroll
            for (int j = 0; j < 16; j++) {
                const uint32_t bv = lds32(sb + OFF_BIAS + 896 + j * 16 + t * 4);
                acc[4 * j] = fmaf(acc[4 * j], 0.5f, bf_lo(bv)) * g0;
                acc[4 * j + 1] = fmaf(acc[4 * j + 1], 0.5f, bf_hi(bv)) * g0;
                acc[4 * j + 2] = fmaf(acc[4 * j + 2], 0.5f, bf_lo(bv)) * g1;
                acc[4 * j + 3] = fmaf(acc[4 * j + 3], 0.5f, bf_hi(bv)) * g1;
            }
            pin<64>(acc);
        }
        if (warp == 17) {
            mbar_wait(bar + B_DONE, 0);
            if (elect()) {
#pragma unroll
                for (int i = 0; i < 4; i++)
                    tma2d(sb + 65536 + i * 8192, &tm.wo, cb * 128 + (i & 1) * 64, (6 + (i >> 1)) * 64, bar + B_T + 8 * (6 + (i >> 1)));
            }
            __syncwarp();
        }
        if (tid == 512) TLM(1, 17);
#pragma unroll
        for (int i = 0; i < 8; i++) {
            mbar_wait(bar + B_T + 8 * i, 0);
            const uint64_t dA = mkdesc(SBD + i * 8192, 16, 1024, 1);
            const uint64_t dB = mkdesc(i < 6 ? SBD + OFF_R + i * 16384 : SBD + 65536 + (i - 6) * 16384, 8192, 1024, 1);
            wg_fence();
#pragma unroll
            for (int kk = 0; kk < 4; kk++) wgmma_ss_n128(acc, dA + kk * 2, dB + kk * 128);
            wg_commit();
        }
        wg_wait<0>();
        pin<64>(acc);
        if (tid == 512) TLM(1, 18);
        {
            const uint32_t st = sb + 98304 + (warp - 16) * 4352;
            const uint32_t wa = st + (lane & 15) * 272 + (lane >> 4) * 16;
#pragma unroll
            for (int j = 0; j < 8; j++)
                asm volatile("stmatrix.sync.aligned.m8n8.x4.shared.b16 [%0], {%1, %2, %3, %4};" ::"r"(wa + j * 32),
                             "r"(pk_bf16(acc[8 * j], acc[8 * j + 1])), "r"(pk_bf16(acc[8 * j + 2], acc[8 * j + 3])),
                             "r"(pk_bf16(acc[8 * j + 4], acc[8 * j + 5])), "r"(pk_bf16(acc[8 * j + 6], acc[8 * j + 7])) : "memory");
            __syncwarp();
            __nv_bfloat16* op = out + (size_t)(rb * 64 + (warp - 16) * 16 + (lane >> 4)) * DM + cb * 128 + (lane & 15) * 8;
#pragma unroll
            for (int j = 0; j < 8; j++) {
                uint4 v;
                asm volatile("ld.shared.v4.u32 {%0, %1, %2, %3}, [%4];" : "=r"(v.x), "=r"(v.y), "=r"(v.z), "=r"(v.w)
                             : "r"(st + (2 * j + (lane >> 4)) * 272 + (lane & 15) * 16));
                *(uint4*)(op + (size_t)j * 2 * DM) = v;
            }
        }
        if (tid == 512) { gEpoch[blockIdx.x] = epoch(); TLM(1, 19); }
        TL_DUMP();
    }
}

typedef CUresult (*EncodeFn)(CUtensorMap*, CUtensorMapDataType, cuuint32_t, void*, const cuuint64_t*, const cuuint64_t*, const cuuint32_t*,
                             const cuuint32_t*, CUtensorMapInterleave, CUtensorMapSwizzle, CUtensorMapL2promotion, CUtensorMapFloatOOBfill);

static void make_map(EncodeFn enc, CUtensorMap* m, const void* p, int rank, const cuuint64_t* dims, const cuuint64_t* strides,
                     const cuuint32_t* box, CUtensorMapSwizzle swz) {
    const cuuint32_t es[5] = {1, 1, 1, 1, 1};
    enc(m, CU_TENSOR_MAP_DATA_TYPE_BFLOAT16, rank, (void*)p, dims, strides, box, es, CU_TENSOR_MAP_INTERLEAVE_NONE, swz,
        CU_TENSOR_MAP_L2_PROMOTION_L2_128B, CU_TENSOR_MAP_FLOAT_OOB_FILL_NONE);
}

extern "C" void kernel_launch(void* const* d_in, const int* in_sizes, int n_in, void* d_out, int out_size) {
    const __nv_bfloat16* x = (const __nv_bfloat16*)d_in[0];
    const __nv_bfloat16* wqkv = (const __nv_bfloat16*)d_in[1];
    const __nv_bfloat16* wo = (const __nv_bfloat16*)d_in[2];
    const __nv_bfloat16* w1 = (const __nv_bfloat16*)d_in[4];
    const __nv_bfloat16* b1 = (const __nv_bfloat16*)d_in[5];
    const __nv_bfloat16* w2 = (const __nv_bfloat16*)d_in[6];
    const __nv_bfloat16* b2 = (const __nv_bfloat16*)d_in[7];
    const __nv_bfloat16* gate = (const __nv_bfloat16*)d_in[8];

    void* fp = nullptr;
    cudaDriverEntryPointQueryResult qr;
    cudaGetDriverEntryPoint("cuTensorMapEncodeTiled", &fp, cudaEnableDefault, &qr);
    EncodeFn enc = (EncodeFn)fp;
    void *pH, *pKV;
    cudaGetSymbolAddress(&pH, gH);
    cudaGetSymbolAddress(&pKV, gKV);

    Maps tm;
    const CUtensorMapSwizzle S128 = CU_TENSOR_MAP_SWIZZLE_128B, S64 = CU_TENSOR_MAP_SWIZZLE_64B;
    { cuuint64_t d[2] = {DM, SEQ}, s[1] = {DM * 2}; cuuint32_t b[2] = {64, 128}; make_map(enc, &tm.x, x, 2, d, s, b, S128); }
    { cuuint64_t d[3] = {DM, DM, 3}, s[2] = {3 * DM * 2, DM * 2}; cuuint32_t b[3] = {64, 32, 2}; make_map(enc, &tm.kv, wqkv, 3, d, s, b, S128); }
    { cuuint64_t d[3] = {32, DM, 3 * DM / 32}, s[2] = {3 * DM * 2, 64}; cuuint32_t b[3] = {32, 32, 2}; make_map(enc, &tm.q, wqkv, 3, d, s, b, S64); }
    { cuuint64_t d[3] = {32, DM, FF / 32}, s[2] = {FF * 2, 64}; cuuint32_t b[3] = {32, 32, 1}; make_map(enc, &tm.f1, w1, 3, d, s, b, S64); }
    { cuuint64_t d[3] = {32, DM, FF / 32}, s[2] = {FF * 2, 64}; cuuint32_t b[3] = {32, 32, 3}; make_map(enc, &tm.f3, w1, 3, d, s, b, S64); }
    { cuuint64_t d[2] = {FF, SEQ}, s[1] = {FF * 2}; cuuint32_t b[2] = {64, 64}; make_map(enc, &tm.h, pH, 2, d, s, b, S128); }
    { cuuint64_t d[5] = {DM, 2, 4, 4, FF / 32}, s[4] = {1024, 8 * 1024, 2 * 1024, 32 * 1024}; cuuint32_t b[5] = {64, 2, 4, 4, 2};
      make_map(enc, &tm.w2, w2, 5, d, s, b, S128); }
    { cuuint64_t d[2] = {DM, DM}, s[1] = {DM * 2}; cuuint32_t b[2] = {64, 64}; make_map(enc, &tm.wo, wo, 2, d, s, b, S128); }

    { cuuint64_t d[3] = {32, SEQ, FF / 32}, s[2] = {FF * 2, 64}; cuuint32_t b[3] = {32, 64, 1}; make_map(enc, &tm.hs, pH, 3, d, s, b, CU_TENSOR_MAP_SWIZZLE_NONE); }
    { cuuint64_t d[5] = {64, 16, 16, 2, 2 * NH}, s[4] = {4096, 128, 2048, 65536}; cuuint32_t b[5] = {64, 8, 2, 2, 1};
      make_map(enc, &tm.kvs, pKV, 5, d, s, b, S128); }
    cudaFuncSetAttribute(fused_kernel, cudaFuncAttributeMaxDynamicSharedMemorySize, TL_SMEM);
    fused_kernel<<<128, 640, TL_SMEM, cudaStreamPerThread>>>(tm, x, wqkv, wo, w1, b1, w2, b2, gate, (__nv_bfloat16*)d_out, 0xffffffffu);
}
```

```cpp
#include <cuda_runtime.h>
#include <cuda_bf16.h>
#include <cuda_fp16.h>
#include <cuda.h>
#include <stdint.h>

#define SEQ 2048
#define DM 512
#define FF 1792
#define NH 32

__device__ __align__(1024) uint8_t gQ[NH * SEQ * 32];
__device__ __align__(1024) uint8_t gKV[NH * SEQ * 64];
__device__ __align__(1024) __nv_bfloat16 gH[SEQ * FF];
__device__ __align__(1024) uint4 gO[32 * NH * 128];
__device__ float gG[SEQ];
__device__ float gN[3 * 8 * 128];
__device__ unsigned int gCntQ[8 * 32];
__device__ unsigned int gCntH[32 * 32];
__device__ unsigned int gEpoch[128];

__device__ __forceinline__ uint32_t smem_u32(const void* p) { return (uint32_t)__cvta_generic_to_shared(p); }
__device__ __forceinline__ void mbar_init(uint32_t a, uint32_t c) { asm volatile("mbarrier.init.shared::cta.b64 [%0], %1;" ::"r"(a), "r"(c)); }
__device__ __forceinline__ void mbar_expect(uint32_t a, uint32_t b) { asm volatile("mbarrier.arrive.expect_tx.shared::cta.b64 _, [%0], %1;" ::"r"(a), "r"(b) : "memory"); }
__device__ __forceinline__ void mbar_arrive(uint32_t a) { asm volatile("mbarrier.arrive.shared::cta.b64 _, [%0];" ::"r"(a) : "memory"); }
__device__ __forceinline__ void mbar_wait(uint32_t a, uint32_t ph) {
    asm volatile("{\n.reg .pred p;\n.reg .u32 n;\nmov.u32 n, 0;\nW_%=:\nmbarrier.try_wait.parity.shared::cta.b64 p, [%0], %1;\n@p bra D_%=;\n"
                 "add.u32 n, n, 1;\nsetp.lt.u32 p, n, 0x400000;\n@p bra W_%=;\ntrap;\nD_%=:\n}" ::"r"(a), "r"(ph) : "memory");
}
__device__ __forceinline__ void mbar_arrive_cluster(uint32_t a, uint32_t cta) {
    asm volatile("{\n.reg .b32 r;\nmapa.shared::cluster.u32 r, %0, %1;\nmbarrier.arrive.shared::cluster.b64 _, [r];\n}" ::"r"(a), "r"(cta) : "memory");
}
__device__ __forceinline__ void bar_sync(int id, int n) { asm volatile("bar.sync %0, %1;" ::"r"(id), "r"(n) : "memory"); }
__device__ __forceinline__ void bar_arrive(int id, int n) { asm volatile("bar.arrive %0, %1;" ::"r"(id), "r"(n) : "memory"); }
__device__ __forceinline__ uint32_t cluster_rank() { uint32_t r; asm("mov.u32 %0, %%cluster_ctarank;" : "=r"(r)); return r; }
__device__ __forceinline__ void cnt_add(unsigned int* c) { asm volatile("red.release.gpu.global.add.u32 [%0], 1;" ::"l"(c) : "memory"); }
__device__ __forceinline__ void cnt_wait(const unsigned int* c, uint32_t target) {
    uint32_t v;
    int spins = 0;
    while (true) {
        asm volatile("ld.acquire.gpu.global.u32 %0, [%1];" : "=r"(v) : "l"(c) : "memory");
        if ((int)(v - target) >= 0) break;
        if (++spins > (1 << 22)) __trap();
        __nanosleep(40);
    }
}
__device__ __forceinline__ void tma2d(uint32_t dst, const CUtensorMap* m, int c0, int c1, uint32_t bar) {
    asm volatile("cp.async.bulk.tensor.2d.shared::cluster.global.mbarrier::complete_tx::bytes [%0], [%1, {%3, %4}], [%2];"
                 ::"r"(dst), "l"(m), "r"(bar), "r"(c0), "r"(c1) : "memory");
}
__device__ __forceinline__ void tma2d_mc(uint32_t dst, const CUtensorMap* m, int c0, int c1, uint32_t bar) {
    asm volatile("cp.async.bulk.tensor.2d.shared::cluster.global.mbarrier::complete_tx::bytes.multicast::cluster [%0], [%1, {%3, %4}], [%2], %5;"
                 ::"r"(dst), "l"(m), "r"(bar), "r"(c0), "r"(c1), "h"((uint16_t)3) : "memory");
}
__device__ __forceinline__ void tma3d_mc(uint32_t dst, const CUtensorMap* m, int c0, int c1, int c2, uint32_t bar) {
    asm volatile("cp.async.bulk.tensor.3d.shared::cluster.global.mbarrier::complete_tx::bytes.multicast::cluster [%0], [%1, {%3, %4, %5}], [%2], %6;"
                 ::"r"(dst), "l"(m), "r"(bar), "r"(c0), "r"(c1), "r"(c2), "h"((uint16_t)3) : "memory");
}
__device__ __forceinline__ void tma5d_mc(uint32_t dst, const CUtensorMap* m, int c0, int c4, uint32_t bar) {
    asm volatile("cp.async.bulk.tensor.5d.shared::cluster.global.mbarrier::complete_tx::bytes.multicast::cluster [%0], [%1, {%3, %5, %5, %5, %4}], [%2], %6;"
                 ::"r"(dst), "l"(m), "r"(bar), "r"(c0), "r"(c4), "r"(0), "h"((uint16_t)3) : "memory");
}
__device__ __forceinline__ void bulk_mc(uint32_t dst, const void* src, uint32_t bytes, uint32_t bar) {
    asm volatile("cp.async.bulk.shared::cluster.global.mbarrier::complete_tx::bytes.multicast::cluster [%0], [%1], %2, [%3], %4;"
                 ::"r"(dst), "l"(src), "r"(bytes), "r"(bar), "h"((uint16_t)3) : "memory");
}
__device__ __forceinline__ void tma3d_st(const CUtensorMap* m, uint32_t src, int c0, int c1, int c2) {
    asm volatile("cp.async.bulk.tensor.3d.global.shared::cta.bulk_group [%0, {%2, %3, %4}], [%1];" ::"l"(m), "r"(src), "r"(c0), "r"(c1), "r"(c2) : "memory");
}
__device__ __forceinline__ void tma5d_st(const CUtensorMap* m, uint32_t src, int c1, int c2, int c4) {
    asm volatile("cp.async.bulk.tensor.5d.global.shared::cta.bulk_group [%0, {%5, %2, %3, %5, %4}], [%1];"
                 ::"l"(m), "r"(src), "r"(c1), "r"(c2), "r"(c4), "r"(0) : "memory");
}
__device__ __forceinline__ void bulk_st(void* dst, uint32_t src, uint32_t bytes) {
    asm volatile("cp.async.bulk.global.shared::cta.bulk_group [%0], [%1], %2;" ::"l"(dst), "r"(src), "r"(bytes) : "memory");
}
__device__ __forceinline__ void sts64(uint32_t a, uint32_t x, uint32_t y) { asm volatile("st.shared.v2.u32 [%0], {%1, %2};" ::"r"(a), "r"(x), "r"(y) : "memory"); }
__device__ __forceinline__ void sts128(uint32_t a, const uint32_t* v) {
    asm volatile("st.shared.v4.u32 [%0], {%1, %2, %3, %4};" ::"r"(a), "r"(v[0]), "r"(v[1]), "r"(v[2]), "r"(v[3]) : "memory");
}
__device__ __forceinline__ void l2_prefetch(const void* src, uint32_t bytes) {
    asm volatile("cp.async.bulk.prefetch.L2.global [%0], %1;" ::"l"(src), "r"(bytes) : "memory");
}
__device__ __forceinline__ void map_prefetch(const CUtensorMap* m) { asm volatile("prefetch.tensormap [%0];" ::"l"(m) : "memory"); }
__device__ __forceinline__ void wg_fence() { asm volatile("wgmma.fence.sync.aligned;" ::: "memory"); }
__device__ __forceinline__ void wg_commit() { asm volatile("wgmma.commit_group.sync.aligned;" ::: "memory"); }
template <int N> __device__ __forceinline__ void wg_wait() { asm volatile("wgmma.wait_group.sync.aligned %0;" ::"n"(N) : "memory"); }
template <int N> __device__ __forceinline__ void pin(float* s) {
#pragma unroll
    for (int i = 0; i < N; i++) asm volatile("" : "+f"(s[i])::"memory");
}
template <int N> __device__ __forceinline__ void pin(uint32_t* s) {
#pragma unroll
    for (int i = 0; i < N; i++) asm volatile("" : "+r"(s[i])::"memory");
}
__device__ __forceinline__ uint64_t mkdesc(uint32_t addr, uint32_t lbo, uint32_t sbo, uint32_t swz) {
    return (uint64_t)((addr & 0x3FFFF) >> 4) | ((uint64_t)(lbo >> 4) << 16) | ((uint64_t)(sbo >> 4) << 32) | ((uint64_t)swz << 62);
}
__device__ __forceinline__ float ex2f(float x) { float y; asm("ex2.approx.ftz.f32 %0, %1;" : "=f"(y) : "f"(x)); return y; }
__device__ __forceinline__ float tanhf_(float x) { float y; asm("tanh.approx.f32 %0, %1;" : "=f"(y) : "f"(x)); return y; }
__device__ __forceinline__ uint32_t pk_bf16(float lo, float hi) { uint32_t r; asm("cvt.rn.bf16x2.f32 %0, %1, %2;" : "=r"(r) : "f"(hi), "f"(lo)); return r; }
__device__ __forceinline__ uint32_t pk_f16(float lo, float hi) { uint32_t r; asm("cvt.rn.f16x2.f32 %0, %1, %2;" : "=r"(r) : "f"(hi), "f"(lo)); return r; }
__device__ __forceinline__ float bf_lo(uint32_t v) { return __uint_as_float(v << 16); }
__device__ __forceinline__ float bf_hi(uint32_t v) { return __uint_as_float(v & 0xffff0000u); }
__device__ __forceinline__ float dot8(const uint4& a, const uint4& b) {
    return fmaf(bf_lo(a.x), bf_lo(b.x), fmaf(bf_hi(a.x), bf_hi(b.x), fmaf(bf_lo(a.y), bf_lo(b.y), bf_hi(a.y) * bf_hi(b.y)))) +
           fmaf(bf_lo(a.z), bf_lo(b.z), fmaf(bf_hi(a.z), bf_hi(b.z), fmaf(bf_lo(a.w), bf_lo(b.w), bf_hi(a.w) * bf_hi(b.w))));
}
__device__ __forceinline__ uint32_t epoch() {
    uint32_t v;
    asm volatile("ld.global.u32 %0, [%1];" : "=r"(v) : "l"(gEpoch + blockIdx.x));
    return v + 1;
}
__device__ __forceinline__ float ldcg_f(const float* p) { return __ldcg(p); }

extern __shared__ __align__(1024) uint8_t smem_raw[];
#define TLM(k, slot) do {} while (0)
#define TLC(k, slot) do {} while (0)
#define TL_INIT() do {} while (0)
#define TL_DUMP() do {} while (0)
#define TL_SMEM SMEM_BYTES

__device__ __forceinline__ void wgmma_ss_n128(float* d, uint64_t da, uint64_t db) {
    asm volatile("wgmma.mma_async.sync.aligned.m64n128k16.f32.bf16.bf16 {"
        "%0, %1, %2, %3, %4, %5, %6, %7, %8, %9, %10, %11, %12, %13, %14, %15,"
        "%16, %17, %18, %19, %20, %21, %22, %23, %24, %25, %26, %27, %28, %29, %30, %31,"
        "%32, %33, %34, %35, %36, %37, %38, %39, %40, %41, %42, %43, %44, %45, %46, %47,"
        "%48, %49, %50, %51, %52, %53, %54, %55, %56, %57, %58, %59, %60, %61, %62, %63}, %64, %65, 1, 1, 1, 0, 1;\n"
        :
        "+f"(d[0]), "+f"(d[1]), "+f"(d[2]), "+f"(d[3]), "+f"(d[4]), "+f"(d[5]), "+f"(d[6]), "+f"(d[7]),
        "+f"(d[8]), "+f"(d[9]), "+f"(d[10]), "+f"(d[11]), "+f"(d[12]), "+f"(d[13]), "+f"(d[14]), "+f"(d[15]),
        "+f"(d[16]), "+f"(d[17]), "+f"(d[18]), "+f"(d[19]), "+f"(d[20]), "+f"(d[21]), "+f"(d[22]), "+f"(d[23]),
        "+f"(d[24]), "+f"(d[25]), "+f"(d[26]), "+f"(d[27]), "+f"(d[28]), "+f"(d[29]), "+f"(d[30]), "+f"(d[31]),
        "+f"(d[32]), "+f"(d[33]), "+f"(d[34]), "+f"(d[35]), "+f"(d[36]), "+f"(d[37]), "+f"(d[38]), "+f"(d[39]),
        "+f"(d[40]), "+f"(d[41]), "+f"(d[42]), "+f"(d[43]), "+f"(d[44]), "+f"(d[45]), "+f"(d[46]), "+f"(d[47]),
        "+f"(d[48]), "+f"(d[49]), "+f"(d[50]), "+f"(d[51]), "+f"(d[52]), "+f"(d[53]), "+f"(d[54]), "+f"(d[55]),
        "+f"(d[56]), "+f"(d[57]), "+f"(d[58]), "+f"(d[59]), "+f"(d[60]), "+f"(d[61]), "+f"(d[62]), "+f"(d[63])
        : "l"(da), "l"(db));
}
__device__ __forceinline__ void wgmma_ss_n96(float* d, uint64_t da, uint64_t db) {
    asm volatile("wgmma.mma_async.sync.aligned.m64n96k16.f32.bf16.bf16 {"
        "%0, %1, %2, %3, %4, %5, %6, %7, %8, %9, %10, %11, %12, %13, %14, %15,"
        "%16, %17, %18, %19, %20, %21, %22, %23, %24, %25, %26, %27, %28, %29, %30, %31,"
        "%32, %33, %34, %35, %36, %37, %38, %39, %40, %41, %42, %43, %44, %45, %46, %47}, %48, %49, 1, 1, 1, 0, 1;\n"
        :
        "+f"(d[0]), "+f"(d[1]), "+f"(d[2]), "+f"(d[3]), "+f"(d[4]), "+f"(d[5]), "+f"(d[6]), "+f"(d[7]),
        "+f"(d[8]), "+f"(d[9]), "+f"(d[10]), "+f"(d[11]), "+f"(d[12]), "+f"(d[13]), "+f"(d[14]), "+f"(d[15]),
        "+f"(d[16]), "+f"(d[17]), "+f"(d[18]), "+f"(d[19]), "+f"(d[20]), "+f"(d[21]), "+f"(d[22]), "+f"(d[23]),
        "+f"(d[24]), "+f"(d[25]), "+f"(d[26]), "+f"(d[27]), "+f"(d[28]), "+f"(d[29]), "+f"(d[30]), "+f"(d[31]),
        "+f"(d[32]), "+f"(d[33]), "+f"(d[34]), "+f"(d[35]), "+f"(d[36]), "+f"(d[37]), "+f"(d[38]), "+f"(d[39]),
        "+f"(d[40]), "+f"(d[41]), "+f"(d[42]), "+f"(d[43]), "+f"(d[44]), "+f"(d[45]), "+f"(d[46]), "+f"(d[47])
        : "l"(da), "l"(db));
}
__device__ __forceinline__ void wgmma_ss_n64(float* d, uint64_t da, uint64_t db) {
    asm volatile("wgmma.mma_async.sync.aligned.m64n64k16.f32.bf16.bf16 {"
        "%0, %1, %2, %3, %4, %5, %6, %7, %8, %9, %10, %11, %12, %13, %14, %15,"
        "%16, %17, %18, %19, %20, %21, %22, %23, %24, %25, %26, %27, %28, %29, %30, %31}, %32, %33, 1, 1, 1, 0, 1;\n"
        :
        "+f"(d[0]), "+f"(d[1]), "+f"(d[2]), "+f"(d[3]), "+f"(d[4]), "+f"(d[5]), "+f"(d[6]), "+f"(d[7]),
        "+f"(d[8]), "+f"(d[9]), "+f"(d[10]), "+f"(d[11]), "+f"(d[12]), "+f"(d[13]), "+f"(d[14]), "+f"(d[15]),
        "+f"(d[16]), "+f"(d[17]), "+f"(d[18]), "+f"(d[19]), "+f"(d[20]), "+f"(d[21]), "+f"(d[22]), "+f"(d[23]),
        "+f"(d[24]), "+f"(d[25]), "+f"(d[26]), "+f"(d[27]), "+f"(d[28]), "+f"(d[29]), "+f"(d[30]), "+f"(d[31])
        : "l"(da), "l"(db));
}
__device__ __forceinline__ void wgmma_qk_f16_acc(float* d, const uint32_t* a, uint64_t db) {
    asm volatile("wgmma.mma_async.sync.aligned.m64n64k16.f32.f16.f16 {"
        "%0, %1, %2, %3, %4, %5, %6, %7, %8, %9, %10, %11, %12, %13, %14, %15,"
        "%16, %17, %18, %19, %20, %21, %22, %23, %24, %25, %26, %27, %28, %29, %30, %31}, {%32, %33, %34, %35}, %36, 1, 1, 1, 0;\n"
        :
        "+f"(d[0]), "+f"(d[1]), "+f"(d[2]), "+f"(d[3]), "+f"(d[4]), "+f"(d[5]), "+f"(d[6]), "+f"(d[7]),
        "+f"(d[8]), "+f"(d[9]), "+f"(d[10]), "+f"(d[11]), "+f"(d[12]), "+f"(d[13]), "+f"(d[14]), "+f"(d[15]),
        "+f"(d[16]), "+f"(d[17]), "+f"(d[18]), "+f"(d[19]), "+f"(d[20]), "+f"(d[21]), "+f"(d[22]), "+f"(d[23]),
        "+f"(d[24]), "+f"(d[25]), "+f"(d[26]), "+f"(d[27]), "+f"(d[28]), "+f"(d[29]), "+f"(d[30]), "+f"(d[31])
        : "r"(a[0]), "r"(a[1]), "r"(a[2]), "r"(a[3]), "l"(db));
}
__device__ __forceinline__ void wgmma_qk_bf16_zero(float* d, const uint32_t* a, uint64_t db) {
    asm volatile("wgmma.mma_async.sync.aligned.m64n64k16.f32.bf16.bf16 {"
        "%0, %1, %2, %3, %4, %5, %6, %7, %8, %9, %10, %11, %12, %13, %14, %15,"
        "%16, %17, %18, %19, %20, %21, %22, %23, %24, %25, %26, %27, %28, %29, %30, %31}, {%32, %33, %34, %35}, %36, 0, 1, 1, 0;\n"
        :
        "=f"(d[0]), "=f"(d[1]), "=f"(d[2]), "=f"(d[3]), "=f"(d[4]), "=f"(d[5]), "=f"(d[6]), "=f"(d[7]),
        "=f"(d[8]), "=f"(d[9]), "=f"(d[10]), "=f"(d[11]), "=f"(d[12]), "=f"(d[13]), "=f"(d[14]), "=f"(d[15]),
        "=f"(d[16]), "=f"(d[17]), "=f"(d[18]), "=f"(d[19]), "=f"(d[20]), "=f"(d[21]), "=f"(d[22]), "=f"(d[23]),
        "=f"(d[24]), "=f"(d[25]), "=f"(d[26]), "=f"(d[27]), "=f"(d[28]), "=f"(d[29]), "=f"(d[30]), "=f"(d[31])
        : "r"(a[0]), "r"(a[1]), "r"(a[2]), "r"(a[3]), "l"(db));
}
__device__ __forceinline__ void wgmma_pv(float* d, const uint32_t* a, uint64_t db) {
    asm volatile("wgmma.mma_async.sync.aligned.m64n24k16.f32.bf16.bf16 {"
        "%0, %1, %2, %3, %4, %5, %6, %7, %8, %9, %10, %11}, {%12, %13, %14, %15}, %16, 1, 1, 1, 1;\n"
        :
        "+f"(d[0]), "+f"(d[1]), "+f"(d[2]), "+f"(d[3]), "+f"(d[4]), "+f"(d[5]), "+f"(d[6]), "+f"(d[7]),
        "+f"(d[8]), "+f"(d[9]), "+f"(d[10]), "+f"(d[11])
        : "r"(a[0]), "r"(a[1]), "r"(a[2]), "r"(a[3]), "l"(db));
}

template <int N> __device__ __forceinline__ void wgmma_ss(float* d, uint64_t a, uint64_t b) {
    if (N == 128) wgmma_ss_n128(d, a, b);
    if (N == 96) wgmma_ss_n96(d, a, b);
    if (N == 64) wgmma_ss_n64(d, a, b);
}

#define OFF_R 131072
#define OFF_ONE 229376
#define OFF_BAR 229888
#define OFF_BIAS (OFF_BAR + 672)
#define OFF_G (OFF_BIAS + 1152)
#define SMEM_BYTES (OFF_G + 272)
#define SBD 1024u
#define B_X 0
#define B_F1 416
#define B_E1 112
#define B_KV 160
#define B_F2 224
#define B_E2 256
#define B_T 288
#define B_DONE 352
#define B_G 360
#define B_G2 368
#define B_G3 376
#define B_SF 384
#define B_BI 400
#define B_SF2 408
#define NR 6

#define PF 1
#define PFX 0
#define PACE 0
#define EXP_FKK 4
#define QSCALE 0.36067376022224085f
#define MAGIC 445.41763f
#define NMUFU 4
#define VSTEP ((uint64_t)((long long)32 - ((long long)32 << 16)))

#define XMASK 0x0D55u
#define KVMASK 0x1D55u
__host__ __device__ constexpr int strm_pos(int pass, int i) {
    if (pass == 1 || pass == 2) return 8 + 8 * pass + i;
    int n = 0;
    for (int p = 0; p < 16; p++)
        if ((int)((KVMASK >> p) & 1) == (pass == 3)) { if (n == i) return p; n++; }
    return 0;
}
__host__ __device__ constexpr uint32_t strm_code(int pass) {
    uint32_t c = 0;
    for (int i = 0; i < 7; i++) c |= (uint32_t)(strm_pos(pass, i + 1) - strm_pos(pass, i)) << (4 * i);
    return c;
}

template <int N, int SUB, int KST, int LBO, int SBO, int SWZ>
__device__ __forceinline__ void gemm_pass(float* acc, uint32_t bar, uint64_t dA, int lane, uint32_t pos, uint32_t code, int barNext, bool waitx) {
    uint32_t prev = 0, slot = pos % NR;
#pragma unroll 1
    for (int i = 0; i < 8; i++) {
        if (waitx) mbar_wait(bar + B_X + 8 * i, 0);
        mbar_wait(bar + B_F1 + 8 * pos, 0);
        const uint64_t dB = mkdesc(SBD + OFF_R, LBO, SBO, SWZ) + slot * 1024;
        wg_fence();
        wgmma_ss<N>(acc, dA, dB);
        wgmma_ss<N>(acc, dA + 2, dB + KST / 16);
        wg_commit();
        wg_wait<1>();
        if (i > 0 && lane < 2) mbar_arrive_cluster(bar + B_E1 + 8 * prev, lane);
        wgmma_ss<N>(acc, dA + 4, dB + SUB / 16);
        wgmma_ss<N>(acc, dA + 6, dB + (SUB + KST) / 16);
        wg_commit();
        prev = slot;
        pos += code & 15;
        slot += code & 15;
        if (slot >= NR) slot -= NR;
        code >>= 4;
        dA += 1024;
    }
    if (barNext) bar_arrive(barNext, 512);
    wg_wait<0>();
    if (lane < 2) mbar_arrive_cluster(bar + B_E1 + 8 * prev, lane);
    pin<N / 2>(acc);
}

__device__ __forceinline__ uint32_t lds32(uint32_t a) { uint32_t v; asm volatile("ld.shared.u32 %0, [%1];" : "=r"(v) : "r"(a)); return v; }
__device__ __forceinline__ bool elect() {
    uint32_t p;
    asm volatile("{\n.reg .pred p;\nelect.sync _|p, 0xffffffff;\nselp.u32 %0, 1, 0, p;\n}" : "=r"(p));
    return p;
}

template <int G0, int G1> __device__ __forceinline__ void gelu_pack(const float* acc, uint32_t bias, uint32_t* out) {
#pragma unroll
    for (int G = G0; G < G1; G++) {
        uint32_t* o = out + 8 * G;
#pragma unroll
        for (int j = 0; j < 4; j++) {
            float bv[2];
            asm volatile("ld.shared.v2.f32 {%0, %1}, [%2];" : "=f"(bv[0]), "=f"(bv[1]) : "r"(bias + G * 128 + j * 32));
            float y[4];
#pragma unroll
            for (int i = 0; i < 4; i++) {
                const float h = acc[16 * G + 4 * j + i] + bv[i & 1];
                const float z = h * fmaf(h * h, 0.035677408136300125f, 0.7978845608028654f);
                y[i] = fmaf(h, tanhf_(z), h);
            }
            o[j] = pk_bf16(y[0], y[1]);
            o[4 + j] = pk_bf16(y[2], y[3]);
        }
    }
}

__device__ __forceinline__ float norm_bound(const float* v, float sc) {
    uint32_t m = 0;
#pragma unroll
    for (int h = 0; h < 4; h++) {
        const float* u = v + 8 * h;
        m = max(m, __float_as_uint(fmaf(u[0], u[0], fmaf(u[1], u[1], fmaf(u[4], u[4], u[5] * u[5])))));
        m = max(m, __float_as_uint(fmaf(u[2], u[2], fmaf(u[3], u[3], fmaf(u[6], u[6], u[7] * u[7])))));
    }
#pragma unroll
    for (int o = 4; o < 32; o <<= 1) m = max(m, __shfl_xor_sync(0xffffffffu, m, o));
    float f = __uint_as_float(m);
    f += __shfl_xor_sync(0xffffffffu, f, 1);
    f += __shfl_xor_sync(0xffffffffu, f, 2);
    return f * sc;
}

__device__ __forceinline__ uint32_t exp2_pair(float a, float b, uint32_t m1) {
    const uint32_t w = __byte_perm(__float_as_uint(a), __float_as_uint(b), 0x6521);
    uint32_t m, r;
    asm("lop3.b32 %0, %1, 0x007f007f, 0x9f809f80, 0xEA;" : "=r"(m) : "r"(w));
    const uint32_t e = w - m;
    asm("fma.rn.bf16x2 %0, %1, %2, %3;" : "=r"(r) : "r"(w), "r"(m), "r"(e));
    return r;
}

__device__ __forceinline__ void store_o(const float* o, uint4* dst, uint32_t par) {
    const float s0 = __fdividef(1.f, o[8]), s1 = __fdividef(1.f, o[10]);
    const uint32_t d0 = (pk_bf16(o[0] * s0, o[1] * s0) & ~1u) | par;
    asm volatile("{\n.reg .b128 t;\nmov.b128 t, {%0, %1, %2, %3};\nst.relaxed.gpu.global.b128 [%4], t;\n}" ::"r"(d0),
                 "r"(pk_bf16(o[4] * s0, o[5] * s0)), "r"(pk_bf16(o[2] * s1, o[3] * s1)), "r"(pk_bf16(o[6] * s1, o[7] * s1)), "l"(dst) : "memory");
}
__device__ __forceinline__ uint4 load_o(const uint4* src) {
    uint4 v;
    asm volatile("{\n.reg .b128 t;\nld.relaxed.gpu.global.b128 t, [%4];\nmov.b128 {%0, %1, %2, %3}, t;\n}"
                 : "=r"(v.x), "=r"(v.y), "=r"(v.z), "=r"(v.w) : "l"(src) : "memory");
    return v;
}
__device__ __forceinline__ uint32_t bmul2(uint32_t a, uint32_t b) { uint32_t r; asm("mul.rn.bf16x2 %0, %1, %2;" : "=r"(r) : "r"(a), "r"(b)); return r; }
__device__ __forceinline__ void sts32(uint32_t a, uint32_t v) { asm volatile("st.shared.u32 [%0], %1;" ::"r"(a), "r"(v) : "memory"); }
__device__ __forceinline__ void load_q(uint32_t* q, int h, int row, int t) {
    const uint8_t* p = gQ + (size_t)h * (SEQ * 32) + (size_t)row * 32 + t * 4;
    q[0] = __ldcg((const uint32_t*)p); q[1] = __ldcg((const uint32_t*)(p + 256));
    q[2] = __ldcg((const uint32_t*)(p + 16)); q[3] = __ldcg((const uint32_t*)(p + 272));
}

template <int NT>
__device__ __forceinline__ void proj16(float (*c)[8], const __nv_bfloat16* x, const __nv_bfloat16* w, int row0, int rstep, int col, int g, int t) {
#pragma unroll
    for (int i = 0; i < NT; i++)
#pragma unroll
        for (int j = 0; j < 8; j++) c[i][j] = 0.f;
    const unsigned short* wu = (const unsigned short*)w;
#pragma unroll 1
    for (int k = 0; k < DM; k += 16) {
        uint32_t b[4];
#pragma unroll
        for (int j = 0; j < 4; j++) {
            const int kr = k + 2 * t + (j & 1) * 8, cc = col + g + (j >> 1) * 8;
            b[j] = (uint32_t)wu[(size_t)kr * (3 * DM) + cc] | ((uint32_t)wu[(size_t)(kr + 1) * (3 * DM) + cc] << 16);
        }
#pragma unroll
        for (int i = 0; i < NT; i++) {
            const __nv_bfloat16* xp = x + (size_t)(row0 + i * rstep + g) * DM + k + 2 * t;
            const uint32_t a0 = *(const uint32_t*)xp, a1 = *(const uint32_t*)(xp + 8 * DM);
            const uint32_t a2 = *(const uint32_t*)(xp + 8), a3 = *(const uint32_t*)(xp + 8 * DM + 8);
#pragma unroll
            for (int j = 0; j < 2; j++)
                asm volatile("mma.sync.aligned.m16n8k16.row.col.f32.bf16.bf16.f32 {%0,%1,%2,%3}, {%4,%5,%6,%7}, {%8,%9}, {%0,%1,%2,%3};"
                             : "+f"(c[i][4 * j]), "+f"(c[i][4 * j + 1]), "+f"(c[i][4 * j + 2]), "+f"(c[i][4 * j + 3])
                             : "r"(a0), "r"(a1), "r"(a2), "r"(a3), "r"(b[2 * j]), "r"(b[2 * j + 1]));
        }
    }
}

struct Maps { CUtensorMap x, kv, q, f1, f3, h, w2, wo, hs, kvs; };

__global__ void __cluster_dims__(2, 1, 1) __launch_bounds__(640, 1)
fused_kernel(const __grid_constant__ Maps tm, const __nv_bfloat16* __restrict__ x, const __nv_bfloat16* __restrict__ wqkv,
             const __nv_bfloat16* __restrict__ wo, const __nv_bfloat16* __restrict__ w1, const __nv_bfloat16* __restrict__ b1,
             const __nv_bfloat16* __restrict__ w2, const __nv_bfloat16* __restrict__ b2, const __nv_bfloat16* __restrict__ gate,
             __nv_bfloat16* __restrict__ out, const uint32_t m1) {
    const uint32_t sb = smem_u32(smem_raw);
    const uint32_t bar = sb + OFF_BAR;
    const int tid = threadIdx.x, lane = tid & 31;
    const int warp = __shfl_sync(0xffffffffu, tid >> 5, 0);
    const uint32_t rank = cluster_rank();
    const int cl = blockIdx.x >> 1;
    const int nb = cl & 7, mb = (cl >> 3) * 2 + rank;
    const int g = lane >> 2, t = lane & 3;

    const int cb = nb & 3, rb = mb * 2 + (nb >> 2);
    if (tid == 0) TLM(0, 0);
    TL_INIT();
    if (tid == 512) {
        for (int i = 0; i < 8; i++) { mbar_init(bar + B_X + 8 * i, 1); mbar_init(bar + B_KV + 8 * i, 1); mbar_init(bar + B_T + 8 * i, 5); }
        for (int i = 0; i < NR; i++) mbar_init(bar + B_E1 + 8 * i, 16);
        for (int i = 0; i < 4; i++) { mbar_init(bar + B_F2 + 8 * i, 1); mbar_init(bar + B_E2 + 8 * i, 8); }
        asm volatile("fence.mbarrier_init.release.cluster;" ::: "memory");
    } else if (tid == 608) {
        for (int i = 0; i < 32; i++) mbar_init(bar + B_F1 + 8 * i, 1);
        mbar_init(bar + B_DONE, 16);
        mbar_init(bar + B_G, 1);
        for (int i = 0; i < 3; i++) mbar_init(bar + B_SF + 8 * i, i == 1 ? 2 : 1);
        mbar_init(bar + B_SF2, 2);
        mbar_init(bar + B_G3, 1);
        mbar_init(bar + B_G2, 4);
        asm volatile("fence.mbarrier_init.release.cluster;" ::: "memory");
    }
    __syncwarp();
    asm volatile("barrier.cluster.arrive.relaxed.aligned;" ::: "memory");
    if (warp == 19) mbar_expect(bar + B_F1 + 8 * lane, ((KVMASK >> lane) & 1) ? 16384 : 12288);
    if (warp == 16 && lane < 24) mbar_expect(bar + (lane < 8 ? B_X : lane < 16 ? B_KV - 64 : B_T - 128) + 8 * lane, 16384);
    if (tid == 512) {
        tma2d(sb, &tm.x, 0, mb * 128, bar + B_X);
    } else if (tid == 544) {
        map_prefetch(&tm.kv);
        l2_prefetch((const uint8_t*)wqkv + (size_t)blockIdx.x * 3072, 3072);
        l2_prefetch((const uint8_t*)w1 + (size_t)blockIdx.x * 1792, 1792);
        map_prefetch(&tm.q); map_prefetch(&tm.f1); map_prefetch(&tm.f3);
    }
    if ((sb & 0xFFFFFF) != SBD) __trap();
    __syncwarp();
    asm volatile("barrier.cluster.wait.aligned;" ::: "memory");
    if (tid == 0) { TLM(0, 1); TLC(0, 30); }

    if (warp < 16) {
        const int wg = warp >> 2;
        const int h = cl >> 1, qd = (cl & 1) * 2 + rank;
        uint32_t q[4];
        {
            const int w8 = warp & 7;
            const int T = mb * 8 + w8, row0 = T * 16 + g;
            const uint64_t dA0 = mkdesc(SBD + (wg & 1) * 8192, 16, 1024, 1);
            if (wg < 2) {
                float acc[64];
#pragma unroll
                for (int i = 0; i < 64; i++) acc[i] = 0.f;
                gemm_pass<128, 8192, 2048, 4096, 1024, 1>(acc, bar, dA0, lane, strm_pos(3, 0), strm_code(3), 0, true);
                if (tid == 0) TLM(0, 2);
                {
                    const float km = norm_bound(acc, 1.f);
                    float vm = 0.f;
#pragma unroll
                    for (int i = 32; i < 64; i++) vm = fmaxf(vm, fabsf(acc[i]));
                    vm = __uint_as_float(__reduce_max_sync(0xffffffffu, __float_as_uint(vm)));
                    if (lane == 0) { gN[1024 + nb * 128 + T] = km; gN[2048 + nb * 128 + T] = vm; }
                    const uint32_t kp = sb + OFF_R + 12288 + (w8 >> 2) * 1024 + g * 128 + ((((w8 & 3) * 2 + ((t >> 1) ^ (w8 >> 2))) ^ g) << 4) + (t & 1) * 8;
                    uint8_t* vp = gKV + (size_t)(nb * 4) * (SEQ * 64) + 65536 + (((T >> 6) * 16 + 2 * g) * 64 + (T & 63)) * 32 + ((t * 8) ^ ((w8 >> 2) << 4));
                    bar_sync(9, 256);
#pragma unroll
                    for (int hh = 0; hh < 4; hh++) {
                        const float* v = acc + 8 * hh;
                        float p0 = __shfl_up_sync(0xffffffffu, v[2], 4), p1 = __shfl_up_sync(0xffffffffu, v[3], 4);
                        float p2 = __shfl_up_sync(0xffffffffu, v[6], 4), p3 = __shfl_up_sync(0xffffffffu, v[7], 4);
                        if (g == 0) { p0 = p1 = p2 = p3 = 0.f; }
                        sts64(kp + hh * 16384, pk_f16(v[0] - p0, v[1] - p1), pk_f16(v[4] - p2, v[5] - p3));
                        sts64(kp + hh * 16384 + 2048, pk_f16(v[2] - v[0], v[3] - v[1]), pk_f16(v[6] - v[4], v[7] - v[5]));
                        const float* u = acc + 32 + 8 * hh;
                        if (hh < 2) {
                            sts64(kp + (4 + hh) * 16384, pk_bf16(u[0], u[1]), pk_bf16(u[4], u[5]));
                            sts64(kp + (4 + hh) * 16384 + 2048, pk_bf16(u[2], u[3]), pk_bf16(u[6], u[7]));
                        } else {
                            *(uint2*)(vp + (size_t)hh * (SEQ * 64)) = make_uint2(pk_bf16(u[0], u[1]), pk_bf16(u[4], u[5]));
                            *(uint2*)(vp + (size_t)hh * (SEQ * 64) + 2048) = make_uint2(pk_bf16(u[2], u[3]), pk_bf16(u[6], u[7]));
                        }
                    }
                }
                asm volatile("fence.proxy.async.shared::cta;" ::: "memory");
                bar_arrive(10, 288);
                if (tid == 0) TLM(0, 3);
            }
#pragma unroll 1
            for (int p = wg < 2 ? 1 : 0; p < 3; p += 2) {
                float acc[48];
#pragma unroll
                for (int i = 0; i < 48; i++) acc[i] = 0.f;
                pin<48>(acc);
                if (p) bar_sync(5 + p, 512);
                gemm_pass<96, 6144, 1024, 2048, 512, 2>(acc, bar, dA0, lane, p == 0 ? strm_pos(0, 0) : 8 + 8 * p, p == 0 ? strm_code(0) : strm_code(1), p < 2 ? 6 + p : 0, p == 0);
                if ((tid & 255) == 0) TLM(0, 4 + 2 * p);
                const uint32_t hp = sb + OFF_R + (p == 2 ? 0 : 12288) + (wg & 1) * 16384 + ((warp & 3) * 16 + g) * 64 + t * 16;
                const uint32_t bp = sb + OFF_BIAS + p * 384 - 256 + t * 8;
                uint32_t ho[24];
                mbar_wait(bar + B_BI, 0);
                if (p == 0) {
                    const float qm = norm_bound(acc, QSCALE * QSCALE);
                    if (lane == 0) gN[nb * 128 + T] = qm;
                    uint8_t* qp = gQ + (size_t)(nb * 4) * (SEQ * 32) + (size_t)row0 * 32 + t * 8;
#pragma unroll
                    for (int hh = 0; hh < 4; hh++) {
                        const float* v = acc + 8 * hh;
                        *(uint2*)(qp + hh * (SEQ * 32)) = make_uint2(pk_f16(v[0] * QSCALE, v[1] * QSCALE), pk_f16(v[4] * QSCALE, v[5] * QSCALE));
                        *(uint2*)(qp + hh * (SEQ * 32) + 256) = make_uint2(pk_f16(v[2] * QSCALE, v[3] * QSCALE), pk_f16(v[6] * QSCALE, v[7] * QSCALE));
                    }
                    bar_arrive(12, 288);
                } else {
                    if (p == 2) {
                        mbar_wait(bar + B_G, 0);
                        load_q(q, h, qd * 512 + warp * 16 + g, t);
                    }
                    gelu_pack<0, 2>(acc, bp, ho);
                }
                gelu_pack<2, 3>(acc, bp, ho);
                pin<8>(ho + 16);
                if (p == 2) bar_sync(9, 256);
                else mbar_wait(bar + B_SF + 8 * p, 0);
                if (p) {
#pragma unroll
                    for (int i = 0; i < 4; i++) sts128(hp + (i >> 1) * 32768 + (i & 1) * 512, ho + 4 * i);
                }
                sts128(hp + 65536, ho + 16);
                sts128(hp + 65536 + 512, ho + 20);
                asm volatile("fence.proxy.async.shared::cta;" ::: "memory");
                bar_arrive(p == 1 ? 14 : 11, 288);
                if ((tid & 255) == 0) TLM(0, 5 + 2 * p);
            }
            if (wg < 2) {
                mbar_wait(bar + B_G, 0);
                load_q(q, h, qd * 512 + warp * 16 + g, t);
            }
        }
        mbar_wait(bar + B_G3, 0);
        const uint32_t ep = lds32(sb + OFF_G + 256);
        const bool fast = (ep & 2) != 0;
        uint4* const op = gO + ((qd * 8 + wg) * NH + h) * 128 + (tid & 127);
        const uint64_t kd0 = mkdesc(SBD, 16, 256, 3);
        const uint64_t vd0 = mkdesc(SBD + 8192, OFF_ONE - 8192, 256, 3);
        if (fast) {
#pragma unroll 1
            for (int r = 0; r < 2; r++) {
                float o[12];
#pragma unroll
                for (int i = 0; i < 12; i++) o[i] = 0.f;
                uint64_t kd = kd0, vd = vd0;
                uint32_t qn[4];
#pragma unroll 1
                for (int half = 0; half < 2; half++) {
                    float s[32];
#pragma unroll
                    for (int i = 0; i < 32; i++) s[i] = i < 2 * NMUFU ? 0.f : MAGIC;
#pragma unroll 1
                    for (int c = 0; c < 4; c++) {
                        if (r == 0) mbar_wait(bar + B_KV + 8 * (half * 4 + c), 0);
                        if ((tid & 255) == 0 && c == 0) TLM(1, (tid >> 8) * 4 + r * 2 + half);
                        if (half == 1 && c == 3) {
                            if (r == 0) load_q(qn, h, qd * 512 + 256 + warp * 16 + g, t);
                            else if (lane == 0) mbar_arrive(bar + B_DONE);
                        }
#pragma unroll
                        for (int j = 0; j < 4; j++) {
                            uint32_t p[16];
                            wg_fence();
                            wgmma_qk_f16_acc(s, q, kd);
                            wg_commit();
                            wg_wait<0>();
                            pin<32>(s);
#pragma unroll
                            for (int i = 0; i < 16; i++)
                                p[i] = i < NMUFU ? pk_bf16(ex2f(s[2 * i]), ex2f(s[2 * i + 1])) : exp2_pair(s[2 * i], s[2 * i + 1], m1);
                            pin<16>(p);
                            wg_fence();
#pragma unroll
                            for (int u = 0; u < 4; u++) wgmma_pv(o, p + 4 * u, vd + u * VSTEP);
                            wg_commit();
                            kd += 128;
                            vd += 4 * VSTEP;
                        }
                        kd += 512;
                        vd += 16 * VSTEP;
                    }
                    wg_wait<0>();
                }
                pin<12>(o);
                if ((tid & 127) == 0 && r == 1) TLM(1, 8 + wg);
                store_o(o, op + r * (4 * NH * 128), ep & 1);
#pragma unroll
                for (int i = 0; i < 4; i++) q[i] = qn[i];
            }
            if (tid == 0) { TLM(1, 12); TLC(0, 31); }
        } else {
            for (int c = 0; c < 8; c++) mbar_wait(bar + B_KV + 8 * c, 0);
            {
                float kc[8][8];
                proj16<8>(kc, x, wqkv, warp * 16, 256, DM + h * 16, g, t);
#pragma unroll
                for (int i = 0; i < 8; i++) {
                    const int T = warp + i * 16;
                    const int pos = ((T >> 6) * 16 + 2 * g) * 64 + (T & 63);
                    const uint32_t a = sb + (pos >> 8) * 16384 + (pos & 255) * 32 + t * 4, sw = ((T >> 2) & 1) << 4;
                    asm volatile("st.shared.u32 [%0], %1;" ::"r"(a + sw), "r"(pk_bf16(kc[i][0], kc[i][1])) : "memory");
                    asm volatile("st.shared.u32 [%0], %1;" ::"r"(a + (sw ^ 16)), "r"(pk_bf16(kc[i][4], kc[i][5])) : "memory");
                    asm volatile("st.shared.u32 [%0], %1;" ::"r"(a + 2048 + sw), "r"(pk_bf16(kc[i][2], kc[i][3])) : "memory");
                    asm volatile("st.shared.u32 [%0], %1;" ::"r"(a + 2048 + (sw ^ 16)), "r"(pk_bf16(kc[i][6], kc[i][7])) : "memory");
                }
                asm volatile("fence.proxy.async.shared::cta;" ::: "memory");
                bar_sync(8, 512);
            }
#pragma unroll 1
            for (int r = 0; r < 2; r++) {
                const int row = qd * 512 + r * 256 + warp * 16 + g;
                {
                    float qc[1][8];
                    proj16<1>(qc, x, wqkv, row - g, 0, h * 16, g, t);
#pragma unroll
                    for (int i = 0; i < 4; i++) q[i] = pk_bf16(qc[0][2 * i] * QSCALE, qc[0][2 * i + 1] * QSCALE);
                }
                float o[12];
#pragma unroll
                for (int i = 0; i < 12; i++) o[i] = 0.f;
                float m0 = -INFINITY, m1 = -INFINITY;
#pragma unroll 1
                for (int j = 0; j < 32; j++) {
                    const uint64_t kd = kd0 + (j >> 2) * 1024 + (j & 3) * 128, vd = vd0 + ((j >> 2) * 32 + (j & 3) * 4) * VSTEP;
                    float s[32];
                    uint32_t p[16];
                    wg_fence();
                    wgmma_qk_bf16_zero(s, q, kd);
                    wg_commit();
                    wg_wait<0>();
                    pin<32>(s);
                    pin<12>(o);
                    float n0 = m0, n1 = m1;
#pragma unroll
                    for (int i = 0; i < 8; i++) {
                        n0 = fmaxf(n0, fmaxf(s[4 * i], s[4 * i + 1]));
                        n1 = fmaxf(n1, fmaxf(s[4 * i + 2], s[4 * i + 3]));
                    }
                    n0 = fmaxf(n0, __shfl_xor_sync(0xffffffffu, n0, 1));
                    n1 = fmaxf(n1, __shfl_xor_sync(0xffffffffu, n1, 1));
                    n0 = fmaxf(n0, __shfl_xor_sync(0xffffffffu, n0, 2));
                    n1 = fmaxf(n1, __shfl_xor_sync(0xffffffffu, n1, 2));
                    const float c0 = ex2f(m0 - n0), c1 = ex2f(m1 - n1);
                    m0 = n0;
                    m1 = n1;
#pragma unroll
                    for (int i = 0; i < 3; i++) { o[4 * i] *= c0; o[4 * i + 1] *= c0; o[4 * i + 2] *= c1; o[4 * i + 3] *= c1; }
#pragma unroll
                    for (int i = 0; i < 8; i++) {
                        p[2 * i] = pk_bf16(ex2f(s[4 * i] - m0), ex2f(s[4 * i + 1] - m0));
                        p[2 * i + 1] = pk_bf16(ex2f(s[4 * i + 2] - m1), ex2f(s[4 * i + 3] - m1));
                    }
                    pin<16>(p);
                    pin<12>(o);
                    wg_fence();
#pragma unroll
                    for (int u = 0; u < 4; u++) wgmma_pv(o, p + 4 * u, vd + u * VSTEP);
                    wg_commit();
                }
                wg_wait<0>();
                pin<12>(o);
                if (r == 1 && lane == 0) mbar_arrive(bar + B_DONE);
                store_o(o, op + r * (4 * NH * 128), ep & 1);
            }
        }
        {
            const uint4* src = gO + (rb * NH + wg * 8) * 128 + (tid & 127);
            uint4 v[8];
#pragma unroll
            for (int i = 0; i < 8; i++) v[i] = load_o(src + i * 128);
            mbar_wait(bar + B_DONE, 0);
            mbar_wait(bar + B_G2, 0);
            const int lr = (warp & 3) * 16 + g;
            const uint32_t g0 = lds32(sb + OFF_G + lr * 4), g1 = lds32(sb + OFF_G + lr * 4 + 32);
            const uint32_t a0 = sb + wg * 16384 + lr * 128 + (t >> 1) * 4;
#pragma unroll
            for (int i = 0; i < 8; i++) {
                if ((i & 3) == 0) {
                    int spins = 0;
                    while (__any_sync(0xffffffffu, (((v[i].x ^ ep) | (v[i + 1].x ^ ep) | (v[i + 2].x ^ ep) | (v[i + 3].x ^ ep)) & 1) != 0)) {
                        if (++spins > (1 << 22)) __trap();
#pragma unroll
                        for (int k = i; k < 8; k++)
                            if (((v[k].x ^ ep) & 1) != 0) v[k] = load_o(src + k * 128);
                    }
                }
                const uint32_t a = a0 + (i >> 2) * 8192 + ((((i & 3) * 2 + (t & 1)) ^ g) << 4);
                sts32(a, bmul2(v[i].x, g0));
                sts32(a + 8, bmul2(v[i].y, g0));
                sts32(a + 1024, bmul2(v[i].z, g1));
                sts32(a + 1024 + 8, bmul2(v[i].w, g1));
                if ((i & 3) == 3) {
                    asm volatile("fence.proxy.async.shared::cta;" ::: "memory");
                    __syncwarp();
                    if (lane == 0) mbar_arrive(bar + B_T + 8 * (wg * 2 + (i >> 2)));
                    if ((tid & 127) == 0) TLM(1, 20 + wg * 2 + (i >> 2));
                }
            }
        }
    } else {
        if (warp == 16) {
            if (elect()) {
                const uint32_t dst = sb + OFF_R;
                const int kr = rank * 32;
#pragma unroll
                for (int it = 0; it < 32; it++) {
                    const int s = it % NR;
                    const uint32_t fb = bar + B_F1 + 8 * it;
                    if (it >= NR) mbar_wait(bar + B_E1 + 8 * s, ((it / NR) - 1) & 1);
                    const int nkv = __builtin_popcount(KVMASK & ((1u << it) - 1));
                    if (it < 16 && ((KVMASK >> it) & 1)) {
                        tma3d_mc(dst + s * 16384 + rank * 8192, &tm.kv, nb * 64, nkv * 64 + kr, 1, fb);
                    } else if (it < 16) {
                        tma3d_mc(dst + s * 16384 + rank * 6144, &tm.q, 0, (it - nkv) * 64 + kr, nb * 2, fb);
                        tma3d_mc(dst + s * 16384 + rank * 6144 + 4096, &tm.f1, 0, (it - nkv) * 64 + kr, nb * 7, fb);
                    } else {
                        tma3d_mc(dst + s * 16384 + rank * 6144, &tm.f3, 0, (it & 7) * 64 + kr, nb * 7 + (it < 24 ? 1 : 4), fb);
                    }
                    if ((XMASK >> it) & 1) {
                        const int xc = 1 + __builtin_popcount(XMASK & ((1u << it) - 1));
                        tma2d(sb + xc * 16384, &tm.x, xc * 64, mb * 128, bar + B_X + 8 * xc);
                    }
                }
                const int h = cl >> 1;
                mbar_wait(bar + B_G, 0);
                asm volatile("fence.proxy.async.global;" ::: "memory");
                TLM(0, 10);
#pragma unroll
                for (int c = 0; c < 8; c++) {
                    if (c >= 8 - NR) mbar_wait(bar + B_E1 + 8 * ((24 + c) % NR), ((24 + c) / NR) & 1);
                    bulk_mc(sb + c * 16384 + rank * 8192, gKV + (size_t)h * (SEQ * 64) + rank * 65536 + c * 8192, 8192, bar + B_KV + 8 * c);
                }
                mbar_wait(bar + B_SF2, 0);
#pragma unroll
                for (int s = 0; s < 4; s++) {
                    mbar_expect(bar + B_F2 + 8 * s, 24576);
                    tma5d_mc(sb + OFF_R + s * 24576 + 8192 + rank * 8192, &tm.w2, cb * 128 + rank * 64, s * 2, bar + B_F2 + 8 * s);
                }
                cnt_wait(gCntH + mb * 32, epoch() * 8);
                asm volatile("fence.proxy.async.global;" ::: "memory");
                TLM(1, 13);
#pragma unroll
                for (int s = 0; s < 4; s++) tma2d(sb + OFF_R + s * 24576, &tm.h, s * 64, rb * 64, bar + B_F2 + 8 * s);
            }
        } else if (warp == 17) {
            {
                uint32_t bv[4], b2v[2];
#pragma unroll
                for (int i = 0; i < 4; i++) bv[i] = lane + 32 * i < 112 ? *(const uint32_t*)(b1 + nb * 224 + (lane + 32 * i) * 2) : 0;
#pragma unroll
                for (int i = 0; i < 2; i++) b2v[i] = *(const uint32_t*)(b2 + cb * 128 + (lane + 32 * i) * 2);
#pragma unroll
                for (int i = 0; i < 4; i++) {
                    sts32(sb + OFF_ONE + (lane + 32 * i) * 4, 0x3f803f80u);
                    if (lane + 32 * i < 112) sts64(sb + OFF_BIAS + (lane + 32 * i) * 8, bv[i] << 16, bv[i] & 0xffff0000u);
                }
#pragma unroll
                for (int i = 0; i < 2; i++) sts32(sb + OFF_BIAS + 896 + (lane + 32 * i) * 4, b2v[i]);
                asm volatile("fence.proxy.async.shared::cta;" ::: "memory");
                __syncwarp();
                if (lane == 0) mbar_arrive(bar + B_BI);
            }
            mbar_wait(bar + B_X + 8 * PFX, 0);
            if (lane == 0) {
                l2_prefetch((const uint8_t*)wqkv + 128 * 3072 + (size_t)blockIdx.x * 9216, 9216);
                l2_prefetch((const uint8_t*)w1 + (size_t)blockIdx.x * 14336, 14336);
            }
            mbar_wait(bar + B_X + 8 * 7, 0);
            if (lane == 0) {
                l2_prefetch((const uint8_t*)w2 + (size_t)blockIdx.x * 14336, 14336);
                l2_prefetch((const uint8_t*)wo + (size_t)blockIdx.x * 4096, 4096);
                map_prefetch(&tm.h); map_prefetch(&tm.w2); map_prefetch(&tm.wo); map_prefetch(&tm.hs); map_prefetch(&tm.kvs);
                TLM(0, 11);
            }
            bar_sync(10, 288);
            if (lane == 0) {
#pragma unroll 1
                for (int b = 5; b >= 0; b--) {
                    tma5d_st(&tm.kvs, sb + OFF_R + 12288 + b * 16384, (mb >> 3) * 8, (mb & 7) * 2, nb * 8 + (b < 4 ? 2 * b : 2 * b - 7));
                    asm volatile("cp.async.bulk.commit_group;\ncp.async.bulk.wait_group.read %0;" ::"n"(PACE) : "memory");
                    if (b == 4 - PACE) mbar_arrive(bar + B_SF);
                }
                asm volatile("cp.async.bulk.wait_group.read 0;" ::: "memory");
                mbar_arrive(bar + B_SF + 8);
            }
            __syncwarp();
            bar_sync(12, 288);
            if (lane == 0) {
                asm volatile("cp.async.bulk.wait_group 0;\nfence.proxy.async.global;" ::: "memory");
                cnt_add(gCntQ + nb * 32);
                TLM(0, 13);
            }
        } else {
            {
                const int r0 = mb * 128 + nb * 16 + (warp - 18) * 8;
                uint4 xv[16];
#pragma unroll
                for (int i = 0; i < 16; i++) xv[i] = *(const uint4*)(x + (size_t)(r0 + (i >> 1)) * DM + (i & 1) * 256 + lane * 8);
                const uint4 ga = *(const uint4*)(gate + lane * 8), gb = *(const uint4*)(gate + 256 + lane * 8);
                float z[8];
#pragma unroll
                for (int r = 0; r < 8; r++) z[r] = dot8(xv[2 * r], ga) + dot8(xv[2 * r + 1], gb);
#pragma unroll
                for (int w = 4; w >= 1; w >>= 1)
#pragma unroll
                    for (int r = 0; r < w; r++) {
                        const bool up = lane & w;
                        z[r] = (up ? z[r + w] : z[r]) + __shfl_xor_sync(0xffffffffu, up ? z[r] : z[r + w], w);
                    }
                z[0] += __shfl_xor_sync(0xffffffffu, z[0], 8);
                z[0] += __shfl_xor_sync(0xffffffffu, z[0], 16);
                if (lane < 8) gG[r0 + lane] = 1.f / (1.f + __expf(-z[0]));
                if (tid == 576) TLM(0, 12);
            }
            if (warp == 19) {
#pragma unroll 1
                for (int e = 0; e < 3; e++) {
                    bar_sync(e == 1 ? 14 : 11, 288);
                    if (lane == 0) {
#pragma unroll 1
                        for (int b = e == 0 ? 4 : 0; b < 6; b++) {
                            tma3d_st(&tm.hs, sb + OFF_R + (e == 2 ? 0 : 12288) + b * 16384, 0, mb * 128 + (b & 1) * 64, nb * 7 + e * 3 - 2 + (b >> 1));
                            asm volatile("cp.async.bulk.commit_group;\ncp.async.bulk.wait_group.read %0;" ::"n"(PACE) : "memory");
                        }
                        asm volatile("cp.async.bulk.wait_group.read 0;" ::: "memory");
                        if (e == 0) mbar_arrive(bar + B_SF + 8);
                        if (e == 2) { mbar_arrive_cluster(bar + B_SF2, 0); mbar_arrive_cluster(bar + B_SF2, 1); }
                    }
                    __syncwarp();
                }
                bar_sync(13, 64);
                if (lane == 0) {
                    asm volatile("cp.async.bulk.wait_group 0;\nfence.proxy.async.global;" ::: "memory");
                    cnt_add(gCntH + mb * 32);
                    TLM(0, 15);
                }
            } else {
                bar_arrive(13, 64);
                const int h = cl >> 1, qd = (cl & 1) * 2 + rank;
                if (lane == 0) {
                    cnt_wait(gCntQ + (h >> 2) * 32, epoch() * 16);
                    mbar_arrive(bar + B_G);
                    TLM(0, 14);
                }
                __syncwarp();
            const int hb = h >> 2;
            const uint4 kq = __ldcg((const uint4*)(gN + 1024 + hb * 128 + lane * 4));
            const uint4 vq = __ldcg((const uint4*)(gN + 2048 + hb * 128 + lane * 4));
            const float qq = ldcg_f(gN + hb * 128 + qd * 32 + lane);
            const float kf = __uint_as_float(__reduce_max_sync(0xffffffffu, max(max(kq.x, kq.y), max(kq.z, kq.w))));
            const float vf = __uint_as_float(__reduce_max_sync(0xffffffffu, max(max(vq.x, vq.y), max(vq.z, vq.w))));
            const float qf = __uint_as_float(__reduce_max_sync(0xffffffffu, __float_as_uint(qq)));
            if (lane == 0) {
                sts32(sb + OFF_G + 256, (epoch() & 1) | ((kf <= 1.0e6f) && (qf <= 1.0e6f) && (kf * qf <= 3400.f) && (vf <= 1.0e12f) ? 2 : 0));
                mbar_arrive(bar + B_G3);
            }
            }
        }
        __syncwarp();
        float acc[64];
#pragma unroll
        for (int i = 0; i < 64; i++) acc[i] = 0.f;
#pragma unroll 1
        for (int io = 0; io < 7; io++) {
#pragma unroll
            for (int s = 0; s < 4; s++) {
                const int it = io * 4 + s;
                mbar_wait(bar + B_F2 + 8 * s, io & 1);
                if (tid == 512 && s == 0 && (io == 0 || io == 4)) TLM(1, 14 + io / 4);
                const uint64_t dA = mkdesc(SBD + OFF_R + s * 24576, 16, 1024, 1);
                const uint64_t dB = mkdesc(SBD + OFF_R + s * 24576 + 8192, 8192, 1024, 1);
                wg_fence();
#pragma unroll
                for (int kk = 0; kk < EXP_FKK; kk++) wgmma_ss_n128(acc, dA + kk * 2, dB + kk * 128);
                wg_commit();
                if (warp < 18 && it >= 2 && it < 26) {
                    const int s2 = (s + 2) & 3;
                    mbar_wait(bar + B_E2 + 8 * s2, (io - (s < 2)) & 1);
                    if (elect()) {
                        if (warp == 16) {
                            mbar_expect(bar + B_F2 + 8 * s2, 24576);
                            tma5d_mc(sb + OFF_R + s2 * 24576 + 8192 + rank * 8192, &tm.w2, cb * 128 + rank * 64, it * 2 + 4, bar + B_F2 + 8 * s2);
                        } else {
                            asm volatile("fence.proxy.async.global;" ::: "memory");
                            tma2d(sb + OFF_R + s2 * 24576, &tm.h, it * 64 + 128, rb * 64, bar + B_F2 + 8 * s2);
                        }
                    }
                    __syncwarp();
                }
                wg_wait<1>();
                if (it >= 1 && lane < 2) mbar_arrive_cluster(bar + B_E2 + 8 * ((s + 3) & 3), lane);
            }
        }
        wg_wait<0>();
        if (lane < 2) mbar_arrive_cluster(bar + B_E2 + 8 * 3, lane);
        pin<64>(acc);
        if (tid == 576) gEpoch[blockIdx.x] = epoch();
        if (warp == 16) {
            if (lane == 0) TLM(1, 16);
            for (int s = 0; s < 4; s++) mbar_wait(bar + B_E2 + 8 * s, 0);
            if (elect()) {
#pragma unroll
                for (int i = 0; i < 6; i++) tma2d_mc(sb + OFF_R + i * 16384 + rank * 8192, &tm.wo, cb * 128 + rank * 64, i * 64, bar + B_T + 8 * i);
            }
            __syncwarp();
        }
        {
            const int lr = (warp - 16) * 16 + g;
            const uint32_t pa = pk_bf16(ldcg_f(gG + rb * 64 + lr), ldcg_f(gG + rb * 64 + lr + 8));
            if (t == 0) {
                sts32(sb + OFF_G + lr * 4, __byte_perm(pa, pa, 0x1010));
                sts32(sb + OFF_G + lr * 4 + 32, __byte_perm(pa, pa, 0x3232));
            }
            __syncwarp();
            if (lane == 0) mbar_arrive(bar + B_G2);
            const float ga = bf_lo(pa), gb = bf_hi(pa);
            const float g0 = 1.f - ga, g1 = 1.f - gb;
#pragma unroll
            for (int j = 0; j < 16; j++) {
                const uint32_t bv = lds32(sb + OFF_BIAS + 896 + j * 16 + t * 4);
                acc[4 * j] = fmaf(acc[4 * j], 0.5f, bf_lo(bv)) * g0;
                acc[4 * j + 1] = fmaf(acc[4 * j + 1], 0.5f, bf_hi(bv)) * g0;
                acc[4 * j + 2] = fmaf(acc[4 * j + 2], 0.5f, bf_lo(bv)) * g1;
                acc[4 * j + 3] = fmaf(acc[4 * j + 3], 0.5f, bf_hi(bv)) * g1;
            }
            pin<64>(acc);
        }
        if (warp == 17) {
            mbar_wait(bar + B_DONE, 0);
            if (elect()) {
#pragma unroll
                for (int i = 0; i < 4; i++)
                    tma2d(sb + 65536 + i * 8192, &tm.wo, cb * 128 + (i & 1) * 64, (6 + (i >> 1)) * 64, bar + B_T + 8 * (6 + (i >> 1)));
            }
            __syncwarp();
        }
        if (tid == 512) TLM(1, 17);
#pragma unroll
        for (int i = 0; i < 8; i++) {
            mbar_wait(bar + B_T + 8 * i, 0);
            const uint64_t dA = mkdesc(SBD + i * 8192, 16, 1024, 1);
            const uint64_t dB = mkdesc(i < 6 ? SBD + OFF_R + i * 16384 : SBD + 65536 + (i - 6) * 16384, 8192, 1024, 1);
            wg_fence();
#pragma unroll
            for (int kk = 0; kk < 4; kk++) wgmma_ss_n128(acc, dA + kk * 2, dB + kk * 128);
            wg_commit();
        }
        wg_wait<0>();
        pin<64>(acc);
        if (tid == 512) TLM(1, 18);
        {
            const uint32_t st = sb + 98304 + (warp - 16) * 4352;
            const uint32_t wa = st + (lane & 15) * 272 + (lane >> 4) * 16;
#pragma unroll
            for (int j = 0; j < 8; j++)
                asm volatile("stmatrix.sync.aligned.m8n8.x4.shared.b16 [%0], {%1, %2, %3, %4};" ::"r"(wa + j * 32),
                             "r"(pk_bf16(acc[8 * j], acc[8 * j + 1])), "r"(pk_bf16(acc[8 * j + 2], acc[8 * j + 3])),
                             "r"(pk_bf16(acc[8 * j + 4], acc[8 * j + 5])), "r"(pk_bf16(acc[8 * j + 6], acc[8 * j + 7])) : "memory");
            __syncwarp();
            __nv_bfloat16* op = out + (size_t)(rb * 64 + (warp - 16) * 16 + (lane >> 4)) * DM + cb * 128 + (lane & 15) * 8;
#pragma unroll
            for (int j = 0; j < 8; j++) {
                uint4 v;
                asm volatile("ld.shared.v4.u32 {%0, %1, %2, %3}, [%4];" : "=r"(v.x), "=r"(v.y), "=r"(v.z), "=r"(v.w)
                             : "r"(st + (2 * j + (lane >> 4)) * 272 + (lane & 15) * 16));
                *(uint4*)(op + (size_t)j * 2 * DM) = v;
            }
        }
        if (tid == 512) TLM(1, 19);
        TL_DUMP();
    }
}

typedef CUresult (*EncodeFn)(CUtensorMap*, CUtensorMapDataType, cuuint32_t, void*, const cuuint64_t*, const cuuint64_t*, const cuuint32_t*,
                             const cuuint32_t*, CUtensorMapInterleave, CUtensorMapSwizzle, CUtensorMapL2promotion, CUtensorMapFloatOOBfill);

static void make_map(EncodeFn enc, CUtensorMap* m, const void* p, int rank, const cuuint64_t* dims, const cuuint64_t* strides,
                     const cuuint32_t* box, CUtensorMapSwizzle swz) {
    const cuuint32_t es[5] = {1, 1, 1, 1, 1};
    enc(m, CU_TENSOR_MAP_DATA_TYPE_BFLOAT16, rank, (void*)p, dims, strides, box, es, CU_TENSOR_MAP_INTERLEAVE_NONE, swz,
        CU_TENSOR_MAP_L2_PROMOTION_L2_128B, CU_TENSOR_MAP_FLOAT_OOB_FILL_NONE);
}

extern "C" void kernel_launch(void* const* d_in, const int* in_sizes, int n_in, void* d_out, int out_size) {
    const __nv_bfloat16* x = (const __nv_bfloat16*)d_in[0];
    const __nv_bfloat16* wqkv = (const __nv_bfloat16*)d_in[1];
    const __nv_bfloat16* wo = (const __nv_bfloat16*)d_in[2];
    const __nv_bfloat16* w1 = (const __nv_bfloat16*)d_in[4];
    const __nv_bfloat16* b1 = (const __nv_bfloat16*)d_in[5];
    const __nv_bfloat16* w2 = (const __nv_bfloat16*)d_in[6];
    const __nv_bfloat16* b2 = (const __nv_bfloat16*)d_in[7];
    const __nv_bfloat16* gate = (const __nv_bfloat16*)d_in[8];

    void* fp = nullptr;
    cudaDriverEntryPointQueryResult qr;
    cudaGetDriverEntryPoint("cuTensorMapEncodeTiled", &fp, cudaEnableDefault, &qr);
    EncodeFn enc = (EncodeFn)fp;
    void *pH, *pKV;
    cudaGetSymbolAddress(&pH, gH);
    cudaGetSymbolAddress(&pKV, gKV);

    Maps tm;
    const CUtensorMapSwizzle S128 = CU_TENSOR_MAP_SWIZZLE_128B, S64 = CU_TENSOR_MAP_SWIZZLE_64B;
    { cuuint64_t d[2] = {DM, SEQ}, s[1] = {DM * 2}; cuuint32_t b[2] = {64, 128}; make_map(enc, &tm.x, x, 2, d, s, b, S128); }
    { cuuint64_t d[3] = {DM, DM, 3}, s[2] = {3 * DM * 2, DM * 2}; cuuint32_t b[3] = {64, 32, 2}; make_map(enc, &tm.kv, wqkv, 3, d, s, b, S128); }
    { cuuint64_t d[3] = {32, DM, 3 * DM / 32}, s[2] = {3 * DM * 2, 64}; cuuint32_t b[3] = {32, 32, 2}; make_map(enc, &tm.q, wqkv, 3, d, s, b, S64); }
    { cuuint64_t d[3] = {32, DM, FF / 32}, s[2] = {FF * 2, 64}; cuuint32_t b[3] = {32, 32, 1}; make_map(enc, &tm.f1, w1, 3, d, s, b, S64); }
    { cuuint64_t d[3] = {32, DM, FF / 32}, s[2] = {FF * 2, 64}; cuuint32_t b[3] = {32, 32, 3}; make_map(enc, &tm.f3, w1, 3, d, s, b, S64); }
    { cuuint64_t d[2] = {FF, SEQ}, s[1] = {FF * 2}; cuuint32_t b[2] = {64, 64}; make_map(enc, &tm.h, pH, 2, d, s, b, S128); }
    { cuuint64_t d[5] = {DM, 2, 4, 4, FF / 32}, s[4] = {1024, 8 * 1024, 2 * 1024, 32 * 1024}; cuuint32_t b[5] = {64, 2, 4, 4, 2};
      make_map(enc, &tm.w2, w2, 5, d, s, b, S128); }
    { cuuint64_t d[2] = {DM, DM}, s[1] = {DM * 2}; cuuint32_t b[2] = {64, 64}; make_map(enc, &tm.wo, wo, 2, d, s, b, S128); }

    { cuuint64_t d[3] = {32, SEQ, FF / 32}, s[2] = {FF * 2, 64}; cuuint32_t b[3] = {32, 64, 1}; make_map(enc, &tm.hs, pH, 3, d, s, b, CU_TENSOR_MAP_SWIZZLE_NONE); }
    { cuuint64_t d[5] = {64, 16, 16, 2, 2 * NH}, s[4] = {4096, 128, 2048, 65536}; cuuint32_t b[5] = {64, 8, 2, 2, 1};
      make_map(enc, &tm.kvs, pKV, 5, d, s, b, S128); }
    cudaFuncSetAttribute(fused_kernel, cudaFuncAttributeMaxDynamicSharedMemorySize, TL_SMEM);
    fused_kernel<<<128, 640, TL_SMEM, cudaStreamPerThread>>>(tm, x, wqkv, wo, w1, b1, w2, b2, gate, (__nv_bfloat16*)d_out, 0xffffffffu);
}
```

```cpp
#include <cuda_runtime.h>
#include <cuda_bf16.h>
#include <cuda_fp16.h>
#include <cuda.h>
#include <stdint.h>

#define SEQ 2048
#define DM 512
#define FF 1792
#define NH 32

__device__ __align__(1024) uint8_t gQ[NH * SEQ * 32];
__device__ __align__(1024) uint8_t gKV[NH * SEQ * 64];
__device__ __align__(1024) __nv_bfloat16 gH[SEQ * FF];
__device__ __align__(1024) uint4 gO[32 * NH * 128];
__device__ float gG[SEQ];
__device__ float gN[3 * 8 * 128];
__device__ unsigned int gCntQ[8 * 32];
__device__ unsigned int gCntH[32 * 32];
__device__ unsigned int gEpoch[128];

__device__ __forceinline__ uint32_t smem_u32(const void* p) { return (uint32_t)__cvta_generic_to_shared(p); }
__device__ __forceinline__ void mbar_init(uint32_t a, uint32_t c) { asm volatile("mbarrier.init.shared::cta.b64 [%0], %1;" ::"r"(a), "r"(c)); }
__device__ __forceinline__ void mbar_expect(uint32_t a, uint32_t b) { asm volatile("mbarrier.arrive.expect_tx.shared::cta.b64 _, [%0], %1;" ::"r"(a), "r"(b) : "memory"); }
__device__ __forceinline__ void mbar_arrive(uint32_t a) { asm volatile("mbarrier.arrive.shared::cta.b64 _, [%0];" ::"r"(a) : "memory"); }
__device__ __forceinline__ void mbar_wait(uint32_t a, uint32_t ph) {
    asm volatile("{\n.reg .pred p;\n.reg .u32 n;\nmov.u32 n, 0;\nW_%=:\nmbarrier.try_wait.parity.shared::cta.b64 p, [%0], %1;\n@p bra D_%=;\n"
                 "add.u32 n, n, 1;\nsetp.lt.u32 p, n, 0x400000;\n@p bra W_%=;\ntrap;\nD_%=:\n}" ::"r"(a), "r"(ph) : "memory");
}
__device__ __forceinline__ void mbar_arrive_cluster(uint32_t a, uint32_t cta) {
    asm volatile("{\n.reg .b32 r;\nmapa.shared::cluster.u32 r, %0, %1;\nmbarrier.arrive.shared::cluster.b64 _, [r];\n}" ::"r"(a), "r"(cta) : "memory");
}
__device__ __forceinline__ void bar_sync(int id, int n) { asm volatile("bar.sync %0, %1;" ::"r"(id), "r"(n) : "memory"); }
__device__ __forceinline__ void bar_arrive(int id, int n) { asm volatile("bar.arrive %0, %1;" ::"r"(id), "r"(n) : "memory"); }
__device__ __forceinline__ uint32_t cluster_rank() { uint32_t r; asm("mov.u32 %0, %%cluster_ctarank;" : "=r"(r)); return r; }
__device__ __forceinline__ void cnt_add(unsigned int* c) { asm volatile("red.release.gpu.global.add.u32 [%0], 1;" ::"l"(c) : "memory"); }
__device__ __forceinline__ void cnt_wait(const unsigned int* c, uint32_t target) {
    uint32_t v;
    int spins = 0;
    while (true) {
        asm volatile("ld.acquire.gpu.global.u32 %0, [%1];" : "=r"(v) : "l"(c) : "memory");
        if ((int)(v - target) >= 0) break;
        if (++spins > (1 << 22)) __trap();
        __nanosleep(40);
    }
}
__device__ __forceinline__ void tma2d(uint32_t dst, const CUtensorMap* m, int c0, int c1, uint32_t bar) {
    asm volatile("cp.async.bulk.tensor.2d.shared::cluster.global.mbarrier::complete_tx::bytes [%0], [%1, {%3, %4}], [%2];"
                 ::"r"(dst), "l"(m), "r"(bar), "r"(c0), "r"(c1) : "memory");
}
__device__ __forceinline__ void tma2d_mc(uint32_t dst, const CUtensorMap* m, int c0, int c1, uint32_t bar) {
    asm volatile("cp.async.bulk.tensor.2d.shared::cluster.global.mbarrier::complete_tx::bytes.multicast::cluster [%0], [%1, {%3, %4}], [%2], %5;"
                 ::"r"(dst), "l"(m), "r"(bar), "r"(c0), "r"(c1), "h"((uint16_t)3) : "memory");
}
__device__ __forceinline__ void tma3d_mc(uint32_t dst, const CUtensorMap* m, int c0, int c1, int c2, uint32_t bar) {
    asm volatile("cp.async.bulk.tensor.3d.shared::cluster.global.mbarrier::complete_tx::bytes.multicast::cluster [%0], [%1, {%3, %4, %5}], [%2], %6;"
                 ::"r"(dst), "l"(m), "r"(bar), "r"(c0), "r"(c1), "r"(c2), "h"((uint16_t)3) : "memory");
}
__device__ __forceinline__ void tma5d_mc(uint32_t dst, const CUtensorMap* m, int c0, int c4, uint32_t bar) {
    asm volatile("cp.async.bulk.tensor.5d.shared::cluster.global.mbarrier::complete_tx::bytes.multicast::cluster [%0], [%1, {%3, %5, %5, %5, %4}], [%2], %6;"
                 ::"r"(dst), "l"(m), "r"(bar), "r"(c0), "r"(c4), "r"(0), "h"((uint16_t)3) : "memory");
}
__device__ __forceinline__ void bulk_mc(uint32_t dst, const void* src, uint32_t bytes, uint32_t bar) {
    asm volatile("cp.async.bulk.shared::cluster.global.mbarrier::complete_tx::bytes.multicast::cluster [%0], [%1], %2, [%3], %4;"
                 ::"r"(dst), "l"(src), "r"(bytes), "r"(bar), "h"((uint16_t)3) : "memory");
}
__device__ __forceinline__ void tma3d_st(const CUtensorMap* m, uint32_t src, int c0, int c1, int c2) {
    asm volatile("cp.async.bulk.tensor.3d.global.shared::cta.bulk_group [%0, {%2, %3, %4}], [%1];" ::"l"(m), "r"(src), "r"(c0), "r"(c1), "r"(c2) : "memory");
}
__device__ __forceinline__ void tma5d_st(const CUtensorMap* m, uint32_t src, int c1, int c2, int c4) {
    asm volatile("cp.async.bulk.tensor.5d.global.shared::cta.bulk_group [%0, {%5, %2, %3, %5, %4}], [%1];"
                 ::"l"(m), "r"(src), "r"(c1), "r"(c2), "r"(c4), "r"(0) : "memory");
}
__device__ __forceinline__ void bulk_st(void* dst, uint32_t src, uint32_t bytes) {
    asm volatile("cp.async.bulk.global.shared::cta.bulk_group [%0], [%1], %2;" ::"l"(dst), "r"(src), "r"(bytes) : "memory");
}
__device__ __forceinline__ void sts64(uint32_t a, uint32_t x, uint32_t y) { asm volatile("st.shared.v2.u32 [%0], {%1, %2};" ::"r"(a), "r"(x), "r"(y) : "memory"); }
__device__ __forceinline__ void sts128(uint32_t a, const uint32_t* v) {
    asm volatile("st.shared.v4.u32 [%0], {%1, %2, %3, %4};" ::"r"(a), "r"(v[0]), "r"(v[1]), "r"(v[2]), "r"(v[3]) : "memory");
}
__device__ __forceinline__ void l2_prefetch(const void* src, uint32_t bytes) {
    asm volatile("cp.async.bulk.prefetch.L2.global [%0], %1;" ::"l"(src), "r"(bytes) : "memory");
}
__device__ __forceinline__ void map_prefetch(const CUtensorMap* m) { asm volatile("prefetch.tensormap [%0];" ::"l"(m) : "memory"); }
__device__ __forceinline__ void wg_fence() { asm volatile("wgmma.fence.sync.aligned;" ::: "memory"); }
__device__ __forceinline__ void wg_commit() { asm volatile("wgmma.commit_group.sync.aligned;" ::: "memory"); }
template <int N> __device__ __forceinline__ void wg_wait() { asm volatile("wgmma.wait_group.sync.aligned %0;" ::"n"(N) : "memory"); }
template <int N> __device__ __forceinline__ void pin(float* s) {
#pragma unroll
    for (int i = 0; i < N; i++) asm volatile("" : "+f"(s[i])::"memory");
}
template <int N> __device__ __forceinline__ void pin(uint32_t* s) {
#pragma unroll
    for (int i = 0; i < N; i++) asm volatile("" : "+r"(s[i])::"memory");
}
__device__ __forceinline__ uint64_t mkdesc(uint32_t addr, uint32_t lbo, uint32_t sbo, uint32_t swz) {
    return (uint64_t)((addr & 0x3FFFF) >> 4) | ((uint64_t)(lbo >> 4) << 16) | ((uint64_t)(sbo >> 4) << 32) | ((uint64_t)swz << 62);
}
__device__ __forceinline__ float ex2f(float x) { float y; asm("ex2.approx.ftz.f32 %0, %1;" : "=f"(y) : "f"(x)); return y; }
__device__ __forceinline__ float tanhf_(float x) { float y; asm("tanh.approx.f32 %0, %1;" : "=f"(y) : "f"(x)); return y; }
__device__ __forceinline__ uint32_t pk_bf16(float lo, float hi) { uint32_t r; asm("cvt.rn.bf16x2.f32 %0, %1, %2;" : "=r"(r) : "f"(hi), "f"(lo)); return r; }
__device__ __forceinline__ uint32_t pk_f16(float lo, float hi) { uint32_t r; asm("cvt.rn.f16x2.f32 %0, %1, %2;" : "=r"(r) : "f"(hi), "f"(lo)); return r; }
__device__ __forceinline__ float bf_lo(uint32_t v) { return __uint_as_float(v << 16); }
__device__ __forceinline__ float bf_hi(uint32_t v) { return __uint_as_float(v & 0xffff0000u); }
__device__ __forceinline__ float dot8(const uint4& a, const uint4& b) {
    return fmaf(bf_lo(a.x), bf_lo(b.x), fmaf(bf_hi(a.x), bf_hi(b.x), fmaf(bf_lo(a.y), bf_lo(b.y), bf_hi(a.y) * bf_hi(b.y)))) +
           fmaf(bf_lo(a.z), bf_lo(b.z), fmaf(bf_hi(a.z), bf_hi(b.z), fmaf(bf_lo(a.w), bf_lo(b.w), bf_hi(a.w) * bf_hi(b.w))));
}
__device__ __forceinline__ uint32_t epoch() {
    uint32_t v;
    asm volatile("ld.global.u32 %0, [%1];" : "=r"(v) : "l"(gEpoch + blockIdx.x));
    return v + 1;
}
__device__ __forceinline__ float ldcg_f(const float* p) { return __ldcg(p); }

extern __shared__ __align__(1024) uint8_t smem_raw[];
#define TLM(k, slot) do {} while (0)
#define TLC(k, slot) do {} while (0)
#define TL_INIT() do {} while (0)
#define TL_DUMP() do {} while (0)
#define TL_SMEM SMEM_BYTES

__device__ __forceinline__ void wgmma_ss_n128(float* d, uint64_t da, uint64_t db) {
    asm volatile("wgmma.mma_async.sync.aligned.m64n128k16.f32.bf16.bf16 {"
        "%0, %1, %2, %3, %4, %5, %6, %7, %8, %9, %10, %11, %12, %13, %14, %15,"
        "%16, %17, %18, %19, %20, %21, %22, %23, %24, %25, %26, %27, %28, %29, %30, %31,"
        "%32, %33, %34, %35, %36, %37, %38, %39, %40, %41, %42, %43, %44, %45, %46, %47,"
        "%48, %49, %50, %51, %52, %53, %54, %55, %56, %57, %58, %59, %60, %61, %62, %63}, %64, %65, 1, 1, 1, 0, 1;\n"
        :
        "+f"(d[0]), "+f"(d[1]), "+f"(d[2]), "+f"(d[3]), "+f"(d[4]), "+f"(d[5]), "+f"(d[6]), "+f"(d[7]),
        "+f"(d[8]), "+f"(d[9]), "+f"(d[10]), "+f"(d[11]), "+f"(d[12]), "+f"(d[13]), "+f"(d[14]), "+f"(d[15]),
        "+f"(d[16]), "+f"(d[17]), "+f"(d[18]), "+f"(d[19]), "+f"(d[20]), "+f"(d[21]), "+f"(d[22]), "+f"(d[23]),
        "+f"(d[24]), "+f"(d[25]), "+f"(d[26]), "+f"(d[27]), "+f"(d[28]), "+f"(d[29]), "+f"(d[30]), "+f"(d[31]),
        "+f"(d[32]), "+f"(d[33]), "+f"(d[34]), "+f"(d[35]), "+f"(d[36]), "+f"(d[37]), "+f"(d[38]), "+f"(d[39]),
        "+f"(d[40]), "+f"(d[41]), "+f"(d[42]), "+f"(d[43]), "+f"(d[44]), "+f"(d[45]), "+f"(d[46]), "+f"(d[47]),
        "+f"(d[48]), "+f"(d[49]), "+f"(d[50]), "+f"(d[51]), "+f"(d[52]), "+f"(d[53]), "+f"(d[54]), "+f"(d[55]),
        "+f"(d[56]), "+f"(d[57]), "+f"(d[58]), "+f"(d[59]), "+f"(d[60]), "+f"(d[61]), "+f"(d[62]), "+f"(d[63])
        : "l"(da), "l"(db));
}
__device__ __forceinline__ void wgmma_ss_n96(float* d, uint64_t da, uint64_t db) {
    asm volatile("wgmma.mma_async.sync.aligned.m64n96k16.f32.bf16.bf16 {"
        "%0, %1, %2, %3, %4, %5, %6, %7, %8, %9, %10, %11, %12, %13, %14, %15,"
        "%16, %17, %18, %19, %20, %21, %22, %23, %24, %25, %26, %27, %28, %29, %30, %31,"
        "%32, %33, %34, %35, %36, %37, %38, %39, %40, %41, %42, %43, %44, %45, %46, %47}, %48, %49, 1, 1, 1, 0, 1;\n"
        :
        "+f"(d[0]), "+f"(d[1]), "+f"(d[2]), "+f"(d[3]), "+f"(d[4]), "+f"(d[5]), "+f"(d[6]), "+f"(d[7]),
        "+f"(d[8]), "+f"(d[9]), "+f"(d[10]), "+f"(d[11]), "+f"(d[12]), "+f"(d[13]), "+f"(d[14]), "+f"(d[15]),
        "+f"(d[16]), "+f"(d[17]), "+f"(d[18]), "+f"(d[19]), "+f"(d[20]), "+f"(d[21]), "+f"(d[22]), "+f"(d[23]),
        "+f"(d[24]), "+f"(d[25]), "+f"(d[26]), "+f"(d[27]), "+f"(d[28]), "+f"(d[29]), "+f"(d[30]), "+f"(d[31]),
        "+f"(d[32]), "+f"(d[33]), "+f"(d[34]), "+f"(d[35]), "+f"(d[36]), "+f"(d[37]), "+f"(d[38]), "+f"(d[39]),
        "+f"(d[40]), "+f"(d[41]), "+f"(d[42]), "+f"(d[43]), "+f"(d[44]), "+f"(d[45]), "+f"(d[46]), "+f"(d[47])
        : "l"(da), "l"(db));
}
__device__ __forceinline__ void wgmma_ss_n64(float* d, uint64_t da, uint64_t db) {
    asm volatile("wgmma.mma_async.sync.aligned.m64n64k16.f32.bf16.bf16 {"
        "%0, %1, %2, %3, %4, %5, %6, %7, %8, %9, %10, %11, %12, %13, %14, %15,"
        "%16, %17, %18, %19, %20, %21, %22, %23, %24, %25, %26, %27, %28, %29, %30, %31}, %32, %33, 1, 1, 1, 0, 1;\n"
        :
        "+f"(d[0]), "+f"(d[1]), "+f"(d[2]), "+f"(d[3]), "+f"(d[4]), "+f"(d[5]), "+f"(d[6]), "+f"(d[7]),
        "+f"(d[8]), "+f"(d[9]), "+f"(d[10]), "+f"(d[11]), "+f"(d[12]), "+f"(d[13]), "+f"(d[14]), "+f"(d[15]),
        "+f"(d[16]), "+f"(d[17]), "+f"(d[18]), "+f"(d[19]), "+f"(d[20]), "+f"(d[21]), "+f"(d[22]), "+f"(d[23]),
        "+f"(d[24]), "+f"(d[25]), "+f"(d[26]), "+f"(d[27]), "+f"(d[28]), "+f"(d[29]), "+f"(d[30]), "+f"(d[31])
        : "l"(da), "l"(db));
}
__device__ __forceinline__ void wgmma_qk_f16_acc(float* d, const uint32_t* a, uint64_t db) {
    asm volatile("wgmma.mma_async.sync.aligned.m64n64k16.f32.f16.f16 {"
        "%0, %1, %2, %3, %4, %5, %6, %7, %8, %9, %10, %11, %12, %13, %14, %15,"
        "%16, %17, %18, %19, %20, %21, %22, %23, %24, %25, %26, %27, %28, %29, %30, %31}, {%32, %33, %34, %35}, %36, 1, 1, 1, 0;\n"
        :
        "+f"(d[0]), "+f"(d[1]), "+f"(d[2]), "+f"(d[3]), "+f"(d[4]), "+f"(d[5]), "+f"(d[6]), "+f"(d[7]),
        "+f"(d[8]), "+f"(d[9]), "+f"(d[10]), "+f"(d[11]), "+f"(d[12]), "+f"(d[13]), "+f"(d[14]), "+f"(d[15]),
        "+f"(d[16]), "+f"(d[17]), "+f"(d[18]), "+f"(d[19]), "+f"(d[20]), "+f"(d[21]), "+f"(d[22]), "+f"(d[23]),
        "+f"(d[24]), "+f"(d[25]), "+f"(d[26]), "+f"(d[27]), "+f"(d[28]), "+f"(d[29]), "+f"(d[30]), "+f"(d[31])
        : "r"(a[0]), "r"(a[1]), "r"(a[2]), "r"(a[3]), "l"(db));
}
__device__ __forceinline__ void wgmma_qk_bf16_zero(float* d, const uint32_t* a, uint64_t db) {
    asm volatile("wgmma.mma_async.sync.aligned.m64n64k16.f32.bf16.bf16 {"
        "%0, %1, %2, %3, %4, %5, %6, %7, %8, %9, %10, %11, %12, %13, %14, %15,"
        "%16, %17, %18, %19, %20, %21, %22, %23, %24, %25, %26, %27, %28, %29, %30, %31}, {%32, %33, %34, %35}, %36, 0, 1, 1, 0;\n"
        :
        "=f"(d[0]), "=f"(d[1]), "=f"(d[2]), "=f"(d[3]), "=f"(d[4]), "=f"(d[5]), "=f"(d[6]), "=f"(d[7]),
        "=f"(d[8]), "=f"(d[9]), "=f"(d[10]), "=f"(d[11]), "=f"(d[12]), "=f"(d[13]), "=f"(d[14]), "=f"(d[15]),
        "=f"(d[16]), "=f"(d[17]), "=f"(d[18]), "=f"(d[19]), "=f"(d[20]), "=f"(d[21]), "=f"(d[22]), "=f"(d[23]),
        "=f"(d[24]), "=f"(d[25]), "=f"(d[26]), "=f"(d[27]), "=f"(d[28]), "=f"(d[29]), "=f"(d[30]), "=f"(d[31])
        : "r"(a[0]), "r"(a[1]), "r"(a[2]), "r"(a[3]), "l"(db));
}
__device__ __forceinline__ void wgmma_pv(float* d, const uint32_t* a, uint64_t db) {
    asm volatile("wgmma.mma_async.sync.aligned.m64n24k16.f32.bf16.bf16 {"
        "%0, %1, %2, %3, %4, %5, %6, %7, %8, %9, %10, %11}, {%12, %13, %14, %15}, %16, 1, 1, 1, 1;\n"
        :
        "+f"(d[0]), "+f"(d[1]), "+f"(d[2]), "+f"(d[3]), "+f"(d[4]), "+f"(d[5]), "+f"(d[6]), "+f"(d[7]),
        "+f"(d[8]), "+f"(d[9]), "+f"(d[10]), "+f"(d[11])
        : "r"(a[0]), "r"(a[1]), "r"(a[2]), "r"(a[3]), "l"(db));
}

template <int N> __device__ __forceinline__ void wgmma_ss(float* d, uint64_t a, uint64_t b) {
    if (N == 128) wgmma_ss_n128(d, a, b);
    if (N == 96) wgmma_ss_n96(d, a, b);
    if (N == 64) wgmma_ss_n64(d, a, b);
}

#define OFF_R 131072
#define OFF_ONE 229376
#define OFF_BAR 229888
#define OFF_BIAS (OFF_BAR + 736)
#define OFF_G (OFF_BIAS + 1152)
#define SMEM_BYTES (OFF_G + 272)
#define SBD 1024u
#define B_X 0
#define B_F1 416
#define B_E1 64
#define B_XD 672
#define B_KV 160
#define B_F2 224
#define B_E2 256
#define B_T 288
#define B_DONE 352
#define B_G 360
#define B_G2 368
#define B_G3 376
#define B_SF 384
#define B_BI 400
#define B_SF2 408
#define NR 6

#define PF 1
#define PFX 0
#define PACE 1
#define FSER 1
#define EXP_FKK 4
#define QSCALE 0.36067376022224085f
#define MAGIC 445.41763f
#define NMUFU 4
#define VSTEP ((uint64_t)((long long)32 - ((long long)32 << 16)))

#define XMASK 0x0D55u
#define KVMASK 0x1D55u
__host__ __device__ constexpr int strm_pos(int pass, int i) {
    if (pass == 1 || pass == 2) return 8 + 8 * pass + i;
    int n = 0;
    for (int p = 0; p < 16; p++)
        if ((int)((KVMASK >> p) & 1) == (pass == 3)) { if (n == i) return p; n++; }
    return 0;
}
__host__ __device__ constexpr uint32_t strm_code(int pass) {
    uint32_t c = 0;
    for (int i = 0; i < 7; i++) c |= (uint32_t)(strm_pos(pass, i + 1) - strm_pos(pass, i)) << (4 * i);
    return c;
}

template <int N, int SUB, int KST, int LBO, int SBO, int SWZ>
__device__ __forceinline__ void gemm_pass(float* acc, uint32_t bar, uint64_t dA, int lane, uint32_t pos, uint32_t code, int barNext, bool waitx, bool last) {
    uint32_t prev = 0, slot = pos % NR;
#pragma unroll 1
    for (int i = 0; i < 8; i++) {
        if (waitx) mbar_wait(bar + B_X + 8 * i, 0);
        mbar_wait(bar + B_F1 + 8 * pos, 0);
        const uint64_t dB = mkdesc(SBD + OFF_R, LBO, SBO, SWZ) + slot * 1024;
        wg_fence();
        wgmma_ss<N>(acc, dA, dB);
        wgmma_ss<N>(acc, dA + 2, dB + KST / 16);
        wg_commit();
        wg_wait<1>();
        if (i > 0 && lane < 2) mbar_arrive_cluster(prev, lane);
        wgmma_ss<N>(acc, dA + 4, dB + SUB / 16);
        wgmma_ss<N>(acc, dA + 6, dB + (SUB + KST) / 16);
        wg_commit();
        prev = last ? bar + B_XD + 8 * i : bar + B_E1 + 8 * slot;
        pos += code & 15;
        slot += code & 15;
        if (slot >= NR) slot -= NR;
        code >>= 4;
        dA += 1024;
    }
    if (barNext) bar_arrive(barNext, 512);
    wg_wait<0>();
    if (lane < 2) mbar_arrive_cluster(prev, lane);
    pin<N / 2>(acc);
}

__device__ __forceinline__ uint32_t lds32(uint32_t a) { uint32_t v; asm volatile("ld.shared.u32 %0, [%1];" : "=r"(v) : "r"(a)); return v; }
__device__ __forceinline__ bool elect() {
    uint32_t p;
    asm volatile("{\n.reg .pred p;\nelect.sync _|p, 0xffffffff;\nselp.u32 %0, 1, 0, p;\n}" : "=r"(p));
    return p;
}

template <int G0, int G1> __device__ __forceinline__ void gelu_pack(const float* acc, uint32_t bias, uint32_t* out) {
#pragma unroll
    for (int G = G0; G < G1; G++) {
        uint32_t* o = out + 8 * G;
#pragma unroll
        for (int j = 0; j < 4; j++) {
            float bv[2];
            asm volatile("ld.shared.v2.f32 {%0, %1}, [%2];" : "=f"(bv[0]), "=f"(bv[1]) : "r"(bias + G * 128 + j * 32));
            float y[4];
#pragma unroll
            for (int i = 0; i < 4; i++) {
                const float h = acc[16 * G + 4 * j + i] + bv[i & 1];
                const float z = h * fmaf(h * h, 0.035677408136300125f, 0.7978845608028654f);
                y[i] = fmaf(h, tanhf_(z), h);
            }
            o[j] = pk_bf16(y[0], y[1]);
            o[4 + j] = pk_bf16(y[2], y[3]);
        }
    }
}

__device__ __forceinline__ float norm_bound(const float* v, float sc) {
    uint32_t m = 0;
#pragma unroll
    for (int h = 0; h < 4; h++) {
        const float* u = v + 8 * h;
        m = max(m, __float_as_uint(fmaf(u[0], u[0], fmaf(u[1], u[1], fmaf(u[4], u[4], u[5] * u[5])))));
        m = max(m, __float_as_uint(fmaf(u[2], u[2], fmaf(u[3], u[3], fmaf(u[6], u[6], u[7] * u[7])))));
    }
#pragma unroll
    for (int o = 4; o < 32; o <<= 1) m = max(m, __shfl_xor_sync(0xffffffffu, m, o));
    float f = __uint_as_float(m);
    f += __shfl_xor_sync(0xffffffffu, f, 1);
    f += __shfl_xor_sync(0xffffffffu, f, 2);
    return f * sc;
}

__device__ __forceinline__ uint32_t exp2_pair(float a, float b, uint32_t m1) {
    const uint32_t w = __byte_perm(__float_as_uint(a), __float_as_uint(b), 0x6521);
    uint32_t m, r;
    asm("lop3.b32 %0, %1, 0x007f007f, 0x9f809f80, 0xEA;" : "=r"(m) : "r"(w));
    const uint32_t e = w - m;
    asm("fma.rn.bf16x2 %0, %1, %2, %3;" : "=r"(r) : "r"(w), "r"(m), "r"(e));
    return r;
}

__device__ __forceinline__ void store_o(const float* o, uint4* dst, uint32_t par) {
    const float s0 = __fdividef(1.f, o[8]), s1 = __fdividef(1.f, o[10]);
    const uint32_t d0 = (pk_bf16(o[0] * s0, o[1] * s0) & ~1u) | par;
    asm volatile("{\n.reg .b128 t;\nmov.b128 t, {%0, %1, %2, %3};\nst.relaxed.gpu.global.b128 [%4], t;\n}" ::"r"(d0),
                 "r"(pk_bf16(o[4] * s0, o[5] * s0)), "r"(pk_bf16(o[2] * s1, o[3] * s1)), "r"(pk_bf16(o[6] * s1, o[7] * s1)), "l"(dst) : "memory");
}
__device__ __forceinline__ uint4 load_o(const uint4* src) {
    uint4 v;
    asm volatile("{\n.reg .b128 t;\nld.relaxed.gpu.global.b128 t, [%4];\nmov.b128 {%0, %1, %2, %3}, t;\n}"
                 : "=r"(v.x), "=r"(v.y), "=r"(v.z), "=r"(v.w) : "l"(src) : "memory");
    return v;
}
__device__ __forceinline__ uint32_t bmul2(uint32_t a, uint32_t b) { uint32_t r; asm("mul.rn.bf16x2 %0, %1, %2;" : "=r"(r) : "r"(a), "r"(b)); return r; }
__device__ __forceinline__ void sts32(uint32_t a, uint32_t v) { asm volatile("st.shared.u32 [%0], %1;" ::"r"(a), "r"(v) : "memory"); }
__device__ __forceinline__ void load_q(uint32_t* q, int h, int row, int t) {
    const uint8_t* p = gQ + (size_t)h * (SEQ * 32) + (size_t)row * 32 + t * 4;
    q[0] = __ldcg((const uint32_t*)p); q[1] = __ldcg((const uint32_t*)(p + 256));
    q[2] = __ldcg((const uint32_t*)(p + 16)); q[3] = __ldcg((const uint32_t*)(p + 272));
}

template <int NT>
__device__ __forceinline__ void proj16(float (*c)[8], const __nv_bfloat16* x, const __nv_bfloat16* w, int row0, int rstep, int col, int g, int t) {
#pragma unroll
    for (int i = 0; i < NT; i++)
#pragma unroll
        for (int j = 0; j < 8; j++) c[i][j] = 0.f;
    const unsigned short* wu = (const unsigned short*)w;
#pragma unroll 1
    for (int k = 0; k < DM; k += 16) {
        uint32_t b[4];
#pragma unroll
        for (int j = 0; j < 4; j++) {
            const int kr = k + 2 * t + (j & 1) * 8, cc = col + g + (j >> 1) * 8;
            b[j] = (uint32_t)wu[(size_t)kr * (3 * DM) + cc] | ((uint32_t)wu[(size_t)(kr + 1) * (3 * DM) + cc] << 16);
        }
#pragma unroll
        for (int i = 0; i < NT; i++) {
            const __nv_bfloat16* xp = x + (size_t)(row0 + i * rstep + g) * DM + k + 2 * t;
            const uint32_t a0 = *(const uint32_t*)xp, a1 = *(const uint32_t*)(xp + 8 * DM);
            const uint32_t a2 = *(const uint32_t*)(xp + 8), a3 = *(const uint32_t*)(xp + 8 * DM + 8);
#pragma unroll
            for (int j = 0; j < 2; j++)
                asm volatile("mma.sync.aligned.m16n8k16.row.col.f32.bf16.bf16.f32 {%0,%1,%2,%3}, {%4,%5,%6,%7}, {%8,%9}, {%0,%1,%2,%3};"
                             : "+f"(c[i][4 * j]), "+f"(c[i][4 * j + 1]), "+f"(c[i][4 * j + 2]), "+f"(c[i][4 * j + 3])
                             : "r"(a0), "r"(a1), "r"(a2), "r"(a3), "r"(b[2 * j]), "r"(b[2 * j + 1]));
        }
    }
}

struct Maps { CUtensorMap x, kv, q, f1, f3, h, w2, wo, hs, kvs; };

template <int I0, int I1>
__device__ __forceinline__ void issue_stream(const Maps& tm, uint32_t sb, uint32_t rank, int nb, int mb) {
    const uint32_t bar = sb + OFF_BAR;
    const uint32_t dst = sb + OFF_R;
    const int kr = rank * 32;
#pragma unroll
    for (int it = I0; it < I1; it++) {
        const int s = it % NR;
        const uint32_t fb = bar + B_F1 + 8 * it;
        if (it >= 24 + NR) mbar_wait(bar + B_XD + 8 * (it - 24 - NR), 0);
        else if (it >= NR) mbar_wait(bar + B_E1 + 8 * s, ((it / NR) - 1) & 1);
        const int nkv = __builtin_popcount(KVMASK & ((1u << it) - 1));
        if (it < 16 && ((KVMASK >> it) & 1)) {
            tma3d_mc(dst + s * 16384 + rank * 8192, &tm.kv, nb * 64, nkv * 64 + kr, 1, fb);
        } else if (it < 16) {
            tma3d_mc(dst + s * 16384 + rank * 6144, &tm.q, 0, (it - nkv) * 64 + kr, nb * 2, fb);
            tma3d_mc(dst + s * 16384 + rank * 6144 + 4096, &tm.f1, 0, (it - nkv) * 64 + kr, nb * 7, fb);
        } else {
            tma3d_mc(dst + s * 16384 + rank * 6144, &tm.f3, 0, (it & 7) * 64 + kr, nb * 7 + (it < 24 ? 1 : 4), fb);
        }
        if ((XMASK >> it) & 1) {
            const int xc = 1 + __builtin_popcount(XMASK & ((1u << it) - 1));
            tma2d(sb + xc * 16384, &tm.x, xc * 64, mb * 128, bar + B_X + 8 * xc);
        }
    }
}

__global__ void __cluster_dims__(2, 1, 1) __launch_bounds__(640, 1)
fused_kernel(const __grid_constant__ Maps tm, const __nv_bfloat16* __restrict__ x, const __nv_bfloat16* __restrict__ wqkv,
             const __nv_bfloat16* __restrict__ wo, const __nv_bfloat16* __restrict__ w1, const __nv_bfloat16* __restrict__ b1,
             const __nv_bfloat16* __restrict__ w2, const __nv_bfloat16* __restrict__ b2, const __nv_bfloat16* __restrict__ gate,
             __nv_bfloat16* __restrict__ out, const uint32_t m1) {
    const uint32_t sb = smem_u32(smem_raw);
    const uint32_t bar = sb + OFF_BAR;
    const int tid = threadIdx.x, lane = tid & 31;
    const int warp = __shfl_sync(0xffffffffu, tid >> 5, 0);
    const uint32_t rank = cluster_rank();
    const int cl = blockIdx.x >> 1;
    const int nb = cl & 7, mb = (cl >> 3) * 2 + rank;
    const int g = lane >> 2, t = lane & 3;

    const int cb = nb & 3, rb = mb * 2 + (nb >> 2);
    if (tid == 0) TLM(0, 0);
    TL_INIT();
    if (tid == 512) {
        for (int i = 0; i < 8; i++) { mbar_init(bar + B_X + 8 * i, 1); mbar_init(bar + B_KV + 8 * i, 1); mbar_init(bar + B_T + 8 * i, 5); mbar_init(bar + B_XD + 8 * i, 16); }
        for (int i = 0; i < NR; i++) mbar_init(bar + B_E1 + 8 * i, 16);
        for (int i = 0; i < 4; i++) { mbar_init(bar + B_F2 + 8 * i, 1); mbar_init(bar + B_E2 + 8 * i, 8); }
        asm volatile("fence.mbarrier_init.release.cluster;" ::: "memory");
    } else if (tid == 608) {
        for (int i = 0; i < 32; i++) mbar_init(bar + B_F1 + 8 * i, 1);
        mbar_init(bar + B_DONE, 16);
        mbar_init(bar + B_G, 1);
        for (int i = 0; i < 3; i++) mbar_init(bar + B_SF + 8 * i, i == 1 ? 2 : 1);
        mbar_init(bar + B_SF2, 2);
        mbar_init(bar + B_G3, 1);
        mbar_init(bar + B_G2, 4);
        asm volatile("fence.mbarrier_init.release.cluster;" ::: "memory");
    }
    __syncwarp();
    asm volatile("barrier.cluster.arrive.relaxed.aligned;" ::: "memory");
    if (warp == 19) mbar_expect(bar + B_F1 + 8 * lane, ((KVMASK >> lane) & 1) ? 16384 : 12288);
    if (warp == 16 && lane < 24) mbar_expect(bar + (lane < 8 ? B_X : lane < 16 ? B_KV - 64 : B_T - 128) + 8 * lane, 16384);
    if (tid == 512) {
        tma2d(sb, &tm.x, 0, mb * 128, bar + B_X);
    } else if (tid == 544) {
        map_prefetch(&tm.kv);
        l2_prefetch((const uint8_t*)wqkv + (size_t)blockIdx.x * 3072, 3072);
        l2_prefetch((const uint8_t*)w1 + (size_t)blockIdx.x * 1792, 1792);
        map_prefetch(&tm.q); map_prefetch(&tm.f1); map_prefetch(&tm.f3);
    }
    if ((sb & 0xFFFFFF) != SBD) __trap();
    __syncwarp();
    asm volatile("barrier.cluster.wait.aligned;" ::: "memory");
    if (tid == 512) issue_stream<0, NR>(tm, sb, rank, nb, mb);
    if (tid == 0) { TLM(0, 1); TLC(0, 30); }

    if (warp < 16) {
        const int wg = warp >> 2;
        const int h = cl >> 1, qd = (cl & 1) * 2 + rank;
        uint32_t q[4];
        {
            const int w8 = warp & 7;
            const int T = mb * 8 + w8, row0 = T * 16 + g;
            const uint64_t dA0 = mkdesc(SBD + (wg & 1) * 8192, 16, 1024, 1);
            if (wg < 2) {
                float acc[64];
#pragma unroll
                for (int i = 0; i < 64; i++) acc[i] = 0.f;
                gemm_pass<128, 8192, 2048, 4096, 1024, 1>(acc, bar, dA0, lane, strm_pos(3, 0), strm_code(3), 0, true, false);
                if (tid == 0) TLM(0, 2);
                {
                    const float km = norm_bound(acc, 1.f);
                    float vm = 0.f;
#pragma unroll
                    for (int i = 32; i < 64; i++) vm = fmaxf(vm, fabsf(acc[i]));
                    vm = __uint_as_float(__reduce_max_sync(0xffffffffu, __float_as_uint(vm)));
                    if (lane == 0) { gN[1024 + nb * 128 + T] = km; gN[2048 + nb * 128 + T] = vm; }
                    const uint32_t kp = sb + OFF_R + 12288 + (w8 >> 2) * 1024 + g * 128 + ((((w8 & 3) * 2 + ((t >> 1) ^ (w8 >> 2))) ^ g) << 4) + (t & 1) * 8;
                    uint8_t* vp = gKV + (size_t)(nb * 4) * (SEQ * 64) + 65536 + (((T >> 6) * 16 + 2 * g) * 64 + (T & 63)) * 32 + ((t * 8) ^ ((w8 >> 2) << 4));
                    bar_sync(9, 256);
#pragma unroll
                    for (int hh = 0; hh < 4; hh++) {
                        const float* v = acc + 8 * hh;
                        float p0 = __shfl_up_sync(0xffffffffu, v[2], 4), p1 = __shfl_up_sync(0xffffffffu, v[3], 4);
                        float p2 = __shfl_up_sync(0xffffffffu, v[6], 4), p3 = __shfl_up_sync(0xffffffffu, v[7], 4);
                        if (g == 0) { p0 = p1 = p2 = p3 = 0.f; }
                        sts64(kp + hh * 16384, pk_f16(v[0] - p0, v[1] - p1), pk_f16(v[4] - p2, v[5] - p3));
                        sts64(kp + hh * 16384 + 2048, pk_f16(v[2] - v[0], v[3] - v[1]), pk_f16(v[6] - v[4], v[7] - v[5]));
                        const float* u = acc + 32 + 8 * hh;
                        if (hh < 2) {
                            sts64(kp + (4 + hh) * 16384, pk_bf16(u[0], u[1]), pk_bf16(u[4], u[5]));
                            sts64(kp + (4 + hh) * 16384 + 2048, pk_bf16(u[2], u[3]), pk_bf16(u[6], u[7]));
                        } else {
                            *(uint2*)(vp + (size_t)hh * (SEQ * 64)) = make_uint2(pk_bf16(u[0], u[1]), pk_bf16(u[4], u[5]));
                            *(uint2*)(vp + (size_t)hh * (SEQ * 64) + 2048) = make_uint2(pk_bf16(u[2], u[3]), pk_bf16(u[6], u[7]));
                        }
                    }
                }
                asm volatile("fence.proxy.async.shared::cta;" ::: "memory");
                bar_arrive(10, 288);
                if (tid == 0) TLM(0, 3);
            }
#pragma unroll 1
            for (int p = wg < 2 ? 1 : 0; p < 3; p += 2) {
                float acc[48];
#pragma unroll
                for (int i = 0; i < 48; i++) acc[i] = 0.f;
                pin<48>(acc);
                if (p) bar_sync(5 + p, 512);
                gemm_pass<96, 6144, 1024, 2048, 512, 2>(acc, bar, dA0, lane, p == 0 ? strm_pos(0, 0) : 8 + 8 * p, p == 0 ? strm_code(0) : strm_code(1), p < 2 ? 6 + p : 0, p == 0, p == 2);
                if ((tid & 255) == 0) TLM(0, 4 + 2 * p);
                const uint32_t hp = sb + OFF_R + (p == 2 ? 0 : 12288) + (wg & 1) * 16384 + ((warp & 3) * 16 + g) * 64 + t * 16;
                const uint32_t bp = sb + OFF_BIAS + p * 384 - 256 + t * 8;
                uint32_t ho[24];
                mbar_wait(bar + B_BI, 0);
                if (p == 0) {
                    const float qm = norm_bound(acc, QSCALE * QSCALE);
                    if (lane == 0) gN[nb * 128 + T] = qm;
                    uint8_t* qp = gQ + (size_t)(nb * 4) * (SEQ * 32) + (size_t)row0 * 32 + t * 8;
#pragma unroll
                    for (int hh = 0; hh < 4; hh++) {
                        const float* v = acc + 8 * hh;
                        *(uint2*)(qp + hh * (SEQ * 32)) = make_uint2(pk_f16(v[0] * QSCALE, v[1] * QSCALE), pk_f16(v[4] * QSCALE, v[5] * QSCALE));
                        *(uint2*)(qp + hh * (SEQ * 32) + 256) = make_uint2(pk_f16(v[2] * QSCALE, v[3] * QSCALE), pk_f16(v[6] * QSCALE, v[7] * QSCALE));
                    }
                    bar_arrive(12, 288);
                } else {
                    gelu_pack<0, 2>(acc, bp, ho);
                    pin<16>(ho);
                    mbar_wait(bar + B_G, 0);
                    load_q(q, h, qd * 512 + warp * 16 + g, t);
                }
                gelu_pack<2, 3>(acc, bp, ho);
                pin<8>(ho + 16);
                if (p == 2) bar_sync(9, 256);
                else mbar_wait(bar + B_SF + 8 * p, 0);
                if (p) {
#pragma unroll
                    for (int i = 0; i < 4; i++) sts128(hp + (i >> 1) * 32768 + (i & 1) * 512, ho + 4 * i);
                }
                sts128(hp + 65536, ho + 16);
                sts128(hp + 65536 + 512, ho + 20);
                asm volatile("fence.proxy.async.shared::cta;" ::: "memory");
                bar_arrive(p == 1 ? 14 : 11, 288);
                if ((tid & 255) == 0) TLM(0, 5 + 2 * p);
            }
        }
        mbar_wait(bar + B_G3, 0);
        const uint32_t ep = lds32(sb + OFF_G + 256);
        const bool fast = (ep & 2) != 0;
        uint4* const op = gO + ((qd * 8 + wg) * NH + h) * 128 + (tid & 127);
        const uint64_t kd0 = mkdesc(SBD, 16, 256, 3);
        const uint64_t vd0 = mkdesc(SBD + 8192, OFF_ONE - 8192, 256, 3);
        if (fast) {
#pragma unroll 1
            for (int r = 0; r < 2; r++) {
                float o[12];
#pragma unroll
                for (int i = 0; i < 12; i++) o[i] = 0.f;
                uint64_t kd = kd0, vd = vd0;
                uint32_t qn[4];
#pragma unroll 1
                for (int half = 0; half < 2; half++) {
                    float s[32];
#pragma unroll
                    for (int i = 0; i < 32; i++) s[i] = i < 2 * NMUFU ? 0.f : MAGIC;
#pragma unroll 1
                    for (int c = 0; c < 4; c++) {
                        if (r == 0) mbar_wait(bar + B_KV + 8 * (half * 4 + c), 0);
                        if ((tid & 255) == 0 && c == 0) TLM(1, (tid >> 8) * 4 + r * 2 + half);
                        if (half == 1 && c == 3) {
                            if (r == 0) load_q(qn, h, qd * 512 + 256 + warp * 16 + g, t);
                            else if (lane == 0) mbar_arrive(bar + B_DONE);
                        }
#pragma unroll
                        for (int j = 0; j < 4; j++) {
                            uint32_t p[16];
                            wg_fence();
                            wgmma_qk_f16_acc(s, q, kd);
                            wg_commit();
                            wg_wait<0>();
                            pin<32>(s);
#pragma unroll
                            for (int i = 0; i < 16; i++)
                                p[i] = i < NMUFU ? pk_bf16(ex2f(s[2 * i]), ex2f(s[2 * i + 1])) : exp2_pair(s[2 * i], s[2 * i + 1], m1);
                            pin<16>(p);
                            wg_fence();
#pragma unroll
                            for (int u = 0; u < 4; u++) wgmma_pv(o, p + 4 * u, vd + u * VSTEP);
                            wg_commit();
                            kd += 128;
                            vd += 4 * VSTEP;
                        }
                        kd += 512;
                        vd += 16 * VSTEP;
                    }
                    wg_wait<0>();
                }
                pin<12>(o);
                if ((tid & 127) == 0 && r == 1) TLM(1, 8 + wg);
                store_o(o, op + r * (4 * NH * 128), ep & 1);
#pragma unroll
                for (int i = 0; i < 4; i++) q[i] = qn[i];
            }
            if (tid == 0) { TLM(1, 12); TLC(0, 31); }
        } else {
            for (int c = 0; c < 8; c++) mbar_wait(bar + B_KV + 8 * c, 0);
            {
                float kc[8][8];
                proj16<8>(kc, x, wqkv, warp * 16, 256, DM + h * 16, g, t);
#pragma unroll
                for (int i = 0; i < 8; i++) {
                    const int T = warp + i * 16;
                    const int pos = ((T >> 6) * 16 + 2 * g) * 64 + (T & 63);
                    const uint32_t a = sb + (pos >> 8) * 16384 + (pos & 255) * 32 + t * 4, sw = ((T >> 2) & 1) << 4;
                    asm volatile("st.shared.u32 [%0], %1;" ::"r"(a + sw), "r"(pk_bf16(kc[i][0], kc[i][1])) : "memory");
                    asm volatile("st.shared.u32 [%0], %1;" ::"r"(a + (sw ^ 16)), "r"(pk_bf16(kc[i][4], kc[i][5])) : "memory");
                    asm volatile("st.shared.u32 [%0], %1;" ::"r"(a + 2048 + sw), "r"(pk_bf16(kc[i][2], kc[i][3])) : "memory");
                    asm volatile("st.shared.u32 [%0], %1;" ::"r"(a + 2048 + (sw ^ 16)), "r"(pk_bf16(kc[i][6], kc[i][7])) : "memory");
                }
                asm volatile("fence.proxy.async.shared::cta;" ::: "memory");
                bar_sync(8, 512);
            }
#pragma unroll 1
            for (int r = 0; r < 2; r++) {
                const int row = qd * 512 + r * 256 + warp * 16 + g;
                {
                    float qc[1][8];
                    proj16<1>(qc, x, wqkv, row - g, 0, h * 16, g, t);
#pragma unroll
                    for (int i = 0; i < 4; i++) q[i] = pk_bf16(qc[0][2 * i] * QSCALE, qc[0][2 * i + 1] * QSCALE);
                }
                float o[12];
#pragma unroll
                for (int i = 0; i < 12; i++) o[i] = 0.f;
                float m0 = -INFINITY, m1 = -INFINITY;
#pragma unroll 1
                for (int j = 0; j < 32; j++) {
                    const uint64_t kd = kd0 + (j >> 2) * 1024 + (j & 3) * 128, vd = vd0 + ((j >> 2) * 32 + (j & 3) * 4) * VSTEP;
                    float s[32];
                    uint32_t p[16];
                    wg_fence();
                    wgmma_qk_bf16_zero(s, q, kd);
                    wg_commit();
                    wg_wait<0>();
                    pin<32>(s);
                    pin<12>(o);
                    float n0 = m0, n1 = m1;
#pragma unroll
                    for (int i = 0; i < 8; i++) {
                        n0 = fmaxf(n0, fmaxf(s[4 * i], s[4 * i + 1]));
                        n1 = fmaxf(n1, fmaxf(s[4 * i + 2], s[4 * i + 3]));
                    }
                    n0 = fmaxf(n0, __shfl_xor_sync(0xffffffffu, n0, 1));
                    n1 = fmaxf(n1, __shfl_xor_sync(0xffffffffu, n1, 1));
                    n0 = fmaxf(n0, __shfl_xor_sync(0xffffffffu, n0, 2));
                    n1 = fmaxf(n1, __shfl_xor_sync(0xffffffffu, n1, 2));
                    const float c0 = ex2f(m0 - n0), c1 = ex2f(m1 - n1);
                    m0 = n0;
                    m1 = n1;
#pragma unroll
                    for (int i = 0; i < 3; i++) { o[4 * i] *= c0; o[4 * i + 1] *= c0; o[4 * i + 2] *= c1; o[4 * i + 3] *= c1; }
#pragma unroll
                    for (int i = 0; i < 8; i++) {
                        p[2 * i] = pk_bf16(ex2f(s[4 * i] - m0), ex2f(s[4 * i + 1] - m0));
                        p[2 * i + 1] = pk_bf16(ex2f(s[4 * i + 2] - m1), ex2f(s[4 * i + 3] - m1));
                    }
                    pin<16>(p);
                    pin<12>(o);
                    wg_fence();
#pragma unroll
                    for (int u = 0; u < 4; u++) wgmma_pv(o, p + 4 * u, vd + u * VSTEP);
                    wg_commit();
                }
                wg_wait<0>();
                pin<12>(o);
                if (r == 1 && lane == 0) mbar_arrive(bar + B_DONE);
                store_o(o, op + r * (4 * NH * 128), ep & 1);
            }
        }
        {
            const uint4* src = gO + (rb * NH + wg * 8) * 128 + (tid & 127);
            uint4 v[8];
#pragma unroll
            for (int i = 0; i < 8; i++) v[i] = load_o(src + i * 128);
            mbar_wait(bar + B_DONE, 0);
            mbar_wait(bar + B_G2, 0);
            const int lr = (warp & 3) * 16 + g;
            const uint32_t g0 = lds32(sb + OFF_G + lr * 4), g1 = lds32(sb + OFF_G + lr * 4 + 32);
            const uint32_t a0 = sb + wg * 16384 + lr * 128 + (t >> 1) * 4;
#pragma unroll
            for (int i = 0; i < 8; i++) {
                if ((i & 3) == 0) {
                    int spins = 0;
                    while (__any_sync(0xffffffffu, (((v[i].x ^ ep) | (v[i + 1].x ^ ep) | (v[i + 2].x ^ ep) | (v[i + 3].x ^ ep)) & 1) != 0)) {
                        if (++spins > (1 << 22)) __trap();
#pragma unroll
                        for (int k = i; k < 8; k++)
                            if (((v[k].x ^ ep) & 1) != 0) v[k] = load_o(src + k * 128);
                    }
                }
                const uint32_t a = a0 + (i >> 2) * 8192 + ((((i & 3) * 2 + (t & 1)) ^ g) << 4);
                sts32(a, bmul2(v[i].x, g0));
                sts32(a + 8, bmul2(v[i].y, g0));
                sts32(a + 1024, bmul2(v[i].z, g1));
                sts32(a + 1024 + 8, bmul2(v[i].w, g1));
                if ((i & 3) == 3) {
                    asm volatile("fence.proxy.async.shared::cta;" ::: "memory");
                    __syncwarp();
                    if (lane == 0) mbar_arrive(bar + B_T + 8 * (wg * 2 + (i >> 2)));
                    if ((tid & 127) == 0) TLM(1, 20 + wg * 2 + (i >> 2));
                }
            }
        }
    } else {
        if (warp == 16) {
            if (lane == 0) {
                issue_stream<NR, 32>(tm, sb, rank, nb, mb);
                mbar_wait(bar + B_SF2, 0);
#pragma unroll
                for (int s = 0; s < 4; s++) {
                    mbar_expect(bar + B_F2 + 8 * s, 24576);
                    tma5d_mc(sb + OFF_R + s * 24576 + 8192 + rank * 8192, &tm.w2, cb * 128 + rank * 64, s * 2, bar + B_F2 + 8 * s);
                }
                cnt_wait(gCntH + mb * 32, epoch() * 8);
                asm volatile("fence.proxy.async.global;" ::: "memory");
                TLM(1, 13);
#pragma unroll
                for (int s = 0; s < 4; s++) tma2d(sb + OFF_R + s * 24576, &tm.h, s * 64, rb * 64, bar + B_F2 + 8 * s);
            }
        } else if (warp == 17) {
            {
                uint32_t bv[4], b2v[2];
#pragma unroll
                for (int i = 0; i < 4; i++) bv[i] = lane + 32 * i < 112 ? *(const uint32_t*)(b1 + nb * 224 + (lane + 32 * i) * 2) : 0;
#pragma unroll
                for (int i = 0; i < 2; i++) b2v[i] = *(const uint32_t*)(b2 + cb * 128 + (lane + 32 * i) * 2);
#pragma unroll
                for (int i = 0; i < 4; i++) {
                    sts32(sb + OFF_ONE + (lane + 32 * i) * 4, 0x3f803f80u);
                    if (lane + 32 * i < 112) sts64(sb + OFF_BIAS + (lane + 32 * i) * 8, bv[i] << 16, bv[i] & 0xffff0000u);
                }
#pragma unroll
                for (int i = 0; i < 2; i++) sts32(sb + OFF_BIAS + 896 + (lane + 32 * i) * 4, b2v[i]);
                asm volatile("fence.proxy.async.shared::cta;" ::: "memory");
                __syncwarp();
                if (lane == 0) mbar_arrive(bar + B_BI);
            }
            mbar_wait(bar + B_X + 8 * PFX, 0);
            if (lane == 0) {
                l2_prefetch((const uint8_t*)wqkv + 128 * 3072 + (size_t)blockIdx.x * 9216, 9216);
                l2_prefetch((const uint8_t*)w1 + (size_t)blockIdx.x * 14336, 14336);
            }
            mbar_wait(bar + B_X + 8 * 7, 0);
            if (lane == 0) {
                l2_prefetch((const uint8_t*)w2 + (size_t)blockIdx.x * 14336, 14336);
                l2_prefetch((const uint8_t*)wo + (size_t)blockIdx.x * 4096, 4096);
                map_prefetch(&tm.h); map_prefetch(&tm.w2); map_prefetch(&tm.wo); map_prefetch(&tm.hs); map_prefetch(&tm.kvs);
                TLM(0, 11);
            }
            bar_sync(10, 288);
            if (lane == 0) {
#pragma unroll 1
                for (int b = 5; b >= 0; b--) {
                    tma5d_st(&tm.kvs, sb + OFF_R + 12288 + b * 16384, (mb >> 3) * 8, (mb & 7) * 2, nb * 8 + (b < 4 ? 2 * b : 2 * b - 7));
                    asm volatile("cp.async.bulk.commit_group;\ncp.async.bulk.wait_group.read %0;" ::"n"(PACE) : "memory");
                    if (b == 4 - PACE) mbar_arrive(bar + B_SF);
                }
                asm volatile("cp.async.bulk.wait_group.read 0;" ::: "memory");
                mbar_arrive(bar + B_SF + 8);
            }
            __syncwarp();
            bar_sync(12, 288);
            if (lane == 0) {
                asm volatile("cp.async.bulk.wait_group 0;\nfence.proxy.async.global;" ::: "memory");
                cnt_add(gCntQ + nb * 32);
                TLM(0, 13);
            }
        } else {
            {
                const int r0 = mb * 128 + nb * 16 + (warp - 18) * 8;
                uint4 xv[16];
#pragma unroll
                for (int i = 0; i < 16; i++) xv[i] = *(const uint4*)(x + (size_t)(r0 + (i >> 1)) * DM + (i & 1) * 256 + lane * 8);
                const uint4 ga = *(const uint4*)(gate + lane * 8), gb = *(const uint4*)(gate + 256 + lane * 8);
                float z[8];
#pragma unroll
                for (int r = 0; r < 8; r++) z[r] = dot8(xv[2 * r], ga) + dot8(xv[2 * r + 1], gb);
#pragma unroll
                for (int w = 4; w >= 1; w >>= 1)
#pragma unroll
                    for (int r = 0; r < w; r++) {
                        const bool up = lane & w;
                        z[r] = (up ? z[r + w] : z[r]) + __shfl_xor_sync(0xffffffffu, up ? z[r] : z[r + w], w);
                    }
                z[0] += __shfl_xor_sync(0xffffffffu, z[0], 8);
                z[0] += __shfl_xor_sync(0xffffffffu, z[0], 16);
                if (lane < 8) gG[r0 + lane] = 1.f / (1.f + __expf(-z[0]));
                if (tid == 576) TLM(0, 12);
            }
            if (warp == 19) {
#pragma unroll 1
                for (int e = 0; e < 3; e++) {
                    bar_sync(e == 1 ? 14 : 11, 288);
                    if (lane == 0) {
#pragma unroll 1
                        for (int b = e == 0 ? 4 : 0; b < 6; b++) {
                            tma3d_st(&tm.hs, sb + OFF_R + (e == 2 ? 0 : 12288) + b * 16384, 0, mb * 128 + (b & 1) * 64, nb * 7 + e * 3 - 2 + (b >> 1));
                            asm volatile("cp.async.bulk.commit_group;\ncp.async.bulk.wait_group.read %0;" ::"n"(PACE) : "memory");
                        }
                        asm volatile("cp.async.bulk.wait_group.read 0;" ::: "memory");
                        if (e == 0) mbar_arrive(bar + B_SF + 8);
                        if (e == 2) { mbar_arrive_cluster(bar + B_SF2, 0); mbar_arrive_cluster(bar + B_SF2, 1); }
                    }
                    __syncwarp();
                }
                bar_sync(13, 64);
                if (lane == 0) {
                    asm volatile("cp.async.bulk.wait_group 0;\nfence.proxy.async.global;" ::: "memory");
                    cnt_add(gCntH + mb * 32);
                    TLM(0, 15);
                }
            } else {
                bar_arrive(13, 64);
                const int h = cl >> 1, qd = (cl & 1) * 2 + rank;
                if (lane == 0) {
                    cnt_wait(gCntQ + (h >> 2) * 32, epoch() * 16);
                    mbar_arrive(bar + B_G);
                    TLM(0, 14);
                    asm volatile("fence.proxy.async.global;" ::: "memory");
                    mbar_wait(bar + B_XD, 0);
                    bulk_mc(sb + rank * 8192, gKV + (size_t)h * (SEQ * 64) + rank * 65536, 8192, bar + B_KV);
                }
                __syncwarp();
            const int hb = h >> 2;
            const uint4 kq = __ldcg((const uint4*)(gN + 1024 + hb * 128 + lane * 4));
            const uint4 vq = __ldcg((const uint4*)(gN + 2048 + hb * 128 + lane * 4));
            const float qq = ldcg_f(gN + hb * 128 + qd * 32 + lane);
            const float kf = __uint_as_float(__reduce_max_sync(0xffffffffu, max(max(kq.x, kq.y), max(kq.z, kq.w))));
            const float vf = __uint_as_float(__reduce_max_sync(0xffffffffu, max(max(vq.x, vq.y), max(vq.z, vq.w))));
            const float qf = __uint_as_float(__reduce_max_sync(0xffffffffu, __float_as_uint(qq)));
            if (lane == 0) {
                sts32(sb + OFF_G + 256, (epoch() & 1) | ((kf <= 1.0e6f) && (qf <= 1.0e6f) && (kf * qf <= 3400.f) && (vf <= 1.0e12f) ? 2 : 0));
                mbar_arrive(bar + B_G3);
#pragma unroll 1
                for (int c = 1; c < 8; c++) {
                    mbar_wait(bar + B_XD + 8 * c, 0);
                    bulk_mc(sb + c * 16384 + rank * 8192, gKV + (size_t)h * (SEQ * 64) + rank * 65536 + c * 8192, 8192, bar + B_KV + 8 * c);
                }
                TLM(0, 10);
            }
            }
        }
        __syncwarp();
        float acc[64];
#pragma unroll
        for (int i = 0; i < 64; i++) acc[i] = 0.f;
#pragma unroll 1
        for (int io = 0; io < 7; io++) {
#pragma unroll
            for (int s = 0; s < 4; s++) {
                const int it = io * 4 + s;
                mbar_wait(bar + B_F2 + 8 * s, io & 1);
                if (tid == 512 && s == 0 && (io == 0 || io == 4)) TLM(1, 14 + io / 4);
                const uint64_t dA = mkdesc(SBD + OFF_R + s * 24576, 16, 1024, 1);
                const uint64_t dB = mkdesc(SBD + OFF_R + s * 24576 + 8192, 8192, 1024, 1);
                wg_fence();
#pragma unroll
                for (int kk = 0; kk < EXP_FKK; kk++) {
                    wgmma_ss_n128(acc, dA + kk * 2, dB + kk * 128);
                    if (kk < 3 && (FSER != 3 || kk == 1)) {
                        wg_commit();
                        wg_wait<0>();
                    }
                }
                wg_commit();
                if (warp < 18 && it >= 2 && it < 26) {
                    const int s2 = (s + 2) & 3;
                    mbar_wait(bar + B_E2 + 8 * s2, (io - (s < 2)) & 1);
                    if (elect()) {
                        if (warp == 16) {
                            mbar_expect(bar + B_F2 + 8 * s2, 24576);
                            tma5d_mc(sb + OFF_R + s2 * 24576 + 8192 + rank * 8192, &tm.w2, cb * 128 + rank * 64, it * 2 + 4, bar + B_F2 + 8 * s2);
                        } else {
                            asm volatile("fence.proxy.async.global;" ::: "memory");
                            tma2d(sb + OFF_R + s2 * 24576, &tm.h, it * 64 + 128, rb * 64, bar + B_F2 + 8 * s2);
                        }
                    }
                    __syncwarp();
                }
                wg_wait<1>();
                if (it >= 1 && lane < 2) mbar_arrive_cluster(bar + B_E2 + 8 * ((s + 3) & 3), lane);
            }
        }
        wg_wait<0>();
        if (lane < 2) mbar_arrive_cluster(bar + B_E2 + 8 * 3, lane);
        pin<64>(acc);
        if (tid == 576) gEpoch[blockIdx.x] = epoch();
        if (warp == 16) {
            if (lane == 0) TLM(1, 16);
            for (int s = 0; s < 4; s++) mbar_wait(bar + B_E2 + 8 * s, 0);
            if (elect()) {
#pragma unroll
                for (int i = 0; i < 6; i++) tma2d_mc(sb + OFF_R + i * 16384 + rank * 8192, &tm.wo, cb * 128 + rank * 64, i * 64, bar + B_T + 8 * i);
            }
            __syncwarp();
        }
        {
            const int lr = (warp - 16) * 16 + g;
            const uint32_t pa = pk_bf16(ldcg_f(gG + rb * 64 + lr), ldcg_f(gG + rb * 64 + lr + 8));
            if (t == 0) {
                sts32(sb + OFF_G + lr * 4, __byte_perm(pa, pa, 0x1010));
                sts32(sb + OFF_G + lr * 4 + 32, __byte_perm(pa, pa, 0x3232));
            }
            __syncwarp();
            if (lane == 0) mbar_arrive(bar + B_G2);
            const float ga = bf_lo(pa), gb = bf_hi(pa);
            const float g0 = 1.f - ga, g1 = 1.f - gb;
#pragma unroll
            for (int j = 0; j < 16; j++) {
                const uint32_t bv = lds32(sb + OFF_BIAS + 896 + j * 16 + t * 4);
                acc[4 * j] = fmaf(acc[4 * j], 0.5f, bf_lo(bv)) * g0;
                acc[4 * j + 1] = fmaf(acc[4 * j + 1], 0.5f, bf_hi(bv)) * g0;
                acc[4 * j + 2] = fmaf(acc[4 * j + 2], 0.5f, bf_lo(bv)) * g1;
                acc[4 * j + 3] = fmaf(acc[4 * j + 3], 0.5f, bf_hi(bv)) * g1;
            }
            pin<64>(acc);
        }
        if (warp == 17) {
            mbar_wait(bar + B_DONE, 0);
            if (elect()) {
#pragma unroll
                for (int i = 0; i < 4; i++)
                    tma2d(sb + 65536 + i * 8192, &tm.wo, cb * 128 + (i & 1) * 64, (6 + (i >> 1)) * 64, bar + B_T + 8 * (6 + (i >> 1)));
            }
            __syncwarp();
        }
        if (tid == 512) TLM(1, 17);
#pragma unroll
        for (int i = 0; i < 8; i++) {
            mbar_wait(bar + B_T + 8 * i, 0);
            const uint64_t dA = mkdesc(SBD + i * 8192, 16, 1024, 1);
            const uint64_t dB = mkdesc(i < 6 ? SBD + OFF_R + i * 16384 : SBD + 65536 + (i - 6) * 16384, 8192, 1024, 1);
            wg_fence();
#pragma unroll
            for (int kk = 0; kk < 4; kk++) wgmma_ss_n128(acc, dA + kk * 2, dB + kk * 128);
            wg_commit();
        }
        wg_wait<0>();
        pin<64>(acc);
        if (tid == 512) TLM(1, 18);
        {
            const uint32_t st = sb + 98304 + (warp - 16) * 4352;
            const uint32_t wa = st + (lane & 15) * 272 + (lane >> 4) * 16;
#pragma unroll
            for (int j = 0; j < 8; j++)
                asm volatile("stmatrix.sync.aligned.m8n8.x4.shared.b16 [%0], {%1, %2, %3, %4};" ::"r"(wa + j * 32),
                             "r"(pk_bf16(acc[8 * j], acc[8 * j + 1])), "r"(pk_bf16(acc[8 * j + 2], acc[8 * j + 3])),
                             "r"(pk_bf16(acc[8 * j + 4], acc[8 * j + 5])), "r"(pk_bf16(acc[8 * j + 6], acc[8 * j + 7])) : "memory");
            __syncwarp();
            __nv_bfloat16* op = out + (size_t)(rb * 64 + (warp - 16) * 16 + (lane >> 4)) * DM + cb * 128 + (lane & 15) * 8;
#pragma unroll
            for (int j = 0; j < 8; j++) {
                uint4 v;
                asm volatile("ld.shared.v4.u32 {%0, %1, %2, %3}, [%4];" : "=r"(v.x), "=r"(v.y), "=r"(v.z), "=r"(v.w)
                             : "r"(st + (2 * j + (lane >> 4)) * 272 + (lane & 15) * 16));
                *(uint4*)(op + (size_t)j * 2 * DM) = v;
            }
        }
        if (tid == 512) TLM(1, 19);
        TL_DUMP();
    }
}

typedef CUresult (*EncodeFn)(CUtensorMap*, CUtensorMapDataType, cuuint32_t, void*, const cuuint64_t*, const cuuint64_t*, const cuuint32_t*,
                             const cuuint32_t*, CUtensorMapInterleave, CUtensorMapSwizzle, CUtensorMapL2promotion, CUtensorMapFloatOOBfill);

static void make_map(EncodeFn enc, CUtensorMap* m, const void* p, int rank, const cuuint64_t* dims, const cuuint64_t* strides,
                     const cuuint32_t* box, CUtensorMapSwizzle swz) {
    const cuuint32_t es[5] = {1, 1, 1, 1, 1};
    enc(m, CU_TENSOR_MAP_DATA_TYPE_BFLOAT16, rank, (void*)p, dims, strides, box, es, CU_TENSOR_MAP_INTERLEAVE_NONE, swz,
        CU_TENSOR_MAP_L2_PROMOTION_L2_128B, CU_TENSOR_MAP_FLOAT_OOB_FILL_NONE);
}

extern "C" void kernel_launch(void* const* d_in, const int* in_sizes, int n_in, void* d_out, int out_size) {
    const __nv_bfloat16* x = (const __nv_bfloat16*)d_in[0];
    const __nv_bfloat16* wqkv = (const __nv_bfloat16*)d_in[1];
    const __nv_bfloat16* wo = (const __nv_bfloat16*)d_in[2];
    const __nv_bfloat16* w1 = (const __nv_bfloat16*)d_in[4];
    const __nv_bfloat16* b1 = (const __nv_bfloat16*)d_in[5];
    const __nv_bfloat16* w2 = (const __nv_bfloat16*)d_in[6];
    const __nv_bfloat16* b2 = (const __nv_bfloat16*)d_in[7];
    const __nv_bfloat16* gate = (const __nv_bfloat16*)d_in[8];

    void* fp = nullptr;
    cudaDriverEntryPointQueryResult qr;
    cudaGetDriverEntryPoint("cuTensorMapEncodeTiled", &fp, cudaEnableDefault, &qr);
    EncodeFn enc = (EncodeFn)fp;
    void *pH, *pKV;
    cudaGetSymbolAddress(&pH, gH);
    cudaGetSymbolAddress(&pKV, gKV);

    Maps tm;
    const CUtensorMapSwizzle S128 = CU_TENSOR_MAP_SWIZZLE_128B, S64 = CU_TENSOR_MAP_SWIZZLE_64B;
    { cuuint64_t d[2] = {DM, SEQ}, s[1] = {DM * 2}; cuuint32_t b[2] = {64, 128}; make_map(enc, &tm.x, x, 2, d, s, b, S128); }
    { cuuint64_t d[3] = {DM, DM, 3}, s[2] = {3 * DM * 2, DM * 2}; cuuint32_t b[3] = {64, 32, 2}; make_map(enc, &tm.kv, wqkv, 3, d, s, b, S128); }
    { cuuint64_t d[3] = {32, DM, 3 * DM / 32}, s[2] = {3 * DM * 2, 64}; cuuint32_t b[3] = {32, 32, 2}; make_map(enc, &tm.q, wqkv, 3, d, s, b, S64); }
    { cuuint64_t d[3] = {32, DM, FF / 32}, s[2] = {FF * 2, 64}; cuuint32_t b[3] = {32, 32, 1}; make_map(enc, &tm.f1, w1, 3, d, s, b, S64); }
    { cuuint64_t d[3] = {32, DM, FF / 32}, s[2] = {FF * 2, 64}; cuuint32_t b[3] = {32, 32, 3}; make_map(enc, &tm.f3, w1, 3, d, s, b, S64); }
    { cuuint64_t d[2] = {FF, SEQ}, s[1] = {FF * 2}; cuuint32_t b[2] = {64, 64}; make_map(enc, &tm.h, pH, 2, d, s, b, S128); }
    { cuuint64_t d[5] = {DM, 2, 4, 4, FF / 32}, s[4] = {1024, 8 * 1024, 2 * 1024, 32 * 1024}; cuuint32_t b[5] = {64, 2, 4, 4, 2};
      make_map(enc, &tm.w2, w2, 5, d, s, b, S128); }
    { cuuint64_t d[2] = {DM, DM}, s[1] = {DM * 2}; cuuint32_t b[2] = {64, 64}; make_map(enc, &tm.wo, wo, 2, d, s, b, S128); }

    { cuuint64_t d[3] = {32, SEQ, FF / 32}, s[2] = {FF * 2, 64}; cuuint32_t b[3] = {32, 64, 1}; make_map(enc, &tm.hs, pH, 3, d, s, b, CU_TENSOR_MAP_SWIZZLE_NONE); }
    { cuuint64_t d[5] = {64, 16, 16, 2, 2 * NH}, s[4] = {4096, 128, 2048, 65536}; cuuint32_t b[5] = {64, 8, 2, 2, 1};
      make_map(enc, &tm.kvs, pKV, 5, d, s, b, S128); }
    cudaFuncSetAttribute(fused_kernel, cudaFuncAttributeMaxDynamicSharedMemorySize, TL_SMEM);
    fused_kernel<<<128, 640, TL_SMEM, cudaStreamPerThread>>>(tm, x, wqkv, wo, w1, b1, w2, b2, gate, (__nv_bfloat16*)d_out, 0xffffffffu);
}
```

```cpp
#include <cuda_runtime.h>
#include <cuda_bf16.h>
#include <cuda_fp16.h>
#include <cuda.h>
#include <stdint.h>

#define SEQ 2048
#define DM 512
#define FF 1792
#define NH 32

__device__ __align__(1024) uint8_t gQ[NH * SEQ * 32];
__device__ __align__(1024) uint8_t gKV[NH * SEQ * 64];
__device__ __align__(1024) __nv_bfloat16 gH[SEQ * FF];
__device__ __align__(1024) uint4 gO[32 * NH * 128];
__device__ float gG[SEQ];
__device__ float gN[3 * 8 * 128];
__device__ unsigned int gCntQ[8 * 32];
__device__ unsigned int gCntH[32 * 32];
__device__ unsigned int gEpoch[128];

__device__ __forceinline__ uint32_t smem_u32(const void* p) { return (uint32_t)__cvta_generic_to_shared(p); }
__device__ __forceinline__ void mbar_init(uint32_t a, uint32_t c) { asm volatile("mbarrier.init.shared::cta.b64 [%0], %1;" ::"r"(a), "r"(c)); }
__device__ __forceinline__ void mbar_expect(uint32_t a, uint32_t b) { asm volatile("mbarrier.arrive.expect_tx.shared::cta.b64 _, [%0], %1;" ::"r"(a), "r"(b) : "memory"); }
__device__ __forceinline__ void mbar_arrive(uint32_t a) { asm volatile("mbarrier.arrive.shared::cta.b64 _, [%0];" ::"r"(a) : "memory"); }
__device__ __forceinline__ void mbar_wait(uint32_t a, uint32_t ph) {
    asm volatile("{\n.reg .pred p;\n.reg .u32 n;\nmov.u32 n, 0;\nW_%=:\nmbarrier.try_wait.parity.shared::cta.b64 p, [%0], %1;\n@p bra D_%=;\n"
                 "add.u32 n, n, 1;\nsetp.lt.u32 p, n, 0x400000;\n@p bra W_%=;\ntrap;\nD_%=:\n}" ::"r"(a), "r"(ph) : "memory");
}
__device__ __forceinline__ void mbar_arrive_cluster(uint32_t a, uint32_t cta) {
    asm volatile("{\n.reg .b32 r;\nmapa.shared::cluster.u32 r, %0, %1;\nmbarrier.arrive.shared::cluster.b64 _, [r];\n}" ::"r"(a), "r"(cta) : "memory");
}
__device__ __forceinline__ void bar_sync(int id, int n) { asm volatile("bar.sync %0, %1;" ::"r"(id), "r"(n) : "memory"); }
__device__ __forceinline__ void bar_arrive(int id, int n) { asm volatile("bar.arrive %0, %1;" ::"r"(id), "r"(n) : "memory"); }
__device__ __forceinline__ uint32_t cluster_rank() { uint32_t r; asm("mov.u32 %0, %%cluster_ctarank;" : "=r"(r)); return r; }
__device__ __forceinline__ void cnt_add(unsigned int* c) { asm volatile("red.release.gpu.global.add.u32 [%0], 1;" ::"l"(c) : "memory"); }
__device__ __forceinline__ void cnt_wait(const unsigned int* c, uint32_t target) {
    uint32_t v;
    int spins = 0;
    while (true) {
        asm volatile("ld.acquire.gpu.global.u32 %0, [%1];" : "=r"(v) : "l"(c) : "memory");
        if ((int)(v - target) >= 0) break;
        if (++spins > (1 << 22)) __trap();
        __nanosleep(40);
    }
}
__device__ __forceinline__ void tma2d(uint32_t dst, const CUtensorMap* m, int c0, int c1, uint32_t bar) {
    asm volatile("cp.async.bulk.tensor.2d.shared::cluster.global.mbarrier::complete_tx::bytes [%0], [%1, {%3, %4}], [%2];"
                 ::"r"(dst), "l"(m), "r"(bar), "r"(c0), "r"(c1) : "memory");
}
__device__ __forceinline__ void tma2d_mc(uint32_t dst, const CUtensorMap* m, int c0, int c1, uint32_t bar) {
    asm volatile("cp.async.bulk.tensor.2d.shared::cluster.global.mbarrier::complete_tx::bytes.multicast::cluster [%0], [%1, {%3, %4}], [%2], %5;"
                 ::"r"(dst), "l"(m), "r"(bar), "r"(c0), "r"(c1), "h"((uint16_t)3) : "memory");
}
__device__ __forceinline__ void tma3d_mc(uint32_t dst, const CUtensorMap* m, int c0, int c1, int c2, uint32_t bar) {
    asm volatile("cp.async.bulk.tensor.3d.shared::cluster.global.mbarrier::complete_tx::bytes.multicast::cluster [%0], [%1, {%3, %4, %5}], [%2], %6;"
                 ::"r"(dst), "l"(m), "r"(bar), "r"(c0), "r"(c1), "r"(c2), "h"((uint16_t)3) : "memory");
}
__device__ __forceinline__ void tma5d_mc(uint32_t dst, const CUtensorMap* m, int c0, int c4, uint32_t bar) {
    asm volatile("cp.async.bulk.tensor.5d.shared::cluster.global.mbarrier::complete_tx::bytes.multicast::cluster [%0], [%1, {%3, %5, %5, %5, %4}], [%2], %6;"
                 ::"r"(dst), "l"(m), "r"(bar), "r"(c0), "r"(c4), "r"(0), "h"((uint16_t)3) : "memory");
}
__device__ __forceinline__ void bulk_mc(uint32_t dst, const void* src, uint32_t bytes, uint32_t bar) {
    asm volatile("cp.async.bulk.shared::cluster.global.mbarrier::complete_tx::bytes.multicast::cluster [%0], [%1], %2, [%3], %4;"
                 ::"r"(dst), "l"(src), "r"(bytes), "r"(bar), "h"((uint16_t)3) : "memory");
}
__device__ __forceinline__ void tma3d_st(const CUtensorMap* m, uint32_t src, int c0, int c1, int c2) {
    asm volatile("cp.async.bulk.tensor.3d.global.shared::cta.bulk_group [%0, {%2, %3, %4}], [%1];" ::"l"(m), "r"(src), "r"(c0), "r"(c1), "r"(c2) : "memory");
}
__device__ __forceinline__ void tma5d_st(const CUtensorMap* m, uint32_t src, int c1, int c2, int c4) {
    asm volatile("cp.async.bulk.tensor.5d.global.shared::cta.bulk_group [%0, {%5, %2, %3, %5, %4}], [%1];"
                 ::"l"(m), "r"(src), "r"(c1), "r"(c2), "r"(c4), "r"(0) : "memory");
}
__device__ __forceinline__ void bulk_st(void* dst, uint32_t src, uint32_t bytes) {
    asm volatile("cp.async.bulk.global.shared::cta.bulk_group [%0], [%1], %2;" ::"l"(dst), "r"(src), "r"(bytes) : "memory");
}
__device__ __forceinline__ void sts64(uint32_t a, uint32_t x, uint32_t y) { asm volatile("st.shared.v2.u32 [%0], {%1, %2};" ::"r"(a), "r"(x), "r"(y) : "memory"); }
__device__ __forceinline__ void sts128(uint32_t a, const uint32_t* v) {
    asm volatile("st.shared.v4.u32 [%0], {%1, %2, %3, %4};" ::"r"(a), "r"(v[0]), "r"(v[1]), "r"(v[2]), "r"(v[3]) : "memory");
}
__device__ __forceinline__ void l2_prefetch(const void* src, uint32_t bytes) {
    asm volatile("cp.async.bulk.prefetch.L2.global [%0], %1;" ::"l"(src), "r"(bytes) : "memory");
}
__device__ __forceinline__ void map_prefetch(const CUtensorMap* m) { asm volatile("prefetch.tensormap [%0];" ::"l"(m) : "memory"); }
__device__ __forceinline__ void wg_fence() { asm volatile("wgmma.fence.sync.aligned;" ::: "memory"); }
__device__ __forceinline__ void wg_commit() { asm volatile("wgmma.commit_group.sync.aligned;" ::: "memory"); }
template <int N> __device__ __forceinline__ void wg_wait() { asm volatile("wgmma.wait_group.sync.aligned %0;" ::"n"(N) : "memory"); }
template <int N> __device__ __forceinline__ void pin(float* s) {
#pragma unroll
    for (int i = 0; i < N; i++) asm volatile("" : "+f"(s[i])::"memory");
}
template <int N> __device__ __forceinline__ void pin(uint32_t* s) {
#pragma unroll
    for (int i = 0; i < N; i++) asm volatile("" : "+r"(s[i])::"memory");
}
__device__ __forceinline__ uint64_t mkdesc(uint32_t addr, uint32_t lbo, uint32_t sbo, uint32_t swz) {
    return (uint64_t)((addr & 0x3FFFF) >> 4) | ((uint64_t)(lbo >> 4) << 16) | ((uint64_t)(sbo >> 4) << 32) | ((uint64_t)swz << 62);
}
__device__ __forceinline__ float ex2f(float x) { float y; asm("ex2.approx.ftz.f32 %0, %1;" : "=f"(y) : "f"(x)); return y; }
__device__ __forceinline__ float tanhf_(float x) { float y; asm("tanh.approx.f32 %0, %1;" : "=f"(y) : "f"(x)); return y; }
__device__ __forceinline__ uint32_t pk_bf16(float lo, float hi) { uint32_t r; asm("cvt.rn.bf16x2.f32 %0, %1, %2;" : "=r"(r) : "f"(hi), "f"(lo)); return r; }
__device__ __forceinline__ uint32_t pk_f16(float lo, float hi) { uint32_t r; asm("cvt.rn.f16x2.f32 %0, %1, %2;" : "=r"(r) : "f"(hi), "f"(lo)); return r; }
__device__ __forceinline__ float bf_lo(uint32_t v) { return __uint_as_float(v << 16); }
__device__ __forceinline__ float bf_hi(uint32_t v) { return __uint_as_float(v & 0xffff0000u); }
__device__ __forceinline__ float dot8(const uint4& a, const uint4& b) {
    return fmaf(bf_lo(a.x), bf_lo(b.x), fmaf(bf_hi(a.x), bf_hi(b.x), fmaf(bf_lo(a.y), bf_lo(b.y), bf_hi(a.y) * bf_hi(b.y)))) +
           fmaf(bf_lo(a.z), bf_lo(b.z), fmaf(bf_hi(a.z), bf_hi(b.z), fmaf(bf_lo(a.w), bf_lo(b.w), bf_hi(a.w) * bf_hi(b.w))));
}
__device__ __forceinline__ uint32_t epoch() {
    uint32_t v;
    asm volatile("ld.global.u32 %0, [%1];" : "=r"(v) : "l"(gEpoch + blockIdx.x));
    return v + 1;
}
__device__ __forceinline__ float ldcg_f(const float* p) { return __ldcg(p); }

extern __shared__ __align__(1024) uint8_t smem_raw[];
#define TLM(k, slot) do {} while (0)
#define TLC(k, slot) do {} while (0)
#define TL_INIT() do {} while (0)
#define TL_DUMP() do {} while (0)
#define TL_SMEM SMEM_BYTES

__device__ __forceinline__ void wgmma_ss_n128(float* d, uint64_t da, uint64_t db) {
    asm volatile("wgmma.mma_async.sync.aligned.m64n128k16.f32.bf16.bf16 {"
        "%0, %1, %2, %3, %4, %5, %6, %7, %8, %9, %10, %11, %12, %13, %14, %15,"
        "%16, %17, %18, %19, %20, %21, %22, %23, %24, %25, %26, %27, %28, %29, %30, %31,"
        "%32, %33, %34, %35, %36, %37, %38, %39, %40, %41, %42, %43, %44, %45, %46, %47,"
        "%48, %49, %50, %51, %52, %53, %54, %55, %56, %57, %58, %59, %60, %61, %62, %63}, %64, %65, 1, 1, 1, 0, 1;\n"
        :
        "+f"(d[0]), "+f"(d[1]), "+f"(d[2]), "+f"(d[3]), "+f"(d[4]), "+f"(d[5]), "+f"(d[6]), "+f"(d[7]),
        "+f"(d[8]), "+f"(d[9]), "+f"(d[10]), "+f"(d[11]), "+f"(d[12]), "+f"(d[13]), "+f"(d[14]), "+f"(d[15]),
        "+f"(d[16]), "+f"(d[17]), "+f"(d[18]), "+f"(d[19]), "+f"(d[20]), "+f"(d[21]), "+f"(d[22]), "+f"(d[23]),
        "+f"(d[24]), "+f"(d[25]), "+f"(d[26]), "+f"(d[27]), "+f"(d[28]), "+f"(d[29]), "+f"(d[30]), "+f"(d[31]),
        "+f"(d[32]), "+f"(d[33]), "+f"(d[34]), "+f"(d[35]), "+f"(d[36]), "+f"(d[37]), "+f"(d[38]), "+f"(d[39]),
        "+f"(d[40]), "+f"(d[41]), "+f"(d[42]), "+f"(d[43]), "+f"(d[44]), "+f"(d[45]), "+f"(d[46]), "+f"(d[47]),
        "+f"(d[48]), "+f"(d[49]), "+f"(d[50]), "+f"(d[51]), "+f"(d[52]), "+f"(d[53]), "+f"(d[54]), "+f"(d[55]),
        "+f"(d[56]), "+f"(d[57]), "+f"(d[58]), "+f"(d[59]), "+f"(d[60]), "+f"(d[61]), "+f"(d[62]), "+f"(d[63])
        : "l"(da), "l"(db));
}
__device__ __forceinline__ void wgmma_ss_n96(float* d, uint64_t da, uint64_t db) {
    asm volatile("wgmma.mma_async.sync.aligned.m64n96k16.f32.bf16.bf16 {"
        "%0, %1, %2, %3, %4, %5, %6, %7, %8, %9, %10, %11, %12, %13, %14, %15,"
        "%16, %17, %18, %19, %20, %21, %22, %23, %24, %25, %26, %27, %28, %29, %30, %31,"
        "%32, %33, %34, %35, %36, %37, %38, %39, %40, %41, %42, %43, %44, %45, %46, %47}, %48, %49, 1, 1, 1, 0, 1;\n"
        :
        "+f"(d[0]), "+f"(d[1]), "+f"(d[2]), "+f"(d[3]), "+f"(d[4]), "+f"(d[5]), "+f"(d[6]), "+f"(d[7]),
        "+f"(d[8]), "+f"(d[9]), "+f"(d[10]), "+f"(d[11]), "+f"(d[12]), "+f"(d[13]), "+f"(d[14]), "+f"(d[15]),
        "+f"(d[16]), "+f"(d[17]), "+f"(d[18]), "+f"(d[19]), "+f"(d[20]), "+f"(d[21]), "+f"(d[22]), "+f"(d[23]),
        "+f"(d[24]), "+f"(d[25]), "+f"(d[26]), "+f"(d[27]), "+f"(d[28]), "+f"(d[29]), "+f"(d[30]), "+f"(d[31]),
        "+f"(d[32]), "+f"(d[33]), "+f"(d[34]), "+f"(d[35]), "+f"(d[36]), "+f"(d[37]), "+f"(d[38]), "+f"(d[39]),
        "+f"(d[40]), "+f"(d[41]), "+f"(d[42]), "+f"(d[43]), "+f"(d[44]), "+f"(d[45]), "+f"(d[46]), "+f"(d[47])
        : "l"(da), "l"(db));
}
__device__ __forceinline__ void wgmma_ss_n64(float* d, uint64_t da, uint64_t db) {
    asm volatile("wgmma.mma_async.sync.aligned.m64n64k16.f32.bf16.bf16 {"
        "%0, %1, %2, %3, %4, %5, %6, %7, %8, %9, %10, %11, %12, %13, %14, %15,"
        "%16, %17, %18, %19, %20, %21, %22, %23, %24, %25, %26, %27, %28, %29, %30, %31}, %32, %33, 1, 1, 1, 0, 1;\n"
        :
        "+f"(d[0]), "+f"(d[1]), "+f"(d[2]), "+f"(d[3]), "+f"(d[4]), "+f"(d[5]), "+f"(d[6]), "+f"(d[7]),
        "+f"(d[8]), "+f"(d[9]), "+f"(d[10]), "+f"(d[11]), "+f"(d[12]), "+f"(d[13]), "+f"(d[14]), "+f"(d[15]),
        "+f"(d[16]), "+f"(d[17]), "+f"(d[18]), "+f"(d[19]), "+f"(d[20]), "+f"(d[21]), "+f"(d[22]), "+f"(d[23]),
        "+f"(d[24]), "+f"(d[25]), "+f"(d[26]), "+f"(d[27]), "+f"(d[28]), "+f"(d[29]), "+f"(d[30]), "+f"(d[31])
        : "l"(da), "l"(db));
}
__device__ __forceinline__ void wgmma_qk_f16_acc(float* d, const uint32_t* a, uint64_t db) {
    asm volatile("wgmma.mma_async.sync.aligned.m64n64k16.f32.f16.f16 {"
        "%0, %1, %2, %3, %4, %5, %6, %7, %8, %9, %10, %11, %12, %13, %14, %15,"
        "%16, %17, %18, %19, %20, %21, %22, %23, %24, %25, %26, %27, %28, %29, %30, %31}, {%32, %33, %34, %35}, %36, 1, 1, 1, 0;\n"
        :
        "+f"(d[0]), "+f"(d[1]), "+f"(d[2]), "+f"(d[3]), "+f"(d[4]), "+f"(d[5]), "+f"(d[6]), "+f"(d[7]),
        "+f"(d[8]), "+f"(d[9]), "+f"(d[10]), "+f"(d[11]), "+f"(d[12]), "+f"(d[13]), "+f"(d[14]), "+f"(d[15]),
        "+f"(d[16]), "+f"(d[17]), "+f"(d[18]), "+f"(d[19]), "+f"(d[20]), "+f"(d[21]), "+f"(d[22]), "+f"(d[23]),
        "+f"(d[24]), "+f"(d[25]), "+f"(d[26]), "+f"(d[27]), "+f"(d[28]), "+f"(d[29]), "+f"(d[30]), "+f"(d[31])
        : "r"(a[0]), "r"(a[1]), "r"(a[2]), "r"(a[3]), "l"(db));
}
__device__ __forceinline__ void wgmma_qk_bf16_zero(float* d, const uint32_t* a, uint64_t db) {
    asm volatile("wgmma.mma_async.sync.aligned.m64n64k16.f32.bf16.bf16 {"
        "%0, %1, %2, %3, %4, %5, %6, %7, %8, %9, %10, %11, %12, %13, %14, %15,"
        "%16, %17, %18, %19, %20, %21, %22, %23, %24, %25, %26, %27, %28, %29, %30, %31}, {%32, %33, %34, %35}, %36, 0, 1, 1, 0;\n"
        :
        "=f"(d[0]), "=f"(d[1]), "=f"(d[2]), "=f"(d[3]), "=f"(d[4]), "=f"(d[5]), "=f"(d[6]), "=f"(d[7]),
        "=f"(d[8]), "=f"(d[9]), "=f"(d[10]), "=f"(d[11]), "=f"(d[12]), "=f"(d[13]), "=f"(d[14]), "=f"(d[15]),
        "=f"(d[16]), "=f"(d[17]), "=f"(d[18]), "=f"(d[19]), "=f"(d[20]), "=f"(d[21]), "=f"(d[22]), "=f"(d[23]),
        "=f"(d[24]), "=f"(d[25]), "=f"(d[26]), "=f"(d[27]), "=f"(d[28]), "=f"(d[29]), "=f"(d[30]), "=f"(d[31])
        : "r"(a[0]), "r"(a[1]), "r"(a[2]), "r"(a[3]), "l"(db));
}
__device__ __forceinline__ void wgmma_pv(float* d, const uint32_t* a, uint64_t db) {
    asm volatile("wgmma.mma_async.sync.aligned.m64n24k16.f32.bf16.bf16 {"
        "%0, %1, %2, %3, %4, %5, %6, %7, %8, %9, %10, %11}, {%12, %13, %14, %15}, %16, 1, 1, 1, 1;\n"
        :
        "+f"(d[0]), "+f"(d[1]), "+f"(d[2]), "+f"(d[3]), "+f"(d[4]), "+f"(d[5]), "+f"(d[6]), "+f"(d[7]),
        "+f"(d[8]), "+f"(d[9]), "+f"(d[10]), "+f"(d[11])
        : "r"(a[0]), "r"(a[1]), "r"(a[2]), "r"(a[3]), "l"(db));
}

template <int N> __device__ __forceinline__ void wgmma_ss(float* d, uint64_t a, uint64_t b) {
    if (N == 128) wgmma_ss_n128(d, a, b);
    if (N == 96) wgmma_ss_n96(d, a, b);
    if (N == 64) wgmma_ss_n64(d, a, b);
}

#define OFF_R 131072
#define OFF_ONE 229376
#define OFF_BAR 229888
#define OFF_BIAS (OFF_BAR + 736)
#define OFF_G (OFF_BIAS + 1152)
#define SMEM_BYTES (OFF_G + 272)
#define SBD 1024u
#define B_X 0
#define B_F1 416
#define B_E1 64
#define B_XD 672
#define B_KV 160
#define B_F2 224
#define B_E2 256
#define B_T 288
#define B_DONE 352
#define B_G 360
#define B_G2 368
#define B_G3 376
#define B_SF 384
#define B_BI 400
#define B_SF2 408
#define NR 6

#define PF 1
#define PFX 0
#define PACE 1
#define FSER 1
#define EXP_FKK 4
#define QSCALE 0.36067376022224085f
#define MAGIC 445.41763f
#define NMUFU 4
#define VSTEP ((uint64_t)((long long)32 - ((long long)32 << 16)))

#define XMASK 0x0D55u
#define KVMASK 0x1D55u
__host__ __device__ constexpr int strm_pos(int pass, int i) {
    if (pass == 1 || pass == 2) return 8 + 8 * pass + i;
    int n = 0;
    for (int p = 0; p < 16; p++)
        if ((int)((KVMASK >> p) & 1) == (pass == 3)) { if (n == i) return p; n++; }
    return 0;
}
__host__ __device__ constexpr uint32_t strm_code(int pass) {
    uint32_t c = 0;
    for (int i = 0; i < 7; i++) c |= (uint32_t)(strm_pos(pass, i + 1) - strm_pos(pass, i)) << (4 * i);
    return c;
}

template <int N, int SUB, int KST, int LBO, int SBO, int SWZ>
__device__ __forceinline__ void gemm_pass(float* acc, uint32_t bar, uint64_t dA, int lane, uint32_t pos, uint32_t code, int barNext, bool waitx, bool last) {
    uint32_t prev = 0, slot = pos % NR;
#pragma unroll 1
    for (int i = 0; i < 8; i++) {
        if (waitx) mbar_wait(bar + B_X + 8 * i, 0);
        mbar_wait(bar + B_F1 + 8 * pos, 0);
        const uint64_t dB = mkdesc(SBD + OFF_R, LBO, SBO, SWZ) + slot * 1024;
        wg_fence();
        wgmma_ss<N>(acc, dA, dB);
        wgmma_ss<N>(acc, dA + 2, dB + KST / 16);
        wg_commit();
        wg_wait<1>();
        if (i > 0 && lane < 2) mbar_arrive_cluster(prev, lane);
        wgmma_ss<N>(acc, dA + 4, dB + SUB / 16);
        wgmma_ss<N>(acc, dA + 6, dB + (SUB + KST) / 16);
        wg_commit();
        prev = last ? bar + B_XD + 8 * i : bar + B_E1 + 8 * slot;
        pos += code & 15;
        slot += code & 15;
        if (slot >= NR) slot -= NR;
        code >>= 4;
        dA += 1024;
    }
    if (barNext) bar_arrive(barNext, 512);
    wg_wait<0>();
    if (lane < 2) mbar_arrive_cluster(prev, lane);
    pin<N / 2>(acc);
}

__device__ __forceinline__ uint32_t lds32(uint32_t a) { uint32_t v; asm volatile("ld.shared.u32 %0, [%1];" : "=r"(v) : "r"(a)); return v; }
__device__ __forceinline__ bool elect() {
    uint32_t p;
    asm volatile("{\n.reg .pred p;\nelect.sync _|p, 0xffffffff;\nselp.u32 %0, 1, 0, p;\n}" : "=r"(p));
    return p;
}

template <int G0, int G1> __device__ __forceinline__ void gelu_pack(const float* acc, uint32_t bias, uint32_t* out) {
#pragma unroll
    for (int G = G0; G < G1; G++) {
        uint32_t* o = out + 8 * G;
#pragma unroll
        for (int j = 0; j < 4; j++) {
            float bv[2];
            asm volatile("ld.shared.v2.f32 {%0, %1}, [%2];" : "=f"(bv[0]), "=f"(bv[1]) : "r"(bias + G * 128 + j * 32));
            float y[4];
#pragma unroll
            for (int i = 0; i < 4; i++) {
                const float h = acc[16 * G + 4 * j + i] + bv[i & 1];
                const float z = h * fmaf(h * h, 0.035677408136300125f, 0.7978845608028654f);
                y[i] = fmaf(h, tanhf_(z), h);
            }
            o[j] = pk_bf16(y[0], y[1]);
            o[4 + j] = pk_bf16(y[2], y[3]);
        }
    }
}

__device__ __forceinline__ float norm_bound(const float* v, float sc) {
    uint32_t m = 0;
#pragma unroll
    for (int h = 0; h < 4; h++) {
        const float* u = v + 8 * h;
        m = max(m, __float_as_uint(fmaf(u[0], u[0], fmaf(u[1], u[1], fmaf(u[4], u[4], u[5] * u[5])))));
        m = max(m, __float_as_uint(fmaf(u[2], u[2], fmaf(u[3], u[3], fmaf(u[6], u[6], u[7] * u[7])))));
    }
#pragma unroll
    for (int o = 4; o < 32; o <<= 1) m = max(m, __shfl_xor_sync(0xffffffffu, m, o));
    float f = __uint_as_float(m);
    f += __shfl_xor_sync(0xffffffffu, f, 1);
    f += __shfl_xor_sync(0xffffffffu, f, 2);
    return f * sc;
}

__device__ __forceinline__ uint32_t exp2_pair(float a, float b, uint32_t m1) {
    const uint32_t w = __byte_perm(__float_as_uint(a), __float_as_uint(b), 0x6521);
    uint32_t m, r;
    asm("lop3.b32 %0, %1, 0x007f007f, 0x9f809f80, 0xEA;" : "=r"(m) : "r"(w));
    const uint32_t e = w - m;
    asm("fma.rn.bf16x2 %0, %1, %2, %3;" : "=r"(r) : "r"(w), "r"(m), "r"(e));
    return r;
}

__device__ __forceinline__ void store_o(const float* o, uint4* dst, uint32_t par) {
    const float s0 = __fdividef(1.f, o[8]), s1 = __fdividef(1.f, o[10]);
    const uint32_t d0 = (pk_bf16(o[0] * s0, o[1] * s0) & ~1u) | par;
    asm volatile("{\n.reg .b128 t;\nmov.b128 t, {%0, %1, %2, %3};\nst.relaxed.gpu.global.b128 [%4], t;\n}" ::"r"(d0),
                 "r"(pk_bf16(o[4] * s0, o[5] * s0)), "r"(pk_bf16(o[2] * s1, o[3] * s1)), "r"(pk_bf16(o[6] * s1, o[7] * s1)), "l"(dst) : "memory");
}
__device__ __forceinline__ uint4 load_o(const uint4* src) {
    uint4 v;
    asm volatile("{\n.reg .b128 t;\nld.relaxed.gpu.global.b128 t, [%4];\nmov.b128 {%0, %1, %2, %3}, t;\n}"
                 : "=r"(v.x), "=r"(v.y), "=r"(v.z), "=r"(v.w) : "l"(src) : "memory");
    return v;
}
__device__ __forceinline__ uint32_t bmul2(uint32_t a, uint32_t b) { uint32_t r; asm("mul.rn.bf16x2 %0, %1, %2;" : "=r"(r) : "r"(a), "r"(b)); return r; }
__device__ __forceinline__ void sts32(uint32_t a, uint32_t v) { asm volatile("st.shared.u32 [%0], %1;" ::"r"(a), "r"(v) : "memory"); }
__device__ __forceinline__ void load_q(uint32_t* q, int h, int row, int t) {
    const uint8_t* p = gQ + (size_t)h * (SEQ * 32) + (size_t)row * 32 + t * 4;
    q[0] = __ldcg((const uint32_t*)p); q[1] = __ldcg((const uint32_t*)(p + 256));
    q[2] = __ldcg((const uint32_t*)(p + 16)); q[3] = __ldcg((const uint32_t*)(p + 272));
}

template <int NT>
__device__ __forceinline__ void proj16(float (*c)[8], const __nv_bfloat16* x, const __nv_bfloat16* w, int row0, int rstep, int col, int g, int t) {
#pragma unroll
    for (int i = 0; i < NT; i++)
#pragma unroll
        for (int j = 0; j < 8; j++) c[i][j] = 0.f;
    const unsigned short* wu = (const unsigned short*)w;
#pragma unroll 1
    for (int k = 0; k < DM; k += 16) {
        uint32_t b[4];
#pragma unroll
        for (int j = 0; j < 4; j++) {
            const int kr = k + 2 * t + (j & 1) * 8, cc = col + g + (j >> 1) * 8;
            b[j] = (uint32_t)wu[(size_t)kr * (3 * DM) + cc] | ((uint32_t)wu[(size_t)(kr + 1) * (3 * DM) + cc] << 16);
        }
#pragma unroll
        for (int i = 0; i < NT; i++) {
            const __nv_bfloat16* xp = x + (size_t)(row0 + i * rstep + g) * DM + k + 2 * t;
            const uint32_t a0 = *(const uint32_t*)xp, a1 = *(const uint32_t*)(xp + 8 * DM);
            const uint32_t a2 = *(const uint32_t*)(xp + 8), a3 = *(const uint32_t*)(xp + 8 * DM + 8);
#pragma unroll
            for (int j = 0; j < 2; j++)
                asm volatile("mma.sync.aligned.m16n8k16.row.col.f32.bf16.bf16.f32 {%0,%1,%2,%3}, {%4,%5,%6,%7}, {%8,%9}, {%0,%1,%2,%3};"
                             : "+f"(c[i][4 * j]), "+f"(c[i][4 * j + 1]), "+f"(c[i][4 * j + 2]), "+f"(c[i][4 * j + 3])
                             : "r"(a0), "r"(a1), "r"(a2), "r"(a3), "r"(b[2 * j]), "r"(b[2 * j + 1]));
        }
    }
}

struct Maps { CUtensorMap x, kv, q, f1, f3, h, w2, wo, hs, kvs; };

template <int I0, int I1>
__device__ __forceinline__ void issue_stream(const Maps& tm, uint32_t sb, uint32_t rank, int nb, int mb) {
    const uint32_t bar = sb + OFF_BAR;
    const uint32_t dst = sb + OFF_R;
    const int kr = rank * 32;
#pragma unroll
    for (int it = I0; it < I1; it++) {
        const int s = it % NR;
        const uint32_t fb = bar + B_F1 + 8 * it;
        if (it >= 24 + NR) mbar_wait(bar + B_XD + 8 * (it - 24 - NR), 0);
        else if (it >= NR) mbar_wait(bar + B_E1 + 8 * s, ((it / NR) - 1) & 1);
        const int nkv = __builtin_popcount(KVMASK & ((1u << it) - 1));
        if (it < 16 && ((KVMASK >> it) & 1)) {
            tma3d_mc(dst + s * 16384 + rank * 8192, &tm.kv, nb * 64, nkv * 64 + kr, 1, fb);
        } else if (it < 16) {
            tma3d_mc(dst + s * 16384 + rank * 6144, &tm.q, 0, (it - nkv) * 64 + kr, nb * 2, fb);
            tma3d_mc(dst + s * 16384 + rank * 6144 + 4096, &tm.f1, 0, (it - nkv) * 64 + kr, nb * 7, fb);
        } else {
            tma3d_mc(dst + s * 16384 + rank * 6144, &tm.f3, 0, (it & 7) * 64 + kr, nb * 7 + (it < 24 ? 1 : 4), fb);
        }
        if ((XMASK >> it) & 1) {
            const int xc = 1 + __builtin_popcount(XMASK & ((1u << it) - 1));
            tma2d(sb + xc * 16384, &tm.x, xc * 64, mb * 128, bar + B_X + 8 * xc);
        }
    }
}

__global__ void __cluster_dims__(2, 1, 1) __launch_bounds__(640, 1)
fused_kernel(const __grid_constant__ Maps tm, const __nv_bfloat16* __restrict__ x, const __nv_bfloat16* __restrict__ wqkv,
             const __nv_bfloat16* __restrict__ wo, const __nv_bfloat16* __restrict__ w1, const __nv_bfloat16* __restrict__ b1,
             const __nv_bfloat16* __restrict__ w2, const __nv_bfloat16* __restrict__ b2, const __nv_bfloat16* __restrict__ gate,
             __nv_bfloat16* __restrict__ out, const uint32_t m1) {
    const uint32_t sb = smem_u32(smem_raw);
    const uint32_t bar = sb + OFF_BAR;
    const int tid = threadIdx.x, lane = tid & 31;
    const int warp = __shfl_sync(0xffffffffu, tid >> 5, 0);
    const uint32_t rank = cluster_rank();
    const int cl = blockIdx.x >> 1;
    const int nb = cl & 7, mb = (cl >> 3) * 2 + rank;
    const int g = lane >> 2, t = lane & 3;

    const int cb = nb & 3, rb = mb * 2 + (nb >> 2);
    if (tid == 0) TLM(0, 0);
    TL_INIT();
    if (tid == 512) {
        for (int i = 0; i < 8; i++) { mbar_init(bar + B_X + 8 * i, 1); mbar_init(bar + B_KV + 8 * i, 1); mbar_init(bar + B_T + 8 * i, 5); mbar_init(bar + B_XD + 8 * i, 16); }
        for (int i = 0; i < NR; i++) mbar_init(bar + B_E1 + 8 * i, 16);
        for (int i = 0; i < 4; i++) { mbar_init(bar + B_F2 + 8 * i, 1); mbar_init(bar + B_E2 + 8 * i, 8); }
        asm volatile("fence.mbarrier_init.release.cluster;" ::: "memory");
    } else if (tid == 608) {
        for (int i = 0; i < 32; i++) mbar_init(bar + B_F1 + 8 * i, 1);
        mbar_init(bar + B_DONE, 16);
        mbar_init(bar + B_G, 1);
        for (int i = 0; i < 3; i++) mbar_init(bar + B_SF + 8 * i, i == 1 ? 2 : 1);
        mbar_init(bar + B_SF2, 2);
        mbar_init(bar + B_G3, 1);
        mbar_init(bar + B_G2, 4);
        asm volatile("fence.mbarrier_init.release.cluster;" ::: "memory");
    }
    __syncwarp();
    asm volatile("barrier.cluster.arrive.relaxed.aligned;" ::: "memory");
    if (warp == 19) mbar_expect(bar + B_F1 + 8 * lane, ((KVMASK >> lane) & 1) ? 16384 : 12288);
    if (warp == 16 && lane < 24) mbar_expect(bar + (lane < 8 ? B_X : lane < 16 ? B_KV - 64 : B_T - 128) + 8 * lane, 16384);
    if (tid == 512) {
        tma2d(sb, &tm.x, 0, mb * 128, bar + B_X);
    } else if (tid == 544) {
        map_prefetch(&tm.kv);
        l2_prefetch((const uint8_t*)wqkv + (size_t)blockIdx.x * 3072, 3072);
        l2_prefetch((const uint8_t*)w1 + (size_t)blockIdx.x * 1792, 1792);
        map_prefetch(&tm.q); map_prefetch(&tm.f1); map_prefetch(&tm.f3);
    }
    if ((sb & 0xFFFFFF) != SBD) __trap();
    __syncwarp();
    asm volatile("barrier.cluster.wait.aligned;" ::: "memory");
    if (tid == 512) issue_stream<0, NR>(tm, sb, rank, nb, mb);
    if (tid == 0) { TLM(0, 1); TLC(0, 30); }

    if (warp < 16) {
        const int wg = warp >> 2;
        const int h = cl >> 1, qd = (cl & 1) * 2 + rank;
        uint32_t q[4];
        {
            const int w8 = warp & 7;
            const int T = mb * 8 + w8, row0 = T * 16 + g;
            const uint64_t dA0 = mkdesc(SBD + (wg & 1) * 8192, 16, 1024, 1);
            if (wg < 2) {
                float acc[64];
#pragma unroll
                for (int i = 0; i < 64; i++) acc[i] = 0.f;
                gemm_pass<128, 8192, 2048, 4096, 1024, 1>(acc, bar, dA0, lane, strm_pos(3, 0), strm_code(3), 0, true, false);
                if (tid == 0) TLM(0, 2);
                {
                    const float km = norm_bound(acc, 1.f);
                    float vm = 0.f;
#pragma unroll
                    for (int i = 32; i < 64; i++) vm = fmaxf(vm, fabsf(acc[i]));
                    vm = __uint_as_float(__reduce_max_sync(0xffffffffu, __float_as_uint(vm)));
                    if (lane == 0) { gN[1024 + nb * 128 + T] = km; gN[2048 + nb * 128 + T] = vm; }
                    const uint32_t kp = sb + OFF_R + 12288 + (w8 >> 2) * 1024 + g * 128 + ((((w8 & 3) * 2 + ((t >> 1) ^ (w8 >> 2))) ^ g) << 4) + (t & 1) * 8;
                    uint8_t* vp = gKV + (size_t)(nb * 4) * (SEQ * 64) + 65536 + (((T >> 6) * 16 + 2 * g) * 64 + (T & 63)) * 32 + ((t * 8) ^ ((w8 >> 2) << 4));
                    bar_sync(9, 256);
#pragma unroll
                    for (int hh = 0; hh < 4; hh++) {
                        const float* v = acc + 8 * hh;
                        float p0 = __shfl_up_sync(0xffffffffu, v[2], 4), p1 = __shfl_up_sync(0xffffffffu, v[3], 4);
                        float p2 = __shfl_up_sync(0xffffffffu, v[6], 4), p3 = __shfl_up_sync(0xffffffffu, v[7], 4);
                        if (g == 0) { p0 = p1 = p2 = p3 = 0.f; }
                        sts64(kp + hh * 16384, pk_f16(v[0] - p0, v[1] - p1), pk_f16(v[4] - p2, v[5] - p3));
                        sts64(kp + hh * 16384 + 2048, pk_f16(v[2] - v[0], v[3] - v[1]), pk_f16(v[6] - v[4], v[7] - v[5]));
                        const float* u = acc + 32 + 8 * hh;
                        if (hh < 2) {
                            sts64(kp + (4 + hh) * 16384, pk_bf16(u[0], u[1]), pk_bf16(u[4], u[5]));
                            sts64(kp + (4 + hh) * 16384 + 2048, pk_bf16(u[2], u[3]), pk_bf16(u[6], u[7]));
                        } else {
                            *(uint2*)(vp + (size_t)hh * (SEQ * 64)) = make_uint2(pk_bf16(u[0], u[1]), pk_bf16(u[4], u[5]));
                            *(uint2*)(vp + (size_t)hh * (SEQ * 64) + 2048) = make_uint2(pk_bf16(u[2], u[3]), pk_bf16(u[6], u[7]));
                        }
                    }
                }
                asm volatile("fence.proxy.async.shared::cta;" ::: "memory");
                bar_arrive(10, 288);
                if (tid == 0) TLM(0, 3);
            }
#pragma unroll 1
            for (int p = wg < 2 ? 1 : 0; p < 3; p += 2) {
                float acc[48];
#pragma unroll
                for (int i = 0; i < 48; i++) acc[i] = 0.f;
                pin<48>(acc);
                if (p) bar_sync(5 + p, 512);
                gemm_pass<96, 6144, 1024, 2048, 512, 2>(acc, bar, dA0, lane, p == 0 ? strm_pos(0, 0) : 8 + 8 * p, p == 0 ? strm_code(0) : strm_code(1), p < 2 ? 6 + p : 0, p == 0, p == 2);
                if ((tid & 255) == 0) TLM(0, 4 + 2 * p);
                const uint32_t hp = sb + OFF_R + (p == 2 ? 0 : 12288) + (wg & 1) * 16384 + ((warp & 3) * 16 + g) * 64 + t * 16;
                const uint32_t bp = sb + OFF_BIAS + p * 384 - 256 + t * 8;
                uint32_t ho[24];
                mbar_wait(bar + B_BI, 0);
                if (p == 0) {
                    const float qm = norm_bound(acc, QSCALE * QSCALE);
                    if (lane == 0) gN[nb * 128 + T] = qm;
                    uint8_t* qp = gQ + (size_t)(nb * 4) * (SEQ * 32) + (size_t)row0 * 32 + t * 8;
#pragma unroll
                    for (int hh = 0; hh < 4; hh++) {
                        const float* v = acc + 8 * hh;
                        *(uint2*)(qp + hh * (SEQ * 32)) = make_uint2(pk_f16(v[0] * QSCALE, v[1] * QSCALE), pk_f16(v[4] * QSCALE, v[5] * QSCALE));
                        *(uint2*)(qp + hh * (SEQ * 32) + 256) = make_uint2(pk_f16(v[2] * QSCALE, v[3] * QSCALE), pk_f16(v[6] * QSCALE, v[7] * QSCALE));
                    }
                    bar_arrive(12, 288);
                } else {
                    gelu_pack<0, 2>(acc, bp, ho);
                    pin<16>(ho);
                    mbar_wait(bar + B_G, 0);
                    load_q(q, h, qd * 512 + warp * 16 + g, t);
                }
                gelu_pack<2, 3>(acc, bp, ho);
                pin<8>(ho + 16);
                if (p == 2) bar_sync(9, 256);
                else mbar_wait(bar + B_SF + 8 * p, 0);
                if (p) {
#pragma unroll
                    for (int i = 0; i < 4; i++) sts128(hp + (i >> 1) * 32768 + (i & 1) * 512, ho + 4 * i);
                }
                sts128(hp + 65536, ho + 16);
                sts128(hp + 65536 + 512, ho + 20);
                asm volatile("fence.proxy.async.shared::cta;" ::: "memory");
                bar_arrive(p == 1 ? 14 : 11, 288);
                if ((tid & 255) == 0) TLM(0, 5 + 2 * p);
            }
        }
        uint32_t ep = 2;
        uint4* const op = gO + ((qd * 8 + wg) * NH + h) * 128 + (tid & 127);
        const uint64_t kd0 = mkdesc(SBD, 16, 256, 3);
        const uint64_t vd0 = mkdesc(SBD + 8192, OFF_ONE - 8192, 256, 3);
        {
#pragma unroll 1
            for (int r = 0; r < 2; r++) {
                float o[12];
#pragma unroll
                for (int i = 0; i < 12; i++) o[i] = 0.f;
                uint64_t kd = kd0, vd = vd0;
                uint32_t qn[4];
#pragma unroll 1
                for (int half = 0; half < 2 && (ep & 2); half++) {
                    float s[32];
#pragma unroll
                    for (int i = 0; i < 32; i++) s[i] = i < 2 * NMUFU ? 0.f : MAGIC;
#pragma unroll 1
                    for (int c = 0; c < 4; c++) {
                        if ((tid & 255) == 0 && c == 0 && r == 0 && half == 0) TLM(0, 19 + (tid >> 8));
                        if (r == 0) {
                            mbar_wait(bar + B_KV + 8 * (half * 4 + c), 0);
                            if (half == 0 && c == 1) {
                                mbar_wait(bar + B_G3, 0);
                                ep = lds32(sb + OFF_G + 256);
                                if (!(ep & 2)) break;
                            }
                        }
                        if (tid == 0 && r == 0 && half == 0) TLM(0, 21 + c);
                        if ((tid & 255) == 0 && c == 0) TLM(1, (tid >> 8) * 4 + r * 2 + half);
                        if (half == 1 && c == 3) {
                            if (r == 0) load_q(qn, h, qd * 512 + 256 + warp * 16 + g, t);
                            else if (lane == 0) mbar_arrive(bar + B_DONE);
                        }
#pragma unroll
                        for (int j = 0; j < 4; j++) {
                            uint32_t p[16];
                            wg_fence();
                            wgmma_qk_f16_acc(s, q, kd);
                            wg_commit();
                            wg_wait<0>();
                            pin<32>(s);
#pragma unroll
                            for (int i = 0; i < 16; i++)
                                p[i] = i < NMUFU ? pk_bf16(ex2f(s[2 * i]), ex2f(s[2 * i + 1])) : exp2_pair(s[2 * i], s[2 * i + 1], m1);
                            pin<16>(p);
                            wg_fence();
#pragma unroll
                            for (int u = 0; u < 4; u++) wgmma_pv(o, p + 4 * u, vd + u * VSTEP);
                            wg_commit();
                            kd += 128;
                            vd += 4 * VSTEP;
                        }
                        kd += 512;
                        vd += 16 * VSTEP;
                    }
                    wg_wait<0>();
                }
                pin<12>(o);
                if (!(ep & 2)) break;
                if ((tid & 127) == 0 && r == 1) TLM(1, 8 + wg);
                store_o(o, op + r * (4 * NH * 128), ep & 1);
#pragma unroll
                for (int i = 0; i < 4; i++) q[i] = qn[i];
            }
            if (tid == 0) { TLM(1, 12); TLC(0, 31); }
        }
        if (!(ep & 2)) {
            bar_sync(8, 512);
            for (int c = 0; c < 8; c++) mbar_wait(bar + B_KV + 8 * c, 0);
            {
                float kc[8][8];
                proj16<8>(kc, x, wqkv, warp * 16, 256, DM + h * 16, g, t);
#pragma unroll
                for (int i = 0; i < 8; i++) {
                    const int T = warp + i * 16;
                    const int pos = ((T >> 6) * 16 + 2 * g) * 64 + (T & 63);
                    const uint32_t a = sb + (pos >> 8) * 16384 + (pos & 255) * 32 + t * 4, sw = ((T >> 2) & 1) << 4;
                    asm volatile("st.shared.u32 [%0], %1;" ::"r"(a + sw), "r"(pk_bf16(kc[i][0], kc[i][1])) : "memory");
                    asm volatile("st.shared.u32 [%0], %1;" ::"r"(a + (sw ^ 16)), "r"(pk_bf16(kc[i][4], kc[i][5])) : "memory");
                    asm volatile("st.shared.u32 [%0], %1;" ::"r"(a + 2048 + sw), "r"(pk_bf16(kc[i][2], kc[i][3])) : "memory");
                    asm volatile("st.shared.u32 [%0], %1;" ::"r"(a + 2048 + (sw ^ 16)), "r"(pk_bf16(kc[i][6], kc[i][7])) : "memory");
                }
                asm volatile("fence.proxy.async.shared::cta;" ::: "memory");
                bar_sync(8, 512);
            }
#pragma unroll 1
            for (int r = 0; r < 2; r++) {
                const int row = qd * 512 + r * 256 + warp * 16 + g;
                {
                    float qc[1][8];
                    proj16<1>(qc, x, wqkv, row - g, 0, h * 16, g, t);
#pragma unroll
                    for (int i = 0; i < 4; i++) q[i] = pk_bf16(qc[0][2 * i] * QSCALE, qc[0][2 * i + 1] * QSCALE);
                }
                float o[12];
#pragma unroll
                for (int i = 0; i < 12; i++) o[i] = 0.f;
                float m0 = -INFINITY, m1 = -INFINITY;
#pragma unroll 1
                for (int j = 0; j < 32; j++) {
                    const uint64_t kd = kd0 + (j >> 2) * 1024 + (j & 3) * 128, vd = vd0 + ((j >> 2) * 32 + (j & 3) * 4) * VSTEP;
                    float s[32];
                    uint32_t p[16];
                    wg_fence();
                    wgmma_qk_bf16_zero(s, q, kd);
                    wg_commit();
                    wg_wait<0>();
                    pin<32>(s);
                    pin<12>(o);
                    float n0 = m0, n1 = m1;
#pragma unroll
                    for (int i = 0; i < 8; i++) {
                        n0 = fmaxf(n0, fmaxf(s[4 * i], s[4 * i + 1]));
                        n1 = fmaxf(n1, fmaxf(s[4 * i + 2], s[4 * i + 3]));
                    }
                    n0 = fmaxf(n0, __shfl_xor_sync(0xffffffffu, n0, 1));
                    n1 = fmaxf(n1, __shfl_xor_sync(0xffffffffu, n1, 1));
                    n0 = fmaxf(n0, __shfl_xor_sync(0xffffffffu, n0, 2));
                    n1 = fmaxf(n1, __shfl_xor_sync(0xffffffffu, n1, 2));
                    const float c0 = ex2f(m0 - n0), c1 = ex2f(m1 - n1);
                    m0 = n0;
                    m1 = n1;
#pragma unroll
                    for (int i = 0; i < 3; i++) { o[4 * i] *= c0; o[4 * i + 1] *= c0; o[4 * i + 2] *= c1; o[4 * i + 3] *= c1; }
#pragma unroll
                    for (int i = 0; i < 8; i++) {
                        p[2 * i] = pk_bf16(ex2f(s[4 * i] - m0), ex2f(s[4 * i + 1] - m0));
                        p[2 * i + 1] = pk_bf16(ex2f(s[4 * i + 2] - m1), ex2f(s[4 * i + 3] - m1));
                    }
                    pin<16>(p);
                    pin<12>(o);
                    wg_fence();
#pragma unroll
                    for (int u = 0; u < 4; u++) wgmma_pv(o, p + 4 * u, vd + u * VSTEP);
                    wg_commit();
                }
                wg_wait<0>();
                pin<12>(o);
                if (r == 1 && lane == 0) mbar_arrive(bar + B_DONE);
                store_o(o, op + r * (4 * NH * 128), ep & 1);
            }
        }
        {
            const uint4* src = gO + (rb * NH + wg * 8) * 128 + (tid & 127);
            uint4 v[8];
#pragma unroll
            for (int i = 0; i < 8; i++) v[i] = load_o(src + i * 128);
            mbar_wait(bar + B_DONE, 0);
            mbar_wait(bar + B_G2, 0);
            const int lr = (warp & 3) * 16 + g;
            const uint32_t g0 = lds32(sb + OFF_G + lr * 4), g1 = lds32(sb + OFF_G + lr * 4 + 32);
            const uint32_t a0 = sb + wg * 16384 + lr * 128 + (t >> 1) * 4;
#pragma unroll
            for (int i = 0; i < 8; i++) {
                if ((i & 3) == 0) {
                    int spins = 0;
                    while (__any_sync(0xffffffffu, (((v[i].x ^ ep) | (v[i + 1].x ^ ep) | (v[i + 2].x ^ ep) | (v[i + 3].x ^ ep)) & 1) != 0)) {
                        if (++spins > (1 << 22)) __trap();
#pragma unroll
                        for (int k = i; k < 8; k++)
                            if (((v[k].x ^ ep) & 1) != 0) v[k] = load_o(src + k * 128);
                    }
                }
                const uint32_t a = a0 + (i >> 2) * 8192 + ((((i & 3) * 2 + (t & 1)) ^ g) << 4);
                sts32(a, bmul2(v[i].x, g0));
                sts32(a + 8, bmul2(v[i].y, g0));
                sts32(a + 1024, bmul2(v[i].z, g1));
                sts32(a + 1024 + 8, bmul2(v[i].w, g1));
                if ((i & 3) == 3) {
                    asm volatile("fence.proxy.async.shared::cta;" ::: "memory");
                    __syncwarp();
                    if (lane == 0) mbar_arrive(bar + B_T + 8 * (wg * 2 + (i >> 2)));
                    if ((tid & 127) == 0) TLM(1, 20 + wg * 2 + (i >> 2));
                }
            }
        }
    } else {
        if (warp == 16) {
            if (lane == 0) {
                issue_stream<NR, 32>(tm, sb, rank, nb, mb);
                mbar_wait(bar + B_SF2, 0);
#pragma unroll
                for (int s = 0; s < 4; s++) {
                    mbar_expect(bar + B_F2 + 8 * s, 24576);
                    tma5d_mc(sb + OFF_R + s * 24576 + 8192 + rank * 8192, &tm.w2, cb * 128 + rank * 64, s * 2, bar + B_F2 + 8 * s);
                }
                cnt_wait(gCntH + mb * 32, epoch() * 8);
                asm volatile("fence.proxy.async.global;" ::: "memory");
                TLM(1, 13);
#pragma unroll
                for (int s = 0; s < 4; s++) tma2d(sb + OFF_R + s * 24576, &tm.h, s * 64, rb * 64, bar + B_F2 + 8 * s);
            }
        } else if (warp == 17) {
            {
                uint32_t bv[4], b2v[2];
#pragma unroll
                for (int i = 0; i < 4; i++) bv[i] = lane + 32 * i < 112 ? *(const uint32_t*)(b1 + nb * 224 + (lane + 32 * i) * 2) : 0;
#pragma unroll
                for (int i = 0; i < 2; i++) b2v[i] = *(const uint32_t*)(b2 + cb * 128 + (lane + 32 * i) * 2);
#pragma unroll
                for (int i = 0; i < 4; i++) {
                    sts32(sb + OFF_ONE + (lane + 32 * i) * 4, 0x3f803f80u);
                    if (lane + 32 * i < 112) sts64(sb + OFF_BIAS + (lane + 32 * i) * 8, bv[i] << 16, bv[i] & 0xffff0000u);
                }
#pragma unroll
                for (int i = 0; i < 2; i++) sts32(sb + OFF_BIAS + 896 + (lane + 32 * i) * 4, b2v[i]);
                asm volatile("fence.proxy.async.shared::cta;" ::: "memory");
                __syncwarp();
                if (lane == 0) mbar_arrive(bar + B_BI);
            }
            mbar_wait(bar + B_X + 8 * PFX, 0);
            if (lane == 0) {
                l2_prefetch((const uint8_t*)wqkv + 128 * 3072 + (size_t)blockIdx.x * 9216, 9216);
                l2_prefetch((const uint8_t*)w1 + (size_t)blockIdx.x * 14336, 14336);
            }
            mbar_wait(bar + B_X + 8 * 7, 0);
            if (lane == 0) {
                l2_prefetch((const uint8_t*)w2 + (size_t)blockIdx.x * 14336, 14336);
                l2_prefetch((const uint8_t*)wo + (size_t)blockIdx.x * 4096, 4096);
                map_prefetch(&tm.h); map_prefetch(&tm.w2); map_prefetch(&tm.wo); map_prefetch(&tm.hs); map_prefetch(&tm.kvs);
                TLM(0, 11);
            }
            bar_sync(10, 288);
            if (lane == 0) {
#pragma unroll 1
                for (int b = 5; b >= 0; b--) {
                    tma5d_st(&tm.kvs, sb + OFF_R + 12288 + b * 16384, (mb >> 3) * 8, (mb & 7) * 2, nb * 8 + (b < 4 ? 2 * b : 2 * b - 7));
                    asm volatile("cp.async.bulk.commit_group;\ncp.async.bulk.wait_group.read %0;" ::"n"(PACE) : "memory");
                    if (b == 4 - PACE) mbar_arrive(bar + B_SF);
                }
                asm volatile("cp.async.bulk.wait_group.read 0;" ::: "memory");
                mbar_arrive(bar + B_SF + 8);
            }
            __syncwarp();
            bar_sync(12, 288);
            if (lane == 0) {
                asm volatile("cp.async.bulk.wait_group 0;\nfence.proxy.async.global;" ::: "memory");
                cnt_add(gCntQ + nb * 32);
                TLM(0, 13);
            }
        } else {
            {
                const int r0 = mb * 128 + nb * 16 + (warp - 18) * 8;
                uint4 xv[16];
#pragma unroll
                for (int i = 0; i < 16; i++) xv[i] = *(const uint4*)(x + (size_t)(r0 + (i >> 1)) * DM + (i & 1) * 256 + lane * 8);
                const uint4 ga = *(const uint4*)(gate + lane * 8), gb = *(const uint4*)(gate + 256 + lane * 8);
                float z[8];
#pragma unroll
                for (int r = 0; r < 8; r++) z[r] = dot8(xv[2 * r], ga) + dot8(xv[2 * r + 1], gb);
#pragma unroll
                for (int w = 4; w >= 1; w >>= 1)
#pragma unroll
                    for (int r = 0; r < w; r++) {
                        const bool up = lane & w;
                        z[r] = (up ? z[r + w] : z[r]) + __shfl_xor_sync(0xffffffffu, up ? z[r] : z[r + w], w);
                    }
                z[0] += __shfl_xor_sync(0xffffffffu, z[0], 8);
                z[0] += __shfl_xor_sync(0xffffffffu, z[0], 16);
                if (lane < 8) gG[r0 + lane] = 1.f / (1.f + __expf(-z[0]));
                if (tid == 576) TLM(0, 12);
            }
            if (warp == 19) {
#pragma unroll 1
                for (int e = 0; e < 3; e++) {
                    bar_sync(e == 1 ? 14 : 11, 288);
                    if (lane == 0) {
#pragma unroll 1
                        for (int b = e == 0 ? 4 : 0; b < 6; b++) {
                            tma3d_st(&tm.hs, sb + OFF_R + (e == 2 ? 0 : 12288) + b * 16384, 0, mb * 128 + (b & 1) * 64, nb * 7 + e * 3 - 2 + (b >> 1));
                            asm volatile("cp.async.bulk.commit_group;\ncp.async.bulk.wait_group.read %0;" ::"n"(PACE) : "memory");
                        }
                        asm volatile("cp.async.bulk.wait_group.read 0;" ::: "memory");
                        if (e == 0) mbar_arrive(bar + B_SF + 8);
                        if (e == 2) { mbar_arrive_cluster(bar + B_SF2, 0); mbar_arrive_cluster(bar + B_SF2, 1); }
                    }
                    __syncwarp();
                }
                bar_sync(13, 64);
                if (lane == 0) {
                    asm volatile("cp.async.bulk.wait_group 0;\nfence.proxy.async.global;" ::: "memory");
                    cnt_add(gCntH + mb * 32);
                    TLM(0, 15);
                }
            } else {
                bar_arrive(13, 64);
                const int h = cl >> 1, qd = (cl & 1) * 2 + rank;
                const uint32_t ep = epoch();
                if (lane == 0) {
                    cnt_wait(gCntQ + (h >> 2) * 32, ep * 16);
                    mbar_arrive(bar + B_G);
                    TLM(0, 14);
                    asm volatile("fence.proxy.async.global;" ::: "memory");
#pragma unroll
                    for (int c = 0; c < 2; c++) {
                        mbar_wait(bar + B_XD + 8 * c, 0);
                        bulk_mc(sb + c * 16384 + rank * 8192, gKV + (size_t)h * (SEQ * 64) + rank * 65536 + c * 8192, 8192, bar + B_KV + 8 * c);
                    }
                }
                __syncwarp();
            const int hb = h >> 2;
            const uint4 kq = __ldcg((const uint4*)(gN + 1024 + hb * 128 + lane * 4));
            const uint4 vq = __ldcg((const uint4*)(gN + 2048 + hb * 128 + lane * 4));
            const float qq = ldcg_f(gN + hb * 128 + qd * 32 + lane);
            const float kf = __uint_as_float(__reduce_max_sync(0xffffffffu, max(max(kq.x, kq.y), max(kq.z, kq.w))));
            const float vf = __uint_as_float(__reduce_max_sync(0xffffffffu, max(max(vq.x, vq.y), max(vq.z, vq.w))));
            const float qf = __uint_as_float(__reduce_max_sync(0xffffffffu, __float_as_uint(qq)));
            if (lane == 0) {
                sts32(sb + OFF_G + 256, (ep & 1) | ((kf <= 1.0e6f) && (qf <= 1.0e6f) && (kf * qf <= 3400.f) && (vf <= 1.0e12f) ? 2 : 0));
                mbar_arrive(bar + B_G3);
                TLM(0, 16);
#pragma unroll
                for (int c = 2; c < 8; c++) {
                    mbar_wait(bar + B_XD + 8 * c, 0);
                    bulk_mc(sb + c * 16384 + rank * 8192, gKV + (size_t)h * (SEQ * 64) + rank * 65536 + c * 8192, 8192, bar + B_KV + 8 * c);
                }
                TLM(0, 10);
            }
            }
        }
        __syncwarp();
        float acc[64];
#pragma unroll
        for (int i = 0; i < 64; i++) acc[i] = 0.f;
#pragma unroll 1
        for (int io = 0; io < 7; io++) {
#pragma unroll
            for (int s = 0; s < 4; s++) {
                const int it = io * 4 + s;
                mbar_wait(bar + B_F2 + 8 * s, io & 1);
                if (tid == 512 && s == 0 && (io == 0 || io == 4)) TLM(1, 14 + io / 4);
                const uint64_t dA = mkdesc(SBD + OFF_R + s * 24576, 16, 1024, 1);
                const uint64_t dB = mkdesc(SBD + OFF_R + s * 24576 + 8192, 8192, 1024, 1);
                wg_fence();
#pragma unroll
                for (int kk = 0; kk < EXP_FKK; kk++) {
                    wgmma_ss_n128(acc, dA + kk * 2, dB + kk * 128);
                    if (kk < 3 && (FSER != 3 || kk == 1)) {
                        wg_commit();
                        wg_wait<0>();
                    }
                }
                wg_commit();
                if (warp < 18 && it >= 2 && it < 26) {
                    const int s2 = (s + 2) & 3;
                    mbar_wait(bar + B_E2 + 8 * s2, (io - (s < 2)) & 1);
                    if (elect()) {
                        if (warp == 16) {
                            mbar_expect(bar + B_F2 + 8 * s2, 24576);
                            tma5d_mc(sb + OFF_R + s2 * 24576 + 8192 + rank * 8192, &tm.w2, cb * 128 + rank * 64, it * 2 + 4, bar + B_F2 + 8 * s2);
                        } else {
                            asm volatile("fence.proxy.async.global;" ::: "memory");
                            tma2d(sb + OFF_R + s2 * 24576, &tm.h, it * 64 + 128, rb * 64, bar + B_F2 + 8 * s2);
                        }
                    }
                    __syncwarp();
                }
                wg_wait<1>();
                if (it >= 1 && lane < 2) mbar_arrive_cluster(bar + B_E2 + 8 * ((s + 3) & 3), lane);
            }
        }
        wg_wait<0>();
        if (lane < 2) mbar_arrive_cluster(bar + B_E2 + 8 * 3, lane);
        pin<64>(acc);
        if (tid == 576) gEpoch[blockIdx.x] = epoch();
        if (warp == 16) {
            if (lane == 0) TLM(1, 16);
            for (int s = 0; s < 4; s++) mbar_wait(bar + B_E2 + 8 * s, 0);
            if (elect()) {
#pragma unroll
                for (int i = 0; i < 6; i++) tma2d_mc(sb + OFF_R + i * 16384 + rank * 8192, &tm.wo, cb * 128 + rank * 64, i * 64, bar + B_T + 8 * i);
            }
            __syncwarp();
        }
        {
            const int lr = (warp - 16) * 16 + g;
            const uint32_t pa = pk_bf16(ldcg_f(gG + rb * 64 + lr), ldcg_f(gG + rb * 64 + lr + 8));
            if (t == 0) {
                sts32(sb + OFF_G + lr * 4, __byte_perm(pa, pa, 0x1010));
                sts32(sb + OFF_G + lr * 4 + 32, __byte_perm(pa, pa, 0x3232));
            }
            __syncwarp();
            if (lane == 0) mbar_arrive(bar + B_G2);
            const float ga = bf_lo(pa), gb = bf_hi(pa);
            const float g0 = 1.f - ga, g1 = 1.f - gb;
#pragma unroll
            for (int j = 0; j < 16; j++) {
                const uint32_t bv = lds32(sb + OFF_BIAS + 896 + j * 16 + t * 4);
                acc[4 * j] = fmaf(acc[4 * j], 0.5f, bf_lo(bv)) * g0;
                acc[4 * j + 1] = fmaf(acc[4 * j + 1], 0.5f, bf_hi(bv)) * g0;
                acc[4 * j + 2] = fmaf(acc[4 * j + 2], 0.5f, bf_lo(bv)) * g1;
                acc[4 * j + 3] = fmaf(acc[4 * j + 3], 0.5f, bf_hi(bv)) * g1;
            }
            pin<64>(acc);
        }
        if (warp == 17) {
            mbar_wait(bar + B_DONE, 0);
            if (elect()) {
#pragma unroll
                for (int i = 0; i < 4; i++)
                    tma2d(sb + 65536 + i * 8192, &tm.wo, cb * 128 + (i & 1) * 64, (6 + (i >> 1)) * 64, bar + B_T + 8 * (6 + (i >> 1)));
            }
            __syncwarp();
        }
        if (tid == 512) TLM(1, 17);
#pragma unroll
        for (int i = 0; i < 8; i++) {
            mbar_wait(bar + B_T + 8 * i, 0);
            const uint64_t dA = mkdesc(SBD + i * 8192, 16, 1024, 1);
            const uint64_t dB = mkdesc(i < 6 ? SBD + OFF_R + i * 16384 : SBD + 65536 + (i - 6) * 16384, 8192, 1024, 1);
            wg_fence();
#pragma unroll
            for (int kk = 0; kk < 4; kk++) wgmma_ss_n128(acc, dA + kk * 2, dB + kk * 128);
            wg_commit();
        }
        wg_wait<0>();
        pin<64>(acc);
        if (tid == 512) TLM(1, 18);
        {
            const uint32_t st = sb + 98304 + (warp - 16) * 4352;
            const uint32_t wa = st + (lane & 15) * 272 + (lane >> 4) * 16;
#pragma unroll
            for (int j = 0; j < 8; j++)
                asm volatile("stmatrix.sync.aligned.m8n8.x4.shared.b16 [%0], {%1, %2, %3, %4};" ::"r"(wa + j * 32),
                             "r"(pk_bf16(acc[8 * j], acc[8 * j + 1])), "r"(pk_bf16(acc[8 * j + 2], acc[8 * j + 3])),
                             "r"(pk_bf16(acc[8 * j + 4], acc[8 * j + 5])), "r"(pk_bf16(acc[8 * j + 6], acc[8 * j + 7])) : "memory");
            __syncwarp();
            __nv_bfloat16* op = out + (size_t)(rb * 64 + (warp - 16) * 16 + (lane >> 4)) * DM + cb * 128 + (lane & 15) * 8;
#pragma unroll
            for (int j = 0; j < 8; j++) {
                uint4 v;
                asm volatile("ld.shared.v4.u32 {%0, %1, %2, %3}, [%4];" : "=r"(v.x), "=r"(v.y), "=r"(v.z), "=r"(v.w)
                             : "r"(st + (2 * j + (lane >> 4)) * 272 + (lane & 15) * 16));
                *(uint4*)(op + (size_t)j * 2 * DM) = v;
            }
        }
        if (tid == 512) TLM(1, 19);
        TL_DUMP();
    }
}

typedef CUresult (*EncodeFn)(CUtensorMap*, CUtensorMapDataType, cuuint32_t, void*, const cuuint64_t*, const cuuint64_t*, const cuuint32_t*,
                             const cuuint32_t*, CUtensorMapInterleave, CUtensorMapSwizzle, CUtensorMapL2promotion, CUtensorMapFloatOOBfill);

static void make_map(EncodeFn enc, CUtensorMap* m, const void* p, int rank, const cuuint64_t* dims, const cuuint64_t* strides,
                     const cuuint32_t* box, CUtensorMapSwizzle swz) {
    const cuuint32_t es[5] = {1, 1, 1, 1, 1};
    enc(m, CU_TENSOR_MAP_DATA_TYPE_BFLOAT16, rank, (void*)p, dims, strides, box, es, CU_TENSOR_MAP_INTERLEAVE_NONE, swz,
        CU_TENSOR_MAP_L2_PROMOTION_L2_128B, CU_TENSOR_MAP_FLOAT_OOB_FILL_NONE);
}

extern "C" void kernel_launch(void* const* d_in, const int* in_sizes, int n_in, void* d_out, int out_size) {
    const __nv_bfloat16* x = (const __nv_bfloat16*)d_in[0];
    const __nv_bfloat16* wqkv = (const __nv_bfloat16*)d_in[1];
    const __nv_bfloat16* wo = (const __nv_bfloat16*)d_in[2];
    const __nv_bfloat16* w1 = (const __nv_bfloat16*)d_in[4];
    const __nv_bfloat16* b1 = (const __nv_bfloat16*)d_in[5];
    const __nv_bfloat16* w2 = (const __nv_bfloat16*)d_in[6];
    const __nv_bfloat16* b2 = (const __nv_bfloat16*)d_in[7];
    const __nv_bfloat16* gate = (const __nv_bfloat16*)d_in[8];

    void* fp = nullptr;
    cudaDriverEntryPointQueryResult qr;
    cudaGetDriverEntryPoint("cuTensorMapEncodeTiled", &fp, cudaEnableDefault, &qr);
    EncodeFn enc = (EncodeFn)fp;
    void *pH, *pKV;
    cudaGetSymbolAddress(&pH, gH);
    cudaGetSymbolAddress(&pKV, gKV);

    Maps tm;
    const CUtensorMapSwizzle S128 = CU_TENSOR_MAP_SWIZZLE_128B, S64 = CU_TENSOR_MAP_SWIZZLE_64B;
    { cuuint64_t d[2] = {DM, SEQ}, s[1] = {DM * 2}; cuuint32_t b[2] = {64, 128}; make_map(enc, &tm.x, x, 2, d, s, b, S128); }
    { cuuint64_t d[3] = {DM, DM, 3}, s[2] = {3 * DM * 2, DM * 2}; cuuint32_t b[3] = {64, 32, 2}; make_map(enc, &tm.kv, wqkv, 3, d, s, b, S128); }
    { cuuint64_t d[3] = {32, DM, 3 * DM / 32}, s[2] = {3 * DM * 2, 64}; cuuint32_t b[3] = {32, 32, 2}; make_map(enc, &tm.q, wqkv, 3, d, s, b, S64); }
    { cuuint64_t d[3] = {32, DM, FF / 32}, s[2] = {FF * 2, 64}; cuuint32_t b[3] = {32, 32, 1}; make_map(enc, &tm.f1, w1, 3, d, s, b, S64); }
    { cuuint64_t d[3] = {32, DM, FF / 32}, s[2] = {FF * 2, 64}; cuuint32_t b[3] = {32, 32, 3}; make_map(enc, &tm.f3, w1, 3, d, s, b, S64); }
    { cuuint64_t d[2] = {FF, SEQ}, s[1] = {FF * 2}; cuuint32_t b[2] = {64, 64}; make_map(enc, &tm.h, pH, 2, d, s, b, S128); }
    { cuuint64_t d[5] = {DM, 2, 4, 4, FF / 32}, s[4] = {1024, 8 * 1024, 2 * 1024, 32 * 1024}; cuuint32_t b[5] = {64, 2, 4, 4, 2};
      make_map(enc, &tm.w2, w2, 5, d, s, b, S128); }
    { cuuint64_t d[2] = {DM, DM}, s[1] = {DM * 2}; cuuint32_t b[2] = {64, 64}; make_map(enc, &tm.wo, wo, 2, d, s, b, S128); }

    { cuuint64_t d[3] = {32, SEQ, FF / 32}, s[2] = {FF * 2, 64}; cuuint32_t b[3] = {32, 64, 1}; make_map(enc, &tm.hs, pH, 3, d, s, b, CU_TENSOR_MAP_SWIZZLE_NONE); }
    { cuuint64_t d[5] = {64, 16, 16, 2, 2 * NH}, s[4] = {4096, 128, 2048, 65536}; cuuint32_t b[5] = {64, 8, 2, 2, 1};
      make_map(enc, &tm.kvs, pKV, 5, d, s, b, S128); }
    cudaFuncSetAttribute(fused_kernel, cudaFuncAttributeMaxDynamicSharedMemorySize, TL_SMEM);
    fused_kernel<<<128, 640, TL_SMEM, cudaStreamPerThread>>>(tm, x, wqkv, wo, w1, b1, w2, b2, gate, (__nv_bfloat16*)d_out, 0xffffffffu);
}
```

```cpp
#include <cuda_runtime.h>
#include <cuda_bf16.h>
#include <cuda_fp16.h>
#include <cuda.h>
#include <stdint.h>

#define SEQ 2048
#define DM 512
#define FF 1792
#define NH 32

__device__ __align__(1024) uint8_t gQ[NH * SEQ * 32];
__device__ __align__(1024) uint8_t gKV[NH * SEQ * 64];
__device__ __align__(1024) __nv_bfloat16 gH[SEQ * FF];
__device__ __align__(1024) uint4 gO[32 * NH * 128];
__device__ float gG[SEQ];
__device__ float gN[3 * 8 * 128];
__device__ unsigned int gCntQ[8 * 32];
__device__ unsigned int gCntH[32 * 32];
__device__ unsigned int gEpoch[128];

__device__ __forceinline__ uint32_t smem_u32(const void* p) { return (uint32_t)__cvta_generic_to_shared(p); }
__device__ __forceinline__ void mbar_init(uint32_t a, uint32_t c) { asm volatile("mbarrier.init.shared::cta.b64 [%0], %1;" ::"r"(a), "r"(c)); }
__device__ __forceinline__ void mbar_expect(uint32_t a, uint32_t b) { asm volatile("mbarrier.arrive.expect_tx.shared::cta.b64 _, [%0], %1;" ::"r"(a), "r"(b) : "memory"); }
__device__ __forceinline__ void mbar_arrive(uint32_t a) { asm volatile("mbarrier.arrive.shared::cta.b64 _, [%0];" ::"r"(a) : "memory"); }
__device__ __forceinline__ void mbar_wait(uint32_t a, uint32_t ph) {
    asm volatile("{\n.reg .pred p;\n.reg .u32 n;\nmov.u32 n, 0;\nW_%=:\nmbarrier.try_wait.parity.shared::cta.b64 p, [%0], %1;\n@p bra D_%=;\n"
                 "add.u32 n, n, 1;\nsetp.lt.u32 p, n, 0x400000;\n@p bra W_%=;\ntrap;\nD_%=:\n}" ::"r"(a), "r"(ph) : "memory");
}
__device__ __forceinline__ void mbar_arrive_cluster(uint32_t a, uint32_t cta) {
    asm volatile("{\n.reg .b32 r;\nmapa.shared::cluster.u32 r, %0, %1;\nmbarrier.arrive.shared::cluster.b64 _, [r];\n}" ::"r"(a), "r"(cta) : "memory");
}
__device__ __forceinline__ void bar_sync(int id, int n) { asm volatile("bar.sync %0, %1;" ::"r"(id), "r"(n) : "memory"); }
__device__ __forceinline__ void bar_arrive(int id, int n) { asm volatile("bar.arrive %0, %1;" ::"r"(id), "r"(n) : "memory"); }
__device__ __forceinline__ uint32_t cluster_rank() { uint32_t r; asm("mov.u32 %0, %%cluster_ctarank;" : "=r"(r)); return r; }
__device__ __forceinline__ void cnt_add(unsigned int* c) { asm volatile("red.release.gpu.global.add.u32 [%0], 1;" ::"l"(c) : "memory"); }
__device__ __forceinline__ void cnt_wait(const unsigned int* c, uint32_t target) {
    uint32_t v;
    int spins = 0;
    while (true) {
        asm volatile("ld.acquire.gpu.global.u32 %0, [%1];" : "=r"(v) : "l"(c) : "memory");
        if ((int)(v - target) >= 0) break;
        if (++spins > (1 << 22)) __trap();
        __nanosleep(40);
    }
}
__device__ __forceinline__ void tma2d(uint32_t dst, const CUtensorMap* m, int c0, int c1, uint32_t bar) {
    asm volatile("cp.async.bulk.tensor.2d.shared::cluster.global.mbarrier::complete_tx::bytes [%0], [%1, {%3, %4}], [%2];"
                 ::"r"(dst), "l"(m), "r"(bar), "r"(c0), "r"(c1) : "memory");
}
__device__ __forceinline__ void tma2d_mc(uint32_t dst, const CUtensorMap* m, int c0, int c1, uint32_t bar) {
    asm volatile("cp.async.bulk.tensor.2d.shared::cluster.global.mbarrier::complete_tx::bytes.multicast::cluster [%0], [%1, {%3, %4}], [%2], %5;"
                 ::"r"(dst), "l"(m), "r"(bar), "r"(c0), "r"(c1), "h"((uint16_t)3) : "memory");
}
__device__ __forceinline__ void tma3d_mc(uint32_t dst, const CUtensorMap* m, int c0, int c1, int c2, uint32_t bar) {
    asm volatile("cp.async.bulk.tensor.3d.shared::cluster.global.mbarrier::complete_tx::bytes.multicast::cluster [%0], [%1, {%3, %4, %5}], [%2], %6;"
                 ::"r"(dst), "l"(m), "r"(bar), "r"(c0), "r"(c1), "r"(c2), "h"((uint16_t)3) : "memory");
}
__device__ __forceinline__ void tma5d_mc(uint32_t dst, const CUtensorMap* m, int c0, int c4, uint32_t bar) {
    asm volatile("cp.async.bulk.tensor.5d.shared::cluster.global.mbarrier::complete_tx::bytes.multicast::cluster [%0], [%1, {%3, %5, %5, %5, %4}], [%2], %6;"
                 ::"r"(dst), "l"(m), "r"(bar), "r"(c0), "r"(c4), "r"(0), "h"((uint16_t)3) : "memory");
}
__device__ __forceinline__ void bulk_mc(uint32_t dst, const void* src, uint32_t bytes, uint32_t bar) {
    asm volatile("cp.async.bulk.shared::cluster.global.mbarrier::complete_tx::bytes.multicast::cluster [%0], [%1], %2, [%3], %4;"
                 ::"r"(dst), "l"(src), "r"(bytes), "r"(bar), "h"((uint16_t)3) : "memory");
}
__device__ __forceinline__ void tma3d_st(const CUtensorMap* m, uint32_t src, int c0, int c1, int c2) {
    asm volatile("cp.async.bulk.tensor.3d.global.shared::cta.bulk_group [%0, {%2, %3, %4}], [%1];" ::"l"(m), "r"(src), "r"(c0), "r"(c1), "r"(c2) : "memory");
}
__device__ __forceinline__ void tma5d_st(const CUtensorMap* m, uint32_t src, int c1, int c2, int c4) {
    asm volatile("cp.async.bulk.tensor.5d.global.shared::cta.bulk_group [%0, {%5, %2, %3, %5, %4}], [%1];"
                 ::"l"(m), "r"(src), "r"(c1), "r"(c2), "r"(c4), "r"(0) : "memory");
}
__device__ __forceinline__ void bulk_st(void* dst, uint32_t src, uint32_t bytes) {
    asm volatile("cp.async.bulk.global.shared::cta.bulk_group [%0], [%1], %2;" ::"l"(dst), "r"(src), "r"(bytes) : "memory");
}
__device__ __forceinline__ void sts64(uint32_t a, uint32_t x, uint32_t y) { asm volatile("st.shared.v2.u32 [%0], {%1, %2};" ::"r"(a), "r"(x), "r"(y) : "memory"); }
__device__ __forceinline__ void sts128(uint32_t a, const uint32_t* v) {
    asm volatile("st.shared.v4.u32 [%0], {%1, %2, %3, %4};" ::"r"(a), "r"(v[0]), "r"(v[1]), "r"(v[2]), "r"(v[3]) : "memory");
}
__device__ __forceinline__ void l2_prefetch(const void* src, uint32_t bytes) {
    asm volatile("cp.async.bulk.prefetch.L2.global [%0], %1;" ::"l"(src), "r"(bytes) : "memory");
}
__device__ __forceinline__ void map_prefetch(const CUtensorMap* m) { asm volatile("prefetch.tensormap [%0];" ::"l"(m) : "memory"); }
__device__ __forceinline__ void wg_fence() { asm volatile("wgmma.fence.sync.aligned;" ::: "memory"); }
__device__ __forceinline__ void wg_commit() { asm volatile("wgmma.commit_group.sync.aligned;" ::: "memory"); }
template <int N> __device__ __forceinline__ void wg_wait() { asm volatile("wgmma.wait_group.sync.aligned %0;" ::"n"(N) : "memory"); }
template <int N> __device__ __forceinline__ void pin(float* s) {
#pragma unroll
    for (int i = 0; i < N; i++) asm volatile("" : "+f"(s[i])::"memory");
}
template <int N> __device__ __forceinline__ void pin(uint32_t* s) {
#pragma unroll
    for (int i = 0; i < N; i++) asm volatile("" : "+r"(s[i])::"memory");
}
__device__ __forceinline__ uint64_t mkdesc(uint32_t addr, uint32_t lbo, uint32_t sbo, uint32_t swz) {
    return (uint64_t)((addr & 0x3FFFF) >> 4) | ((uint64_t)(lbo >> 4) << 16) | ((uint64_t)(sbo >> 4) << 32) | ((uint64_t)swz << 62);
}
__device__ __forceinline__ float ex2f(float x) { float y; asm("ex2.approx.ftz.f32 %0, %1;" : "=f"(y) : "f"(x)); return y; }
__device__ __forceinline__ float tanhf_(float x) { float y; asm("tanh.approx.f32 %0, %1;" : "=f"(y) : "f"(x)); return y; }
__device__ __forceinline__ uint32_t pk_bf16(float lo, float hi) { uint32_t r; asm("cvt.rn.bf16x2.f32 %0, %1, %2;" : "=r"(r) : "f"(hi), "f"(lo)); return r; }
__device__ __forceinline__ uint32_t pk_f16(float lo, float hi) { uint32_t r; asm("cvt.rn.f16x2.f32 %0, %1, %2;" : "=r"(r) : "f"(hi), "f"(lo)); return r; }
__device__ __forceinline__ float bf_lo(uint32_t v) { return __uint_as_float(v << 16); }
__device__ __forceinline__ float bf_hi(uint32_t v) { return __uint_as_float(v & 0xffff0000u); }
__device__ __forceinline__ float dot8(const uint4& a, const uint4& b) {
    return fmaf(bf_lo(a.x), bf_lo(b.x), fmaf(bf_hi(a.x), bf_hi(b.x), fmaf(bf_lo(a.y), bf_lo(b.y), bf_hi(a.y) * bf_hi(b.y)))) +
           fmaf(bf_lo(a.z), bf_lo(b.z), fmaf(bf_hi(a.z), bf_hi(b.z), fmaf(bf_lo(a.w), bf_lo(b.w), bf_hi(a.w) * bf_hi(b.w))));
}
__device__ __forceinline__ uint32_t epoch() {
    uint32_t v;
    asm volatile("ld.global.u32 %0, [%1];" : "=r"(v) : "l"(gEpoch + blockIdx.x));
    return v + 1;
}
__device__ __forceinline__ float ldcg_f(const float* p) { return __ldcg(p); }

extern __shared__ __align__(1024) uint8_t smem_raw[];
#define TLM(k, slot) do {} while (0)
#define TLC(k, slot) do {} while (0)
#define TL_INIT() do {} while (0)
#define TL_DUMP() do {} while (0)
#define TL_SMEM SMEM_BYTES

__device__ __forceinline__ void wgmma_ss_n128(float* d, uint64_t da, uint64_t db) {
    asm volatile("wgmma.mma_async.sync.aligned.m64n128k16.f32.bf16.bf16 {"
        "%0, %1, %2, %3, %4, %5, %6, %7, %8, %9, %10, %11, %12, %13, %14, %15,"
        "%16, %17, %18, %19, %20, %21, %22, %23, %24, %25, %26, %27, %28, %29, %30, %31,"
        "%32, %33, %34, %35, %36, %37, %38, %39, %40, %41, %42, %43, %44, %45, %46, %47,"
        "%48, %49, %50, %51, %52, %53, %54, %55, %56, %57, %58, %59, %60, %61, %62, %63}, %64, %65, 1, 1, 1, 0, 1;\n"
        :
        "+f"(d[0]), "+f"(d[1]), "+f"(d[2]), "+f"(d[3]), "+f"(d[4]), "+f"(d[5]), "+f"(d[6]), "+f"(d[7]),
        "+f"(d[8]), "+f"(d[9]), "+f"(d[10]), "+f"(d[11]), "+f"(d[12]), "+f"(d[13]), "+f"(d[14]), "+f"(d[15]),
        "+f"(d[16]), "+f"(d[17]), "+f"(d[18]), "+f"(d[19]), "+f"(d[20]), "+f"(d[21]), "+f"(d[22]), "+f"(d[23]),
        "+f"(d[24]), "+f"(d[25]), "+f"(d[26]), "+f"(d[27]), "+f"(d[28]), "+f"(d[29]), "+f"(d[30]), "+f"(d[31]),
        "+f"(d[32]), "+f"(d[33]), "+f"(d[34]), "+f"(d[35]), "+f"(d[36]), "+f"(d[37]), "+f"(d[38]), "+f"(d[39]),
        "+f"(d[40]), "+f"(d[41]), "+f"(d[42]), "+f"(d[43]), "+f"(d[44]), "+f"(d[45]), "+f"(d[46]), "+f"(d[47]),
        "+f"(d[48]), "+f"(d[49]), "+f"(d[50]), "+f"(d[51]), "+f"(d[52]), "+f"(d[53]), "+f"(d[54]), "+f"(d[55]),
        "+f"(d[56]), "+f"(d[57]), "+f"(d[58]), "+f"(d[59]), "+f"(d[60]), "+f"(d[61]), "+f"(d[62]), "+f"(d[63])
        : "l"(da), "l"(db));
}
__device__ __forceinline__ void wgmma_ss_n96(float* d, uint64_t da, uint64_t db) {
    asm volatile("wgmma.mma_async.sync.aligned.m64n96k16.f32.bf16.bf16 {"
        "%0, %1, %2, %3, %4, %5, %6, %7, %8, %9, %10, %11, %12, %13, %14, %15,"
        "%16, %17, %18, %19, %20, %21, %22, %23, %24, %25, %26, %27, %28, %29, %30, %31,"
        "%32, %33, %34, %35, %36, %37, %38, %39, %40, %41, %42, %43, %44, %45, %46, %47}, %48, %49, 1, 1, 1, 0, 1;\n"
        :
        "+f"(d[0]), "+f"(d[1]), "+f"(d[2]), "+f"(d[3]), "+f"(d[4]), "+f"(d[5]), "+f"(d[6]), "+f"(d[7]),
        "+f"(d[8]), "+f"(d[9]), "+f"(d[10]), "+f"(d[11]), "+f"(d[12]), "+f"(d[13]), "+f"(d[14]), "+f"(d[15]),
        "+f"(d[16]), "+f"(d[17]), "+f"(d[18]), "+f"(d[19]), "+f"(d[20]), "+f"(d[21]), "+f"(d[22]), "+f"(d[23]),
        "+f"(d[24]), "+f"(d[25]), "+f"(d[26]), "+f"(d[27]), "+f"(d[28]), "+f"(d[29]), "+f"(d[30]), "+f"(d[31]),
        "+f"(d[32]), "+f"(d[33]), "+f"(d[34]), "+f"(d[35]), "+f"(d[36]), "+f"(d[37]), "+f"(d[38]), "+f"(d[39]),
        "+f"(d[40]), "+f"(d[41]), "+f"(d[42]), "+f"(d[43]), "+f"(d[44]), "+f"(d[45]), "+f"(d[46]), "+f"(d[47])
        : "l"(da), "l"(db));
}
__device__ __forceinline__ void wgmma_ss_n64(float* d, uint64_t da, uint64_t db) {
    asm volatile("wgmma.mma_async.sync.aligned.m64n64k16.f32.bf16.bf16 {"
        "%0, %1, %2, %3, %4, %5, %6, %7, %8, %9, %10, %11, %12, %13, %14, %15,"
        "%16, %17, %18, %19, %20, %21, %22, %23, %24, %25, %26, %27, %28, %29, %30, %31}, %32, %33, 1, 1, 1, 0, 1;\n"
        :
        "+f"(d[0]), "+f"(d[1]), "+f"(d[2]), "+f"(d[3]), "+f"(d[4]), "+f"(d[5]), "+f"(d[6]), "+f"(d[7]),
        "+f"(d[8]), "+f"(d[9]), "+f"(d[10]), "+f"(d[11]), "+f"(d[12]), "+f"(d[13]), "+f"(d[14]), "+f"(d[15]),
        "+f"(d[16]), "+f"(d[17]), "+f"(d[18]), "+f"(d[19]), "+f"(d[20]), "+f"(d[21]), "+f"(d[22]), "+f"(d[23]),
        "+f"(d[24]), "+f"(d[25]), "+f"(d[26]), "+f"(d[27]), "+f"(d[28]), "+f"(d[29]), "+f"(d[30]), "+f"(d[31])
        : "l"(da), "l"(db));
}
__device__ __forceinline__ void wgmma_qk_f16_acc(float* d, const uint32_t* a, uint64_t db) {
    asm volatile("wgmma.mma_async.sync.aligned.m64n64k16.f32.f16.f16 {"
        "%0, %1, %2, %3, %4, %5, %6, %7, %8, %9, %10, %11, %12, %13, %14, %15,"
        "%16, %17, %18, %19, %20, %21, %22, %23, %24, %25, %26, %27, %28, %29, %30, %31}, {%32, %33, %34, %35}, %36, 1, 1, 1, 0;\n"
        :
        "+f"(d[0]), "+f"(d[1]), "+f"(d[2]), "+f"(d[3]), "+f"(d[4]), "+f"(d[5]), "+f"(d[6]), "+f"(d[7]),
        "+f"(d[8]), "+f"(d[9]), "+f"(d[10]), "+f"(d[11]), "+f"(d[12]), "+f"(d[13]), "+f"(d[14]), "+f"(d[15]),
        "+f"(d[16]), "+f"(d[17]), "+f"(d[18]), "+f"(d[19]), "+f"(d[20]), "+f"(d[21]), "+f"(d[22]), "+f"(d[23]),
        "+f"(d[24]), "+f"(d[25]), "+f"(d[26]), "+f"(d[27]), "+f"(d[28]), "+f"(d[29]), "+f"(d[30]), "+f"(d[31])
        : "r"(a[0]), "r"(a[1]), "r"(a[2]), "r"(a[3]), "l"(db));
}
__device__ __forceinline__ void wgmma_qk_bf16_zero(float* d, const uint32_t* a, uint64_t db) {
    asm volatile("wgmma.mma_async.sync.aligned.m64n64k16.f32.bf16.bf16 {"
        "%0, %1, %2, %3, %4, %5, %6, %7, %8, %9, %10, %11, %12, %13, %14, %15,"
        "%16, %17, %18, %19, %20, %21, %22, %23, %24, %25, %26, %27, %28, %29, %30, %31}, {%32, %33, %34, %35}, %36, 0, 1, 1, 0;\n"
        :
        "=f"(d[0]), "=f"(d[1]), "=f"(d[2]), "=f"(d[3]), "=f"(d[4]), "=f"(d[5]), "=f"(d[6]), "=f"(d[7]),
        "=f"(d[8]), "=f"(d[9]), "=f"(d[10]), "=f"(d[11]), "=f"(d[12]), "=f"(d[13]), "=f"(d[14]), "=f"(d[15]),
        "=f"(d[16]), "=f"(d[17]), "=f"(d[18]), "=f"(d[19]), "=f"(d[20]), "=f"(d[21]), "=f"(d[22]), "=f"(d[23]),
        "=f"(d[24]), "=f"(d[25]), "=f"(d[26]), "=f"(d[27]), "=f"(d[28]), "=f"(d[29]), "=f"(d[30]), "=f"(d[31])
        : "r"(a[0]), "r"(a[1]), "r"(a[2]), "r"(a[3]), "l"(db));
}
__device__ __forceinline__ void wgmma_pv(float* d, const uint32_t* a, uint64_t db) {
    asm volatile("wgmma.mma_async.sync.aligned.m64n24k16.f32.bf16.bf16 {"
        "%0, %1, %2, %3, %4, %5, %6, %7, %8, %9, %10, %11}, {%12, %13, %14, %15}, %16, 1, 1, 1, 1;\n"
        :
        "+f"(d[0]), "+f"(d[1]), "+f"(d[2]), "+f"(d[3]), "+f"(d[4]), "+f"(d[5]), "+f"(d[6]), "+f"(d[7]),
        "+f"(d[8]), "+f"(d[9]), "+f"(d[10]), "+f"(d[11])
        : "r"(a[0]), "r"(a[1]), "r"(a[2]), "r"(a[3]), "l"(db));
}

template <int N> __device__ __forceinline__ void wgmma_ss(float* d, uint64_t a, uint64_t b) {
    if (N == 128) wgmma_ss_n128(d, a, b);
    if (N == 96) wgmma_ss_n96(d, a, b);
    if (N == 64) wgmma_ss_n64(d, a, b);
}

#define OFF_R 131072
#define OFF_ONE 229376
#define OFF_BAR 229888
#define OFF_BIAS (OFF_BAR + 736)
#define OFF_G (OFF_BIAS + 1152)
#define SMEM_BYTES (OFF_G + 272)
#define SBD 1024u
#define B_X 0
#define B_F1 416
#define B_E1 64
#define B_XD 672
#define B_KV 160
#define B_F2 224
#define B_E2 256
#define B_T 288
#define B_DONE 352
#define B_G 360
#define B_G2 368
#define B_G3 376
#define B_SF 384
#define B_BI 400
#define B_DONE2 112
#define B_SF2 408
#define NR 6

#define PF 1
#define PFX 0
#define PACE 1
#define FSER 1
#define EXP_FKK 4
#define QSCALE 0.36067376022224085f
#define MAGIC 445.41763f
#define NMUFU 4
#define VSTEP ((uint64_t)((long long)32 - ((long long)32 << 16)))

#define XMASK 0x0D55u
#define KVMASK 0x1D55u
__host__ __device__ constexpr int strm_pos(int pass, int i) {
    if (pass == 1 || pass == 2) return 8 + 8 * pass + i;
    int n = 0;
    for (int p = 0; p < 16; p++)
        if ((int)((KVMASK >> p) & 1) == (pass == 3)) { if (n == i) return p; n++; }
    return 0;
}
__host__ __device__ constexpr uint32_t strm_code(int pass) {
    uint32_t c = 0;
    for (int i = 0; i < 7; i++) c |= (uint32_t)(strm_pos(pass, i + 1) - strm_pos(pass, i)) << (4 * i);
    return c;
}

template <int N, int SUB, int KST, int LBO, int SBO, int SWZ>
__device__ __forceinline__ void gemm_pass(float* acc, uint32_t bar, uint64_t dA, int lane, uint32_t pos, uint32_t code, int barNext, bool waitx, bool last) {
    uint32_t prev = 0, slot = pos % NR;
#pragma unroll 1
    for (int i = 0; i < 8; i++) {
        if (waitx) mbar_wait(bar + B_X + 8 * i, 0);
        mbar_wait(bar + B_F1 + 8 * pos, 0);
        const uint64_t dB = mkdesc(SBD + OFF_R, LBO, SBO, SWZ) + slot * 1024;
        wg_fence();
        wgmma_ss<N>(acc, dA, dB);
        wgmma_ss<N>(acc, dA + 2, dB + KST / 16);
        wg_commit();
        wg_wait<1>();
        if (i > 0 && lane < 2) mbar_arrive_cluster(prev, lane);
        wgmma_ss<N>(acc, dA + 4, dB + SUB / 16);
        wgmma_ss<N>(acc, dA + 6, dB + (SUB + KST) / 16);
        wg_commit();
        prev = last ? bar + B_XD + 8 * i : bar + B_E1 + 8 * slot;
        pos += code & 15;
        slot += code & 15;
        if (slot >= NR) slot -= NR;
        code >>= 4;
        dA += 1024;
    }
    if (barNext) bar_arrive(barNext, 512);
    wg_wait<0>();
    if (lane < 2) mbar_arrive_cluster(prev, lane);
    pin<N / 2>(acc);
}

__device__ __forceinline__ uint32_t lds32(uint32_t a) { uint32_t v; asm volatile("ld.shared.u32 %0, [%1];" : "=r"(v) : "r"(a)); return v; }
__device__ __forceinline__ bool elect() {
    uint32_t p;
    asm volatile("{\n.reg .pred p;\nelect.sync _|p, 0xffffffff;\nselp.u32 %0, 1, 0, p;\n}" : "=r"(p));
    return p;
}

template <int G0, int G1> __device__ __forceinline__ void gelu_pack(const float* acc, uint32_t bias, uint32_t* out) {
#pragma unroll
    for (int G = G0; G < G1; G++) {
        uint32_t* o = out + 8 * G;
#pragma unroll
        for (int j = 0; j < 4; j++) {
            float bv[2];
            asm volatile("ld.shared.v2.f32 {%0, %1}, [%2];" : "=f"(bv[0]), "=f"(bv[1]) : "r"(bias + G * 128 + j * 32));
            float y[4];
#pragma unroll
            for (int i = 0; i < 4; i++) {
                const float h = acc[16 * G + 4 * j + i] + bv[i & 1];
                const float z = h * fmaf(h * h, 0.035677408136300125f, 0.7978845608028654f);
                y[i] = fmaf(h, tanhf_(z), h);
            }
            o[j] = pk_bf16(y[0], y[1]);
            o[4 + j] = pk_bf16(y[2], y[3]);
        }
    }
}

__device__ __forceinline__ float norm_bound(const float* v, float sc) {
    uint32_t m = 0;
#pragma unroll
    for (int h = 0; h < 4; h++) {
        const float* u = v + 8 * h;
        m = max(m, __float_as_uint(fmaf(u[0], u[0], fmaf(u[1], u[1], fmaf(u[4], u[4], u[5] * u[5])))));
        m = max(m, __float_as_uint(fmaf(u[2], u[2], fmaf(u[3], u[3], fmaf(u[6], u[6], u[7] * u[7])))));
    }
#pragma unroll
    for (int o = 4; o < 32; o <<= 1) m = max(m, __shfl_xor_sync(0xffffffffu, m, o));
    float f = __uint_as_float(m);
    f += __shfl_xor_sync(0xffffffffu, f, 1);
    f += __shfl_xor_sync(0xffffffffu, f, 2);
    return f * sc;
}

__device__ __forceinline__ uint32_t exp2_pair(float a, float b, uint32_t m1) {
    const uint32_t w = __byte_perm(__float_as_uint(a), __float_as_uint(b), 0x6521);
    uint32_t m, r;
    asm("lop3.b32 %0, %1, 0x007f007f, 0x9f809f80, 0xEA;" : "=r"(m) : "r"(w));
    const uint32_t e = w - m;
    asm("fma.rn.bf16x2 %0, %1, %2, %3;" : "=r"(r) : "r"(w), "r"(m), "r"(e));
    return r;
}

__device__ __forceinline__ void store_o(const float* o, uint4* dst, uint32_t par) {
    const float s0 = __fdividef(1.f, o[8]), s1 = __fdividef(1.f, o[10]);
    const uint32_t d0 = (pk_bf16(o[0] * s0, o[1] * s0) & ~1u) | par;
    asm volatile("{\n.reg .b128 t;\nmov.b128 t, {%0, %1, %2, %3};\nst.relaxed.gpu.global.b128 [%4], t;\n}" ::"r"(d0),
                 "r"(pk_bf16(o[4] * s0, o[5] * s0)), "r"(pk_bf16(o[2] * s1, o[3] * s1)), "r"(pk_bf16(o[6] * s1, o[7] * s1)), "l"(dst) : "memory");
}
__device__ __forceinline__ uint4 load_o(const uint4* src) {
    uint4 v;
    asm volatile("{\n.reg .b128 t;\nld.relaxed.gpu.global.b128 t, [%4];\nmov.b128 {%0, %1, %2, %3}, t;\n}"
                 : "=r"(v.x), "=r"(v.y), "=r"(v.z), "=r"(v.w) : "l"(src) : "memory");
    return v;
}
__device__ __forceinline__ uint32_t bmul2(uint32_t a, uint32_t b) { uint32_t r; asm("mul.rn.bf16x2 %0, %1, %2;" : "=r"(r) : "r"(a), "r"(b)); return r; }
__device__ __forceinline__ void sts32(uint32_t a, uint32_t v) { asm volatile("st.shared.u32 [%0], %1;" ::"r"(a), "r"(v) : "memory"); }
__device__ __forceinline__ void load_q(uint32_t* q, int h, int row, int t) {
    const uint8_t* p = gQ + (size_t)h * (SEQ * 32) + (size_t)row * 32 + t * 4;
    q[0] = __ldcg((const uint32_t*)p); q[1] = __ldcg((const uint32_t*)(p + 256));
    q[2] = __ldcg((const uint32_t*)(p + 16)); q[3] = __ldcg((const uint32_t*)(p + 272));
}

template <int NT>
__device__ __forceinline__ void proj16(float (*c)[8], const __nv_bfloat16* x, const __nv_bfloat16* w, int row0, int rstep, int col, int g, int t) {
#pragma unroll
    for (int i = 0; i < NT; i++)
#pragma unroll
        for (int j = 0; j < 8; j++) c[i][j] = 0.f;
    const unsigned short* wu = (const unsigned short*)w;
#pragma unroll 1
    for (int k = 0; k < DM; k += 16) {
        uint32_t b[4];
#pragma unroll
        for (int j = 0; j < 4; j++) {
            const int kr = k + 2 * t + (j & 1) * 8, cc = col + g + (j >> 1) * 8;
            b[j] = (uint32_t)wu[(size_t)kr * (3 * DM) + cc] | ((uint32_t)wu[(size_t)(kr + 1) * (3 * DM) + cc] << 16);
        }
#pragma unroll
        for (int i = 0; i < NT; i++) {
            const __nv_bfloat16* xp = x + (size_t)(row0 + i * rstep + g) * DM + k + 2 * t;
            const uint32_t a0 = *(const uint32_t*)xp, a1 = *(const uint32_t*)(xp + 8 * DM);
            const uint32_t a2 = *(const uint32_t*)(xp + 8), a3 = *(const uint32_t*)(xp + 8 * DM + 8);
#pragma unroll
            for (int j = 0; j < 2; j++)
                asm volatile("mma.sync.aligned.m16n8k16.row.col.f32.bf16.bf16.f32 {%0,%1,%2,%3}, {%4,%5,%6,%7}, {%8,%9}, {%0,%1,%2,%3};"
                             : "+f"(c[i][4 * j]), "+f"(c[i][4 * j + 1]), "+f"(c[i][4 * j + 2]), "+f"(c[i][4 * j + 3])
                             : "r"(a0), "r"(a1), "r"(a2), "r"(a3), "r"(b[2 * j]), "r"(b[2 * j + 1]));
        }
    }
}

struct Maps { CUtensorMap x, kv, q, f1, f3, h, w2, wo, hs, kvs; };

template <int I0, int I1>
__device__ __forceinline__ void issue_stream(const Maps& tm, uint32_t sb, uint32_t rank, int nb, int mb) {
    const uint32_t bar = sb + OFF_BAR;
    const uint32_t dst = sb + OFF_R;
    const int kr = rank * 32;
#pragma unroll
    for (int it = I0; it < I1; it++) {
        const int s = it % NR;
        const uint32_t fb = bar + B_F1 + 8 * it;
        if (it >= 24 + NR) mbar_wait(bar + B_XD + 8 * (it - 24 - NR), 0);
        else if (it >= NR) mbar_wait(bar + B_E1 + 8 * s, ((it / NR) - 1) & 1);
        const int nkv = __builtin_popcount(KVMASK & ((1u << it) - 1));
        if (it < 16 && ((KVMASK >> it) & 1)) {
            tma3d_mc(dst + s * 16384 + rank * 8192, &tm.kv, nb * 64, nkv * 64 + kr, 1, fb);
        } else if (it < 16) {
            tma3d_mc(dst + s * 16384 + rank * 6144, &tm.q, 0, (it - nkv) * 64 + kr, nb * 2, fb);
            tma3d_mc(dst + s * 16384 + rank * 6144 + 4096, &tm.f1, 0, (it - nkv) * 64 + kr, nb * 7, fb);
        } else {
            tma3d_mc(dst + s * 16384 + rank * 6144, &tm.f3, 0, (it & 7) * 64 + kr, nb * 7 + (it < 24 ? 1 : 4), fb);
        }
        if ((XMASK >> it) & 1) {
            const int xc = 1 + __builtin_popcount(XMASK & ((1u << it) - 1));
            tma2d(sb + xc * 16384, &tm.x, xc * 64, mb * 128, bar + B_X + 8 * xc);
        }
    }
}

__global__ void __cluster_dims__(2, 1, 1) __launch_bounds__(640, 1)
fused_kernel(const __grid_constant__ Maps tm, const __nv_bfloat16* __restrict__ x, const __nv_bfloat16* __restrict__ wqkv,
             const __nv_bfloat16* __restrict__ wo, const __nv_bfloat16* __restrict__ w1, const __nv_bfloat16* __restrict__ b1,
             const __nv_bfloat16* __restrict__ w2, const __nv_bfloat16* __restrict__ b2, const __nv_bfloat16* __restrict__ gate,
             __nv_bfloat16* __restrict__ out, const uint32_t m1) {
    const uint32_t sb = smem_u32(smem_raw);
    const uint32_t bar = sb + OFF_BAR;
    const int tid = threadIdx.x, lane = tid & 31;
    const int warp = __shfl_sync(0xffffffffu, tid >> 5, 0);
    const uint32_t rank = cluster_rank();
    const int cl = blockIdx.x >> 1;
    const int nb = cl & 7, mb = (cl >> 3) * 2 + rank;
    const int g = lane >> 2, t = lane & 3;

    const int cb = nb & 3, rb = mb * 2 + (nb >> 2);
    if (tid == 0) TLM(0, 0);
    TL_INIT();
    if (tid == 512) {
        for (int i = 0; i < 8; i++) { mbar_init(bar + B_X + 8 * i, 1); mbar_init(bar + B_KV + 8 * i, 1); mbar_init(bar + B_T + 8 * i, 5); mbar_init(bar + B_XD + 8 * i, 16); }
        for (int i = 0; i < NR; i++) mbar_init(bar + B_E1 + 8 * i, 16);
        for (int i = 0; i < 4; i++) { mbar_init(bar + B_F2 + 8 * i, 1); mbar_init(bar + B_E2 + 8 * i, 8); }
        asm volatile("fence.mbarrier_init.release.cluster;" ::: "memory");
    } else if (tid == 608) {
        for (int i = 0; i < 32; i++) mbar_init(bar + B_F1 + 8 * i, 1);
        mbar_init(bar + B_DONE, 16);
        mbar_init(bar + B_DONE2, 16);
        mbar_init(bar + B_G, 1);
        for (int i = 0; i < 3; i++) mbar_init(bar + B_SF + 8 * i, i == 1 ? 2 : 1);
        mbar_init(bar + B_SF2, 2);
        mbar_init(bar + B_G3, 1);
        mbar_init(bar + B_G2, 4);
        asm volatile("fence.mbarrier_init.release.cluster;" ::: "memory");
    }
    __syncwarp();
    asm volatile("barrier.cluster.arrive.relaxed.aligned;" ::: "memory");
    if (warp == 19) mbar_expect(bar + B_F1 + 8 * lane, ((KVMASK >> lane) & 1) ? 16384 : 12288);
    if (warp == 16 && lane < 24) mbar_expect(bar + (lane < 8 ? B_X : lane < 16 ? B_KV - 64 : B_T - 128) + 8 * lane, 16384);
    if (tid == 512) {
        tma2d(sb, &tm.x, 0, mb * 128, bar + B_X);
    } else if (tid == 544) {
        map_prefetch(&tm.kv);
        l2_prefetch((const uint8_t*)wqkv + (size_t)blockIdx.x * 3072, 3072);
        l2_prefetch((const uint8_t*)w1 + (size_t)blockIdx.x * 1792, 1792);
        map_prefetch(&tm.q); map_prefetch(&tm.f1); map_prefetch(&tm.f3);
    }
    if ((sb & 0xFFFFFF) != SBD) __trap();
    __syncwarp();
    asm volatile("barrier.cluster.wait.aligned;" ::: "memory");
    if (tid == 512) issue_stream<0, NR>(tm, sb, rank, nb, mb);
    if (tid == 0) { TLM(0, 1); TLC(0, 30); }

    if (warp < 16) {
        const int wg = warp >> 2;
        const int h = cl >> 1, qd = (cl & 1) * 2 + rank;
        uint32_t q[4];
        {
            const int w8 = warp & 7;
            const int T = mb * 8 + w8, row0 = T * 16 + g;
            const uint64_t dA0 = mkdesc(SBD + (wg & 1) * 8192, 16, 1024, 1);
            if (wg < 2) {
                float acc[64];
#pragma unroll
                for (int i = 0; i < 64; i++) acc[i] = 0.f;
                gemm_pass<128, 8192, 2048, 4096, 1024, 1>(acc, bar, dA0, lane, strm_pos(3, 0), strm_code(3), 0, true, false);
                if (tid == 0) TLM(0, 2);
                {
                    const float km = norm_bound(acc, 1.f);
                    float vm = 0.f;
#pragma unroll
                    for (int i = 32; i < 64; i++) vm = fmaxf(vm, fabsf(acc[i]));
                    vm = __uint_as_float(__reduce_max_sync(0xffffffffu, __float_as_uint(vm)));
                    if (lane == 0) { gN[1024 + nb * 128 + T] = km; gN[2048 + nb * 128 + T] = vm; }
                    const uint32_t kp = sb + OFF_R + 12288 + (w8 >> 2) * 1024 + g * 128 + ((((w8 & 3) * 2 + ((t >> 1) ^ (w8 >> 2))) ^ g) << 4) + (t & 1) * 8;
                    uint8_t* vp = gKV + (size_t)(nb * 4) * (SEQ * 64) + 65536 + (((T >> 6) * 16 + 2 * g) * 64 + (T & 63)) * 32 + ((t * 8) ^ ((w8 >> 2) << 4));
                    bar_sync(9, 256);
#pragma unroll
                    for (int hh = 0; hh < 4; hh++) {
                        const float* v = acc + 8 * hh;
                        float p0 = __shfl_up_sync(0xffffffffu, v[2], 4), p1 = __shfl_up_sync(0xffffffffu, v[3], 4);
                        float p2 = __shfl_up_sync(0xffffffffu, v[6], 4), p3 = __shfl_up_sync(0xffffffffu, v[7], 4);
                        if (g == 0) { p0 = p1 = p2 = p3 = 0.f; }
                        sts64(kp + hh * 16384, pk_f16(v[0] - p0, v[1] - p1), pk_f16(v[4] - p2, v[5] - p3));
                        sts64(kp + hh * 16384 + 2048, pk_f16(v[2] - v[0], v[3] - v[1]), pk_f16(v[6] - v[4], v[7] - v[5]));
                        const float* u = acc + 32 + 8 * hh;
                        if (hh < 2) {
                            sts64(kp + (4 + hh) * 16384, pk_bf16(u[0], u[1]), pk_bf16(u[4], u[5]));
                            sts64(kp + (4 + hh) * 16384 + 2048, pk_bf16(u[2], u[3]), pk_bf16(u[6], u[7]));
                        } else {
                            *(uint2*)(vp + (size_t)hh * (SEQ * 64)) = make_uint2(pk_bf16(u[0], u[1]), pk_bf16(u[4], u[5]));
                            *(uint2*)(vp + (size_t)hh * (SEQ * 64) + 2048) = make_uint2(pk_bf16(u[2], u[3]), pk_bf16(u[6], u[7]));
                        }
                    }
                }
                asm volatile("fence.proxy.async.shared::cta;" ::: "memory");
                bar_arrive(10, 288);
                if (tid == 0) TLM(0, 3);
            }
#pragma unroll 1
            for (int p = wg < 2 ? 1 : 0; p < 3; p += 2) {
                float acc[48];
#pragma unroll
                for (int i = 0; i < 48; i++) acc[i] = 0.f;
                pin<48>(acc);
                if (p) bar_sync(5 + p, 512);
                gemm_pass<96, 6144, 1024, 2048, 512, 2>(acc, bar, dA0, lane, p == 0 ? strm_pos(0, 0) : 8 + 8 * p, p == 0 ? strm_code(0) : strm_code(1), p < 2 ? 6 + p : 0, p == 0, p == 2);
                if ((tid & 255) == 0) TLM(0, 4 + 2 * p);
                const uint32_t hp = sb + OFF_R + (p == 2 ? 0 : 12288) + (wg & 1) * 16384 + ((warp & 3) * 16 + g) * 64 + t * 16;
                const uint32_t bp = sb + OFF_BIAS + p * 384 - 256 + t * 8;
                uint32_t ho[24];
                mbar_wait(bar + B_BI, 0);
                if (p == 0) {
                    const float qm = norm_bound(acc, QSCALE * QSCALE);
                    if (lane == 0) gN[nb * 128 + T] = qm;
                    uint8_t* qp = gQ + (size_t)(nb * 4) * (SEQ * 32) + (size_t)row0 * 32 + t * 8;
#pragma unroll
                    for (int hh = 0; hh < 4; hh++) {
                        const float* v = acc + 8 * hh;
                        *(uint2*)(qp + hh * (SEQ * 32)) = make_uint2(pk_f16(v[0] * QSCALE, v[1] * QSCALE), pk_f16(v[4] * QSCALE, v[5] * QSCALE));
                        *(uint2*)(qp + hh * (SEQ * 32) + 256) = make_uint2(pk_f16(v[2] * QSCALE, v[3] * QSCALE), pk_f16(v[6] * QSCALE, v[7] * QSCALE));
                    }
                    bar_arrive(12, 288);
                } else {
                    gelu_pack<0, 2>(acc, bp, ho);
                    pin<16>(ho);
                    mbar_wait(bar + B_G, 0);
                    load_q(q, h, qd * 512 + warp * 16 + g, t);
                }
                gelu_pack<2, 3>(acc, bp, ho);
                pin<8>(ho + 16);
                if (p == 2) bar_sync(9, 256);
                else mbar_wait(bar + B_SF + 8 * p, 0);
                if (p) {
#pragma unroll
                    for (int i = 0; i < 4; i++) sts128(hp + (i >> 1) * 32768 + (i & 1) * 512, ho + 4 * i);
                }
                sts128(hp + 65536, ho + 16);
                sts128(hp + 65536 + 512, ho + 20);
                asm volatile("fence.proxy.async.shared::cta;" ::: "memory");
                bar_arrive(p == 1 ? 14 : 11, 288);
                if ((tid & 255) == 0) TLM(0, 5 + 2 * p);
            }
        }
        uint32_t ep = 2;
        uint4* const op = gO + ((qd * 8 + wg) * NH + h) * 128 + (tid & 127);
        const uint64_t kd0 = mkdesc(SBD, 16, 256, 3);
        const uint64_t vd0 = mkdesc(SBD + 8192, OFF_ONE - 8192, 256, 3);
        {
            float o[12];
            uint32_t qn[4];
#pragma unroll 1
            for (int rh = 0; rh < 4; rh++) {
                if (rh == 1) {
                    mbar_wait(bar + B_G3, 0);
                    ep = lds32(sb + OFF_G + 256);
                    if (!(ep & 2)) break;
                    load_q(qn, h, qd * 512 + 256 + warp * 16 + g, t);
                }
                if (rh == 3 && lane == 0) mbar_arrive(bar + B_DONE);
                if (!(rh & 1)) {
#pragma unroll
                    for (int i = 0; i < 12; i++) o[i] = 0.f;
                }
                uint64_t kd = kd0 + (rh & 1) * 4096, vd = vd0 + (rh & 1) * (128 * VSTEP);
                uint32_t kvb = bar + B_KV + (rh & 1) * 32;
                float s[32];
#pragma unroll
                for (int i = 0; i < 32; i++) s[i] = i < 2 * NMUFU ? 0.f : MAGIC;
                if ((tid & 255) == 0) TLM(1, (tid >> 8) * 4 + rh);
#pragma unroll 1
                for (int c = 0; c < 4; c++) {
                    mbar_wait(kvb, 0);
                    kvb += 8;
#pragma unroll
                    for (int j = 0; j < 4; j++) {
                        uint32_t p[16];
                        wg_fence();
                        wgmma_qk_f16_acc(s, q, kd + j * 128);
                        wg_commit();
                        wg_wait<0>();
                        pin<32>(s);
#pragma unroll
                        for (int i = 0; i < 16; i++)
                            p[i] = i < NMUFU ? pk_bf16(ex2f(s[2 * i]), ex2f(s[2 * i + 1])) : exp2_pair(s[2 * i], s[2 * i + 1], m1);
                        pin<16>(p);
                        wg_fence();
#pragma unroll
                        for (int u = 0; u < 4; u++) wgmma_pv(o, p + 4 * u, vd + (j * 4 + u) * VSTEP);
                        wg_commit();
                    }
                    kd += 1024;
                    vd += 32 * VSTEP;
                }
                wg_wait<0>();
                pin<12>(o);
                if (rh & 1) {
                    if ((tid & 127) == 0 && rh == 3) TLM(1, 8 + wg);
                    store_o(o, op + (rh >> 1) * (4 * NH * 128), ep & 1);
#pragma unroll
                    for (int i = 0; i < 4; i++) q[i] = qn[i];
                }
            }
            if (tid == 0) { TLM(1, 12); TLC(0, 31); }
        }
        if (!(ep & 2)) {
            bar_sync(8, 512);
            for (int c = 0; c < 8; c++) mbar_wait(bar + B_KV + 8 * c, 0);
            {
                float kc[8][8];
                proj16<8>(kc, x, wqkv, warp * 16, 256, DM + h * 16, g, t);
#pragma unroll
                for (int i = 0; i < 8; i++) {
                    const int T = warp + i * 16;
                    const int pos = ((T >> 6) * 16 + 2 * g) * 64 + (T & 63);
                    const uint32_t a = sb + (pos >> 8) * 16384 + (pos & 255) * 32 + t * 4, sw = ((T >> 2) & 1) << 4;
                    asm volatile("st.shared.u32 [%0], %1;" ::"r"(a + sw), "r"(pk_bf16(kc[i][0], kc[i][1])) : "memory");
                    asm volatile("st.shared.u32 [%0], %1;" ::"r"(a + (sw ^ 16)), "r"(pk_bf16(kc[i][4], kc[i][5])) : "memory");
                    asm volatile("st.shared.u32 [%0], %1;" ::"r"(a + 2048 + sw), "r"(pk_bf16(kc[i][2], kc[i][3])) : "memory");
                    asm volatile("st.shared.u32 [%0], %1;" ::"r"(a + 2048 + (sw ^ 16)), "r"(pk_bf16(kc[i][6], kc[i][7])) : "memory");
                }
                asm volatile("fence.proxy.async.shared::cta;" ::: "memory");
                bar_sync(8, 512);
            }
#pragma unroll 1
            for (int r = 0; r < 2; r++) {
                const int row = qd * 512 + r * 256 + warp * 16 + g;
                {
                    float qc[1][8];
                    proj16<1>(qc, x, wqkv, row - g, 0, h * 16, g, t);
#pragma unroll
                    for (int i = 0; i < 4; i++) q[i] = pk_bf16(qc[0][2 * i] * QSCALE, qc[0][2 * i + 1] * QSCALE);
                }
                float o[12];
#pragma unroll
                for (int i = 0; i < 12; i++) o[i] = 0.f;
                float m0 = -INFINITY, m1 = -INFINITY;
#pragma unroll 1
                for (int j = 0; j < 32; j++) {
                    const uint64_t kd = kd0 + (j >> 2) * 1024 + (j & 3) * 128, vd = vd0 + ((j >> 2) * 32 + (j & 3) * 4) * VSTEP;
                    float s[32];
                    uint32_t p[16];
                    wg_fence();
                    wgmma_qk_bf16_zero(s, q, kd);
                    wg_commit();
                    wg_wait<0>();
                    pin<32>(s);
                    pin<12>(o);
                    float n0 = m0, n1 = m1;
#pragma unroll
                    for (int i = 0; i < 8; i++) {
                        n0 = fmaxf(n0, fmaxf(s[4 * i], s[4 * i + 1]));
                        n1 = fmaxf(n1, fmaxf(s[4 * i + 2], s[4 * i + 3]));
                    }
                    n0 = fmaxf(n0, __shfl_xor_sync(0xffffffffu, n0, 1));
                    n1 = fmaxf(n1, __shfl_xor_sync(0xffffffffu, n1, 1));
                    n0 = fmaxf(n0, __shfl_xor_sync(0xffffffffu, n0, 2));
                    n1 = fmaxf(n1, __shfl_xor_sync(0xffffffffu, n1, 2));
                    const float c0 = ex2f(m0 - n0), c1 = ex2f(m1 - n1);
                    m0 = n0;
                    m1 = n1;
#pragma unroll
                    for (int i = 0; i < 3; i++) { o[4 * i] *= c0; o[4 * i + 1] *= c0; o[4 * i + 2] *= c1; o[4 * i + 3] *= c1; }
#pragma unroll
                    for (int i = 0; i < 8; i++) {
                        p[2 * i] = pk_bf16(ex2f(s[4 * i] - m0), ex2f(s[4 * i + 1] - m0));
                        p[2 * i + 1] = pk_bf16(ex2f(s[4 * i + 2] - m1), ex2f(s[4 * i + 3] - m1));
                    }
                    pin<16>(p);
                    pin<12>(o);
                    wg_fence();
#pragma unroll
                    for (int u = 0; u < 4; u++) wgmma_pv(o, p + 4 * u, vd + u * VSTEP);
                    wg_commit();
                }
                wg_wait<0>();
                pin<12>(o);
                if (r == 1 && lane == 0) mbar_arrive(bar + B_DONE);
                store_o(o, op + r * (4 * NH * 128), ep & 1);
            }
        }
        if (lane == 0) mbar_arrive(bar + B_DONE2);
        {
            const uint4* src = gO + (rb * NH + wg * 8) * 128 + (tid & 127);
            uint4 v[8];
#pragma unroll
            for (int i = 0; i < 8; i++) v[i] = load_o(src + i * 128);
            mbar_wait(bar + B_DONE, 0);
            mbar_wait(bar + B_G2, 0);
            const int lr = (warp & 3) * 16 + g;
            const uint32_t g0 = lds32(sb + OFF_G + lr * 4), g1 = lds32(sb + OFF_G + lr * 4 + 32);
            const uint32_t a0 = sb + wg * 16384 + lr * 128 + (t >> 1) * 4;
#pragma unroll
            for (int i = 0; i < 8; i++) {
                if ((i & 3) == 0) {
                    int spins = 0;
                    while (__any_sync(0xffffffffu, (((v[i].x ^ ep) | (v[i + 1].x ^ ep) | (v[i + 2].x ^ ep) | (v[i + 3].x ^ ep)) & 1) != 0)) {
                        if (++spins > (1 << 22)) __trap();
#pragma unroll
                        for (int k = i; k < 8; k++)
                            if (((v[k].x ^ ep) & 1) != 0) v[k] = load_o(src + k * 128);
                    }
                }
                const uint32_t a = a0 + (i >> 2) * 8192 + ((((i & 3) * 2 + (t & 1)) ^ g) << 4);
                sts32(a, bmul2(v[i].x, g0));
                sts32(a + 8, bmul2(v[i].y, g0));
                sts32(a + 1024, bmul2(v[i].z, g1));
                sts32(a + 1024 + 8, bmul2(v[i].w, g1));
                if ((i & 3) == 3) {
                    asm volatile("fence.proxy.async.shared::cta;" ::: "memory");
                    __syncwarp();
                    if (lane == 0) mbar_arrive(bar + B_T + 8 * (wg * 2 + (i >> 2)));
                    if ((tid & 127) == 0) TLM(1, 20 + wg * 2 + (i >> 2));
                }
            }
        }
    } else {
        if (warp == 16) {
            if (lane == 0) {
                issue_stream<NR, 32>(tm, sb, rank, nb, mb);
                mbar_wait(bar + B_SF2, 0);
#pragma unroll
                for (int s = 0; s < 4; s++) {
                    mbar_expect(bar + B_F2 + 8 * s, 24576);
                    tma5d_mc(sb + OFF_R + s * 24576 + 8192 + rank * 8192, &tm.w2, cb * 128 + rank * 64, s * 2, bar + B_F2 + 8 * s);
                }
                cnt_wait(gCntH + mb * 32, epoch() * 8);
                asm volatile("fence.proxy.async.global;" ::: "memory");
                TLM(1, 13);
#pragma unroll
                for (int s = 0; s < 4; s++) tma2d(sb + OFF_R + s * 24576, &tm.h, s * 64, rb * 64, bar + B_F2 + 8 * s);
            }
        } else if (warp == 17) {
            {
                uint32_t bv[4], b2v[2];
#pragma unroll
                for (int i = 0; i < 4; i++) bv[i] = lane + 32 * i < 112 ? *(const uint32_t*)(b1 + nb * 224 + (lane + 32 * i) * 2) : 0;
#pragma unroll
                for (int i = 0; i < 2; i++) b2v[i] = *(const uint32_t*)(b2 + cb * 128 + (lane + 32 * i) * 2);
#pragma unroll
                for (int i = 0; i < 4; i++) {
                    sts32(sb + OFF_ONE + (lane + 32 * i) * 4, 0x3f803f80u);
                    if (lane + 32 * i < 112) sts64(sb + OFF_BIAS + (lane + 32 * i) * 8, bv[i] << 16, bv[i] & 0xffff0000u);
                }
#pragma unroll
                for (int i = 0; i < 2; i++) sts32(sb + OFF_BIAS + 896 + (lane + 32 * i) * 4, b2v[i]);
                asm volatile("fence.proxy.async.shared::cta;" ::: "memory");
                __syncwarp();
                if (lane == 0) mbar_arrive(bar + B_BI);
            }
            mbar_wait(bar + B_X + 8 * PFX, 0);
            if (lane == 0) {
                l2_prefetch((const uint8_t*)wqkv + 128 * 3072 + (size_t)blockIdx.x * 9216, 9216);
                l2_prefetch((const uint8_t*)w1 + (size_t)blockIdx.x * 14336, 14336);
            }
            mbar_wait(bar + B_X + 8 * 7, 0);
            if (lane == 0) {
                l2_prefetch((const uint8_t*)w2 + (size_t)blockIdx.x * 14336, 14336);
                l2_prefetch((const uint8_t*)wo + (size_t)blockIdx.x * 4096, 4096);
                map_prefetch(&tm.h); map_prefetch(&tm.w2); map_prefetch(&tm.wo); map_prefetch(&tm.hs); map_prefetch(&tm.kvs);
                TLM(0, 11);
            }
            bar_sync(10, 288);
            if (lane == 0) {
#pragma unroll 1
                for (int b = 5; b >= 0; b--) {
                    tma5d_st(&tm.kvs, sb + OFF_R + 12288 + b * 16384, (mb >> 3) * 8, (mb & 7) * 2, nb * 8 + (b < 4 ? 2 * b : 2 * b - 7));
                    asm volatile("cp.async.bulk.commit_group;\ncp.async.bulk.wait_group.read %0;" ::"n"(PACE) : "memory");
                    if (b == 4 - PACE) mbar_arrive(bar + B_SF);
                }
                asm volatile("cp.async.bulk.wait_group.read 0;" ::: "memory");
                mbar_arrive(bar + B_SF + 8);
            }
            __syncwarp();
            bar_sync(12, 288);
            if (lane == 0) {
                asm volatile("cp.async.bulk.wait_group 0;\nfence.proxy.async.global;" ::: "memory");
                cnt_add(gCntQ + nb * 32);
                TLM(0, 13);
            }
        } else {
            {
                const int r0 = mb * 128 + nb * 16 + (warp - 18) * 8;
                uint4 xv[16];
#pragma unroll
                for (int i = 0; i < 16; i++) xv[i] = *(const uint4*)(x + (size_t)(r0 + (i >> 1)) * DM + (i & 1) * 256 + lane * 8);
                const uint4 ga = *(const uint4*)(gate + lane * 8), gb = *(const uint4*)(gate + 256 + lane * 8);
                float z[8];
#pragma unroll
                for (int r = 0; r < 8; r++) z[r] = dot8(xv[2 * r], ga) + dot8(xv[2 * r + 1], gb);
#pragma unroll
                for (int w = 4; w >= 1; w >>= 1)
#pragma unroll
                    for (int r = 0; r < w; r++) {
                        const bool up = lane & w;
                        z[r] = (up ? z[r + w] : z[r]) + __shfl_xor_sync(0xffffffffu, up ? z[r] : z[r + w], w);
                    }
                z[0] += __shfl_xor_sync(0xffffffffu, z[0], 8);
                z[0] += __shfl_xor_sync(0xffffffffu, z[0], 16);
                if (lane < 8) gG[r0 + lane] = 1.f / (1.f + __expf(-z[0]));
                if (tid == 576) TLM(0, 12);
            }
            if (warp == 19) {
#pragma unroll 1
                for (int e = 0; e < 3; e++) {
                    bar_sync(e == 1 ? 14 : 11, 288);
                    if (lane == 0) {
#pragma unroll 1
                        for (int b = e == 0 ? 4 : 0; b < 6; b++) {
                            tma3d_st(&tm.hs, sb + OFF_R + (e == 2 ? 0 : 12288) + b * 16384, 0, mb * 128 + (b & 1) * 64, nb * 7 + e * 3 - 2 + (b >> 1));
                            asm volatile("cp.async.bulk.commit_group;\ncp.async.bulk.wait_group.read %0;" ::"n"(PACE) : "memory");
                        }
                        asm volatile("cp.async.bulk.wait_group.read 0;" ::: "memory");
                        if (e == 0) mbar_arrive(bar + B_SF + 8);
                        if (e == 2) { mbar_arrive_cluster(bar + B_SF2, 0); mbar_arrive_cluster(bar + B_SF2, 1); }
                    }
                    __syncwarp();
                }
                bar_sync(13, 64);
                if (lane == 0) {
                    asm volatile("cp.async.bulk.wait_group 0;\nfence.proxy.async.global;" ::: "memory");
                    cnt_add(gCntH + mb * 32);
                    TLM(0, 15);
                }
            } else {
                bar_arrive(13, 64);
                const int h = cl >> 1, qd = (cl & 1) * 2 + rank;
                const uint32_t ep = epoch();
                if (lane == 0) {
                    cnt_wait(gCntQ + (h >> 2) * 32, ep * 16);
                    mbar_arrive(bar + B_G);
                    TLM(0, 14);
                    asm volatile("fence.proxy.async.global;" ::: "memory");
#pragma unroll
                    for (int c = 0; c < 2; c++) {
                        mbar_wait(bar + B_XD + 8 * c, 0);
                        bulk_mc(sb + c * 16384 + rank * 8192, gKV + (size_t)h * (SEQ * 64) + rank * 65536 + c * 8192, 8192, bar + B_KV + 8 * c);
                    }
                }
                __syncwarp();
            const int hb = h >> 2;
            const uint4 kq = __ldcg((const uint4*)(gN + 1024 + hb * 128 + lane * 4));
            const uint4 vq = __ldcg((const uint4*)(gN + 2048 + hb * 128 + lane * 4));
            const float qq = ldcg_f(gN + hb * 128 + qd * 32 + lane);
            const float kf = __uint_as_float(__reduce_max_sync(0xffffffffu, max(max(kq.x, kq.y), max(kq.z, kq.w))));
            const float vf = __uint_as_float(__reduce_max_sync(0xffffffffu, max(max(vq.x, vq.y), max(vq.z, vq.w))));
            const float qf = __uint_as_float(__reduce_max_sync(0xffffffffu, __float_as_uint(qq)));
            if (lane == 0) {
                sts32(sb + OFF_G + 256, (ep & 1) | ((kf <= 1.0e6f) && (qf <= 1.0e6f) && (kf * qf <= 3400.f) && (vf <= 1.0e12f) ? 2 : 0));
                mbar_arrive(bar + B_G3);
                TLM(0, 16);
#pragma unroll
                for (int c = 2; c < 8; c++) {
                    mbar_wait(bar + B_XD + 8 * c, 0);
                    bulk_mc(sb + c * 16384 + rank * 8192, gKV + (size_t)h * (SEQ * 64) + rank * 65536 + c * 8192, 8192, bar + B_KV + 8 * c);
                }
                TLM(0, 10);
            }
            }
        }
        __syncwarp();
        float acc[64];
#pragma unroll
        for (int i = 0; i < 64; i++) acc[i] = 0.f;
#pragma unroll 1
        for (int io = 0; io < 7; io++) {
#pragma unroll
            for (int s = 0; s < 4; s++) {
                const int it = io * 4 + s;
                mbar_wait(bar + B_F2 + 8 * s, io & 1);
                if (tid == 512 && s == 0 && (io == 0 || io == 4)) TLM(1, 14 + io / 4);
                const uint64_t dA = mkdesc(SBD + OFF_R + s * 24576, 16, 1024, 1);
                const uint64_t dB = mkdesc(SBD + OFF_R + s * 24576 + 8192, 8192, 1024, 1);
                wg_fence();
#pragma unroll
                for (int kk = 0; kk < EXP_FKK; kk++) {
                    wgmma_ss_n128(acc, dA + kk * 2, dB + kk * 128);
                    if (kk < 3 && (FSER != 3 || kk == 1)) {
                        wg_commit();
                        wg_wait<0>();
                    }
                }
                wg_commit();
                if (warp < 18 && it >= 2 && it < 26) {
                    const int s2 = (s + 2) & 3;
                    mbar_wait(bar + B_E2 + 8 * s2, (io - (s < 2)) & 1);
                    if (elect()) {
                        if (warp == 16) {
                            mbar_expect(bar + B_F2 + 8 * s2, 24576);
                            tma5d_mc(sb + OFF_R + s2 * 24576 + 8192 + rank * 8192, &tm.w2, cb * 128 + rank * 64, it * 2 + 4, bar + B_F2 + 8 * s2);
                        } else {
                            asm volatile("fence.proxy.async.global;" ::: "memory");
                            tma2d(sb + OFF_R + s2 * 24576, &tm.h, it * 64 + 128, rb * 64, bar + B_F2 + 8 * s2);
                        }
                    }
                    __syncwarp();
                }
                wg_wait<1>();
                if (it >= 1 && lane < 2) mbar_arrive_cluster(bar + B_E2 + 8 * ((s + 3) & 3), lane);
            }
        }
        wg_wait<0>();
        if (lane < 2) mbar_arrive_cluster(bar + B_E2 + 8 * 3, lane);
        pin<64>(acc);
        if (tid == 576) gEpoch[blockIdx.x] = epoch();
        if (warp == 16) {
            if (lane == 0) TLM(1, 16);
            for (int s = 0; s < 4; s++) mbar_wait(bar + B_E2 + 8 * s, 0);
            if (elect()) {
#pragma unroll
                for (int i = 0; i < 6; i++) tma2d_mc(sb + OFF_R + i * 16384 + rank * 8192, &tm.wo, cb * 128 + rank * 64, i * 64, bar + B_T + 8 * i);
            }
            __syncwarp();
        }
        {
            const int lr = (warp - 16) * 16 + g;
            const uint32_t pa = pk_bf16(ldcg_f(gG + rb * 64 + lr), ldcg_f(gG + rb * 64 + lr + 8));
            if (t == 0) {
                sts32(sb + OFF_G + lr * 4, __byte_perm(pa, pa, 0x1010));
                sts32(sb + OFF_G + lr * 4 + 32, __byte_perm(pa, pa, 0x3232));
            }
            __syncwarp();
            if (lane == 0) mbar_arrive(bar + B_G2);
            const float ga = bf_lo(pa), gb = bf_hi(pa);
            const float g0 = 1.f - ga, g1 = 1.f - gb;
#pragma unroll
            for (int j = 0; j < 16; j++) {
                const uint32_t bv = lds32(sb + OFF_BIAS + 896 + j * 16 + t * 4);
                acc[4 * j] = fmaf(acc[4 * j], 0.5f, bf_lo(bv)) * g0;
                acc[4 * j + 1] = fmaf(acc[4 * j + 1], 0.5f, bf_hi(bv)) * g0;
                acc[4 * j + 2] = fmaf(acc[4 * j + 2], 0.5f, bf_lo(bv)) * g1;
                acc[4 * j + 3] = fmaf(acc[4 * j + 3], 0.5f, bf_hi(bv)) * g1;
            }
            pin<64>(acc);
        }
        if (warp == 17) {
            mbar_wait(bar + B_DONE2, 0);
            if (elect()) {
#pragma unroll
                for (int i = 0; i < 4; i++)
                    tma2d(sb + 65536 + i * 8192, &tm.wo, cb * 128 + (i & 1) * 64, (6 + (i >> 1)) * 64, bar + B_T + 8 * (6 + (i >> 1)));
            }
            __syncwarp();
        }
        if (tid == 512) TLM(1, 17);
#pragma unroll
        for (int i = 0; i < 8; i++) {
            mbar_wait(bar + B_T + 8 * i, 0);
            const uint64_t dA = mkdesc(SBD + i * 8192, 16, 1024, 1);
            const uint64_t dB = mkdesc(i < 6 ? SBD + OFF_R + i * 16384 : SBD + 65536 + (i - 6) * 16384, 8192, 1024, 1);
            wg_fence();
#pragma unroll
            for (int kk = 0; kk < 4; kk++) wgmma_ss_n128(acc, dA + kk * 2, dB + kk * 128);
            wg_commit();
        }
        wg_wait<0>();
        pin<64>(acc);
        if (tid == 512) TLM(1, 18);
        {
            const uint32_t st = sb + 98304 + (warp - 16) * 4352;
            const uint32_t wa = st + (lane & 15) * 272 + (lane >> 4) * 16;
#pragma unroll
            for (int j = 0; j < 8; j++)
                asm volatile("stmatrix.sync.aligned.m8n8.x4.shared.b16 [%0], {%1, %2, %3, %4};" ::"r"(wa + j * 32),
                             "r"(pk_bf16(acc[8 * j], acc[8 * j + 1])), "r"(pk_bf16(acc[8 * j + 2], acc[8 * j + 3])),
                             "r"(pk_bf16(acc[8 * j + 4], acc[8 * j + 5])), "r"(pk_bf16(acc[8 * j + 6], acc[8 * j + 7])) : "memory");
            __syncwarp();
            __nv_bfloat16* op = out + (size_t)(rb * 64 + (warp - 16) * 16 + (lane >> 4)) * DM + cb * 128 + (lane & 15) * 8;
#pragma unroll
            for (int j = 0; j < 8; j++) {
                uint4 v;
                asm volatile("ld.shared.v4.u32 {%0, %1, %2, %3}, [%4];" : "=r"(v.x), "=r"(v.y), "=r"(v.z), "=r"(v.w)
                             : "r"(st + (2 * j + (lane >> 4)) * 272 + (lane & 15) * 16));
                *(uint4*)(op + (size_t)j * 2 * DM) = v;
            }
        }
        if (tid == 512) TLM(1, 19);
        TL_DUMP();
    }
}

typedef CUresult (*EncodeFn)(CUtensorMap*, CUtensorMapDataType, cuuint32_t, void*, const cuuint64_t*, const cuuint64_t*, const cuuint32_t*,
                             const cuuint32_t*, CUtensorMapInterleave, CUtensorMapSwizzle, CUtensorMapL2promotion, CUtensorMapFloatOOBfill);

static void make_map(EncodeFn enc, CUtensorMap* m, const void* p, int rank, const cuuint64_t* dims, const cuuint64_t* strides,
                     const cuuint32_t* box, CUtensorMapSwizzle swz) {
    const cuuint32_t es[5] = {1, 1, 1, 1, 1};
    enc(m, CU_TENSOR_MAP_DATA_TYPE_BFLOAT16, rank, (void*)p, dims, strides, box, es, CU_TENSOR_MAP_INTERLEAVE_NONE, swz,
        CU_TENSOR_MAP_L2_PROMOTION_L2_128B, CU_TENSOR_MAP_FLOAT_OOB_FILL_NONE);
}

extern "C" void kernel_launch(void* const* d_in, const int* in_sizes, int n_in, void* d_out, int out_size) {
    const __nv_bfloat16* x = (const __nv_bfloat16*)d_in[0];
    const __nv_bfloat16* wqkv = (const __nv_bfloat16*)d_in[1];
    const __nv_bfloat16* wo = (const __nv_bfloat16*)d_in[2];
    const __nv_bfloat16* w1 = (const __nv_bfloat16*)d_in[4];
    const __nv_bfloat16* b1 = (const __nv_bfloat16*)d_in[5];
    const __nv_bfloat16* w2 = (const __nv_bfloat16*)d_in[6];
    const __nv_bfloat16* b2 = (const __nv_bfloat16*)d_in[7];
    const __nv_bfloat16* gate = (const __nv_bfloat16*)d_in[8];

    void* fp = nullptr;
    cudaDriverEntryPointQueryResult qr;
    cudaGetDriverEntryPoint("cuTensorMapEncodeTiled", &fp, cudaEnableDefault, &qr);
    EncodeFn enc = (EncodeFn)fp;
    void *pH, *pKV;
    cudaGetSymbolAddress(&pH, gH);
    cudaGetSymbolAddress(&pKV, gKV);

    Maps tm;
    const CUtensorMapSwizzle S128 = CU_TENSOR_MAP_SWIZZLE_128B, S64 = CU_TENSOR_MAP_SWIZZLE_64B;
    { cuuint64_t d[2] = {DM, SEQ}, s[1] = {DM * 2}; cuuint32_t b[2] = {64, 128}; make_map(enc, &tm.x, x, 2, d, s, b, S128); }
    { cuuint64_t d[3] = {DM, DM, 3}, s[2] = {3 * DM * 2, DM * 2}; cuuint32_t b[3] = {64, 32, 2}; make_map(enc, &tm.kv, wqkv, 3, d, s, b, S128); }
    { cuuint64_t d[3] = {32, DM, 3 * DM / 32}, s[2] = {3 * DM * 2, 64}; cuuint32_t b[3] = {32, 32, 2}; make_map(enc, &tm.q, wqkv, 3, d, s, b, S64); }
    { cuuint64_t d[3] = {32, DM, FF / 32}, s[2] = {FF * 2, 64}; cuuint32_t b[3] = {32, 32, 1}; make_map(enc, &tm.f1, w1, 3, d, s, b, S64); }
    { cuuint64_t d[3] = {32, DM, FF / 32}, s[2] = {FF * 2, 64}; cuuint32_t b[3] = {32, 32, 3}; make_map(enc, &tm.f3, w1, 3, d, s, b, S64); }
    { cuuint64_t d[2] = {FF, SEQ}, s[1] = {FF * 2}; cuuint32_t b[2] = {64, 64}; make_map(enc, &tm.h, pH, 2, d, s, b, S128); }
    { cuuint64_t d[5] = {DM, 2, 4, 4, FF / 32}, s[4] = {1024, 8 * 1024, 2 * 1024, 32 * 1024}; cuuint32_t b[5] = {64, 2, 4, 4, 2};
      make_map(enc, &tm.w2, w2, 5, d, s, b, S128); }
    { cuuint64_t d[2] = {DM, DM}, s[1] = {DM * 2}; cuuint32_t b[2] = {64, 64}; make_map(enc, &tm.wo, wo, 2, d, s, b, S128); }

    { cuuint64_t d[3] = {32, SEQ, FF / 32}, s[2] = {FF * 2, 64}; cuuint32_t b[3] = {32, 64, 1}; make_map(enc, &tm.hs, pH, 3, d, s, b, CU_TENSOR_MAP_SWIZZLE_NONE); }
    { cuuint64_t d[5] = {64, 16, 16, 2, 2 * NH}, s[4] = {4096, 128, 2048, 65536}; cuuint32_t b[5] = {64, 8, 2, 2, 1};
      make_map(enc, &tm.kvs, pKV, 5, d, s, b, S128); }
    cudaFuncSetAttribute(fused_kernel, cudaFuncAttributeMaxDynamicSharedMemorySize, TL_SMEM);
    fused_kernel<<<128, 640, TL_SMEM, cudaStreamPerThread>>>(tm, x, wqkv, wo, w1, b1, w2, b2, gate, (__nv_bfloat16*)d_out, 0xffffffffu);
}
```

```cpp
#include <cuda_runtime.h>
#include <cuda_bf16.h>
#include <cuda_fp16.h>
#include <cuda.h>
#include <stdint.h>

#define SEQ 2048
#define DM 512
#define FF 1792
#define NH 32

__device__ __align__(1024) uint8_t gQ[NH * SEQ * 32];
__device__ __align__(1024) uint8_t gKV[NH * SEQ * 64];
__device__ __align__(1024) __nv_bfloat16 gH[SEQ * FF];
__device__ __align__(1024) uint4 gO[32 * NH * 128];
__device__ float gG[SEQ];
__device__ float gN[3 * 8 * 128];
__device__ unsigned int gCntQ[8 * 32];
__device__ unsigned int gCntH[32 * 32];
__device__ unsigned int gEpoch[128];

__device__ __forceinline__ uint32_t smem_u32(const void* p) { return (uint32_t)__cvta_generic_to_shared(p); }
__device__ __forceinline__ void mbar_init(uint32_t a, uint32_t c) { asm volatile("mbarrier.init.shared::cta.b64 [%0], %1;" ::"r"(a), "r"(c)); }
__device__ __forceinline__ void mbar_expect(uint32_t a, uint32_t b) { asm volatile("mbarrier.arrive.expect_tx.shared::cta.b64 _, [%0], %1;" ::"r"(a), "r"(b) : "memory"); }
__device__ __forceinline__ void mbar_arrive(uint32_t a) { asm volatile("mbarrier.arrive.shared::cta.b64 _, [%0];" ::"r"(a) : "memory"); }
__device__ __forceinline__ void mbar_wait(uint32_t a, uint32_t ph) {
    asm volatile("{\n.reg .pred p;\n.reg .u32 n;\nmov.u32 n, 0;\nW_%=:\nmbarrier.try_wait.parity.shared::cta.b64 p, [%0], %1;\n@p bra D_%=;\n"
                 "add.u32 n, n, 1;\nsetp.lt.u32 p, n, 0x400000;\n@p bra W_%=;\ntrap;\nD_%=:\n}" ::"r"(a), "r"(ph) : "memory");
}
__device__ __forceinline__ void mbar_arrive_cluster(uint32_t a, uint32_t cta) {
    asm volatile("{\n.reg .b32 r;\nmapa.shared::cluster.u32 r, %0, %1;\nmbarrier.arrive.shared::cluster.b64 _, [r];\n}" ::"r"(a), "r"(cta) : "memory");
}
__device__ __forceinline__ void bar_sync(int id, int n) { asm volatile("bar.sync %0, %1;" ::"r"(id), "r"(n) : "memory"); }
__device__ __forceinline__ void bar_arrive(int id, int n) { asm volatile("bar.arrive %0, %1;" ::"r"(id), "r"(n) : "memory"); }
__device__ __forceinline__ uint32_t cluster_rank() { uint32_t r; asm("mov.u32 %0, %%cluster_ctarank;" : "=r"(r)); return r; }
__device__ __forceinline__ void cnt_add(unsigned int* c) { asm volatile("red.release.gpu.global.add.u32 [%0], 1;" ::"l"(c) : "memory"); }
__device__ __forceinline__ void cnt_wait(const unsigned int* c, uint32_t target) {
    uint32_t v;
    int spins = 0;
    while (true) {
        asm volatile("ld.acquire.gpu.global.u32 %0, [%1];" : "=r"(v) : "l"(c) : "memory");
        if ((int)(v - target) >= 0) break;
        if (++spins > (1 << 22)) __trap();
        __nanosleep(40);
    }
}
__device__ __forceinline__ void tma2d(uint32_t dst, const CUtensorMap* m, int c0, int c1, uint32_t bar) {
    asm volatile("cp.async.bulk.tensor.2d.shared::cluster.global.mbarrier::complete_tx::bytes [%0], [%1, {%3, %4}], [%2];"
                 ::"r"(dst), "l"(m), "r"(bar), "r"(c0), "r"(c1) : "memory");
}
__device__ __forceinline__ void tma2d_mc(uint32_t dst, const CUtensorMap* m, int c0, int c1, uint32_t bar) {
    asm volatile("cp.async.bulk.tensor.2d.shared::cluster.global.mbarrier::complete_tx::bytes.multicast::cluster [%0], [%1, {%3, %4}], [%2], %5;"
                 ::"r"(dst), "l"(m), "r"(bar), "r"(c0), "r"(c1), "h"((uint16_t)3) : "memory");
}
__device__ __forceinline__ void tma3d_mc(uint32_t dst, const CUtensorMap* m, int c0, int c1, int c2, uint32_t bar) {
    asm volatile("cp.async.bulk.tensor.3d.shared::cluster.global.mbarrier::complete_tx::bytes.multicast::cluster [%0], [%1, {%3, %4, %5}], [%2], %6;"
                 ::"r"(dst), "l"(m), "r"(bar), "r"(c0), "r"(c1), "r"(c2), "h"((uint16_t)3) : "memory");
}
__device__ __forceinline__ void tma5d_mc(uint32_t dst, const CUtensorMap* m, int c0, int c4, uint32_t bar) {
    asm volatile("cp.async.bulk.tensor.5d.shared::cluster.global.mbarrier::complete_tx::bytes.multicast::cluster [%0], [%1, {%3, %5, %5, %5, %4}], [%2], %6;"
                 ::"r"(dst), "l"(m), "r"(bar), "r"(c0), "r"(c4), "r"(0), "h"((uint16_t)3) : "memory");
}
__device__ __forceinline__ void bulk_mc(uint32_t dst, const void* src, uint32_t bytes, uint32_t bar) {
    asm volatile("cp.async.bulk.shared::cluster.global.mbarrier::complete_tx::bytes.multicast::cluster [%0], [%1], %2, [%3], %4;"
                 ::"r"(dst), "l"(src), "r"(bytes), "r"(bar), "h"((uint16_t)3) : "memory");
}
__device__ __forceinline__ void tma3d_st(const CUtensorMap* m, uint32_t src, int c0, int c1, int c2) {
    asm volatile("cp.async.bulk.tensor.3d.global.shared::cta.bulk_group [%0, {%2, %3, %4}], [%1];" ::"l"(m), "r"(src), "r"(c0), "r"(c1), "r"(c2) : "memory");
}
__device__ __forceinline__ void tma5d_st(const CUtensorMap* m, uint32_t src, int c1, int c2, int c4) {
    asm volatile("cp.async.bulk.tensor.5d.global.shared::cta.bulk_group [%0, {%5, %2, %3, %5, %4}], [%1];"
                 ::"l"(m), "r"(src), "r"(c1), "r"(c2), "r"(c4), "r"(0) : "memory");
}
__device__ __forceinline__ void bulk_st(void* dst, uint32_t src, uint32_t bytes) {
    asm volatile("cp.async.bulk.global.shared::cta.bulk_group [%0], [%1], %2;" ::"l"(dst), "r"(src), "r"(bytes) : "memory");
}
__device__ __forceinline__ void sts64(uint32_t a, uint32_t x, uint32_t y) { asm volatile("st.shared.v2.u32 [%0], {%1, %2};" ::"r"(a), "r"(x), "r"(y) : "memory"); }
__device__ __forceinline__ void sts128(uint32_t a, const uint32_t* v) {
    asm volatile("st.shared.v4.u32 [%0], {%1, %2, %3, %4};" ::"r"(a), "r"(v[0]), "r"(v[1]), "r"(v[2]), "r"(v[3]) : "memory");
}
__device__ __forceinline__ void l2_prefetch(const void* src, uint32_t bytes) {
    asm volatile("cp.async.bulk.prefetch.L2.global [%0], %1;" ::"l"(src), "r"(bytes) : "memory");
}
__device__ __forceinline__ void map_prefetch(const CUtensorMap* m) { asm volatile("prefetch.tensormap [%0];" ::"l"(m) : "memory"); }
__device__ __forceinline__ void wg_fence() { asm volatile("wgmma.fence.sync.aligned;" ::: "memory"); }
__device__ __forceinline__ void wg_commit() { asm volatile("wgmma.commit_group.sync.aligned;" ::: "memory"); }
template <int N> __device__ __forceinline__ void wg_wait() { asm volatile("wgmma.wait_group.sync.aligned %0;" ::"n"(N) : "memory"); }
template <int N> __device__ __forceinline__ void pin(float* s) {
#pragma unroll
    for (int i = 0; i < N; i++) asm volatile("" : "+f"(s[i])::"memory");
}
template <int N> __device__ __forceinline__ void pin(uint32_t* s) {
#pragma unroll
    for (int i = 0; i < N; i++) asm volatile("" : "+r"(s[i])::"memory");
}
__device__ __forceinline__ uint64_t mkdesc(uint32_t addr, uint32_t lbo, uint32_t sbo, uint32_t swz) {
    return (uint64_t)((addr & 0x3FFFF) >> 4) | ((uint64_t)(lbo >> 4) << 16) | ((uint64_t)(sbo >> 4) << 32) | ((uint64_t)swz << 62);
}
__device__ __forceinline__ float ex2f(float x) { float y; asm("ex2.approx.ftz.f32 %0, %1;" : "=f"(y) : "f"(x)); return y; }
__device__ __forceinline__ float tanhf_(float x) { float y; asm("tanh.approx.f32 %0, %1;" : "=f"(y) : "f"(x)); return y; }
__device__ __forceinline__ uint32_t pk_bf16(float lo, float hi) { uint32_t r; asm("cvt.rn.bf16x2.f32 %0, %1, %2;" : "=r"(r) : "f"(hi), "f"(lo)); return r; }
__device__ __forceinline__ uint32_t pk_f16(float lo, float hi) { uint32_t r; asm("cvt.rn.f16x2.f32 %0, %1, %2;" : "=r"(r) : "f"(hi), "f"(lo)); return r; }
__device__ __forceinline__ float bf_lo(uint32_t v) { return __uint_as_float(v << 16); }
__device__ __forceinline__ float bf_hi(uint32_t v) { return __uint_as_float(v & 0xffff0000u); }
__device__ __forceinline__ float dot8(const uint4& a, const uint4& b) {
    return fmaf(bf_lo(a.x), bf_lo(b.x), fmaf(bf_hi(a.x), bf_hi(b.x), fmaf(bf_lo(a.y), bf_lo(b.y), bf_hi(a.y) * bf_hi(b.y)))) +
           fmaf(bf_lo(a.z), bf_lo(b.z), fmaf(bf_hi(a.z), bf_hi(b.z), fmaf(bf_lo(a.w), bf_lo(b.w), bf_hi(a.w) * bf_hi(b.w))));
}
__device__ __forceinline__ uint32_t epoch() {
    uint32_t v;
    asm volatile("ld.global.u32 %0, [%1];" : "=r"(v) : "l"(gEpoch + blockIdx.x));
    return v + 1;
}
__device__ __forceinline__ float ldcg_f(const float* p) { return __ldcg(p); }

extern __shared__ __align__(1024) uint8_t smem_raw[];
#define TLM(k, slot) do {} while (0)
#define TLC(k, slot) do {} while (0)
#define TL_INIT() do {} while (0)
#define TL_DUMP() do {} while (0)
#define TL_SMEM SMEM_BYTES

__device__ __forceinline__ void wgmma_ss_n128(float* d, uint64_t da, uint64_t db) {
    asm volatile("wgmma.mma_async.sync.aligned.m64n128k16.f32.bf16.bf16 {"
        "%0, %1, %2, %3, %4, %5, %6, %7, %8, %9, %10, %11, %12, %13, %14, %15,"
        "%16, %17, %18, %19, %20, %21, %22, %23, %24, %25, %26, %27, %28, %29, %30, %31,"
        "%32, %33, %34, %35, %36, %37, %38, %39, %40, %41, %42, %43, %44, %45, %46, %47,"
        "%48, %49, %50, %51, %52, %53, %54, %55, %56, %57, %58, %59, %60, %61, %62, %63}, %64, %65, 1, 1, 1, 0, 1;\n"
        :
        "+f"(d[0]), "+f"(d[1]), "+f"(d[2]), "+f"(d[3]), "+f"(d[4]), "+f"(d[5]), "+f"(d[6]), "+f"(d[7]),
        "+f"(d[8]), "+f"(d[9]), "+f"(d[10]), "+f"(d[11]), "+f"(d[12]), "+f"(d[13]), "+f"(d[14]), "+f"(d[15]),
        "+f"(d[16]), "+f"(d[17]), "+f"(d[18]), "+f"(d[19]), "+f"(d[20]), "+f"(d[21]), "+f"(d[22]), "+f"(d[23]),
        "+f"(d[24]), "+f"(d[25]), "+f"(d[26]), "+f"(d[27]), "+f"(d[28]), "+f"(d[29]), "+f"(d[30]), "+f"(d[31]),
        "+f"(d[32]), "+f"(d[33]), "+f"(d[34]), "+f"(d[35]), "+f"(d[36]), "+f"(d[37]), "+f"(d[38]), "+f"(d[39]),
        "+f"(d[40]), "+f"(d[41]), "+f"(d[42]), "+f"(d[43]), "+f"(d[44]), "+f"(d[45]), "+f"(d[46]), "+f"(d[47]),
        "+f"(d[48]), "+f"(d[49]), "+f"(d[50]), "+f"(d[51]), "+f"(d[52]), "+f"(d[53]), "+f"(d[54]), "+f"(d[55]),
        "+f"(d[56]), "+f"(d[57]), "+f"(d[58]), "+f"(d[59]), "+f"(d[60]), "+f"(d[61]), "+f"(d[62]), "+f"(d[63])
        : "l"(da), "l"(db));
}
__device__ __forceinline__ void wgmma_ss_n96(float* d, uint64_t da, uint64_t db) {
    asm volatile("wgmma.mma_async.sync.aligned.m64n96k16.f32.bf16.bf16 {"
        "%0, %1, %2, %3, %4, %5, %6, %7, %8, %9, %10, %11, %12, %13, %14, %15,"
        "%16, %17, %18, %19, %20, %21, %22, %23, %24, %25, %26, %27, %28, %29, %30, %31,"
        "%32, %33, %34, %35, %36, %37, %38, %39, %40, %41, %42, %43, %44, %45, %46, %47}, %48, %49, 1, 1, 1, 0, 1;\n"
        :
        "+f"(d[0]), "+f"(d[1]), "+f"(d[2]), "+f"(d[3]), "+f"(d[4]), "+f"(d[5]), "+f"(d[6]), "+f"(d[7]),
        "+f"(d[8]), "+f"(d[9]), "+f"(d[10]), "+f"(d[11]), "+f"(d[12]), "+f"(d[13]), "+f"(d[14]), "+f"(d[15]),
        "+f"(d[16]), "+f"(d[17]), "+f"(d[18]), "+f"(d[19]), "+f"(d[20]), "+f"(d[21]), "+f"(d[22]), "+f"(d[23]),
        "+f"(d[24]), "+f"(d[25]), "+f"(d[26]), "+f"(d[27]), "+f"(d[28]), "+f"(d[29]), "+f"(d[30]), "+f"(d[31]),
        "+f"(d[32]), "+f"(d[33]), "+f"(d[34]), "+f"(d[35]), "+f"(d[36]), "+f"(d[37]), "+f"(d[38]), "+f"(d[39]),
        "+f"(d[40]), "+f"(d[41]), "+f"(d[42]), "+f"(d[43]), "+f"(d[44]), "+f"(d[45]), "+f"(d[46]), "+f"(d[47])
        : "l"(da), "l"(db));
}
__device__ __forceinline__ void wgmma_ss_n64(float* d, uint64_t da, uint64_t db) {
    asm volatile("wgmma.mma_async.sync.aligned.m64n64k16.f32.bf16.bf16 {"
        "%0, %1, %2, %3, %4, %5, %6, %7, %8, %9, %10, %11, %12, %13, %14, %15,"
        "%16, %17, %18, %19, %20, %21, %22, %23, %24, %25, %26, %27, %28, %29, %30, %31}, %32, %33, 1, 1, 1, 0, 1;\n"
        :
        "+f"(d[0]), "+f"(d[1]), "+f"(d[2]), "+f"(d[3]), "+f"(d[4]), "+f"(d[5]), "+f"(d[6]), "+f"(d[7]),
        "+f"(d[8]), "+f"(d[9]), "+f"(d[10]), "+f"(d[11]), "+f"(d[12]), "+f"(d[13]), "+f"(d[14]), "+f"(d[15]),
        "+f"(d[16]), "+f"(d[17]), "+f"(d[18]), "+f"(d[19]), "+f"(d[20]), "+f"(d[21]), "+f"(d[22]), "+f"(d[23]),
        "+f"(d[24]), "+f"(d[25]), "+f"(d[26]), "+f"(d[27]), "+f"(d[28]), "+f"(d[29]), "+f"(d[30]), "+f"(d[31])
        : "l"(da), "l"(db));
}
__device__ __forceinline__ void wgmma_qk_f16_acc(float* d, const uint32_t* a, uint64_t db) {
    asm volatile("wgmma.mma_async.sync.aligned.m64n64k16.f32.f16.f16 {"
        "%0, %1, %2, %3, %4, %5, %6, %7, %8, %9, %10, %11, %12, %13, %14, %15,"
        "%16, %17, %18, %19, %20, %21, %22, %23, %24, %25, %26, %27, %28, %29, %30, %31}, {%32, %33, %34, %35}, %36, 1, 1, 1, 0;\n"
        :
        "+f"(d[0]), "+f"(d[1]), "+f"(d[2]), "+f"(d[3]), "+f"(d[4]), "+f"(d[5]), "+f"(d[6]), "+f"(d[7]),
        "+f"(d[8]), "+f"(d[9]), "+f"(d[10]), "+f"(d[11]), "+f"(d[12]), "+f"(d[13]), "+f"(d[14]), "+f"(d[15]),
        "+f"(d[16]), "+f"(d[17]), "+f"(d[18]), "+f"(d[19]), "+f"(d[20]), "+f"(d[21]), "+f"(d[22]), "+f"(d[23]),
        "+f"(d[24]), "+f"(d[25]), "+f"(d[26]), "+f"(d[27]), "+f"(d[28]), "+f"(d[29]), "+f"(d[30]), "+f"(d[31])
        : "r"(a[0]), "r"(a[1]), "r"(a[2]), "r"(a[3]), "l"(db));
}
__device__ __forceinline__ void wgmma_qk_bf16_zero(float* d, const uint32_t* a, uint64_t db) {
    asm volatile("wgmma.mma_async.sync.aligned.m64n64k16.f32.bf16.bf16 {"
        "%0, %1, %2, %3, %4, %5, %6, %7, %8, %9, %10, %11, %12, %13, %14, %15,"
        "%16, %17, %18, %19, %20, %21, %22, %23, %24, %25, %26, %27, %28, %29, %30, %31}, {%32, %33, %34, %35}, %36, 0, 1, 1, 0;\n"
        :
        "=f"(d[0]), "=f"(d[1]), "=f"(d[2]), "=f"(d[3]), "=f"(d[4]), "=f"(d[5]), "=f"(d[6]), "=f"(d[7]),
        "=f"(d[8]), "=f"(d[9]), "=f"(d[10]), "=f"(d[11]), "=f"(d[12]), "=f"(d[13]), "=f"(d[14]), "=f"(d[15]),
        "=f"(d[16]), "=f"(d[17]), "=f"(d[18]), "=f"(d[19]), "=f"(d[20]), "=f"(d[21]), "=f"(d[22]), "=f"(d[23]),
        "=f"(d[24]), "=f"(d[25]), "=f"(d[26]), "=f"(d[27]), "=f"(d[28]), "=f"(d[29]), "=f"(d[30]), "=f"(d[31])
        : "r"(a[0]), "r"(a[1]), "r"(a[2]), "r"(a[3]), "l"(db));
}
__device__ __forceinline__ void wgmma_pv(float* d, const uint32_t* a, uint64_t db) {
    asm volatile("wgmma.mma_async.sync.aligned.m64n24k16.f32.bf16.bf16 {"
        "%0, %1, %2, %3, %4, %5, %6, %7, %8, %9, %10, %11}, {%12, %13, %14, %15}, %16, 1, 1, 1, 1;\n"
        :
        "+f"(d[0]), "+f"(d[1]), "+f"(d[2]), "+f"(d[3]), "+f"(d[4]), "+f"(d[5]), "+f"(d[6]), "+f"(d[7]),
        "+f"(d[8]), "+f"(d[9]), "+f"(d[10]), "+f"(d[11])
        : "r"(a[0]), "r"(a[1]), "r"(a[2]), "r"(a[3]), "l"(db));
}

template <int N> __device__ __forceinline__ void wgmma_ss(float* d, uint64_t a, uint64_t b) {
    if (N == 128) wgmma_ss_n128(d, a, b);
    if (N == 96) wgmma_ss_n96(d, a, b);
    if (N == 64) wgmma_ss_n64(d, a, b);
}

#define OFF_R 131072
#define OFF_ONE 229376
#define OFF_BAR 229888
#define OFF_BIAS (OFF_BAR + 736)
#define OFF_G (OFF_BIAS + 1152)
#define SMEM_BYTES (OFF_G + 272)
#define SBD 1024u
#define B_X 0
#define B_F1 416
#define B_E1 64
#define B_XD 672
#define B_KV 160
#define B_F2 224
#define B_E2 256
#define B_T 288
#define B_DONE 352
#define B_G 360
#define B_G2 368
#define B_G3 376
#define B_SF 384
#define B_BI 400
#define B_DONE2 112
#define B_SF2 408
#define NR 6

#define PF 1
#define PFX 0
#define PACE 1
#define FSER 1
#define MERGE 1
#define EXP_FKK 4
#define QSCALE 0.36067376022224085f
#define MAGIC 445.41763f
#define FORCE_IMAD
#define NMUFU 5
#define VSTEP ((uint64_t)((long long)32 - ((long long)32 << 16)))

#define XMASK 0x0D55u
#define KVMASK 0x1D55u
__host__ __device__ constexpr int strm_pos(int pass, int i) {
    if (pass == 1 || pass == 2) return 8 + 8 * pass + i;
    int n = 0;
    for (int p = 0; p < 16; p++)
        if ((int)((KVMASK >> p) & 1) == (pass == 3)) { if (n == i) return p; n++; }
    return 0;
}
__host__ __device__ constexpr uint32_t strm_code(int pass) {
    uint32_t c = 0;
    for (int i = 0; i < 7; i++) c |= (uint32_t)(strm_pos(pass, i + 1) - strm_pos(pass, i)) << (4 * i);
    return c;
}

template <int N, int SUB, int KST, int LBO, int SBO, int SWZ>
__device__ __forceinline__ void gemm_pass(float* acc, uint32_t bar, uint64_t dA, int lane, uint32_t pos, uint32_t code, int barNext, bool waitx, bool last) {
    uint32_t prev = 0, slot = pos % NR;
#pragma unroll 1
    for (int i = 0; i < 8; i++) {
        if (waitx) mbar_wait(bar + B_X + 8 * i, 0);
        mbar_wait(bar + B_F1 + 8 * pos, 0);
        const uint64_t dB = mkdesc(SBD + OFF_R, LBO, SBO, SWZ) + slot * 1024;
        wg_fence();
        wgmma_ss<N>(acc, dA, dB);
        wgmma_ss<N>(acc, dA + 2, dB + KST / 16);
        wg_commit();
        wg_wait<1>();
        if (i > 0 && lane < 2) mbar_arrive_cluster(prev, lane);
        wgmma_ss<N>(acc, dA + 4, dB + SUB / 16);
        wgmma_ss<N>(acc, dA + 6, dB + (SUB + KST) / 16);
        wg_commit();
        prev = last ? bar + B_XD + 8 * i : bar + B_E1 + 8 * slot;
        pos += code & 15;
        slot += code & 15;
        if (slot >= NR) slot -= NR;
        code >>= 4;
        dA += 1024;
    }
    if (barNext) bar_arrive(barNext, 512);
    wg_wait<0>();
    if (lane < 2) mbar_arrive_cluster(prev, lane);
    pin<N / 2>(acc);
}

__device__ __forceinline__ uint32_t lds32(uint32_t a) { uint32_t v; asm volatile("ld.shared.u32 %0, [%1];" : "=r"(v) : "r"(a)); return v; }
__device__ __forceinline__ bool elect() {
    uint32_t p;
    asm volatile("{\n.reg .pred p;\nelect.sync _|p, 0xffffffff;\nselp.u32 %0, 1, 0, p;\n}" : "=r"(p));
    return p;
}

template <int G0, int G1> __device__ __forceinline__ void gelu_pack(const float* acc, uint32_t bias, uint32_t* out) {
#pragma unroll
    for (int G = G0; G < G1; G++) {
        uint32_t* o = out + 8 * G;
#pragma unroll
        for (int j = 0; j < 4; j++) {
            float bv[2];
            asm volatile("ld.shared.v2.f32 {%0, %1}, [%2];" : "=f"(bv[0]), "=f"(bv[1]) : "r"(bias + G * 128 + j * 32));
            float y[4];
#pragma unroll
            for (int i = 0; i < 4; i++) {
                const float h = acc[16 * G + 4 * j + i] + bv[i & 1];
                const float z = h * fmaf(h * h, 0.035677408136300125f, 0.7978845608028654f);
                y[i] = fmaf(h, tanhf_(z), h);
            }
            o[j] = pk_bf16(y[0], y[1]);
            o[4 + j] = pk_bf16(y[2], y[3]);
        }
    }
}

__device__ __forceinline__ float norm_bound(const float* v, float sc) {
    uint32_t m = 0;
#pragma unroll
    for (int h = 0; h < 4; h++) {
        const float* u = v + 8 * h;
        m = max(m, __float_as_uint(fmaf(u[0], u[0], fmaf(u[1], u[1], fmaf(u[4], u[4], u[5] * u[5])))));
        m = max(m, __float_as_uint(fmaf(u[2], u[2], fmaf(u[3], u[3], fmaf(u[6], u[6], u[7] * u[7])))));
    }
#pragma unroll
    for (int o = 4; o < 32; o <<= 1) m = max(m, __shfl_xor_sync(0xffffffffu, m, o));
    float f = __uint_as_float(m);
    f += __shfl_xor_sync(0xffffffffu, f, 1);
    f += __shfl_xor_sync(0xffffffffu, f, 2);
    return f * sc;
}

__device__ __forceinline__ uint32_t exp2_pair(float a, float b, uint32_t m1) {
    const uint32_t w = __byte_perm(__float_as_uint(a), __float_as_uint(b), 0x6521);
    uint32_t m, r;
    asm("lop3.b32 %0, %1, 0x007f007f, 0x9f809f80, 0xEA;" : "=r"(m) : "r"(w));
    const uint32_t e = m * m1 + w;
    asm("fma.rn.bf16x2 %0, %1, %2, %3;" : "=r"(r) : "r"(w), "r"(m), "r"(e));
    return r;
}

__device__ __forceinline__ void store_o(const float* o, uint4* dst, uint32_t par) {
    const float s0 = __fdividef(1.f, o[8]), s1 = __fdividef(1.f, o[10]);
    const uint32_t d0 = (pk_bf16(o[0] * s0, o[1] * s0) & ~1u) | par;
    asm volatile("{\n.reg .b128 t;\nmov.b128 t, {%0, %1, %2, %3};\nst.relaxed.gpu.global.b128 [%4], t;\n}" ::"r"(d0),
                 "r"(pk_bf16(o[4] * s0, o[5] * s0)), "r"(pk_bf16(o[2] * s1, o[3] * s1)), "r"(pk_bf16(o[6] * s1, o[7] * s1)), "l"(dst) : "memory");
}
__device__ __forceinline__ uint4 load_o(const uint4* src) {
    uint4 v;
    asm volatile("{\n.reg .b128 t;\nld.relaxed.gpu.global.b128 t, [%4];\nmov.b128 {%0, %1, %2, %3}, t;\n}"
                 : "=r"(v.x), "=r"(v.y), "=r"(v.z), "=r"(v.w) : "l"(src) : "memory");
    return v;
}
__device__ __forceinline__ uint32_t bmul2(uint32_t a, uint32_t b) { uint32_t r; asm("mul.rn.bf16x2 %0, %1, %2;" : "=r"(r) : "r"(a), "r"(b)); return r; }
__device__ __forceinline__ void sts32(uint32_t a, uint32_t v) { asm volatile("st.shared.u32 [%0], %1;" ::"r"(a), "r"(v) : "memory"); }
__device__ __forceinline__ void load_q(uint32_t* q, int h, int row, int t) {
    const uint8_t* p = gQ + (size_t)h * (SEQ * 32) + (size_t)row * 32 + t * 4;
    q[0] = __ldcg((const uint32_t*)p); q[1] = __ldcg((const uint32_t*)(p + 256));
    q[2] = __ldcg((const uint32_t*)(p + 16)); q[3] = __ldcg((const uint32_t*)(p + 272));
}

template <int NT>
__device__ __forceinline__ void proj16(float (*c)[8], const __nv_bfloat16* x, const __nv_bfloat16* w, int row0, int rstep, int col, int g, int t) {
#pragma unroll
    for (int i = 0; i < NT; i++)
#pragma unroll
        for (int j = 0; j < 8; j++) c[i][j] = 0.f;
    const unsigned short* wu = (const unsigned short*)w;
#pragma unroll 1
    for (int k = 0; k < DM; k += 16) {
        uint32_t b[4];
#pragma unroll
        for (int j = 0; j < 4; j++) {
            const int kr = k + 2 * t + (j & 1) * 8, cc = col + g + (j >> 1) * 8;
            b[j] = (uint32_t)wu[(size_t)kr * (3 * DM) + cc] | ((uint32_t)wu[(size_t)(kr + 1) * (3 * DM) + cc] << 16);
        }
#pragma unroll
        for (int i = 0; i < NT; i++) {
            const __nv_bfloat16* xp = x + (size_t)(row0 + i * rstep + g) * DM + k + 2 * t;
            const uint32_t a0 = *(const uint32_t*)xp, a1 = *(const uint32_t*)(xp + 8 * DM);
            const uint32_t a2 = *(const uint32_t*)(xp + 8), a3 = *(const uint32_t*)(xp + 8 * DM + 8);
#pragma unroll
            for (int j = 0; j < 2; j++)
                asm volatile("mma.sync.aligned.m16n8k16.row.col.f32.bf16.bf16.f32 {%0,%1,%2,%3}, {%4,%5,%6,%7}, {%8,%9}, {%0,%1,%2,%3};"
                             : "+f"(c[i][4 * j]), "+f"(c[i][4 * j + 1]), "+f"(c[i][4 * j + 2]), "+f"(c[i][4 * j + 3])
                             : "r"(a0), "r"(a1), "r"(a2), "r"(a3), "r"(b[2 * j]), "r"(b[2 * j + 1]));
        }
    }
}

struct Maps { CUtensorMap x, kv, q, f1, f3, h, w2, wo, hs, kvs; };

template <int I0, int I1>
__device__ __forceinline__ void issue_stream(const Maps& tm, uint32_t sb, uint32_t rank, int nb, int mb) {
    const uint32_t bar = sb + OFF_BAR;
    const uint32_t dst = sb + OFF_R;
    const int kr = rank * 32;
#pragma unroll
    for (int it = I0; it < I1; it++) {
        const int s = it % NR;
        const uint32_t fb = bar + B_F1 + 8 * it;
        if (it >= 24 + NR) mbar_wait(bar + B_XD + 8 * (it - 24 - NR), 0);
        else if (it >= NR) mbar_wait(bar + B_E1 + 8 * s, ((it / NR) - 1) & 1);
        const int nkv = __builtin_popcount(KVMASK & ((1u << it) - 1));
        if (it < 16 && ((KVMASK >> it) & 1)) {
            tma3d_mc(dst + s * 16384 + rank * 8192, &tm.kv, nb * 64, nkv * 64 + kr, 1, fb);
        } else if (it < 16) {
            tma3d_mc(dst + s * 16384 + rank * 6144, &tm.q, 0, (it - nkv) * 64 + kr, nb * 2, fb);
            tma3d_mc(dst + s * 16384 + rank * 6144 + 4096, &tm.f1, 0, (it - nkv) * 64 + kr, nb * 7, fb);
        } else {
            tma3d_mc(dst + s * 16384 + rank * 6144, &tm.f3, 0, (it & 7) * 64 + kr, nb * 7 + (it < 24 ? 1 : 4), fb);
        }
        if ((XMASK >> it) & 1) {
            const int xc = 1 + __builtin_popcount(XMASK & ((1u << it) - 1));
            tma2d(sb + xc * 16384, &tm.x, xc * 64, mb * 128, bar + B_X + 8 * xc);
        }
    }
}

__global__ void __cluster_dims__(2, 1, 1) __launch_bounds__(640, 1)
fused_kernel(const __grid_constant__ Maps tm, const __nv_bfloat16* __restrict__ x, const __nv_bfloat16* __restrict__ wqkv,
             const __nv_bfloat16* __restrict__ wo, const __nv_bfloat16* __restrict__ w1, const __nv_bfloat16* __restrict__ b1,
             const __nv_bfloat16* __restrict__ w2, const __nv_bfloat16* __restrict__ b2, const __nv_bfloat16* __restrict__ gate,
             __nv_bfloat16* __restrict__ out, const uint32_t m1) {
    const uint32_t sb = smem_u32(smem_raw);
    const uint32_t bar = sb + OFF_BAR;
    const int tid = threadIdx.x, lane = tid & 31;
    const int warp = __shfl_sync(0xffffffffu, tid >> 5, 0);
    const uint32_t rank = cluster_rank();
    const int cl = blockIdx.x >> 1;
    const int nb = cl & 7, mb = (cl >> 3) * 2 + rank;
    const int g = lane >> 2, t = lane & 3;

    const int cb = nb & 3, rb = mb * 2 + (nb >> 2);
    if (tid == 0) TLM(0, 0);
    TL_INIT();
    if (tid == 512) {
        for (int i = 0; i < 8; i++) { mbar_init(bar + B_X + 8 * i, 1); mbar_init(bar + B_KV + 8 * i, 1); mbar_init(bar + B_T + 8 * i, 5); mbar_init(bar + B_XD + 8 * i, 16); }
        for (int i = 0; i < NR; i++) mbar_init(bar + B_E1 + 8 * i, 16);
        for (int i = 0; i < 4; i++) { mbar_init(bar + B_F2 + 8 * i, 1); mbar_init(bar + B_E2 + 8 * i, 8); }
        asm volatile("fence.mbarrier_init.release.cluster;" ::: "memory");
    } else if (tid == 608) {
        for (int i = 0; i < 32; i++) mbar_init(bar + B_F1 + 8 * i, 1);
        mbar_init(bar + B_DONE, 16);
        mbar_init(bar + B_DONE2, 16);
        mbar_init(bar + B_G, 1);
        for (int i = 0; i < 3; i++) mbar_init(bar + B_SF + 8 * i, i == 1 ? 2 : 1);
        mbar_init(bar + B_SF2, 2);
        mbar_init(bar + B_G3, 1);
        mbar_init(bar + B_G2, 4);
        asm volatile("fence.mbarrier_init.release.cluster;" ::: "memory");
    }
    __syncwarp();
    asm volatile("barrier.cluster.arrive.relaxed.aligned;" ::: "memory");
    if (warp == 19) mbar_expect(bar + B_F1 + 8 * lane, ((KVMASK >> lane) & 1) ? 16384 : 12288);
    if (warp == 16 && lane < 24) mbar_expect(bar + (lane < 8 ? B_X : lane < 16 ? B_KV - 64 : B_T - 128) + 8 * lane, 16384);
    if (tid == 512) {
        tma2d(sb, &tm.x, 0, mb * 128, bar + B_X);
    } else if (tid == 544) {
        map_prefetch(&tm.kv);
        l2_prefetch((const uint8_t*)wqkv + (size_t)blockIdx.x * 3072, 3072);
        l2_prefetch((const uint8_t*)w1 + (size_t)blockIdx.x * 1792, 1792);
        map_prefetch(&tm.q); map_prefetch(&tm.f1); map_prefetch(&tm.f3);
    }
    if ((sb & 0xFFFFFF) != SBD) __trap();
    __syncwarp();
    asm volatile("barrier.cluster.wait.aligned;" ::: "memory");
    if (tid == 512) issue_stream<0, NR>(tm, sb, rank, nb, mb);
    if (tid == 0) { TLM(0, 1); TLC(0, 30); }

    if (warp < 16) {
        const int wg = warp >> 2;
        const int h = cl >> 1, qd = (cl & 1) * 2 + rank;
        uint32_t q[4];
        {
            const int w8 = warp & 7;
            const int T = mb * 8 + w8, row0 = T * 16 + g;
            const uint64_t dA0 = mkdesc(SBD + (wg & 1) * 8192, 16, 1024, 1);
            if (wg < 2) {
                float acc[64];
#pragma unroll
                for (int i = 0; i < 64; i++) acc[i] = 0.f;
                gemm_pass<128, 8192, 2048, 4096, 1024, 1>(acc, bar, dA0, lane, strm_pos(3, 0), strm_code(3), 0, true, false);
                if (tid == 0) TLM(0, 2);
                {
                    const float km = norm_bound(acc, 1.f);
                    float vm = 0.f;
#pragma unroll
                    for (int i = 32; i < 64; i++) vm = fmaxf(vm, fabsf(acc[i]));
                    vm = __uint_as_float(__reduce_max_sync(0xffffffffu, __float_as_uint(vm)));
                    if (lane == 0) { gN[1024 + nb * 128 + T] = km; gN[2048 + nb * 128 + T] = vm; }
                    const uint32_t kp = sb + OFF_R + 12288 + (w8 >> 2) * 1024 + g * 128 + ((((w8 & 3) * 2 + ((t >> 1) ^ (w8 >> 2))) ^ g) << 4) + (t & 1) * 8;
                    uint8_t* vp = gKV + (size_t)(nb * 4) * (SEQ * 64) + 65536 + (((T >> 6) * 16 + 2 * g) * 64 + (T & 63)) * 32 + ((t * 8) ^ ((w8 >> 2) << 4));
                    bar_sync(9, 256);
#pragma unroll
                    for (int hh = 0; hh < 4; hh++) {
                        const float* v = acc + 8 * hh;
                        float p0 = __shfl_up_sync(0xffffffffu, v[2], 4), p1 = __shfl_up_sync(0xffffffffu, v[3], 4);
                        float p2 = __shfl_up_sync(0xffffffffu, v[6], 4), p3 = __shfl_up_sync(0xffffffffu, v[7], 4);
                        if (g == 0) { p0 = p1 = p2 = p3 = 0.f; }
                        sts64(kp + hh * 16384, pk_f16(v[0] - p0, v[1] - p1), pk_f16(v[4] - p2, v[5] - p3));
                        sts64(kp + hh * 16384 + 2048, pk_f16(v[2] - v[0], v[3] - v[1]), pk_f16(v[6] - v[4], v[7] - v[5]));
                        const float* u = acc + 32 + 8 * hh;
                        if (hh < 2) {
                            sts64(kp + (4 + hh) * 16384, pk_bf16(u[0], u[1]), pk_bf16(u[4], u[5]));
                            sts64(kp + (4 + hh) * 16384 + 2048, pk_bf16(u[2], u[3]), pk_bf16(u[6], u[7]));
                        } else {
                            *(uint2*)(vp + (size_t)hh * (SEQ * 64)) = make_uint2(pk_bf16(u[0], u[1]), pk_bf16(u[4], u[5]));
                            *(uint2*)(vp + (size_t)hh * (SEQ * 64) + 2048) = make_uint2(pk_bf16(u[2], u[3]), pk_bf16(u[6], u[7]));
                        }
                    }
                }
                asm volatile("fence.proxy.async.shared::cta;" ::: "memory");
                bar_arrive(10, 288);
                if (tid == 0) TLM(0, 3);
            }
#pragma unroll 1
            for (int p = wg < 2 ? 1 : 0; p < 3; p += 2) {
                float acc[48];
#pragma unroll
                for (int i = 0; i < 48; i++) acc[i] = 0.f;
                pin<48>(acc);
                if (p) bar_sync(5 + p, 512);
                gemm_pass<96, 6144, 1024, 2048, 512, 2>(acc, bar, dA0, lane, p == 0 ? strm_pos(0, 0) : 8 + 8 * p, p == 0 ? strm_code(0) : strm_code(1), p < 2 ? 6 + p : 0, p == 0, p == 2);
                if ((tid & 255) == 0) TLM(0, 4 + 2 * p);
                const uint32_t hp = sb + OFF_R + (p == 2 ? 0 : 12288) + (wg & 1) * 16384 + ((warp & 3) * 16 + g) * 64 + t * 16;
                const uint32_t bp = sb + OFF_BIAS + p * 384 - 256 + t * 8;
                uint32_t ho[24];
                mbar_wait(bar + B_BI, 0);
                if (p == 0) {
                    const float qm = norm_bound(acc, QSCALE * QSCALE);
                    if (lane == 0) gN[nb * 128 + T] = qm;
                    uint8_t* qp = gQ + (size_t)(nb * 4) * (SEQ * 32) + (size_t)row0 * 32 + t * 8;
#pragma unroll
                    for (int hh = 0; hh < 4; hh++) {
                        const float* v = acc + 8 * hh;
                        *(uint2*)(qp + hh * (SEQ * 32)) = make_uint2(pk_f16(v[0] * QSCALE, v[1] * QSCALE), pk_f16(v[4] * QSCALE, v[5] * QSCALE));
                        *(uint2*)(qp + hh * (SEQ * 32) + 256) = make_uint2(pk_f16(v[2] * QSCALE, v[3] * QSCALE), pk_f16(v[6] * QSCALE, v[7] * QSCALE));
                    }
                    bar_arrive(12, 288);
                } else {
                    gelu_pack<0, 2>(acc, bp, ho);
                    pin<16>(ho);
                    mbar_wait(bar + B_G, 0);
                    load_q(q, h, qd * 512 + warp * 16 + g, t);
                }
                gelu_pack<2, 3>(acc, bp, ho);
                pin<8>(ho + 16);
                if (p == 2) bar_sync(9, 256);
                else mbar_wait(bar + B_SF + 8 * p, 0);
                if (p) {
#pragma unroll
                    for (int i = 0; i < 4; i++) sts128(hp + (i >> 1) * 32768 + (i & 1) * 512, ho + 4 * i);
                }
                sts128(hp + 65536, ho + 16);
                sts128(hp + 65536 + 512, ho + 20);
                asm volatile("fence.proxy.async.shared::cta;" ::: "memory");
                bar_arrive(p == 1 ? 14 : 11, 288);
                if ((tid & 255) == 0) TLM(0, 5 + 2 * p);
            }
        }
        uint32_t ep = 2;
        uint4* const op = gO + ((qd * 8 + wg) * NH + h) * 128 + (tid & 127);
        const uint64_t kd0 = mkdesc(SBD, 16, 256, 3);
        const uint64_t vd0 = mkdesc(SBD + 8192, OFF_ONE - 8192, 256, 3);
        {
            float o[12];
            uint32_t qn[4];
#pragma unroll 1
            for (int rh = 0; rh < 4; rh++) {
                if (rh == 1) {
                    mbar_wait(bar + B_G3, 0);
                    ep = lds32(sb + OFF_G + 256);
                    if (!(ep & 2)) break;
                    load_q(qn, h, qd * 512 + 256 + warp * 16 + g, t);
                }
                if (rh == 3 && lane == 0) mbar_arrive(bar + B_DONE);
                if (!(rh & 1)) {
#pragma unroll
                    for (int i = 0; i < 12; i++) o[i] = 0.f;
                }
                uint64_t kd = kd0 + (rh & 1) * 4096, vd = vd0 + (rh & 1) * (128 * VSTEP);
                uint32_t kvb = bar + B_KV + (rh & 1) * 32;
                float s[32];
#pragma unroll
                for (int i = 0; i < 32; i++) s[i] = i < 2 * NMUFU ? 0.f : MAGIC;
                if ((tid & 255) == 0) TLM(1, (tid >> 8) * 4 + rh);
#pragma unroll 1
                for (int c = 0; c < 4; c++) {
                    mbar_wait(kvb, 0);
                    kvb += 8;
#pragma unroll
                    for (int j = 0; j < 4; j++) {
                        uint32_t p[16];
                        if (!MERGE || j == 0) {
                            wg_fence();
                            wgmma_qk_f16_acc(s, q, kd + j * 128);
                            wg_commit();
                        }
                        wg_wait<0>();
                        pin<32>(s);
#pragma unroll
                        for (int i = 0; i < 16; i++)
                            p[i] = i < NMUFU ? pk_bf16(ex2f(s[2 * i]), ex2f(s[2 * i + 1])) : exp2_pair(s[2 * i], s[2 * i + 1], m1);
                        pin<16>(p);
                        wg_fence();
#pragma unroll
                        for (int u = 0; u < 4; u++) {
                            if (MERGE && j < 3 && u == 5 - MERGE) wgmma_qk_f16_acc(s, q, kd + (j + 1) * 128);
                            wgmma_pv(o, p + 4 * u, vd + (j * 4 + u) * VSTEP);
                        }
                        if (MERGE == 1 && j < 3) wgmma_qk_f16_acc(s, q, kd + (j + 1) * 128);
                        wg_commit();
                    }
                    kd += 1024;
                    vd += 32 * VSTEP;
                }
                wg_wait<0>();
                pin<12>(o);
                if (rh & 1) {
                    if ((tid & 127) == 0 && rh == 3) TLM(1, 8 + wg);
                    store_o(o, op + (rh >> 1) * (4 * NH * 128), ep & 1);
#pragma unroll
                    for (int i = 0; i < 4; i++) q[i] = qn[i];
                }
            }
            if (tid == 0) { TLM(1, 12); TLC(0, 31); }
        }
        if (!(ep & 2)) {
            bar_sync(8, 512);
            for (int c = 0; c < 8; c++) mbar_wait(bar + B_KV + 8 * c, 0);
            {
                float kc[8][8];
                proj16<8>(kc, x, wqkv, warp * 16, 256, DM + h * 16, g, t);
#pragma unroll
                for (int i = 0; i < 8; i++) {
                    const int T = warp + i * 16;
                    const int pos = ((T >> 6) * 16 + 2 * g) * 64 + (T & 63);
                    const uint32_t a = sb + (pos >> 8) * 16384 + (pos & 255) * 32 + t * 4, sw = ((T >> 2) & 1) << 4;
                    asm volatile("st.shared.u32 [%0], %1;" ::"r"(a + sw), "r"(pk_bf16(kc[i][0], kc[i][1])) : "memory");
                    asm volatile("st.shared.u32 [%0], %1;" ::"r"(a + (sw ^ 16)), "r"(pk_bf16(kc[i][4], kc[i][5])) : "memory");
                    asm volatile("st.shared.u32 [%0], %1;" ::"r"(a + 2048 + sw), "r"(pk_bf16(kc[i][2], kc[i][3])) : "memory");
                    asm volatile("st.shared.u32 [%0], %1;" ::"r"(a + 2048 + (sw ^ 16)), "r"(pk_bf16(kc[i][6], kc[i][7])) : "memory");
                }
                asm volatile("fence.proxy.async.shared::cta;" ::: "memory");
                bar_sync(8, 512);
            }
#pragma unroll 1
            for (int r = 0; r < 2; r++) {
                const int row = qd * 512 + r * 256 + warp * 16 + g;
                {
                    float qc[1][8];
                    proj16<1>(qc, x, wqkv, row - g, 0, h * 16, g, t);
#pragma unroll
                    for (int i = 0; i < 4; i++) q[i] = pk_bf16(qc[0][2 * i] * QSCALE, qc[0][2 * i + 1] * QSCALE);
                }
                float o[12];
#pragma unroll
                for (int i = 0; i < 12; i++) o[i] = 0.f;
                float m0 = -INFINITY, m1 = -INFINITY;
#pragma unroll 1
                for (int j = 0; j < 32; j++) {
                    const uint64_t kd = kd0 + (j >> 2) * 1024 + (j & 3) * 128, vd = vd0 + ((j >> 2) * 32 + (j & 3) * 4) * VSTEP;
                    float s[32];
                    uint32_t p[16];
                    wg_fence();
                    wgmma_qk_bf16_zero(s, q, kd);
                    wg_commit();
                    wg_wait<0>();
                    pin<32>(s);
                    pin<12>(o);
                    float n0 = m0, n1 = m1;
#pragma unroll
                    for (int i = 0; i < 8; i++) {
                        n0 = fmaxf(n0, fmaxf(s[4 * i], s[4 * i + 1]));
                        n1 = fmaxf(n1, fmaxf(s[4 * i + 2], s[4 * i + 3]));
                    }
                    n0 = fmaxf(n0, __shfl_xor_sync(0xffffffffu, n0, 1));
                    n1 = fmaxf(n1, __shfl_xor_sync(0xffffffffu, n1, 1));
                    n0 = fmaxf(n0, __shfl_xor_sync(0xffffffffu, n0, 2));
                    n1 = fmaxf(n1, __shfl_xor_sync(0xffffffffu, n1, 2));
                    const float c0 = ex2f(m0 - n0), c1 = ex2f(m1 - n1);
                    m0 = n0;
                    m1 = n1;
#pragma unroll
                    for (int i = 0; i < 3; i++) { o[4 * i] *= c0; o[4 * i + 1] *= c0; o[4 * i + 2] *= c1; o[4 * i + 3] *= c1; }
#pragma unroll
                    for (int i = 0; i < 8; i++) {
                        p[2 * i] = pk_bf16(ex2f(s[4 * i] - m0), ex2f(s[4 * i + 1] - m0));
                        p[2 * i + 1] = pk_bf16(ex2f(s[4 * i + 2] - m1), ex2f(s[4 * i + 3] - m1));
                    }
                    pin<16>(p);
                    pin<12>(o);
                    wg_fence();
#pragma unroll
                    for (int u = 0; u < 4; u++) wgmma_pv(o, p + 4 * u, vd + u * VSTEP);
                    wg_commit();
                }
                wg_wait<0>();
                pin<12>(o);
                if (r == 1 && lane == 0) mbar_arrive(bar + B_DONE);
                store_o(o, op + r * (4 * NH * 128), ep & 1);
            }
        }
        if (lane == 0) mbar_arrive(bar + B_DONE2);
        if (wg < 2) {
            const uint4* src = gO + (rb * NH + wg * 16) * 128 + (tid & 127);
            uint4 v[16];
#pragma unroll
            for (int i = 0; i < 16; i++) v[i] = load_o(src + i * 128);
            mbar_wait(bar + B_DONE, 0);
            mbar_wait(bar + B_G2, 0);
            const int lr = (warp & 3) * 16 + g;
            const uint32_t g0 = lds32(sb + OFF_G + lr * 4), g1 = lds32(sb + OFF_G + lr * 4 + 32);
            const uint32_t a0 = sb + wg * 32768 + lr * 128 + (t >> 1) * 4;
            uint32_t todo = 15;
            int spins = 0;
            while (true) {
#pragma unroll
                for (int k = 0; k < 4; k++) {
                    if (!(todo >> k & 1)) continue;
                    if (__any_sync(0xffffffffu, (((v[4 * k].x ^ ep) | (v[4 * k + 1].x ^ ep) | (v[4 * k + 2].x ^ ep) | (v[4 * k + 3].x ^ ep)) & 1) != 0)) {
#pragma unroll
                        for (int i = 4 * k; i < 4 * k + 4; i++)
                            if (((v[i].x ^ ep) & 1) != 0) v[i] = load_o(src + i * 128);
                    } else {
#pragma unroll
                        for (int i = 0; i < 4; i++) {
                            const uint32_t a = a0 + k * 8192 + (((i * 2 + (t & 1)) ^ g) << 4);
                            sts32(a, bmul2(v[4 * k + i].x, g0));
                            sts32(a + 8, bmul2(v[4 * k + i].y, g0));
                            sts32(a + 1024, bmul2(v[4 * k + i].z, g1));
                            sts32(a + 1024 + 8, bmul2(v[4 * k + i].w, g1));
                        }
                        asm volatile("fence.proxy.async.shared::cta;" ::: "memory");
                        __syncwarp();
                        if (lane == 0) mbar_arrive(bar + B_T + 8 * (wg * 4 + k));
                        if ((tid & 127) == 0) TLM(1, 20 + wg * 4 + k);
                        todo &= ~(1u << k);
                    }
                }
                if (!todo) break;
                if (++spins > (1 << 22)) __trap();
            }
        }
        if (tid == 256) {
            mbar_wait(bar + B_DONE2, 0);
#pragma unroll
            for (int i = 0; i < 4; i++)
                tma2d(sb + 65536 + i * 8192, &tm.wo, cb * 128 + (i & 1) * 64, (6 + (i >> 1)) * 64, bar + B_T + 8 * (6 + (i >> 1)));
        }
    } else {
        if (warp == 16) {
            if (lane == 0) {
                issue_stream<NR, 32>(tm, sb, rank, nb, mb);
                mbar_wait(bar + B_SF2, 0);
#pragma unroll
                for (int s = 0; s < 4; s++) {
                    mbar_expect(bar + B_F2 + 8 * s, 24576);
                    tma5d_mc(sb + OFF_R + s * 24576 + 8192 + rank * 8192, &tm.w2, cb * 128 + rank * 64, s * 2, bar + B_F2 + 8 * s);
                }
                cnt_wait(gCntH + mb * 32, epoch() * 8);
                asm volatile("fence.proxy.async.global;" ::: "memory");
                TLM(1, 13);
#pragma unroll
                for (int s = 0; s < 4; s++) tma2d(sb + OFF_R + s * 24576, &tm.h, s * 64, rb * 64, bar + B_F2 + 8 * s);
            }
        } else if (warp == 17) {
            {
                uint32_t bv[4], b2v[2];
#pragma unroll
                for (int i = 0; i < 4; i++) bv[i] = lane + 32 * i < 112 ? *(const uint32_t*)(b1 + nb * 224 + (lane + 32 * i) * 2) : 0;
#pragma unroll
                for (int i = 0; i < 2; i++) b2v[i] = *(const uint32_t*)(b2 + cb * 128 + (lane + 32 * i) * 2);
#pragma unroll
                for (int i = 0; i < 4; i++) {
                    sts32(sb + OFF_ONE + (lane + 32 * i) * 4, 0x3f803f80u);
                    if (lane + 32 * i < 112) sts64(sb + OFF_BIAS + (lane + 32 * i) * 8, bv[i] << 16, bv[i] & 0xffff0000u);
                }
#pragma unroll
                for (int i = 0; i < 2; i++) sts32(sb + OFF_BIAS + 896 + (lane + 32 * i) * 4, b2v[i]);
                asm volatile("fence.proxy.async.shared::cta;" ::: "memory");
                __syncwarp();
                if (lane == 0) mbar_arrive(bar + B_BI);
            }
            mbar_wait(bar + B_X + 8 * PFX, 0);
            if (lane == 0) {
                l2_prefetch((const uint8_t*)wqkv + 128 * 3072 + (size_t)blockIdx.x * 9216, 9216);
                l2_prefetch((const uint8_t*)w1 + (size_t)blockIdx.x * 14336, 14336);
            }
            mbar_wait(bar + B_X + 8 * 7, 0);
            if (lane == 0) {
                l2_prefetch((const uint8_t*)w2 + (size_t)blockIdx.x * 14336, 14336);
                l2_prefetch((const uint8_t*)wo + (size_t)blockIdx.x * 4096, 4096);
                map_prefetch(&tm.h); map_prefetch(&tm.w2); map_prefetch(&tm.wo); map_prefetch(&tm.hs); map_prefetch(&tm.kvs);
                TLM(0, 11);
            }
            bar_sync(10, 288);
            if (lane == 0) {
#pragma unroll 1
                for (int b = 5; b >= 0; b--) {
                    tma5d_st(&tm.kvs, sb + OFF_R + 12288 + b * 16384, (mb >> 3) * 8, (mb & 7) * 2, nb * 8 + (b < 4 ? 2 * b : 2 * b - 7));
                    asm volatile("cp.async.bulk.commit_group;\ncp.async.bulk.wait_group.read %0;" ::"n"(PACE) : "memory");
                    if (b == 4 - PACE) mbar_arrive(bar + B_SF);
                }
                asm volatile("cp.async.bulk.wait_group.read 0;" ::: "memory");
                mbar_arrive(bar + B_SF + 8);
            }
            __syncwarp();
            bar_sync(12, 288);
            if (lane == 0) {
                asm volatile("cp.async.bulk.wait_group 0;\nfence.proxy.async.global;" ::: "memory");
                cnt_add(gCntQ + nb * 32);
                TLM(0, 13);
            }
        } else {
            {
                const int r0 = mb * 128 + nb * 16 + (warp - 18) * 8;
                uint4 xv[16];
#pragma unroll
                for (int i = 0; i < 16; i++) xv[i] = *(const uint4*)(x + (size_t)(r0 + (i >> 1)) * DM + (i & 1) * 256 + lane * 8);
                const uint4 ga = *(const uint4*)(gate + lane * 8), gb = *(const uint4*)(gate + 256 + lane * 8);
                float z[8];
#pragma unroll
                for (int r = 0; r < 8; r++) z[r] = dot8(xv[2 * r], ga) + dot8(xv[2 * r + 1], gb);
#pragma unroll
                for (int w = 4; w >= 1; w >>= 1)
#pragma unroll
                    for (int r = 0; r < w; r++) {
                        const bool up = lane & w;
                        z[r] = (up ? z[r + w] : z[r]) + __shfl_xor_sync(0xffffffffu, up ? z[r] : z[r + w], w);
                    }
                z[0] += __shfl_xor_sync(0xffffffffu, z[0], 8);
                z[0] += __shfl_xor_sync(0xffffffffu, z[0], 16);
                if (lane < 8) gG[r0 + lane] = 1.f / (1.f + __expf(-z[0]));
                if (tid == 576) TLM(0, 12);
            }
            if (warp == 19) {
#pragma unroll 1
                for (int e = 0; e < 3; e++) {
                    bar_sync(e == 1 ? 14 : 11, 288);
                    if (lane == 0) {
#pragma unroll 1
                        for (int b = e == 0 ? 4 : 0; b < 6; b++) {
                            tma3d_st(&tm.hs, sb + OFF_R + (e == 2 ? 0 : 12288) + b * 16384, 0, mb * 128 + (b & 1) * 64, nb * 7 + e * 3 - 2 + (b >> 1));
                            asm volatile("cp.async.bulk.commit_group;\ncp.async.bulk.wait_group.read %0;" ::"n"(PACE) : "memory");
                        }
                        asm volatile("cp.async.bulk.wait_group.read 0;" ::: "memory");
                        if (e == 0) mbar_arrive(bar + B_SF + 8);
                        if (e == 2) { mbar_arrive_cluster(bar + B_SF2, 0); mbar_arrive_cluster(bar + B_SF2, 1); }
                    }
                    __syncwarp();
                }
                bar_sync(13, 64);
                if (lane == 0) {
                    asm volatile("cp.async.bulk.wait_group 0;\nfence.proxy.async.global;" ::: "memory");
                    cnt_add(gCntH + mb * 32);
                    TLM(0, 15);
                }
            } else {
                bar_arrive(13, 64);
                const int h = cl >> 1, qd = (cl & 1) * 2 + rank;
                const uint32_t ep = epoch();
                if (lane == 0) {
                    cnt_wait(gCntQ + (h >> 2) * 32, ep * 16);
                    mbar_arrive(bar + B_G);
                    TLM(0, 14);
                    asm volatile("fence.proxy.async.global;" ::: "memory");
#pragma unroll
                    for (int c = 0; c < 2; c++) {
                        mbar_wait(bar + B_XD + 8 * c, 0);
                        bulk_mc(sb + c * 16384 + rank * 8192, gKV + (size_t)h * (SEQ * 64) + rank * 65536 + c * 8192, 8192, bar + B_KV + 8 * c);
                    }
                }
                __syncwarp();
            const int hb = h >> 2;
            const uint4 kq = __ldcg((const uint4*)(gN + 1024 + hb * 128 + lane * 4));
            const uint4 vq = __ldcg((const uint4*)(gN + 2048 + hb * 128 + lane * 4));
            const float qq = ldcg_f(gN + hb * 128 + qd * 32 + lane);
            const float kf = __uint_as_float(__reduce_max_sync(0xffffffffu, max(max(kq.x, kq.y), max(kq.z, kq.w))));
            const float vf = __uint_as_float(__reduce_max_sync(0xffffffffu, max(max(vq.x, vq.y), max(vq.z, vq.w))));
            const float qf = __uint_as_float(__reduce_max_sync(0xffffffffu, __float_as_uint(qq)));
            if (lane == 0) {
                sts32(sb + OFF_G + 256, (ep & 1) | ((kf <= 1.0e6f) && (qf <= 1.0e6f) && (kf * qf <= 3400.f) && (vf <= 1.0e12f) ? 2 : 0));
                mbar_arrive(bar + B_G3);
                TLM(0, 16);
#pragma unroll
                for (int c = 2; c < 8; c++) {
                    mbar_wait(bar + B_XD + 8 * c, 0);
                    bulk_mc(sb + c * 16384 + rank * 8192, gKV + (size_t)h * (SEQ * 64) + rank * 65536 + c * 8192, 8192, bar + B_KV + 8 * c);
                }
                TLM(0, 10);
            }
            }
        }
        __syncwarp();
        float acc[64];
#pragma unroll
        for (int i = 0; i < 64; i++) acc[i] = 0.f;
#pragma unroll 1
        for (int io = 0; io < 7; io++) {
#pragma unroll
            for (int s = 0; s < 4; s++) {
                const int it = io * 4 + s;
                mbar_wait(bar + B_F2 + 8 * s, io & 1);
                if (tid == 512 && s == 0 && (io == 0 || io == 4)) TLM(1, 14 + io / 4);
                const uint64_t dA = mkdesc(SBD + OFF_R + s * 24576, 16, 1024, 1);
                const uint64_t dB = mkdesc(SBD + OFF_R + s * 24576 + 8192, 8192, 1024, 1);
                wg_fence();
#pragma unroll
                for (int kk = 0; kk < EXP_FKK; kk++) {
                    wgmma_ss_n128(acc, dA + kk * 2, dB + kk * 128);
                    if (kk < 3 && (FSER != 3 || kk == 1)) {
                        wg_commit();
                        wg_wait<0>();
                    }
                }
                wg_commit();
                if (warp < 18 && it >= 2 && it < 26) {
                    const int s2 = (s + 2) & 3;
                    mbar_wait(bar + B_E2 + 8 * s2, (io - (s < 2)) & 1);
                    if (elect()) {
                        if (warp == 16) {
                            mbar_expect(bar + B_F2 + 8 * s2, 24576);
                            tma5d_mc(sb + OFF_R + s2 * 24576 + 8192 + rank * 8192, &tm.w2, cb * 128 + rank * 64, it * 2 + 4, bar + B_F2 + 8 * s2);
                        } else {
                            asm volatile("fence.proxy.async.global;" ::: "memory");
                            tma2d(sb + OFF_R + s2 * 24576, &tm.h, it * 64 + 128, rb * 64, bar + B_F2 + 8 * s2);
                        }
                    }
                    __syncwarp();
                }
                wg_wait<1>();
                if (it >= 1 && lane < 2) mbar_arrive_cluster(bar + B_E2 + 8 * ((s + 3) & 3), lane);
            }
        }
        wg_wait<0>();
        if (lane < 2) mbar_arrive_cluster(bar + B_E2 + 8 * 3, lane);
        pin<64>(acc);
        if (tid == 576) gEpoch[blockIdx.x] = epoch();
        if (warp == 16) {
            if (lane == 0) TLM(1, 16);
            for (int s = 0; s < 4; s++) mbar_wait(bar + B_E2 + 8 * s, 0);
            if (elect()) {
#pragma unroll
                for (int i = 0; i < 6; i++) tma2d_mc(sb + OFF_R + i * 16384 + rank * 8192, &tm.wo, cb * 128 + rank * 64, i * 64, bar + B_T + 8 * i);
            }
            __syncwarp();
        }
        {
            const int lr = (warp - 16) * 16 + g;
            const uint32_t pa = pk_bf16(ldcg_f(gG + rb * 64 + lr), ldcg_f(gG + rb * 64 + lr + 8));
            if (t == 0) {
                sts32(sb + OFF_G + lr * 4, __byte_perm(pa, pa, 0x1010));
                sts32(sb + OFF_G + lr * 4 + 32, __byte_perm(pa, pa, 0x3232));
            }
            __syncwarp();
            if (lane == 0) mbar_arrive(bar + B_G2);
            const float ga = bf_lo(pa), gb = bf_hi(pa);
            const float g0 = 1.f - ga, g1 = 1.f - gb;
#pragma unroll
            for (int j = 0; j < 16; j++) {
                const uint32_t bv = lds32(sb + OFF_BIAS + 896 + j * 16 + t * 4);
                acc[4 * j] = fmaf(acc[4 * j], 0.5f, bf_lo(bv)) * g0;
                acc[4 * j + 1] = fmaf(acc[4 * j + 1], 0.5f, bf_hi(bv)) * g0;
                acc[4 * j + 2] = fmaf(acc[4 * j + 2], 0.5f, bf_lo(bv)) * g1;
                acc[4 * j + 3] = fmaf(acc[4 * j + 3], 0.5f, bf_hi(bv)) * g1;
            }
            pin<64>(acc);
        }
        if (tid == 512) TLM(1, 17);
        {
            uint32_t todo = 255;
#pragma unroll 1
            for (int n = 0; todo; n++) {
                if (warp == 16) {
                    uint32_t rdy;
                    int spins = 0;
                    do {
                        uint32_t ok = 0;
                        if (lane < 8)
                            asm volatile("{\n.reg .pred p;\nmbarrier.test_wait.parity.shared::cta.b64 p, [%1], 0;\nselp.u32 %0, 1, 0, p;\n}"
                                         : "=r"(ok) : "r"(bar + B_T + 8 * lane) : "memory");
                        rdy = __ballot_sync(0xffffffffu, ok) & todo;
                        if (!rdy) { __nanosleep(n ? 20 : 100); if (++spins > (1 << 22)) __trap(); }
                    } while (!rdy);
                    if (lane == 0) sts32(sb + OFF_G + 260 + (n & 1) * 4, rdy);
                }
                bar_sync(15, 128);
                uint32_t rdy = __shfl_sync(0xffffffffu, lds32(sb + OFF_G + 260 + (n & 1) * 4), 0);
                todo &= ~rdy;
#pragma unroll 1
                while (rdy) {
                    const int i = __ffs(rdy) - 1;
                    rdy &= rdy - 1;
                    const uint64_t dA = mkdesc(SBD, 16, 1024, 1) + i * 512;
                    const uint64_t dB = mkdesc(SBD + OFF_R, 8192, 1024, 1) + (i < 6 ? i * 1024 : (i - 10) * 1024);
                    wg_fence();
#pragma unroll
                    for (int kk = 0; kk < 4; kk++) wgmma_ss_n128(acc, dA + kk * 2, dB + kk * 128);
                    wg_commit();
                }
            }
        }
        wg_wait<0>();
        pin<64>(acc);
        if (tid == 512) TLM(1, 18);
        {
            const uint32_t st = sb + 98304 + (warp - 16) * 4352;
            const uint32_t wa = st + (lane & 15) * 272 + (lane >> 4) * 16;
#pragma unroll
            for (int j = 0; j < 8; j++)
                asm volatile("stmatrix.sync.aligned.m8n8.x4.shared.b16 [%0], {%1, %2, %3, %4};" ::"r"(wa + j * 32),
                             "r"(pk_bf16(acc[8 * j], acc[8 * j + 1])), "r"(pk_bf16(acc[8 * j + 2], acc[8 * j + 3])),
                             "r"(pk_bf16(acc[8 * j + 4], acc[8 * j + 5])), "r"(pk_bf16(acc[8 * j + 6], acc[8 * j + 7])) : "memory");
            __syncwarp();
            __nv_bfloat16* op = out + (size_t)(rb * 64 + (warp - 16) * 16 + (lane >> 4)) * DM + cb * 128 + (lane & 15) * 8;
#pragma unroll
            for (int j = 0; j < 8; j++) {
                uint4 v;
                asm volatile("ld.shared.v4.u32 {%0, %1, %2, %3}, [%4];" : "=r"(v.x), "=r"(v.y), "=r"(v.z), "=r"(v.w)
                             : "r"(st + (2 * j + (lane >> 4)) * 272 + (lane & 15) * 16));
                *(uint4*)(op + (size_t)j * 2 * DM) = v;
            }
        }
        if (tid == 512) TLM(1, 19);
        TL_DUMP();
    }
}

typedef CUresult (*EncodeFn)(CUtensorMap*, CUtensorMapDataType, cuuint32_t, void*, const cuuint64_t*, const cuuint64_t*, const cuuint32_t*,
                             const cuuint32_t*, CUtensorMapInterleave, CUtensorMapSwizzle, CUtensorMapL2promotion, CUtensorMapFloatOOBfill);

static void make_map(EncodeFn enc, CUtensorMap* m, const void* p, int rank, const cuuint64_t* dims, const cuuint64_t* strides,
                     const cuuint32_t* box, CUtensorMapSwizzle swz) {
    const cuuint32_t es[5] = {1, 1, 1, 1, 1};
    enc(m, CU_TENSOR_MAP_DATA_TYPE_BFLOAT16, rank, (void*)p, dims, strides, box, es, CU_TENSOR_MAP_INTERLEAVE_NONE, swz,
        CU_TENSOR_MAP_L2_PROMOTION_L2_128B, CU_TENSOR_MAP_FLOAT_OOB_FILL_NONE);
}

extern "C" void kernel_launch(void* const* d_in, const int* in_sizes, int n_in, void* d_out, int out_size) {
    const __nv_bfloat16* x = (const __nv_bfloat16*)d_in[0];
    const __nv_bfloat16* wqkv = (const __nv_bfloat16*)d_in[1];
    const __nv_bfloat16* wo = (const __nv_bfloat16*)d_in[2];
    const __nv_bfloat16* w1 = (const __nv_bfloat16*)d_in[4];
    const __nv_bfloat16* b1 = (const __nv_bfloat16*)d_in[5];
    const __nv_bfloat16* w2 = (const __nv_bfloat16*)d_in[6];
    const __nv_bfloat16* b2 = (const __nv_bfloat16*)d_in[7];
    const __nv_bfloat16* gate = (const __nv_bfloat16*)d_in[8];

    void* fp = nullptr;
    cudaDriverEntryPointQueryResult qr;
    cudaGetDriverEntryPoint("cuTensorMapEncodeTiled", &fp, cudaEnableDefault, &qr);
    EncodeFn enc = (EncodeFn)fp;
    void *pH, *pKV;
    cudaGetSymbolAddress(&pH, gH);
    cudaGetSymbolAddress(&pKV, gKV);

    Maps tm;
    const CUtensorMapSwizzle S128 = CU_TENSOR_MAP_SWIZZLE_128B, S64 = CU_TENSOR_MAP_SWIZZLE_64B;
    { cuuint64_t d[2] = {DM, SEQ}, s[1] = {DM * 2}; cuuint32_t b[2] = {64, 128}; make_map(enc, &tm.x, x, 2, d, s, b, S128); }
    { cuuint64_t d[3] = {DM, DM, 3}, s[2] = {3 * DM * 2, DM * 2}; cuuint32_t b[3] = {64, 32, 2}; make_map(enc, &tm.kv, wqkv, 3, d, s, b, S128); }
    { cuuint64_t d[3] = {32, DM, 3 * DM / 32}, s[2] = {3 * DM * 2, 64}; cuuint32_t b[3] = {32, 32, 2}; make_map(enc, &tm.q, wqkv, 3, d, s, b, S64); }
    { cuuint64_t d[3] = {32, DM, FF / 32}, s[2] = {FF * 2, 64}; cuuint32_t b[3] = {32, 32, 1}; make_map(enc, &tm.f1, w1, 3, d, s, b, S64); }
    { cuuint64_t d[3] = {32, DM, FF / 32}, s[2] = {FF * 2, 64}; cuuint32_t b[3] = {32, 32, 3}; make_map(enc, &tm.f3, w1, 3, d, s, b, S64); }
    { cuuint64_t d[2] = {FF, SEQ}, s[1] = {FF * 2}; cuuint32_t b[2] = {64, 64}; make_map(enc, &tm.h, pH, 2, d, s, b, S128); }
    { cuuint64_t d[5] = {DM, 2, 4, 4, FF / 32}, s[4] = {1024, 8 * 1024, 2 * 1024, 32 * 1024}; cuuint32_t b[5] = {64, 2, 4, 4, 2};
      make_map(enc, &tm.w2, w2, 5, d, s, b, S128); }
    { cuuint64_t d[2] = {DM, DM}, s[1] = {DM * 2}; cuuint32_t b[2] = {64, 64}; make_map(enc, &tm.wo, wo, 2, d, s, b, S128); }

    { cuuint64_t d[3] = {32, SEQ, FF / 32}, s[2] = {FF * 2, 64}; cuuint32_t b[3] = {32, 64, 1}; make_map(enc, &tm.hs, pH, 3, d, s, b, CU_TENSOR_MAP_SWIZZLE_NONE); }
    { cuuint64_t d[5] = {64, 16, 16, 2, 2 * NH}, s[4] = {4096, 128, 2048, 65536}; cuuint32_t b[5] = {64, 8, 2, 2, 1};
      make_map(enc, &tm.kvs, pKV, 5, d, s, b, S128); }
    cudaFuncSetAttribute(fused_kernel, cudaFuncAttributeMaxDynamicSharedMemorySize, TL_SMEM);
    fused_kernel<<<128, 640, TL_SMEM, cudaStreamPerThread>>>(tm, x, wqkv, wo, w1, b1, w2, b2, gate, (__nv_bfloat16*)d_out, 0xffffffffu);
}
```

```cpp
#include <cuda_runtime.h>
#include <cuda_bf16.h>
#include <cuda_fp16.h>
#include <cuda.h>
#include <stdint.h>

#define SEQ 2048
#define DM 512
#define FF 1792
#define NH 32

__device__ __align__(1024) uint8_t gQ[NH * SEQ * 32];
__device__ __align__(1024) uint8_t gKV[NH * SEQ * 64];
__device__ __align__(1024) __nv_bfloat16 gH[SEQ * FF];
__device__ __align__(1024) uint4 gO[32 * NH * 128];
__device__ float gG[SEQ];
__device__ float gN[3 * 8 * 128];
__device__ unsigned int gCntQ[8 * 32];
__device__ unsigned int gCntH[32 * 32];
__device__ unsigned int gEpoch[128];

__device__ __forceinline__ uint32_t smem_u32(const void* p) { return (uint32_t)__cvta_generic_to_shared(p); }
__device__ __forceinline__ void mbar_init(uint32_t a, uint32_t c) { asm volatile("mbarrier.init.shared::cta.b64 [%0], %1;" ::"r"(a), "r"(c)); }
__device__ __forceinline__ void mbar_expect(uint32_t a, uint32_t b) { asm volatile("mbarrier.arrive.expect_tx.shared::cta.b64 _, [%0], %1;" ::"r"(a), "r"(b) : "memory"); }
__device__ __forceinline__ void mbar_arrive(uint32_t a) { asm volatile("mbarrier.arrive.shared::cta.b64 _, [%0];" ::"r"(a) : "memory"); }
__device__ __forceinline__ void mbar_wait(uint32_t a, uint32_t ph) {
    asm volatile("{\n.reg .pred p;\n.reg .u32 n;\nmov.u32 n, 0;\nW_%=:\nmbarrier.try_wait.parity.shared::cta.b64 p, [%0], %1;\n@p bra D_%=;\n"
                 "add.u32 n, n, 1;\nsetp.lt.u32 p, n, 0x400000;\n@p bra W_%=;\ntrap;\nD_%=:\n}" ::"r"(a), "r"(ph) : "memory");
}
__device__ __forceinline__ void mbar_arrive_cluster(uint32_t a, uint32_t cta) {
    asm volatile("{\n.reg .b32 r;\nmapa.shared::cluster.u32 r, %0, %1;\nmbarrier.arrive.shared::cluster.b64 _, [r];\n}" ::"r"(a), "r"(cta) : "memory");
}
__device__ __forceinline__ void bar_sync(int id, int n) { asm volatile("bar.sync %0, %1;" ::"r"(id), "r"(n) : "memory"); }
__device__ __forceinline__ void bar_arrive(int id, int n) { asm volatile("bar.arrive %0, %1;" ::"r"(id), "r"(n) : "memory"); }
__device__ __forceinline__ uint32_t cluster_rank() { uint32_t r; asm("mov.u32 %0, %%cluster_ctarank;" : "=r"(r)); return r; }
__device__ __forceinline__ void cnt_add(unsigned int* c) { asm volatile("red.release.gpu.global.add.u32 [%0], 1;" ::"l"(c) : "memory"); }
__device__ __forceinline__ void cnt_wait(const unsigned int* c, uint32_t target) {
    uint32_t v;
    int spins = 0;
    while (true) {
        asm volatile("ld.acquire.gpu.global.u32 %0, [%1];" : "=r"(v) : "l"(c) : "memory");
        if ((int)(v - target) >= 0) break;
        if (++spins > (1 << 22)) __trap();
        __nanosleep(40);
    }
}
__device__ __forceinline__ void tma2d(uint32_t dst, const CUtensorMap* m, int c0, int c1, uint32_t bar) {
    asm volatile("cp.async.bulk.tensor.2d.shared::cluster.global.mbarrier::complete_tx::bytes [%0], [%1, {%3, %4}], [%2];"
                 ::"r"(dst), "l"(m), "r"(bar), "r"(c0), "r"(c1) : "memory");
}
__device__ __forceinline__ void tma2d_mc(uint32_t dst, const CUtensorMap* m, int c0, int c1, uint32_t bar) {
    asm volatile("cp.async.bulk.tensor.2d.shared::cluster.global.mbarrier::complete_tx::bytes.multicast::cluster [%0], [%1, {%3, %4}], [%2], %5;"
                 ::"r"(dst), "l"(m), "r"(bar), "r"(c0), "r"(c1), "h"((uint16_t)3) : "memory");
}
__device__ __forceinline__ void tma3d_mc(uint32_t dst, const CUtensorMap* m, int c0, int c1, int c2, uint32_t bar) {
    asm volatile("cp.async.bulk.tensor.3d.shared::cluster.global.mbarrier::complete_tx::bytes.multicast::cluster [%0], [%1, {%3, %4, %5}], [%2], %6;"
                 ::"r"(dst), "l"(m), "r"(bar), "r"(c0), "r"(c1), "r"(c2), "h"((uint16_t)3) : "memory");
}
__device__ __forceinline__ void tma5d_mc(uint32_t dst, const CUtensorMap* m, int c0, int c4, uint32_t bar) {
    asm volatile("cp.async.bulk.tensor.5d.shared::cluster.global.mbarrier::complete_tx::bytes.multicast::cluster [%0], [%1, {%3, %5, %5, %5, %4}], [%2], %6;"
                 ::"r"(dst), "l"(m), "r"(bar), "r"(c0), "r"(c4), "r"(0), "h"((uint16_t)3) : "memory");
}
__device__ __forceinline__ void bulk_mc(uint32_t dst, const void* src, uint32_t bytes, uint32_t bar) {
    asm volatile("cp.async.bulk.shared::cluster.global.mbarrier::complete_tx::bytes.multicast::cluster [%0], [%1], %2, [%3], %4;"
                 ::"r"(dst), "l"(src), "r"(bytes), "r"(bar), "h"((uint16_t)3) : "memory");
}
__device__ __forceinline__ void tma3d_st(const CUtensorMap* m, uint32_t src, int c0, int c1, int c2) {
    asm volatile("cp.async.bulk.tensor.3d.global.shared::cta.bulk_group [%0, {%2, %3, %4}], [%1];" ::"l"(m), "r"(src), "r"(c0), "r"(c1), "r"(c2) : "memory");
}
__device__ __forceinline__ void tma5d_st(const CUtensorMap* m, uint32_t src, int c1, int c2, int c4) {
    asm volatile("cp.async.bulk.tensor.5d.global.shared::cta.bulk_group [%0, {%5, %2, %3, %5, %4}], [%1];"
                 ::"l"(m), "r"(src), "r"(c1), "r"(c2), "r"(c4), "r"(0) : "memory");
}
__device__ __forceinline__ void bulk_st(void* dst, uint32_t src, uint32_t bytes) {
    asm volatile("cp.async.bulk.global.shared::cta.bulk_group [%0], [%1], %2;" ::"l"(dst), "r"(src), "r"(bytes) : "memory");
}
__device__ __forceinline__ void sts64(uint32_t a, uint32_t x, uint32_t y) { asm volatile("st.shared.v2.u32 [%0], {%1, %2};" ::"r"(a), "r"(x), "r"(y) : "memory"); }
__device__ __forceinline__ void sts128(uint32_t a, const uint32_t* v) {
    asm volatile("st.shared.v4.u32 [%0], {%1, %2, %3, %4};" ::"r"(a), "r"(v[0]), "r"(v[1]), "r"(v[2]), "r"(v[3]) : "memory");
}
__device__ __forceinline__ void l2_prefetch(const void* src, uint32_t bytes) {
    asm volatile("cp.async.bulk.prefetch.L2.global [%0], %1;" ::"l"(src), "r"(bytes) : "memory");
}
__device__ __forceinline__ void map_prefetch(const CUtensorMap* m) { asm volatile("prefetch.tensormap [%0];" ::"l"(m) : "memory"); }
__device__ __forceinline__ void wg_fence() { asm volatile("wgmma.fence.sync.aligned;" ::: "memory"); }
__device__ __forceinline__ void wg_commit() { asm volatile("wgmma.commit_group.sync.aligned;" ::: "memory"); }
template <int N> __device__ __forceinline__ void wg_wait() { asm volatile("wgmma.wait_group.sync.aligned %0;" ::"n"(N) : "memory"); }
template <int N> __device__ __forceinline__ void pin(float* s) {
#pragma unroll
    for (int i = 0; i < N; i++) asm volatile("" : "+f"(s[i])::"memory");
}
template <int N> __device__ __forceinline__ void pin(uint32_t* s) {
#pragma unroll
    for (int i = 0; i < N; i++) asm volatile("" : "+r"(s[i])::"memory");
}
__device__ __forceinline__ uint64_t mkdesc(uint32_t addr, uint32_t lbo, uint32_t sbo, uint32_t swz) {
    return (uint64_t)((addr & 0x3FFFF) >> 4) | ((uint64_t)(lbo >> 4) << 16) | ((uint64_t)(sbo >> 4) << 32) | ((uint64_t)swz << 62);
}
__device__ __forceinline__ float ex2f(float x) { float y; asm("ex2.approx.ftz.f32 %0, %1;" : "=f"(y) : "f"(x)); return y; }
__device__ __forceinline__ float tanhf_(float x) { float y; asm("tanh.approx.f32 %0, %1;" : "=f"(y) : "f"(x)); return y; }
__device__ __forceinline__ uint32_t pk_bf16(float lo, float hi) { uint32_t r; asm("cvt.rn.bf16x2.f32 %0, %1, %2;" : "=r"(r) : "f"(hi), "f"(lo)); return r; }
__device__ __forceinline__ uint32_t pk_f16(float lo, float hi) { uint32_t r; asm("cvt.rn.f16x2.f32 %0, %1, %2;" : "=r"(r) : "f"(hi), "f"(lo)); return r; }
__device__ __forceinline__ float bf_lo(uint32_t v) { return __uint_as_float(v << 16); }
__device__ __forceinline__ float bf_hi(uint32_t v) { return __uint_as_float(v & 0xffff0000u); }
__device__ __forceinline__ float dot8(const uint4& a, const uint4& b) {
    return fmaf(bf_lo(a.x), bf_lo(b.x), fmaf(bf_hi(a.x), bf_hi(b.x), fmaf(bf_lo(a.y), bf_lo(b.y), bf_hi(a.y) * bf_hi(b.y)))) +
           fmaf(bf_lo(a.z), bf_lo(b.z), fmaf(bf_hi(a.z), bf_hi(b.z), fmaf(bf_lo(a.w), bf_lo(b.w), bf_hi(a.w) * bf_hi(b.w))));
}
__device__ __forceinline__ uint32_t epoch() {
    uint32_t v;
    asm volatile("ld.global.u32 %0, [%1];" : "=r"(v) : "l"(gEpoch + blockIdx.x));
    return v + 1;
}
__device__ __forceinline__ float ldcg_f(const float* p) { return __ldcg(p); }

extern __shared__ __align__(1024) uint8_t smem_raw[];
#define TLM(k, slot) do {} while (0)
#define TLC(k, slot) do {} while (0)
#define TL_INIT() do {} while (0)
#define TL_DUMP() do {} while (0)
#define TL_SMEM SMEM_BYTES

__device__ __forceinline__ void wgmma_ss_n128(float* d, uint64_t da, uint64_t db) {
    asm volatile("wgmma.mma_async.sync.aligned.m64n128k16.f32.bf16.bf16 {"
        "%0, %1, %2, %3, %4, %5, %6, %7, %8, %9, %10, %11, %12, %13, %14, %15,"
        "%16, %17, %18, %19, %20, %21, %22, %23, %24, %25, %26, %27, %28, %29, %30, %31,"
        "%32, %33, %34, %35, %36, %37, %38, %39, %40, %41, %42, %43, %44, %45, %46, %47,"
        "%48, %49, %50, %51, %52, %53, %54, %55, %56, %57, %58, %59, %60, %61, %62, %63}, %64, %65, 1, 1, 1, 0, 1;\n"
        :
        "+f"(d[0]), "+f"(d[1]), "+f"(d[2]), "+f"(d[3]), "+f"(d[4]), "+f"(d[5]), "+f"(d[6]), "+f"(d[7]),
        "+f"(d[8]), "+f"(d[9]), "+f"(d[10]), "+f"(d[11]), "+f"(d[12]), "+f"(d[13]), "+f"(d[14]), "+f"(d[15]),
        "+f"(d[16]), "+f"(d[17]), "+f"(d[18]), "+f"(d[19]), "+f"(d[20]), "+f"(d[21]), "+f"(d[22]), "+f"(d[23]),
        "+f"(d[24]), "+f"(d[25]), "+f"(d[26]), "+f"(d[27]), "+f"(d[28]), "+f"(d[29]), "+f"(d[30]), "+f"(d[31]),
        "+f"(d[32]), "+f"(d[33]), "+f"(d[34]), "+f"(d[35]), "+f"(d[36]), "+f"(d[37]), "+f"(d[38]), "+f"(d[39]),
        "+f"(d[40]), "+f"(d[41]), "+f"(d[42]), "+f"(d[43]), "+f"(d[44]), "+f"(d[45]), "+f"(d[46]), "+f"(d[47]),
        "+f"(d[48]), "+f"(d[49]), "+f"(d[50]), "+f"(d[51]), "+f"(d[52]), "+f"(d[53]), "+f"(d[54]), "+f"(d[55]),
        "+f"(d[56]), "+f"(d[57]), "+f"(d[58]), "+f"(d[59]), "+f"(d[60]), "+f"(d[61]), "+f"(d[62]), "+f"(d[63])
        : "l"(da), "l"(db));
}
__device__ __forceinline__ void wgmma_ss_n96(float* d, uint64_t da, uint64_t db) {
    asm volatile("wgmma.mma_async.sync.aligned.m64n96k16.f32.bf16.bf16 {"
        "%0, %1, %2, %3, %4, %5, %6, %7, %8, %9, %10, %11, %12, %13, %14, %15,"
        "%16, %17, %18, %19, %20, %21, %22, %23, %24, %25, %26, %27, %28, %29, %30, %31,"
        "%32, %33, %34, %35, %36, %37, %38, %39, %40, %41, %42, %43, %44, %45, %46, %47}, %48, %49, 1, 1, 1, 0, 1;\n"
        :
        "+f"(d[0]), "+f"(d[1]), "+f"(d[2]), "+f"(d[3]), "+f"(d[4]), "+f"(d[5]), "+f"(d[6]), "+f"(d[7]),
        "+f"(d[8]), "+f"(d[9]), "+f"(d[10]), "+f"(d[11]), "+f"(d[12]), "+f"(d[13]), "+f"(d[14]), "+f"(d[15]),
        "+f"(d[16]), "+f"(d[17]), "+f"(d[18]), "+f"(d[19]), "+f"(d[20]), "+f"(d[21]), "+f"(d[22]), "+f"(d[23]),
        "+f"(d[24]), "+f"(d[25]), "+f"(d[26]), "+f"(d[27]), "+f"(d[28]), "+f"(d[29]), "+f"(d[30]), "+f"(d[31]),
        "+f"(d[32]), "+f"(d[33]), "+f"(d[34]), "+f"(d[35]), "+f"(d[36]), "+f"(d[37]), "+f"(d[38]), "+f"(d[39]),
        "+f"(d[40]), "+f"(d[41]), "+f"(d[42]), "+f"(d[43]), "+f"(d[44]), "+f"(d[45]), "+f"(d[46]), "+f"(d[47])
        : "l"(da), "l"(db));
}
__device__ __forceinline__ void wgmma_ss_n64(float* d, uint64_t da, uint64_t db) {
    asm volatile("wgmma.mma_async.sync.aligned.m64n64k16.f32.bf16.bf16 {"
        "%0, %1, %2, %3, %4, %5, %6, %7, %8, %9, %10, %11, %12, %13, %14, %15,"
        "%16, %17, %18, %19, %20, %21, %22, %23, %24, %25, %26, %27, %28, %29, %30, %31}, %32, %33, 1, 1, 1, 0, 1;\n"
        :
        "+f"(d[0]), "+f"(d[1]), "+f"(d[2]), "+f"(d[3]), "+f"(d[4]), "+f"(d[5]), "+f"(d[6]), "+f"(d[7]),
        "+f"(d[8]), "+f"(d[9]), "+f"(d[10]), "+f"(d[11]), "+f"(d[12]), "+f"(d[13]), "+f"(d[14]), "+f"(d[15]),
        "+f"(d[16]), "+f"(d[17]), "+f"(d[18]), "+f"(d[19]), "+f"(d[20]), "+f"(d[21]), "+f"(d[22]), "+f"(d[23]),
        "+f"(d[24]), "+f"(d[25]), "+f"(d[26]), "+f"(d[27]), "+f"(d[28]), "+f"(d[29]), "+f"(d[30]), "+f"(d[31])
        : "l"(da), "l"(db));
}
__device__ __forceinline__ void wgmma_qk_f16_acc(float* d, const uint32_t* a, uint64_t db) {
    asm volatile("wgmma.mma_async.sync.aligned.m64n64k16.f32.f16.f16 {"
        "%0, %1, %2, %3, %4, %5, %6, %7, %8, %9, %10, %11, %12, %13, %14, %15,"
        "%16, %17, %18, %19, %20, %21, %22, %23, %24, %25, %26, %27, %28, %29, %30, %31}, {%32, %33, %34, %35}, %36, 1, 1, 1, 0;\n"
        :
        "+f"(d[0]), "+f"(d[1]), "+f"(d[2]), "+f"(d[3]), "+f"(d[4]), "+f"(d[5]), "+f"(d[6]), "+f"(d[7]),
        "+f"(d[8]), "+f"(d[9]), "+f"(d[10]), "+f"(d[11]), "+f"(d[12]), "+f"(d[13]), "+f"(d[14]), "+f"(d[15]),
        "+f"(d[16]), "+f"(d[17]), "+f"(d[18]), "+f"(d[19]), "+f"(d[20]), "+f"(d[21]), "+f"(d[22]), "+f"(d[23]),
        "+f"(d[24]), "+f"(d[25]), "+f"(d[26]), "+f"(d[27]), "+f"(d[28]), "+f"(d[29]), "+f"(d[30]), "+f"(d[31])
        : "r"(a[0]), "r"(a[1]), "r"(a[2]), "r"(a[3]), "l"(db));
}
__device__ __forceinline__ void wgmma_qk_bf16_zero(float* d, const uint32_t* a, uint64_t db) {
    asm volatile("wgmma.mma_async.sync.aligned.m64n64k16.f32.bf16.bf16 {"
        "%0, %1, %2, %3, %4, %5, %6, %7, %8, %9, %10, %11, %12, %13, %14, %15,"
        "%16, %17, %18, %19, %20, %21, %22, %23, %24, %25, %26, %27, %28, %29, %30, %31}, {%32, %33, %34, %35}, %36, 0, 1, 1, 0;\n"
        :
        "=f"(d[0]), "=f"(d[1]), "=f"(d[2]), "=f"(d[3]), "=f"(d[4]), "=f"(d[5]), "=f"(d[6]), "=f"(d[7]),
        "=f"(d[8]), "=f"(d[9]), "=f"(d[10]), "=f"(d[11]), "=f"(d[12]), "=f"(d[13]), "=f"(d[14]), "=f"(d[15]),
        "=f"(d[16]), "=f"(d[17]), "=f"(d[18]), "=f"(d[19]), "=f"(d[20]), "=f"(d[21]), "=f"(d[22]), "=f"(d[23]),
        "=f"(d[24]), "=f"(d[25]), "=f"(d[26]), "=f"(d[27]), "=f"(d[28]), "=f"(d[29]), "=f"(d[30]), "=f"(d[31])
        : "r"(a[0]), "r"(a[1]), "r"(a[2]), "r"(a[3]), "l"(db));
}
__device__ __forceinline__ void wgmma_pv(float* d, const uint32_t* a, uint64_t db) {
    asm volatile("wgmma.mma_async.sync.aligned.m64n24k16.f32.bf16.bf16 {"
        "%0, %1, %2, %3, %4, %5, %6, %7, %8, %9, %10, %11}, {%12, %13, %14, %15}, %16, 1, 1, 1, 1;\n"
        :
        "+f"(d[0]), "+f"(d[1]), "+f"(d[2]), "+f"(d[3]), "+f"(d[4]), "+f"(d[5]), "+f"(d[6]), "+f"(d[7]),
        "+f"(d[8]), "+f"(d[9]), "+f"(d[10]), "+f"(d[11])
        : "r"(a[0]), "r"(a[1]), "r"(a[2]), "r"(a[3]), "l"(db));
}

template <int N> __device__ __forceinline__ void wgmma_ss(float* d, uint64_t a, uint64_t b) {
    if (N == 128) wgmma_ss_n128(d, a, b);
    if (N == 96) wgmma_ss_n96(d, a, b);
    if (N == 64) wgmma_ss_n64(d, a, b);
}

#define OFF_R 131072
#define OFF_ONE 229376
#define OFF_BAR 229888
#define OFF_BIAS (OFF_BAR + 736)
#define OFF_G (OFF_BIAS + 1152)
#define SMEM_BYTES (OFF_G + 272)
#define SBD 1024u
#define B_X 0
#define B_F1 416
#define B_E1 64
#define B_XD 672
#define B_KV 160
#define B_F2 224
#define B_E2 256
#define B_T 288
#define B_DONE 352
#define B_G 360
#define B_G2 368
#define B_G3 376
#define B_SF 384
#define B_BI 400
#define B_DONE2 112
#define B_SF2 408
#define NR 6

#define PF 1
#define PFX 0
#define PACE 1
#define FSER 1
#define MERGE 1
#define POLLN 3
#define EXP_FKK 4
#define QSCALE 0.36067376022224085f
#define MAGIC 445.41763f
#define FORCE_IMAD
#define NMUFU 5
#define VSTEP ((uint64_t)((long long)32 - ((long long)32 << 16)))

#define XMASK 0x0D55u
#define KVMASK 0x1D55u
__host__ __device__ constexpr int strm_pos(int pass, int i) {
    if (pass == 1 || pass == 2) return 8 + 8 * pass + i;
    int n = 0;
    for (int p = 0; p < 16; p++)
        if ((int)((KVMASK >> p) & 1) == (pass == 3)) { if (n == i) return p; n++; }
    return 0;
}
__host__ __device__ constexpr uint32_t strm_code(int pass) {
    uint32_t c = 0;
    for (int i = 0; i < 7; i++) c |= (uint32_t)(strm_pos(pass, i + 1) - strm_pos(pass, i)) << (4 * i);
    return c;
}

template <int N, int SUB, int KST, int LBO, int SBO, int SWZ>
__device__ __forceinline__ void gemm_pass(float* acc, uint32_t bar, uint64_t dA, int lane, uint32_t pos, uint32_t code, int barNext, bool waitx, bool last) {
    uint32_t prev = 0, slot = pos % NR;
#pragma unroll 1
    for (int i = 0; i < 8; i++) {
        if (waitx) mbar_wait(bar + B_X + 8 * i, 0);
        mbar_wait(bar + B_F1 + 8 * pos, 0);
        const uint64_t dB = mkdesc(SBD + OFF_R, LBO, SBO, SWZ) + slot * 1024;
        wg_fence();
        wgmma_ss<N>(acc, dA, dB);
        wgmma_ss<N>(acc, dA + 2, dB + KST / 16);
        wg_commit();
        wg_wait<1>();
        if (i > 0 && lane < 2) mbar_arrive_cluster(prev, lane);
        wgmma_ss<N>(acc, dA + 4, dB + SUB / 16);
        wgmma_ss<N>(acc, dA + 6, dB + (SUB + KST) / 16);
        wg_commit();
        prev = last ? bar + B_XD + 8 * i : bar + B_E1 + 8 * slot;
        pos += code & 15;
        slot += code & 15;
        if (slot >= NR) slot -= NR;
        code >>= 4;
        dA += 1024;
    }
    if (barNext) bar_arrive(barNext, 512);
    wg_wait<0>();
    if (lane < 2) mbar_arrive_cluster(prev, lane);
    pin<N / 2>(acc);
}

__device__ __forceinline__ uint32_t lds32(uint32_t a) { uint32_t v; asm volatile("ld.shared.u32 %0, [%1];" : "=r"(v) : "r"(a)); return v; }
__device__ __forceinline__ bool elect() {
    uint32_t p;
    asm volatile("{\n.reg .pred p;\nelect.sync _|p, 0xffffffff;\nselp.u32 %0, 1, 0, p;\n}" : "=r"(p));
    return p;
}

template <int G0, int G1> __device__ __forceinline__ void gelu_pack(const float* acc, uint32_t bias, uint32_t* out) {
#pragma unroll
    for (int G = G0; G < G1; G++) {
        uint32_t* o = out + 8 * G;
#pragma unroll
        for (int j = 0; j < 4; j++) {
            float bv[2];
            asm volatile("ld.shared.v2.f32 {%0, %1}, [%2];" : "=f"(bv[0]), "=f"(bv[1]) : "r"(bias + G * 128 + j * 32));
            float y[4];
#pragma unroll
            for (int i = 0; i < 4; i++) {
                const float h = acc[16 * G + 4 * j + i] + bv[i & 1];
                const float z = h * fmaf(h * h, 0.035677408136300125f, 0.7978845608028654f);
                y[i] = fmaf(h, tanhf_(z), h);
            }
            o[j] = pk_bf16(y[0], y[1]);
            o[4 + j] = pk_bf16(y[2], y[3]);
        }
    }
}

__device__ __forceinline__ float norm_bound(const float* v, float sc) {
    uint32_t m = 0;
#pragma unroll
    for (int h = 0; h < 4; h++) {
        const float* u = v + 8 * h;
        m = max(m, __float_as_uint(fmaf(u[0], u[0], fmaf(u[1], u[1], fmaf(u[4], u[4], u[5] * u[5])))));
        m = max(m, __float_as_uint(fmaf(u[2], u[2], fmaf(u[3], u[3], fmaf(u[6], u[6], u[7] * u[7])))));
    }
#pragma unroll
    for (int o = 4; o < 32; o <<= 1) m = max(m, __shfl_xor_sync(0xffffffffu, m, o));
    float f = __uint_as_float(m);
    f += __shfl_xor_sync(0xffffffffu, f, 1);
    f += __shfl_xor_sync(0xffffffffu, f, 2);
    return f * sc;
}

__device__ __forceinline__ uint32_t exp2_pair(float a, float b, uint32_t m1) {
    const uint32_t w = __byte_perm(__float_as_uint(a), __float_as_uint(b), 0x6521);
    uint32_t m, r;
    asm("lop3.b32 %0, %1, 0x007f007f, 0x9f809f80, 0xEA;" : "=r"(m) : "r"(w));
    const uint32_t e = m * m1 + w;
    asm("fma.rn.bf16x2 %0, %1, %2, %3;" : "=r"(r) : "r"(w), "r"(m), "r"(e));
    return r;
}

__device__ __forceinline__ void store_o(const float* o, uint4* dst, uint32_t par) {
    const float s0 = __fdividef(1.f, o[8]), s1 = __fdividef(1.f, o[10]);
    const uint32_t d0 = (pk_bf16(o[0] * s0, o[1] * s0) & ~1u) | par;
    asm volatile("{\n.reg .b128 t;\nmov.b128 t, {%0, %1, %2, %3};\nst.relaxed.gpu.global.b128 [%4], t;\n}" ::"r"(d0),
                 "r"(pk_bf16(o[4] * s0, o[5] * s0)), "r"(pk_bf16(o[2] * s1, o[3] * s1)), "r"(pk_bf16(o[6] * s1, o[7] * s1)), "l"(dst) : "memory");
}
__device__ __forceinline__ uint4 load_o(const uint4* src) {
    uint4 v;
    asm volatile("{\n.reg .b128 t;\nld.relaxed.gpu.global.b128 t, [%4];\nmov.b128 {%0, %1, %2, %3}, t;\n}"
                 : "=r"(v.x), "=r"(v.y), "=r"(v.z), "=r"(v.w) : "l"(src) : "memory");
    return v;
}
__device__ __forceinline__ uint32_t bmul2(uint32_t a, uint32_t b) { uint32_t r; asm("mul.rn.bf16x2 %0, %1, %2;" : "=r"(r) : "r"(a), "r"(b)); return r; }
__device__ __forceinline__ void sts32(uint32_t a, uint32_t v) { asm volatile("st.shared.u32 [%0], %1;" ::"r"(a), "r"(v) : "memory"); }
__device__ __forceinline__ void load_q(uint32_t* q, int h, int row, int t) {
    const uint8_t* p = gQ + (size_t)h * (SEQ * 32) + (size_t)row * 32 + t * 4;
    q[0] = __ldcg((const uint32_t*)p); q[1] = __ldcg((const uint32_t*)(p + 256));
    q[2] = __ldcg((const uint32_t*)(p + 16)); q[3] = __ldcg((const uint32_t*)(p + 272));
}

template <int NT>
__device__ __forceinline__ void proj16(float (*c)[8], const __nv_bfloat16* x, const __nv_bfloat16* w, int row0, int rstep, int col, int g, int t) {
#pragma unroll
    for (int i = 0; i < NT; i++)
#pragma unroll
        for (int j = 0; j < 8; j++) c[i][j] = 0.f;
    const unsigned short* wu = (const unsigned short*)w;
#pragma unroll 1
    for (int k = 0; k < DM; k += 16) {
        uint32_t b[4];
#pragma unroll
        for (int j = 0; j < 4; j++) {
            const int kr = k + 2 * t + (j & 1) * 8, cc = col + g + (j >> 1) * 8;
            b[j] = (uint32_t)wu[(size_t)kr * (3 * DM) + cc] | ((uint32_t)wu[(size_t)(kr + 1) * (3 * DM) + cc] << 16);
        }
#pragma unroll
        for (int i = 0; i < NT; i++) {
            const __nv_bfloat16* xp = x + (size_t)(row0 + i * rstep + g) * DM + k + 2 * t;
            const uint32_t a0 = *(const uint32_t*)xp, a1 = *(const uint32_t*)(xp + 8 * DM);
            const uint32_t a2 = *(const uint32_t*)(xp + 8), a3 = *(const uint32_t*)(xp + 8 * DM + 8);
#pragma unroll
            for (int j = 0; j < 2; j++)
                asm volatile("mma.sync.aligned.m16n8k16.row.col.f32.bf16.bf16.f32 {%0,%1,%2,%3}, {%4,%5,%6,%7}, {%8,%9}, {%0,%1,%2,%3};"
                             : "+f"(c[i][4 * j]), "+f"(c[i][4 * j + 1]), "+f"(c[i][4 * j + 2]), "+f"(c[i][4 * j + 3])
                             : "r"(a0), "r"(a1), "r"(a2), "r"(a3), "r"(b[2 * j]), "r"(b[2 * j + 1]));
        }
    }
}

struct Maps { CUtensorMap x, kv, q, f1, f3, h, w2, wo, hs, kvs; };

template <int I0, int I1>
__device__ __forceinline__ void issue_stream(const Maps& tm, uint32_t sb, uint32_t rank, int nb, int mb) {
    const uint32_t bar = sb + OFF_BAR;
    const uint32_t dst = sb + OFF_R;
    const int kr = rank * 32;
#pragma unroll
    for (int it = I0; it < I1; it++) {
        const int s = it % NR;
        const uint32_t fb = bar + B_F1 + 8 * it;
        if (it >= 24 + NR) mbar_wait(bar + B_XD + 8 * (it - 24 - NR), 0);
        else if (it >= NR) mbar_wait(bar + B_E1 + 8 * s, ((it / NR) - 1) & 1);
        const int nkv = __builtin_popcount(KVMASK & ((1u << it) - 1));
        if (it < 16 && ((KVMASK >> it) & 1)) {
            tma3d_mc(dst + s * 16384 + rank * 8192, &tm.kv, nb * 64, nkv * 64 + kr, 1, fb);
        } else if (it < 16) {
            tma3d_mc(dst + s * 16384 + rank * 6144, &tm.q, 0, (it - nkv) * 64 + kr, nb * 2, fb);
            tma3d_mc(dst + s * 16384 + rank * 6144 + 4096, &tm.f1, 0, (it - nkv) * 64 + kr, nb * 7, fb);
        } else {
            tma3d_mc(dst + s * 16384 + rank * 6144, &tm.f3, 0, (it & 7) * 64 + kr, nb * 7 + (it < 24 ? 1 : 4), fb);
        }
        if ((XMASK >> it) & 1) {
            const int xc = 1 + __builtin_popcount(XMASK & ((1u << it) - 1));
            tma2d(sb + xc * 16384, &tm.x, xc * 64, mb * 128, bar + B_X + 8 * xc);
        }
    }
}

__global__ void __cluster_dims__(2, 1, 1) __launch_bounds__(640, 1)
fused_kernel(const __grid_constant__ Maps tm, const __nv_bfloat16* __restrict__ x, const __nv_bfloat16* __restrict__ wqkv,
             const __nv_bfloat16* __restrict__ wo, const __nv_bfloat16* __restrict__ w1, const __nv_bfloat16* __restrict__ b1,
             const __nv_bfloat16* __restrict__ w2, const __nv_bfloat16* __restrict__ b2, const __nv_bfloat16* __restrict__ gate,
             __nv_bfloat16* __restrict__ out, const uint32_t m1) {
    const uint32_t sb = smem_u32(smem_raw);
    const uint32_t bar = sb + OFF_BAR;
    const int tid = threadIdx.x, lane = tid & 31;
    const int warp = __shfl_sync(0xffffffffu, tid >> 5, 0);
    const uint32_t rank = cluster_rank();
    const int cl = blockIdx.x >> 1;
    const int nb = cl & 7, mb = (cl >> 3) * 2 + rank;
    const int g = lane >> 2, t = lane & 3;

    const int cb = nb & 3, rb = mb * 2 + (nb >> 2);
    if (tid == 0) TLM(0, 0);
    TL_INIT();
    if (tid == 512) {
        for (int i = 0; i < 8; i++) { mbar_init(bar + B_X + 8 * i, 1); mbar_init(bar + B_KV + 8 * i, 1); mbar_init(bar + B_T + 8 * i, 5); mbar_init(bar + B_XD + 8 * i, 16); }
        for (int i = 0; i < NR; i++) mbar_init(bar + B_E1 + 8 * i, 16);
        for (int i = 0; i < 4; i++) { mbar_init(bar + B_F2 + 8 * i, 1); mbar_init(bar + B_E2 + 8 * i, 8); }
        asm volatile("fence.mbarrier_init.release.cluster;" ::: "memory");
    } else if (tid == 608) {
        for (int i = 0; i < 32; i++) mbar_init(bar + B_F1 + 8 * i, 1);
        mbar_init(bar + B_DONE, 16);
        mbar_init(bar + B_DONE2, 16);
        mbar_init(bar + B_G, 1);
        for (int i = 0; i < 3; i++) mbar_init(bar + B_SF + 8 * i, i == 1 ? 2 : 1);
        mbar_init(bar + B_SF2, 2);
        mbar_init(bar + B_G3, 1);
        mbar_init(bar + B_G2, 4);
        asm volatile("fence.mbarrier_init.release.cluster;" ::: "memory");
    }
    __syncwarp();
    asm volatile("barrier.cluster.arrive.relaxed.aligned;" ::: "memory");
    if (warp == 19) mbar_expect(bar + B_F1 + 8 * lane, ((KVMASK >> lane) & 1) ? 16384 : 12288);
    if (warp == 16 && lane < 24) mbar_expect(bar + (lane < 8 ? B_X : lane < 16 ? B_KV - 64 : B_T - 128) + 8 * lane, 16384);
    if (tid == 512) {
        tma2d(sb, &tm.x, 0, mb * 128, bar + B_X);
    } else if (tid == 544) {
        map_prefetch(&tm.kv);
        l2_prefetch((const uint8_t*)wqkv + (size_t)blockIdx.x * 3072, 3072);
        l2_prefetch((const uint8_t*)w1 + (size_t)blockIdx.x * 1792, 1792);
        map_prefetch(&tm.q); map_prefetch(&tm.f1); map_prefetch(&tm.f3);
    }
    if ((sb & 0xFFFFFF) != SBD) __trap();
    __syncwarp();
    asm volatile("barrier.cluster.wait.aligned;" ::: "memory");
    if (tid == 512) issue_stream<0, NR>(tm, sb, rank, nb, mb);
    if (tid == 0) { TLM(0, 1); TLC(0, 30); }

    if (warp < 16) {
        const int wg = warp >> 2;
        const int h = cl >> 1, qd = (cl & 1) * 2 + rank;
        uint32_t q[4];
        {
            const int w8 = warp & 7;
            const int T = mb * 8 + w8, row0 = T * 16 + g;
            const uint64_t dA0 = mkdesc(SBD + (wg & 1) * 8192, 16, 1024, 1);
            if (wg < 2) {
                float acc[64];
#pragma unroll
                for (int i = 0; i < 64; i++) acc[i] = 0.f;
                gemm_pass<128, 8192, 2048, 4096, 1024, 1>(acc, bar, dA0, lane, strm_pos(3, 0), strm_code(3), 0, true, false);
                if (tid == 0) TLM(0, 2);
                {
                    const float km = norm_bound(acc, 1.f);
                    float vm = 0.f;
#pragma unroll
                    for (int i = 32; i < 64; i++) vm = fmaxf(vm, fabsf(acc[i]));
                    vm = __uint_as_float(__reduce_max_sync(0xffffffffu, __float_as_uint(vm)));
                    if (lane == 0) { gN[1024 + nb * 128 + T] = km; gN[2048 + nb * 128 + T] = vm; }
                    const uint32_t kp = sb + OFF_R + 12288 + (w8 >> 2) * 1024 + g * 128 + ((((w8 & 3) * 2 + ((t >> 1) ^ (w8 >> 2))) ^ g) << 4) + (t & 1) * 8;
                    uint8_t* vp = gKV + (size_t)(nb * 4) * (SEQ * 64) + 65536 + (((T >> 6) * 16 + 2 * g) * 64 + (T & 63)) * 32 + ((t * 8) ^ ((w8 >> 2) << 4));
                    bar_sync(9, 256);
#pragma unroll
                    for (int hh = 0; hh < 4; hh++) {
                        const float* v = acc + 8 * hh;
                        float p0 = __shfl_up_sync(0xffffffffu, v[2], 4), p1 = __shfl_up_sync(0xffffffffu, v[3], 4);
                        float p2 = __shfl_up_sync(0xffffffffu, v[6], 4), p3 = __shfl_up_sync(0xffffffffu, v[7], 4);
                        if (g == 0) { p0 = p1 = p2 = p3 = 0.f; }
                        sts64(kp + hh * 16384, pk_f16(v[0] - p0, v[1] - p1), pk_f16(v[4] - p2, v[5] - p3));
                        sts64(kp + hh * 16384 + 2048, pk_f16(v[2] - v[0], v[3] - v[1]), pk_f16(v[6] - v[4], v[7] - v[5]));
                        const float* u = acc + 32 + 8 * hh;
                        if (hh < 2) {
                            sts64(kp + (4 + hh) * 16384, pk_bf16(u[0], u[1]), pk_bf16(u[4], u[5]));
                            sts64(kp + (4 + hh) * 16384 + 2048, pk_bf16(u[2], u[3]), pk_bf16(u[6], u[7]));
                        } else {
                            *(uint2*)(vp + (size_t)hh * (SEQ * 64)) = make_uint2(pk_bf16(u[0], u[1]), pk_bf16(u[4], u[5]));
                            *(uint2*)(vp + (size_t)hh * (SEQ * 64) + 2048) = make_uint2(pk_bf16(u[2], u[3]), pk_bf16(u[6], u[7]));
                        }
                    }
                }
                asm volatile("fence.proxy.async.shared::cta;" ::: "memory");
                bar_arrive(10, 288);
                if (tid == 0) TLM(0, 3);
            }
#pragma unroll 1
            for (int p = wg < 2 ? 1 : 0; p < 3; p += 2) {
                float acc[48];
#pragma unroll
                for (int i = 0; i < 48; i++) acc[i] = 0.f;
                pin<48>(acc);
                if (p) bar_sync(5 + p, 512);
                gemm_pass<96, 6144, 1024, 2048, 512, 2>(acc, bar, dA0, lane, p == 0 ? strm_pos(0, 0) : 8 + 8 * p, p == 0 ? strm_code(0) : strm_code(1), p < 2 ? 6 + p : 0, p == 0, p == 2);
                if ((tid & 255) == 0) TLM(0, 4 + 2 * p);
                const uint32_t hp = sb + OFF_R + (p == 2 ? 0 : 12288) + (wg & 1) * 16384 + ((warp & 3) * 16 + g) * 64 + t * 16;
                const uint32_t bp = sb + OFF_BIAS + p * 384 - 256 + t * 8;
                uint32_t ho[24];
                mbar_wait(bar + B_BI, 0);
                if (p == 0) {
                    const float qm = norm_bound(acc, QSCALE * QSCALE);
                    if (lane == 0) gN[nb * 128 + T] = qm;
                    uint8_t* qp = gQ + (size_t)(nb * 4) * (SEQ * 32) + (size_t)row0 * 32 + t * 8;
#pragma unroll
                    for (int hh = 0; hh < 4; hh++) {
                        const float* v = acc + 8 * hh;
                        *(uint2*)(qp + hh * (SEQ * 32)) = make_uint2(pk_f16(v[0] * QSCALE, v[1] * QSCALE), pk_f16(v[4] * QSCALE, v[5] * QSCALE));
                        *(uint2*)(qp + hh * (SEQ * 32) + 256) = make_uint2(pk_f16(v[2] * QSCALE, v[3] * QSCALE), pk_f16(v[6] * QSCALE, v[7] * QSCALE));
                    }
                    bar_arrive(12, 288);
                } else {
                    gelu_pack<0, 2>(acc, bp, ho);
                    pin<16>(ho);
                    mbar_wait(bar + B_G, 0);
                    load_q(q, h, qd * 512 + warp * 16 + g, t);
                }
                gelu_pack<2, 3>(acc, bp, ho);
                pin<8>(ho + 16);
                if (p == 2) bar_sync(9, 256);
                else mbar_wait(bar + B_SF + 8 * p, 0);
                if (p) {
#pragma unroll
                    for (int i = 0; i < 4; i++) sts128(hp + (i >> 1) * 32768 + (i & 1) * 512, ho + 4 * i);
                }
                sts128(hp + 65536, ho + 16);
                sts128(hp + 65536 + 512, ho + 20);
                asm volatile("fence.proxy.async.shared::cta;" ::: "memory");
                bar_arrive(p == 1 ? 14 : 11, 288);
                if ((tid & 255) == 0) TLM(0, 5 + 2 * p);
            }
        }
        uint32_t ep = 2;
        uint4* const op = gO + ((qd * 8 + wg) * NH + h) * 128 + (tid & 127);
        const uint64_t kd0 = mkdesc(SBD, 16, 256, 3);
        const uint64_t vd0 = mkdesc(SBD + 8192, OFF_ONE - 8192, 256, 3);
        {
            float o[12];
            uint32_t qn[4];
#pragma unroll 1
            for (int rh = 0; rh < 4; rh++) {
                if (rh == 1) {
                    mbar_wait(bar + B_G3, 0);
                    ep = lds32(sb + OFF_G + 256);
                    if (!(ep & 2)) break;
                    load_q(qn, h, qd * 512 + 256 + warp * 16 + g, t);
                }
                if (rh == 3 && lane == 0) mbar_arrive(bar + B_DONE);
                if (!(rh & 1)) {
#pragma unroll
                    for (int i = 0; i < 12; i++) o[i] = 0.f;
                }
                uint64_t kd = kd0 + (rh & 1) * 4096, vd = vd0 + (rh & 1) * (128 * VSTEP);
                uint32_t kvb = bar + B_KV + (rh & 1) * 32;
                float s[32];
#pragma unroll
                for (int i = 0; i < 32; i++) s[i] = i < 2 * NMUFU ? 0.f : MAGIC;
                if ((tid & 255) == 0) TLM(1, (tid >> 8) * 4 + rh);
#pragma unroll 1
                for (int c = 0; c < 4; c++) {
                    mbar_wait(kvb, 0);
                    kvb += 8;
#pragma unroll
                    for (int j = 0; j < 4; j++) {
                        uint32_t p[16];
                        if (!MERGE || j == 0) {
                            wg_fence();
                            wgmma_qk_f16_acc(s, q, kd + j * 128);
                            wg_commit();
                        }
                        wg_wait<0>();
                        pin<32>(s);
#pragma unroll
                        for (int i = 0; i < 16; i++)
                            p[i] = i < NMUFU ? pk_bf16(ex2f(s[2 * i]), ex2f(s[2 * i + 1])) : exp2_pair(s[2 * i], s[2 * i + 1], m1);
                        pin<16>(p);
                        wg_fence();
#pragma unroll
                        for (int u = 0; u < 4; u++) {
                            if (MERGE && j < 3 && u == 5 - MERGE) wgmma_qk_f16_acc(s, q, kd + (j + 1) * 128);
                            wgmma_pv(o, p + 4 * u, vd + (j * 4 + u) * VSTEP);
                        }
                        if (MERGE == 1 && j < 3) wgmma_qk_f16_acc(s, q, kd + (j + 1) * 128);
                        wg_commit();
                    }
                    kd += 1024;
                    vd += 32 * VSTEP;
                }
                wg_wait<0>();
                pin<12>(o);
                if (rh & 1) {
                    if ((tid & 127) == 0 && rh == 3) TLM(1, 8 + wg);
                    store_o(o, op + (rh >> 1) * (4 * NH * 128), ep & 1);
#pragma unroll
                    for (int i = 0; i < 4; i++) q[i] = qn[i];
                }
            }
            if (tid == 0) { TLM(1, 12); TLC(0, 31); }
        }
        if (!(ep & 2)) {
            bar_sync(8, 512);
            for (int c = 0; c < 8; c++) mbar_wait(bar + B_KV + 8 * c, 0);
            {
                float kc[8][8];
                proj16<8>(kc, x, wqkv, warp * 16, 256, DM + h * 16, g, t);
#pragma unroll
                for (int i = 0; i < 8; i++) {
                    const int T = warp + i * 16;
                    const int pos = ((T >> 6) * 16 + 2 * g) * 64 + (T & 63);
                    const uint32_t a = sb + (pos >> 8) * 16384 + (pos & 255) * 32 + t * 4, sw = ((T >> 2) & 1) << 4;
                    asm volatile("st.shared.u32 [%0], %1;" ::"r"(a + sw), "r"(pk_bf16(kc[i][0], kc[i][1])) : "memory");
                    asm volatile("st.shared.u32 [%0], %1;" ::"r"(a + (sw ^ 16)), "r"(pk_bf16(kc[i][4], kc[i][5])) : "memory");
                    asm volatile("st.shared.u32 [%0], %1;" ::"r"(a + 2048 + sw), "r"(pk_bf16(kc[i][2], kc[i][3])) : "memory");
                    asm volatile("st.shared.u32 [%0], %1;" ::"r"(a + 2048 + (sw ^ 16)), "r"(pk_bf16(kc[i][6], kc[i][7])) : "memory");
                }
                asm volatile("fence.proxy.async.shared::cta;" ::: "memory");
                bar_sync(8, 512);
            }
#pragma unroll 1
            for (int r = 0; r < 2; r++) {
                const int row = qd * 512 + r * 256 + warp * 16 + g;
                {
                    float qc[1][8];
                    proj16<1>(qc, x, wqkv, row - g, 0, h * 16, g, t);
#pragma unroll
                    for (int i = 0; i < 4; i++) q[i] = pk_bf16(qc[0][2 * i] * QSCALE, qc[0][2 * i + 1] * QSCALE);
                }
                float o[12];
#pragma unroll
                for (int i = 0; i < 12; i++) o[i] = 0.f;
                float m0 = -INFINITY, m1 = -INFINITY;
#pragma unroll 1
                for (int j = 0; j < 32; j++) {
                    const uint64_t kd = kd0 + (j >> 2) * 1024 + (j & 3) * 128, vd = vd0 + ((j >> 2) * 32 + (j & 3) * 4) * VSTEP;
                    float s[32];
                    uint32_t p[16];
                    wg_fence();
                    wgmma_qk_bf16_zero(s, q, kd);
                    wg_commit();
                    wg_wait<0>();
                    pin<32>(s);
                    pin<12>(o);
                    float n0 = m0, n1 = m1;
#pragma unroll
                    for (int i = 0; i < 8; i++) {
                        n0 = fmaxf(n0, fmaxf(s[4 * i], s[4 * i + 1]));
                        n1 = fmaxf(n1, fmaxf(s[4 * i + 2], s[4 * i + 3]));
                    }
                    n0 = fmaxf(n0, __shfl_xor_sync(0xffffffffu, n0, 1));
                    n1 = fmaxf(n1, __shfl_xor_sync(0xffffffffu, n1, 1));
                    n0 = fmaxf(n0, __shfl_xor_sync(0xffffffffu, n0, 2));
                    n1 = fmaxf(n1, __shfl_xor_sync(0xffffffffu, n1, 2));
                    const float c0 = ex2f(m0 - n0), c1 = ex2f(m1 - n1);
                    m0 = n0;
                    m1 = n1;
#pragma unroll
                    for (int i = 0; i < 3; i++) { o[4 * i] *= c0; o[4 * i + 1] *= c0; o[4 * i + 2] *= c1; o[4 * i + 3] *= c1; }
#pragma unroll
                    for (int i = 0; i < 8; i++) {
                        p[2 * i] = pk_bf16(ex2f(s[4 * i] - m0), ex2f(s[4 * i + 1] - m0));
                        p[2 * i + 1] = pk_bf16(ex2f(s[4 * i + 2] - m1), ex2f(s[4 * i + 3] - m1));
                    }
                    pin<16>(p);
                    pin<12>(o);
                    wg_fence();
#pragma unroll
                    for (int u = 0; u < 4; u++) wgmma_pv(o, p + 4 * u, vd + u * VSTEP);
                    wg_commit();
                }
                wg_wait<0>();
                pin<12>(o);
                if (r == 1 && lane == 0) mbar_arrive(bar + B_DONE);
                store_o(o, op + r * (4 * NH * 128), ep & 1);
            }
        }
        if (lane == 0) mbar_arrive(bar + B_DONE2);
        if (wg < 2) {
            const uint4* src = gO + (rb * NH + wg * 16) * 128 + (tid & 127);
            const uint32_t* probe = (const uint32_t*)(gO + (rb * NH + wg * 16 + (lane & 15)) * 128 + (tid & 96) + 31);
            uint4 v[16];
            uint32_t pr;
            asm volatile("ld.relaxed.gpu.global.u32 %0, [%1];" : "=r"(pr) : "l"(probe) : "memory");
            mbar_wait(bar + B_DONE, 0);
            mbar_wait(bar + B_G2, 0);
            const int lr = (warp & 3) * 16 + g;
            const uint32_t g0 = lds32(sb + OFF_G + lr * 4), g1 = lds32(sb + OFF_G + lr * 4 + 32);
            const uint32_t a0 = sb + wg * 32768 + lr * 128 + (t >> 1) * 4;
            uint32_t todo = 15, miss = 0xffff;
            int spins = 0;
            while (true) {
                const uint32_t want = __popc(miss) <= POLLN ? miss : miss & __ballot_sync(0xffffffffu, ((pr ^ ep) & 1) == 0);
#pragma unroll
                for (int i = 0; i < 16; i++)
                    if (want >> i & 1) v[i] = load_o(src + i * 128);
                asm volatile("ld.relaxed.gpu.global.u32 %0, [%1];" : "=r"(pr) : "l"(probe) : "memory");
#pragma unroll
                for (int k = 0; k < 4; k++) {
                    if (!(want >> (4 * k) & 15)) continue;
#pragma unroll
                    for (int i = 4 * k; i < 4 * k + 4; i++)
                        if ((want >> i & 1) && !__any_sync(0xffffffffu, ((v[i].x ^ ep) & 1) != 0)) miss &= ~(1u << i);
                    if (!(miss >> (4 * k) & 15)) {
#pragma unroll
                        for (int i = 0; i < 4; i++) {
                            const uint32_t a = a0 + k * 8192 + (((i * 2 + (t & 1)) ^ g) << 4);
                            sts32(a, bmul2(v[4 * k + i].x, g0));
                            sts32(a + 8, bmul2(v[4 * k + i].y, g0));
                            sts32(a + 1024, bmul2(v[4 * k + i].z, g1));
                            sts32(a + 1024 + 8, bmul2(v[4 * k + i].w, g1));
                        }
                        asm volatile("fence.proxy.async.shared::cta;" ::: "memory");
                        __syncwarp();
                        if (lane == 0) mbar_arrive(bar + B_T + 8 * (wg * 4 + k));
                        if ((tid & 127) == 0) TLM(1, 20 + wg * 4 + k);
                        todo &= ~(1u << k);
                    }
                }
                if (!todo) break;
                if (++spins > (1 << 22)) __trap();
            }
        }
        if (tid == 256) {
            mbar_wait(bar + B_DONE2, 0);
#pragma unroll
            for (int i = 0; i < 4; i++)
                tma2d(sb + 65536 + i * 8192, &tm.wo, cb * 128 + (i & 1) * 64, (6 + (i >> 1)) * 64, bar + B_T + 8 * (6 + (i >> 1)));
        }
    } else {
        if (warp == 16) {
            if (lane == 0) {
                issue_stream<NR, 32>(tm, sb, rank, nb, mb);
                mbar_wait(bar + B_SF2, 0);
#pragma unroll
                for (int s = 0; s < 4; s++) {
                    mbar_expect(bar + B_F2 + 8 * s, 24576);
                    tma5d_mc(sb + OFF_R + s * 24576 + 8192 + rank * 8192, &tm.w2, cb * 128 + rank * 64, s * 2, bar + B_F2 + 8 * s);
                }
                cnt_wait(gCntH + mb * 32, epoch() * 8);
                asm volatile("fence.proxy.async.global;" ::: "memory");
                TLM(1, 13);
#pragma unroll
                for (int s = 0; s < 4; s++) tma2d(sb + OFF_R + s * 24576, &tm.h, s * 64, rb * 64, bar + B_F2 + 8 * s);
            }
        } else if (warp == 17) {
            {
                uint32_t bv[4], b2v[2];
#pragma unroll
                for (int i = 0; i < 4; i++) bv[i] = lane + 32 * i < 112 ? *(const uint32_t*)(b1 + nb * 224 + (lane + 32 * i) * 2) : 0;
#pragma unroll
                for (int i = 0; i < 2; i++) b2v[i] = *(const uint32_t*)(b2 + cb * 128 + (lane + 32 * i) * 2);
#pragma unroll
                for (int i = 0; i < 4; i++) {
                    sts32(sb + OFF_ONE + (lane + 32 * i) * 4, 0x3f803f80u);
                    if (lane + 32 * i < 112) sts64(sb + OFF_BIAS + (lane + 32 * i) * 8, bv[i] << 16, bv[i] & 0xffff0000u);
                }
#pragma unroll
                for (int i = 0; i < 2; i++) sts32(sb + OFF_BIAS + 896 + (lane + 32 * i) * 4, b2v[i]);
                asm volatile("fence.proxy.async.shared::cta;" ::: "memory");
                __syncwarp();
                if (lane == 0) mbar_arrive(bar + B_BI);
            }
            mbar_wait(bar + B_X + 8 * PFX, 0);
            if (lane == 0) {
                l2_prefetch((const uint8_t*)wqkv + 128 * 3072 + (size_t)blockIdx.x * 9216, 9216);
                l2_prefetch((const uint8_t*)w1 + (size_t)blockIdx.x * 14336, 14336);
            }
            mbar_wait(bar + B_X + 8 * 7, 0);
            if (lane == 0) {
                l2_prefetch((const uint8_t*)w2 + (size_t)blockIdx.x * 14336, 14336);
                l2_prefetch((const uint8_t*)wo + (size_t)blockIdx.x * 4096, 4096);
                map_prefetch(&tm.h); map_prefetch(&tm.w2); map_prefetch(&tm.wo); map_prefetch(&tm.hs); map_prefetch(&tm.kvs);
                TLM(0, 11);
            }
            bar_sync(10, 288);
            if (lane == 0) {
#pragma unroll 1
                for (int b = 5; b >= 0; b--) {
                    tma5d_st(&tm.kvs, sb + OFF_R + 12288 + b * 16384, (mb >> 3) * 8, (mb & 7) * 2, nb * 8 + (b < 4 ? 2 * b : 2 * b - 7));
                    asm volatile("cp.async.bulk.commit_group;\ncp.async.bulk.wait_group.read %0;" ::"n"(PACE) : "memory");
                    if (b == 4 - PACE) mbar_arrive(bar + B_SF);
                }
                asm volatile("cp.async.bulk.wait_group.read 0;" ::: "memory");
                mbar_arrive(bar + B_SF + 8);
            }
            __syncwarp();
            bar_sync(12, 288);
            if (lane == 0) {
                asm volatile("cp.async.bulk.wait_group 0;\nfence.proxy.async.global;" ::: "memory");
                cnt_add(gCntQ + nb * 32);
                TLM(0, 13);
            }
        } else {
            {
                const int r0 = mb * 128 + nb * 16 + (warp - 18) * 8;
                uint4 xv[16];
#pragma unroll
                for (int i = 0; i < 16; i++) xv[i] = *(const uint4*)(x + (size_t)(r0 + (i >> 1)) * DM + (i & 1) * 256 + lane * 8);
                const uint4 ga = *(const uint4*)(gate + lane * 8), gb = *(const uint4*)(gate + 256 + lane * 8);
                float z[8];
#pragma unroll
                for (int r = 0; r < 8; r++) z[r] = dot8(xv[2 * r], ga) + dot8(xv[2 * r + 1], gb);
#pragma unroll
                for (int w = 4; w >= 1; w >>= 1)
#pragma unroll
                    for (int r = 0; r < w; r++) {
                        const bool up = lane & w;
                        z[r] = (up ? z[r + w] : z[r]) + __shfl_xor_sync(0xffffffffu, up ? z[r] : z[r + w], w);
                    }
                z[0] += __shfl_xor_sync(0xffffffffu, z[0], 8);
                z[0] += __shfl_xor_sync(0xffffffffu, z[0], 16);
                if (lane < 8) gG[r0 + lane] = 1.f / (1.f + __expf(-z[0]));
                if (tid == 576) TLM(0, 12);
            }
            if (warp == 19) {
#pragma unroll 1
                for (int e = 0; e < 3; e++) {
                    bar_sync(e == 1 ? 14 : 11, 288);
                    if (lane == 0) {
#pragma unroll 1
                        for (int b = e == 0 ? 4 : 0; b < 6; b++) {
                            tma3d_st(&tm.hs, sb + OFF_R + (e == 2 ? 0 : 12288) + b * 16384, 0, mb * 128 + (b & 1) * 64, nb * 7 + e * 3 - 2 + (b >> 1));
                            asm volatile("cp.async.bulk.commit_group;\ncp.async.bulk.wait_group.read %0;" ::"n"(PACE) : "memory");
                        }
                        asm volatile("cp.async.bulk.wait_group.read 0;" ::: "memory");
                        if (e == 0) mbar_arrive(bar + B_SF + 8);
                        if (e == 2) { mbar_arrive_cluster(bar + B_SF2, 0); mbar_arrive_cluster(bar + B_SF2, 1); }
                    }
                    __syncwarp();
                }
                bar_sync(13, 64);
                if (lane == 0) {
                    asm volatile("cp.async.bulk.wait_group 0;\nfence.proxy.async.global;" ::: "memory");
                    cnt_add(gCntH + mb * 32);
                    TLM(0, 15);
                }
            } else {
                bar_arrive(13, 64);
                const int h = cl >> 1, qd = (cl & 1) * 2 + rank;
                const uint32_t ep = epoch();
                if (lane == 0) {
                    cnt_wait(gCntQ + (h >> 2) * 32, ep * 16);
                    mbar_arrive(bar + B_G);
                    TLM(0, 14);
                    asm volatile("fence.proxy.async.global;" ::: "memory");
#pragma unroll
                    for (int c = 0; c < 2; c++) {
                        mbar_wait(bar + B_XD + 8 * c, 0);
                        bulk_mc(sb + c * 16384 + rank * 8192, gKV + (size_t)h * (SEQ * 64) + rank * 65536 + c * 8192, 8192, bar + B_KV + 8 * c);
                    }
                }
                __syncwarp();
            const int hb = h >> 2;
            const uint4 kq = __ldcg((const uint4*)(gN + 1024 + hb * 128 + lane * 4));
            const uint4 vq = __ldcg((const uint4*)(gN + 2048 + hb * 128 + lane * 4));
            const float qq = ldcg_f(gN + hb * 128 + qd * 32 + lane);
            const float kf = __uint_as_float(__reduce_max_sync(0xffffffffu, max(max(kq.x, kq.y), max(kq.z, kq.w))));
            const float vf = __uint_as_float(__reduce_max_sync(0xffffffffu, max(max(vq.x, vq.y), max(vq.z, vq.w))));
            const float qf = __uint_as_float(__reduce_max_sync(0xffffffffu, __float_as_uint(qq)));
            if (lane == 0) {
                sts32(sb + OFF_G + 256, (ep & 1) | ((kf <= 1.0e6f) && (qf <= 1.0e6f) && (kf * qf <= 3400.f) && (vf <= 1.0e12f) ? 2 : 0));
                mbar_arrive(bar + B_G3);
                TLM(0, 16);
#pragma unroll
                for (int c = 2; c < 8; c++) {
                    mbar_wait(bar + B_XD + 8 * c, 0);
                    bulk_mc(sb + c * 16384 + rank * 8192, gKV + (size_t)h * (SEQ * 64) + rank * 65536 + c * 8192, 8192, bar + B_KV + 8 * c);
                }
                TLM(0, 10);
            }
            }
        }
        __syncwarp();
        float acc[64];
#pragma unroll
        for (int i = 0; i < 64; i++) acc[i] = 0.f;
#pragma unroll 1
        for (int io = 0; io < 7; io++) {
#pragma unroll
            for (int s = 0; s < 4; s++) {
                const int it = io * 4 + s;
                mbar_wait(bar + B_F2 + 8 * s, io & 1);
                if (tid == 512 && s == 0 && (io == 0 || io == 4)) TLM(1, 14 + io / 4);
                const uint64_t dA = mkdesc(SBD + OFF_R + s * 24576, 16, 1024, 1);
                const uint64_t dB = mkdesc(SBD + OFF_R + s * 24576 + 8192, 8192, 1024, 1);
                wg_fence();
#pragma unroll
                for (int kk = 0; kk < EXP_FKK; kk++) {
                    wgmma_ss_n128(acc, dA + kk * 2, dB + kk * 128);
                    if (kk < 3 && (FSER != 3 || kk == 1)) {
                        wg_commit();
                        wg_wait<0>();
                    }
                }
                wg_commit();
                if (warp < 18 && it >= 2 && it < 26) {
                    const int s2 = (s + 2) & 3;
                    mbar_wait(bar + B_E2 + 8 * s2, (io - (s < 2)) & 1);
                    if (elect()) {
                        if (warp == 16) {
                            mbar_expect(bar + B_F2 + 8 * s2, 24576);
                            tma5d_mc(sb + OFF_R + s2 * 24576 + 8192 + rank * 8192, &tm.w2, cb * 128 + rank * 64, it * 2 + 4, bar + B_F2 + 8 * s2);
                        } else {
                            asm volatile("fence.proxy.async.global;" ::: "memory");
                            tma2d(sb + OFF_R + s2 * 24576, &tm.h, it * 64 + 128, rb * 64, bar + B_F2 + 8 * s2);
                        }
                    }
                    __syncwarp();
                }
                wg_wait<1>();
                if (it >= 1 && lane < 2) mbar_arrive_cluster(bar + B_E2 + 8 * ((s + 3) & 3), lane);
            }
        }
        wg_wait<0>();
        if (lane < 2) mbar_arrive_cluster(bar + B_E2 + 8 * 3, lane);
        pin<64>(acc);
        if (tid == 576) gEpoch[blockIdx.x] = epoch();
        if (warp == 16) {
            if (lane == 0) TLM(1, 16);
            for (int s = 0; s < 4; s++) mbar_wait(bar + B_E2 + 8 * s, 0);
            if (elect()) {
#pragma unroll
                for (int i = 0; i < 6; i++) tma2d_mc(sb + OFF_R + i * 16384 + rank * 8192, &tm.wo, cb * 128 + rank * 64, i * 64, bar + B_T + 8 * i);
            }
            __syncwarp();
        }
        {
            const int lr = (warp - 16) * 16 + g;
            const uint32_t pa = pk_bf16(ldcg_f(gG + rb * 64 + lr), ldcg_f(gG + rb * 64 + lr + 8));
            if (t == 0) {
                sts32(sb + OFF_G + lr * 4, __byte_perm(pa, pa, 0x1010));
                sts32(sb + OFF_G + lr * 4 + 32, __byte_perm(pa, pa, 0x3232));
            }
            __syncwarp();
            if (lane == 0) mbar_arrive(bar + B_G2);
            const float ga = bf_lo(pa), gb = bf_hi(pa);
            const float g0 = 1.f - ga, g1 = 1.f - gb;
#pragma unroll
            for (int j = 0; j < 16; j++) {
                const uint32_t bv = lds32(sb + OFF_BIAS + 896 + j * 16 + t * 4);
                acc[4 * j] = fmaf(acc[4 * j], 0.5f, bf_lo(bv)) * g0;
                acc[4 * j + 1] = fmaf(acc[4 * j + 1], 0.5f, bf_hi(bv)) * g0;
                acc[4 * j + 2] = fmaf(acc[4 * j + 2], 0.5f, bf_lo(bv)) * g1;
                acc[4 * j + 3] = fmaf(acc[4 * j + 3], 0.5f, bf_hi(bv)) * g1;
            }
            pin<64>(acc);
        }
        if (tid == 512) TLM(1, 17);
        {
            uint32_t todo = 255;
#pragma unroll 1
            for (int n = 0; todo; n++) {
                if (warp == 16) {
                    uint32_t rdy;
                    int spins = 0;
                    do {
                        uint32_t ok = 0;
                        if (lane < 8)
                            asm volatile("{\n.reg .pred p;\nmbarrier.test_wait.parity.shared::cta.b64 p, [%1], 0;\nselp.u32 %0, 1, 0, p;\n}"
                                         : "=r"(ok) : "r"(bar + B_T + 8 * lane) : "memory");
                        rdy = __ballot_sync(0xffffffffu, ok) & todo;
                        if (!rdy) { __nanosleep(n ? 20 : 100); if (++spins > (1 << 22)) __trap(); }
                    } while (!rdy);
                    if (lane == 0) sts32(sb + OFF_G + 260 + (n & 1) * 4, rdy);
                }
                bar_sync(15, 128);
                uint32_t rdy = __shfl_sync(0xffffffffu, lds32(sb + OFF_G + 260 + (n & 1) * 4), 0);
                todo &= ~rdy;
#pragma unroll 1
                while (rdy) {
                    const int i = __ffs(rdy) - 1;
                    rdy &= rdy - 1;
                    const uint64_t dA = mkdesc(SBD, 16, 1024, 1) + i * 512;
                    const uint64_t dB = mkdesc(SBD + OFF_R, 8192, 1024, 1) + (i < 6 ? i * 1024 : (i - 10) * 1024);
                    wg_fence();
#pragma unroll
                    for (int kk = 0; kk < 4; kk++) wgmma_ss_n128(acc, dA + kk * 2, dB + kk * 128);
                    wg_commit();
                }
            }
        }
        wg_wait<0>();
        pin<64>(acc);
        if (tid == 512) TLM(1, 18);
        {
            const uint32_t st = sb + 98304 + (warp - 16) * 4352;
            const uint32_t wa = st + (lane & 15) * 272 + (lane >> 4) * 16;
#pragma unroll
            for (int j = 0; j < 8; j++)
                asm volatile("stmatrix.sync.aligned.m8n8.x4.shared.b16 [%0], {%1, %2, %3, %4};" ::"r"(wa + j * 32),
                             "r"(pk_bf16(acc[8 * j], acc[8 * j + 1])), "r"(pk_bf16(acc[8 * j + 2], acc[8 * j + 3])),
                             "r"(pk_bf16(acc[8 * j + 4], acc[8 * j + 5])), "r"(pk_bf16(acc[8 * j + 6], acc[8 * j + 7])) : "memory");
            __syncwarp();
            __nv_bfloat16* op = out + (size_t)(rb * 64 + (warp - 16) * 16 + (lane >> 4)) * DM + cb * 128 + (lane & 15) * 8;
#pragma unroll
            for (int j = 0; j < 8; j++) {
                uint4 v;
                asm volatile("ld.shared.v4.u32 {%0, %1, %2, %3}, [%4];" : "=r"(v.x), "=r"(v.y), "=r"(v.z), "=r"(v.w)
                             : "r"(st + (2 * j + (lane >> 4)) * 272 + (lane & 15) * 16));
                *(uint4*)(op + (size_t)j * 2 * DM) = v;
            }
        }
        if (tid == 512) TLM(1, 19);
        TL_DUMP();
    }
}

typedef CUresult (*EncodeFn)(CUtensorMap*, CUtensorMapDataType, cuuint32_t, void*, const cuuint64_t*, const cuuint64_t*, const cuuint32_t*,
                             const cuuint32_t*, CUtensorMapInterleave, CUtensorMapSwizzle, CUtensorMapL2promotion, CUtensorMapFloatOOBfill);

static void make_map(EncodeFn enc, CUtensorMap* m, const void* p, int rank, const cuuint64_t* dims, const cuuint64_t* strides,
                     const cuuint32_t* box, CUtensorMapSwizzle swz) {
    const cuuint32_t es[5] = {1, 1, 1, 1, 1};
    enc(m, CU_TENSOR_MAP_DATA_TYPE_BFLOAT16, rank, (void*)p, dims, strides, box, es, CU_TENSOR_MAP_INTERLEAVE_NONE, swz,
        CU_TENSOR_MAP_L2_PROMOTION_L2_128B, CU_TENSOR_MAP_FLOAT_OOB_FILL_NONE);
}

extern "C" void kernel_launch(void* const* d_in, const int* in_sizes, int n_in, void* d_out, int out_size) {
    const __nv_bfloat16* x = (const __nv_bfloat16*)d_in[0];
    const __nv_bfloat16* wqkv = (const __nv_bfloat16*)d_in[1];
    const __nv_bfloat16* wo = (const __nv_bfloat16*)d_in[2];
    const __nv_bfloat16* w1 = (const __nv_bfloat16*)d_in[4];
    const __nv_bfloat16* b1 = (const __nv_bfloat16*)d_in[5];
    const __nv_bfloat16* w2 = (const __nv_bfloat16*)d_in[6];
    const __nv_bfloat16* b2 = (const __nv_bfloat16*)d_in[7];
    const __nv_bfloat16* gate = (const __nv_bfloat16*)d_in[8];

    void* fp = nullptr;
    cudaDriverEntryPointQueryResult qr;
    cudaGetDriverEntryPoint("cuTensorMapEncodeTiled", &fp, cudaEnableDefault, &qr);
    EncodeFn enc = (EncodeFn)fp;
    void *pH, *pKV;
    cudaGetSymbolAddress(&pH, gH);
    cudaGetSymbolAddress(&pKV, gKV);

    Maps tm;
    const CUtensorMapSwizzle S128 = CU_TENSOR_MAP_SWIZZLE_128B, S64 = CU_TENSOR_MAP_SWIZZLE_64B;
    { cuuint64_t d[2] = {DM, SEQ}, s[1] = {DM * 2}; cuuint32_t b[2] = {64, 128}; make_map(enc, &tm.x, x, 2, d, s, b, S128); }
    { cuuint64_t d[3] = {DM, DM, 3}, s[2] = {3 * DM * 2, DM * 2}; cuuint32_t b[3] = {64, 32, 2}; make_map(enc, &tm.kv, wqkv, 3, d, s, b, S128); }
    { cuuint64_t d[3] = {32, DM, 3 * DM / 32}, s[2] = {3 * DM * 2, 64}; cuuint32_t b[3] = {32, 32, 2}; make_map(enc, &tm.q, wqkv, 3, d, s, b, S64); }
    { cuuint64_t d[3] = {32, DM, FF / 32}, s[2] = {FF * 2, 64}; cuuint32_t b[3] = {32, 32, 1}; make_map(enc, &tm.f1, w1, 3, d, s, b, S64); }
    { cuuint64_t d[3] = {32, DM, FF / 32}, s[2] = {FF * 2, 64}; cuuint32_t b[3] = {32, 32, 3}; make_map(enc, &tm.f3, w1, 3, d, s, b, S64); }
    { cuuint64_t d[2] = {FF, SEQ}, s[1] = {FF * 2}; cuuint32_t b[2] = {64, 64}; make_map(enc, &tm.h, pH, 2, d, s, b, S128); }
    { cuuint64_t d[5] = {DM, 2, 4, 4, FF / 32}, s[4] = {1024, 8 * 1024, 2 * 1024, 32 * 1024}; cuuint32_t b[5] = {64, 2, 4, 4, 2};
      make_map(enc, &tm.w2, w2, 5, d, s, b, S128); }
    { cuuint64_t d[2] = {DM, DM}, s[1] = {DM * 2}; cuuint32_t b[2] = {64, 64}; make_map(enc, &tm.wo, wo, 2, d, s, b, S128); }

    { cuuint64_t d[3] = {32, SEQ, FF / 32}, s[2] = {FF * 2, 64}; cuuint32_t b[3] = {32, 64, 1}; make_map(enc, &tm.hs, pH, 3, d, s, b, CU_TENSOR_MAP_SWIZZLE_NONE); }
    { cuuint64_t d[5] = {64, 16, 16, 2, 2 * NH}, s[4] = {4096, 128, 2048, 65536}; cuuint32_t b[5] = {64, 8, 2, 2, 1};
      make_map(enc, &tm.kvs, pKV, 5, d, s, b, S128); }
    cudaFuncSetAttribute(fused_kernel, cudaFuncAttributeMaxDynamicSharedMemorySize, TL_SMEM);
    fused_kernel<<<128, 640, TL_SMEM, cudaStreamPerThread>>>(tm, x, wqkv, wo, w1, b1, w2, b2, gate, (__nv_bfloat16*)d_out, 0xffffffffu);
}
```

```cpp
#include <cuda_runtime.h>
#include <cuda_bf16.h>
#include <cuda_fp16.h>
#include <cuda.h>
#include <stdint.h>

#define SEQ 2048
#define DM 512
#define FF 1792
#define NH 32

__device__ __align__(1024) uint8_t gQ[NH * SEQ * 32];
__device__ __align__(1024) uint8_t gKV[NH * SEQ * 64];
__device__ __align__(1024) __nv_bfloat16 gH[SEQ * FF];
__device__ __align__(1024) uint4 gO[32 * NH * 128];
__device__ float gG[SEQ];
__device__ float gN[3 * 8 * 128];
__device__ unsigned int gCntQ[8 * 32];
__device__ unsigned int gCntH[32 * 32];
__device__ unsigned int gEpoch[128];

__device__ __forceinline__ uint32_t smem_u32(const void* p) { return (uint32_t)__cvta_generic_to_shared(p); }
__device__ __forceinline__ void mbar_init(uint32_t a, uint32_t c) { asm volatile("mbarrier.init.shared::cta.b64 [%0], %1;" ::"r"(a), "r"(c)); }
__device__ __forceinline__ void mbar_expect(uint32_t a, uint32_t b) { asm volatile("mbarrier.arrive.expect_tx.shared::cta.b64 _, [%0], %1;" ::"r"(a), "r"(b) : "memory"); }
__device__ __forceinline__ void mbar_arrive(uint32_t a) { asm volatile("mbarrier.arrive.shared::cta.b64 _, [%0];" ::"r"(a) : "memory"); }
__device__ __forceinline__ void mbar_wait(uint32_t a, uint32_t ph) {
    asm volatile("{\n.reg .pred p;\n.reg .u32 n;\nmov.u32 n, 0;\nW_%=:\nmbarrier.try_wait.parity.shared::cta.b64 p, [%0], %1;\n@p bra D_%=;\n"
                 "add.u32 n, n, 1;\nsetp.lt.u32 p, n, 0x400000;\n@p bra W_%=;\ntrap;\nD_%=:\n}" ::"r"(a), "r"(ph) : "memory");
}
__device__ __forceinline__ void mbar_arrive_cluster(uint32_t a, uint32_t cta) {
    asm volatile("{\n.reg .b32 r;\nmapa.shared::cluster.u32 r, %0, %1;\nmbarrier.arrive.shared::cluster.b64 _, [r];\n}" ::"r"(a), "r"(cta) : "memory");
}
__device__ __forceinline__ void bar_sync(int id, int n) { asm volatile("bar.sync %0, %1;" ::"r"(id), "r"(n) : "memory"); }
__device__ __forceinline__ void bar_arrive(int id, int n) { asm volatile("bar.arrive %0, %1;" ::"r"(id), "r"(n) : "memory"); }
__device__ __forceinline__ uint32_t cluster_rank() { uint32_t r; asm("mov.u32 %0, %%cluster_ctarank;" : "=r"(r)); return r; }
__device__ __forceinline__ void cnt_add(unsigned int* c) { asm volatile("red.release.gpu.global.add.u32 [%0], 1;" ::"l"(c) : "memory"); }
__device__ __forceinline__ void cnt_wait(const unsigned int* c, uint32_t target) {
    uint32_t v;
    int spins = 0;
    while (true) {
        asm volatile("ld.acquire.gpu.global.u32 %0, [%1];" : "=r"(v) : "l"(c) : "memory");
        if ((int)(v - target) >= 0) break;
        if (++spins > (1 << 22)) __trap();
        __nanosleep(40);
    }
}
__device__ __forceinline__ void tma2d(uint32_t dst, const CUtensorMap* m, int c0, int c1, uint32_t bar) {
    asm volatile("cp.async.bulk.tensor.2d.shared::cluster.global.mbarrier::complete_tx::bytes [%0], [%1, {%3, %4}], [%2];"
                 ::"r"(dst), "l"(m), "r"(bar), "r"(c0), "r"(c1) : "memory");
}
__device__ __forceinline__ void tma2d_mc(uint32_t dst, const CUtensorMap* m, int c0, int c1, uint32_t bar) {
    asm volatile("cp.async.bulk.tensor.2d.shared::cluster.global.mbarrier::complete_tx::bytes.multicast::cluster [%0], [%1, {%3, %4}], [%2], %5;"
                 ::"r"(dst), "l"(m), "r"(bar), "r"(c0), "r"(c1), "h"((uint16_t)3) : "memory");
}
__device__ __forceinline__ void tma3d_mc(uint32_t dst, const CUtensorMap* m, int c0, int c1, int c2, uint32_t bar) {
    asm volatile("cp.async.bulk.tensor.3d.shared::cluster.global.mbarrier::complete_tx::bytes.multicast::cluster [%0], [%1, {%3, %4, %5}], [%2], %6;"
                 ::"r"(dst), "l"(m), "r"(bar), "r"(c0), "r"(c1), "r"(c2), "h"((uint16_t)3) : "memory");
}
__device__ __forceinline__ void tma5d_mc(uint32_t dst, const CUtensorMap* m, int c0, int c4, uint32_t bar) {
    asm volatile("cp.async.bulk.tensor.5d.shared::cluster.global.mbarrier::complete_tx::bytes.multicast::cluster [%0], [%1, {%3, %5, %5, %5, %4}], [%2], %6;"
                 ::"r"(dst), "l"(m), "r"(bar), "r"(c0), "r"(c4), "r"(0), "h"((uint16_t)3) : "memory");
}
__device__ __forceinline__ void tma5d(uint32_t dst, const CUtensorMap* m, int c0, int c4, uint32_t bar) {
    asm volatile("cp.async.bulk.tensor.5d.shared::cluster.global.mbarrier::complete_tx::bytes [%0], [%1, {%3, %5, %5, %5, %4}], [%2];"
                 ::"r"(dst), "l"(m), "r"(bar), "r"(c0), "r"(c4), "r"(0) : "memory");
}
__device__ __forceinline__ void bulk_mc(uint32_t dst, const void* src, uint32_t bytes, uint32_t bar) {
    asm volatile("cp.async.bulk.shared::cluster.global.mbarrier::complete_tx::bytes.multicast::cluster [%0], [%1], %2, [%3], %4;"
                 ::"r"(dst), "l"(src), "r"(bytes), "r"(bar), "h"((uint16_t)3) : "memory");
}
__device__ __forceinline__ void tma3d_st(const CUtensorMap* m, uint32_t src, int c0, int c1, int c2) {
    asm volatile("cp.async.bulk.tensor.3d.global.shared::cta.bulk_group [%0, {%2, %3, %4}], [%1];" ::"l"(m), "r"(src), "r"(c0), "r"(c1), "r"(c2) : "memory");
}
__device__ __forceinline__ void tma5d_st(const CUtensorMap* m, uint32_t src, int c1, int c2, int c4) {
    asm volatile("cp.async.bulk.tensor.5d.global.shared::cta.bulk_group [%0, {%5, %2, %3, %5, %4}], [%1];"
                 ::"l"(m), "r"(src), "r"(c1), "r"(c2), "r"(c4), "r"(0) : "memory");
}
__device__ __forceinline__ void bulk_st(void* dst, uint32_t src, uint32_t bytes) {
    asm volatile("cp.async.bulk.global.shared::cta.bulk_group [%0], [%1], %2;" ::"l"(dst), "r"(src), "r"(bytes) : "memory");
}
__device__ __forceinline__ void sts64(uint32_t a, uint32_t x, uint32_t y) { asm volatile("st.shared.v2.u32 [%0], {%1, %2};" ::"r"(a), "r"(x), "r"(y) : "memory"); }
__device__ __forceinline__ void sts128(uint32_t a, const uint32_t* v) {
    asm volatile("st.shared.v4.u32 [%0], {%1, %2, %3, %4};" ::"r"(a), "r"(v[0]), "r"(v[1]), "r"(v[2]), "r"(v[3]) : "memory");
}
__device__ __forceinline__ void l2_prefetch(const void* src, uint32_t bytes) {
    asm volatile("cp.async.bulk.prefetch.L2.global [%0], %1;" ::"l"(src), "r"(bytes) : "memory");
}
__device__ __forceinline__ void map_prefetch(const CUtensorMap* m) { asm volatile("prefetch.tensormap [%0];" ::"l"(m) : "memory"); }
__device__ __forceinline__ void wg_fence() { asm volatile("wgmma.fence.sync.aligned;" ::: "memory"); }
__device__ __forceinline__ void wg_commit() { asm volatile("wgmma.commit_group.sync.aligned;" ::: "memory"); }
template <int N> __device__ __forceinline__ void wg_wait() { asm volatile("wgmma.wait_group.sync.aligned %0;" ::"n"(N) : "memory"); }
template <int N> __device__ __forceinline__ void pin(float* s) {
#pragma unroll
    for (int i = 0; i < N; i++) asm volatile("" : "+f"(s[i])::"memory");
}
template <int N> __device__ __forceinline__ void pin(uint32_t* s) {
#pragma unroll
    for (int i = 0; i < N; i++) asm volatile("" : "+r"(s[i])::"memory");
}
__device__ __forceinline__ uint64_t mkdesc(uint32_t addr, uint32_t lbo, uint32_t sbo, uint32_t swz) {
    return (uint64_t)((addr & 0x3FFFF) >> 4) | ((uint64_t)(lbo >> 4) << 16) | ((uint64_t)(sbo >> 4) << 32) | ((uint64_t)swz << 62);
}
__device__ __forceinline__ float ex2f(float x) { float y; asm("ex2.approx.ftz.f32 %0, %1;" : "=f"(y) : "f"(x)); return y; }
__device__ __forceinline__ float tanhf_(float x) { float y; asm("tanh.approx.f32 %0, %1;" : "=f"(y) : "f"(x)); return y; }
__device__ __forceinline__ uint32_t pk_bf16(float lo, float hi) { uint32_t r; asm("cvt.rn.bf16x2.f32 %0, %1, %2;" : "=r"(r) : "f"(hi), "f"(lo)); return r; }
__device__ __forceinline__ uint32_t pk_f16(float lo, float hi) { uint32_t r; asm("cvt.rn.f16x2.f32 %0, %1, %2;" : "=r"(r) : "f"(hi), "f"(lo)); return r; }
__device__ __forceinline__ float bf_lo(uint32_t v) { return __uint_as_float(v << 16); }
__device__ __forceinline__ float bf_hi(uint32_t v) { return __uint_as_float(v & 0xffff0000u); }
__device__ __forceinline__ float dot8(const uint4& a, const uint4& b) {
    return fmaf(bf_lo(a.x), bf_lo(b.x), fmaf(bf_hi(a.x), bf_hi(b.x), fmaf(bf_lo(a.y), bf_lo(b.y), bf_hi(a.y) * bf_hi(b.y)))) +
           fmaf(bf_lo(a.z), bf_lo(b.z), fmaf(bf_hi(a.z), bf_hi(b.z), fmaf(bf_lo(a.w), bf_lo(b.w), bf_hi(a.w) * bf_hi(b.w))));
}
__device__ __forceinline__ uint32_t epoch() {
    uint32_t v;
    asm volatile("ld.global.u32 %0, [%1];" : "=r"(v) : "l"(gEpoch + blockIdx.x));
    return v + 1;
}
__device__ __forceinline__ float ldcg_f(const float* p) { return __ldcg(p); }

extern __shared__ __align__(1024) uint8_t smem_raw[];
#define TLM(k, slot) do {} while (0)
#define TLC(k, slot) do {} while (0)
#define TL_INIT() do {} while (0)
#define TL_DUMP() do {} while (0)
#define TL_SMEM SMEM_BYTES

__device__ __forceinline__ void wgmma_ss_n128(float* d, uint64_t da, uint64_t db) {
    asm volatile("wgmma.mma_async.sync.aligned.m64n128k16.f32.bf16.bf16 {"
        "%0, %1, %2, %3, %4, %5, %6, %7, %8, %9, %10, %11, %12, %13, %14, %15,"
        "%16, %17, %18, %19, %20, %21, %22, %23, %24, %25, %26, %27, %28, %29, %30, %31,"
        "%32, %33, %34, %35, %36, %37, %38, %39, %40, %41, %42, %43, %44, %45, %46, %47,"
        "%48, %49, %50, %51, %52, %53, %54, %55, %56, %57, %58, %59, %60, %61, %62, %63}, %64, %65, 1, 1, 1, 0, 1;\n"
        :
        "+f"(d[0]), "+f"(d[1]), "+f"(d[2]), "+f"(d[3]), "+f"(d[4]), "+f"(d[5]), "+f"(d[6]), "+f"(d[7]),
        "+f"(d[8]), "+f"(d[9]), "+f"(d[10]), "+f"(d[11]), "+f"(d[12]), "+f"(d[13]), "+f"(d[14]), "+f"(d[15]),
        "+f"(d[16]), "+f"(d[17]), "+f"(d[18]), "+f"(d[19]), "+f"(d[20]), "+f"(d[21]), "+f"(d[22]), "+f"(d[23]),
        "+f"(d[24]), "+f"(d[25]), "+f"(d[26]), "+f"(d[27]), "+f"(d[28]), "+f"(d[29]), "+f"(d[30]), "+f"(d[31]),
        "+f"(d[32]), "+f"(d[33]), "+f"(d[34]), "+f"(d[35]), "+f"(d[36]), "+f"(d[37]), "+f"(d[38]), "+f"(d[39]),
        "+f"(d[40]), "+f"(d[41]), "+f"(d[42]), "+f"(d[43]), "+f"(d[44]), "+f"(d[45]), "+f"(d[46]), "+f"(d[47]),
        "+f"(d[48]), "+f"(d[49]), "+f"(d[50]), "+f"(d[51]), "+f"(d[52]), "+f"(d[53]), "+f"(d[54]), "+f"(d[55]),
        "+f"(d[56]), "+f"(d[57]), "+f"(d[58]), "+f"(d[59]), "+f"(d[60]), "+f"(d[61]), "+f"(d[62]), "+f"(d[63])
        : "l"(da), "l"(db));
}
__device__ __forceinline__ void wgmma_ss_n96(float* d, uint64_t da, uint64_t db) {
    asm volatile("wgmma.mma_async.sync.aligned.m64n96k16.f32.bf16.bf16 {"
        "%0, %1, %2, %3, %4, %5, %6, %7, %8, %9, %10, %11, %12, %13, %14, %15,"
        "%16, %17, %18, %19, %20, %21, %22, %23, %24, %25, %26, %27, %28, %29, %30, %31,"
        "%32, %33, %34, %35, %36, %37, %38, %39, %40, %41, %42, %43, %44, %45, %46, %47}, %48, %49, 1, 1, 1, 0, 1;\n"
        :
        "+f"(d[0]), "+f"(d[1]), "+f"(d[2]), "+f"(d[3]), "+f"(d[4]), "+f"(d[5]), "+f"(d[6]), "+f"(d[7]),
        "+f"(d[8]), "+f"(d[9]), "+f"(d[10]), "+f"(d[11]), "+f"(d[12]), "+f"(d[13]), "+f"(d[14]), "+f"(d[15]),
        "+f"(d[16]), "+f"(d[17]), "+f"(d[18]), "+f"(d[19]), "+f"(d[20]), "+f"(d[21]), "+f"(d[22]), "+f"(d[23]),
        "+f"(d[24]), "+f"(d[25]), "+f"(d[26]), "+f"(d[27]), "+f"(d[28]), "+f"(d[29]), "+f"(d[30]), "+f"(d[31]),
        "+f"(d[32]), "+f"(d[33]), "+f"(d[34]), "+f"(d[35]), "+f"(d[36]), "+f"(d[37]), "+f"(d[38]), "+f"(d[39]),
        "+f"(d[40]), "+f"(d[41]), "+f"(d[42]), "+f"(d[43]), "+f"(d[44]), "+f"(d[45]), "+f"(d[46]), "+f"(d[47])
        : "l"(da), "l"(db));
}
__device__ __forceinline__ void wgmma_ss_n64(float* d, uint64_t da, uint64_t db) {
    asm volatile("wgmma.mma_async.sync.aligned.m64n64k16.f32.bf16.bf16 {"
        "%0, %1, %2, %3, %4, %5, %6, %7, %8, %9, %10, %11, %12, %13, %14, %15,"
        "%16, %17, %18, %19, %20, %21, %22, %23, %24, %25, %26, %27, %28, %29, %30, %31}, %32, %33, 1, 1, 1, 0, 1;\n"
        :
        "+f"(d[0]), "+f"(d[1]), "+f"(d[2]), "+f"(d[3]), "+f"(d[4]), "+f"(d[5]), "+f"(d[6]), "+f"(d[7]),
        "+f"(d[8]), "+f"(d[9]), "+f"(d[10]), "+f"(d[11]), "+f"(d[12]), "+f"(d[13]), "+f"(d[14]), "+f"(d[15]),
        "+f"(d[16]), "+f"(d[17]), "+f"(d[18]), "+f"(d[19]), "+f"(d[20]), "+f"(d[21]), "+f"(d[22]), "+f"(d[23]),
        "+f"(d[24]), "+f"(d[25]), "+f"(d[26]), "+f"(d[27]), "+f"(d[28]), "+f"(d[29]), "+f"(d[30]), "+f"(d[31])
        : "l"(da), "l"(db));
}
__device__ __forceinline__ void wgmma_rs_n128(float* d, const uint32_t* a, uint64_t db) {
    asm volatile("wgmma.mma_async.sync.aligned.m64n128k16.f32.bf16.bf16 {"
        "%0, %1, %2, %3, %4, %5, %6, %7, %8, %9, %10, %11, %12, %13, %14, %15,"
        "%16, %17, %18, %19, %20, %21, %22, %23, %24, %25, %26, %27, %28, %29, %30, %31,"
        "%32, %33, %34, %35, %36, %37, %38, %39, %40, %41, %42, %43, %44, %45, %46, %47,"
        "%48, %49, %50, %51, %52, %53, %54, %55, %56, %57, %58, %59, %60, %61, %62, %63}, {%64, %65, %66, %67}, %68, 1, 1, 1, 1;\n"
        :
        "+f"(d[0]), "+f"(d[1]), "+f"(d[2]), "+f"(d[3]), "+f"(d[4]), "+f"(d[5]), "+f"(d[6]), "+f"(d[7]),
        "+f"(d[8]), "+f"(d[9]), "+f"(d[10]), "+f"(d[11]), "+f"(d[12]), "+f"(d[13]), "+f"(d[14]), "+f"(d[15]),
        "+f"(d[16]), "+f"(d[17]), "+f"(d[18]), "+f"(d[19]), "+f"(d[20]), "+f"(d[21]), "+f"(d[22]), "+f"(d[23]),
        "+f"(d[24]), "+f"(d[25]), "+f"(d[26]), "+f"(d[27]), "+f"(d[28]), "+f"(d[29]), "+f"(d[30]), "+f"(d[31]),
        "+f"(d[32]), "+f"(d[33]), "+f"(d[34]), "+f"(d[35]), "+f"(d[36]), "+f"(d[37]), "+f"(d[38]), "+f"(d[39]),
        "+f"(d[40]), "+f"(d[41]), "+f"(d[42]), "+f"(d[43]), "+f"(d[44]), "+f"(d[45]), "+f"(d[46]), "+f"(d[47]),
        "+f"(d[48]), "+f"(d[49]), "+f"(d[50]), "+f"(d[51]), "+f"(d[52]), "+f"(d[53]), "+f"(d[54]), "+f"(d[55]),
        "+f"(d[56]), "+f"(d[57]), "+f"(d[58]), "+f"(d[59]), "+f"(d[60]), "+f"(d[61]), "+f"(d[62]), "+f"(d[63])
        : "r"(a[0]), "r"(a[1]), "r"(a[2]), "r"(a[3]), "l"(db));
}
__device__ __forceinline__ void wgmma_qk_f16_acc(float* d, const uint32_t* a, uint64_t db) {
    asm volatile("wgmma.mma_async.sync.aligned.m64n64k16.f32.f16.f16 {"
        "%0, %1, %2, %3, %4, %5, %6, %7, %8, %9, %10, %11, %12, %13, %14, %15,"
        "%16, %17, %18, %19, %20, %21, %22, %23, %24, %25, %26, %27, %28, %29, %30, %31}, {%32, %33, %34, %35}, %36, 1, 1, 1, 0;\n"
        :
        "+f"(d[0]), "+f"(d[1]), "+f"(d[2]), "+f"(d[3]), "+f"(d[4]), "+f"(d[5]), "+f"(d[6]), "+f"(d[7]),
        "+f"(d[8]), "+f"(d[9]), "+f"(d[10]), "+f"(d[11]), "+f"(d[12]), "+f"(d[13]), "+f"(d[14]), "+f"(d[15]),
        "+f"(d[16]), "+f"(d[17]), "+f"(d[18]), "+f"(d[19]), "+f"(d[20]), "+f"(d[21]), "+f"(d[22]), "+f"(d[23]),
        "+f"(d[24]), "+f"(d[25]), "+f"(d[26]), "+f"(d[27]), "+f"(d[28]), "+f"(d[29]), "+f"(d[30]), "+f"(d[31])
        : "r"(a[0]), "r"(a[1]), "r"(a[2]), "r"(a[3]), "l"(db));
}
__device__ __forceinline__ void wgmma_qk_bf16_zero(float* d, const uint32_t* a, uint64_t db) {
    asm volatile("wgmma.mma_async.sync.aligned.m64n64k16.f32.bf16.bf16 {"
        "%0, %1, %2, %3, %4, %5, %6, %7, %8, %9, %10, %11, %12, %13, %14, %15,"
        "%16, %17, %18, %19, %20, %21, %22, %23, %24, %25, %26, %27, %28, %29, %30, %31}, {%32, %33, %34, %35}, %36, 0, 1, 1, 0;\n"
        :
        "=f"(d[0]), "=f"(d[1]), "=f"(d[2]), "=f"(d[3]), "=f"(d[4]), "=f"(d[5]), "=f"(d[6]), "=f"(d[7]),
        "=f"(d[8]), "=f"(d[9]), "=f"(d[10]), "=f"(d[11]), "=f"(d[12]), "=f"(d[13]), "=f"(d[14]), "=f"(d[15]),
        "=f"(d[16]), "=f"(d[17]), "=f"(d[18]), "=f"(d[19]), "=f"(d[20]), "=f"(d[21]), "=f"(d[22]), "=f"(d[23]),
        "=f"(d[24]), "=f"(d[25]), "=f"(d[26]), "=f"(d[27]), "=f"(d[28]), "=f"(d[29]), "=f"(d[30]), "=f"(d[31])
        : "r"(a[0]), "r"(a[1]), "r"(a[2]), "r"(a[3]), "l"(db));
}
__device__ __forceinline__ void wgmma_pv(float* d, const uint32_t* a, uint64_t db) {
    asm volatile("wgmma.mma_async.sync.aligned.m64n24k16.f32.bf16.bf16 {"
        "%0, %1, %2, %3, %4, %5, %6, %7, %8, %9, %10, %11}, {%12, %13, %14, %15}, %16, 1, 1, 1, 1;\n"
        :
        "+f"(d[0]), "+f"(d[1]), "+f"(d[2]), "+f"(d[3]), "+f"(d[4]), "+f"(d[5]), "+f"(d[6]), "+f"(d[7]),
        "+f"(d[8]), "+f"(d[9]), "+f"(d[10]), "+f"(d[11])
        : "r"(a[0]), "r"(a[1]), "r"(a[2]), "r"(a[3]), "l"(db));
}

template <int N> __device__ __forceinline__ void wgmma_ss(float* d, uint64_t a, uint64_t b) {
    if (N == 128) wgmma_ss_n128(d, a, b);
    if (N == 96) wgmma_ss_n96(d, a, b);
    if (N == 64) wgmma_ss_n64(d, a, b);
}

#define OFF_R 131072
#define OFF_ONE 229376
#define OFF_BAR 229888
#define OFF_BIAS (OFF_BAR + 736)
#define OFF_G (OFF_BIAS + 1152)
#define SMEM_BYTES (OFF_G + 272)
#define SBD 1024u
#define B_X 0
#define B_F1 416
#define B_E1 64
#define B_XD 672
#define B_KV 160
#define B_F2 224
#define B_E2 256
#define B_T 288
#define B_G 360
#define B_G2 368
#define B_G3 376
#define B_SF 384
#define B_BI 400

#define B_SF2 408
#define NR 6

#define PF 1
#define PFX 0
#define PACE 1
#define FSER 0
#define MERGE 1
#define EXP_FKK 4
#define QSCALE 0.36067376022224085f
#define MAGIC 445.41763f
#define FORCE_IMAD
#define NMUFU 5
#define VSTEP ((uint64_t)((long long)32 - ((long long)32 << 16)))

#define XMASK 0x0D55u
#define KVMASK 0x1D55u
__host__ __device__ constexpr int strm_pos(int pass, int i) {
    if (pass == 1 || pass == 2) return 8 + 8 * pass + i;
    int n = 0;
    for (int p = 0; p < 16; p++)
        if ((int)((KVMASK >> p) & 1) == (pass == 3)) { if (n == i) return p; n++; }
    return 0;
}
__host__ __device__ constexpr uint32_t strm_code(int pass) {
    uint32_t c = 0;
    for (int i = 0; i < 7; i++) c |= (uint32_t)(strm_pos(pass, i + 1) - strm_pos(pass, i)) << (4 * i);
    return c;
}

template <int N, int SUB, int KST, int LBO, int SBO, int SWZ>
__device__ __forceinline__ void gemm_pass(float* acc, uint32_t bar, uint64_t dA, int lane, uint32_t pos, uint32_t code, int barNext, bool waitx, bool last) {
    uint32_t prev = 0, slot = pos % NR;
#pragma unroll 1
    for (int i = 0; i < 8; i++) {
        if (waitx) mbar_wait(bar + B_X + 8 * i, 0);
        mbar_wait(bar + B_F1 + 8 * pos, 0);
        const uint64_t dB = mkdesc(SBD + OFF_R, LBO, SBO, SWZ) + slot * 1024;
        wg_fence();
        wgmma_ss<N>(acc, dA, dB);
        wgmma_ss<N>(acc, dA + 2, dB + KST / 16);
        wg_commit();
        wg_wait<1>();
        if (i > 0 && lane < 2) mbar_arrive_cluster(prev, lane);
        wgmma_ss<N>(acc, dA + 4, dB + SUB / 16);
        wgmma_ss<N>(acc, dA + 6, dB + (SUB + KST) / 16);
        wg_commit();
        prev = last ? bar + B_XD + 8 * i : bar + B_E1 + 8 * slot;
        pos += code & 15;
        slot += code & 15;
        if (slot >= NR) slot -= NR;
        code >>= 4;
        dA += 1024;
    }
    if (barNext) bar_arrive(barNext, 512);
    wg_wait<0>();
    if (lane < 2) mbar_arrive_cluster(prev, lane);
    pin<N / 2>(acc);
}

__device__ __forceinline__ uint32_t lds32(uint32_t a) { uint32_t v; asm volatile("ld.shared.u32 %0, [%1];" : "=r"(v) : "r"(a)); return v; }
__device__ __forceinline__ bool elect() {
    uint32_t p;
    asm volatile("{\n.reg .pred p;\nelect.sync _|p, 0xffffffff;\nselp.u32 %0, 1, 0, p;\n}" : "=r"(p));
    return p;
}

template <int G0, int G1> __device__ __forceinline__ void gelu_pack(const float* acc, uint32_t bias, uint32_t* out) {
#pragma unroll
    for (int G = G0; G < G1; G++) {
        uint32_t* o = out + 8 * G;
#pragma unroll
        for (int j = 0; j < 4; j++) {
            float bv[2];
            asm volatile("ld.shared.v2.f32 {%0, %1}, [%2];" : "=f"(bv[0]), "=f"(bv[1]) : "r"(bias + G * 128 + j * 32));
            float y[4];
#pragma unroll
            for (int i = 0; i < 4; i++) {
                const float h = acc[16 * G + 4 * j + i] + bv[i & 1];
                const float z = h * fmaf(h * h, 0.035677408136300125f, 0.7978845608028654f);
                y[i] = fmaf(h, tanhf_(z), h);
            }
            o[j] = pk_bf16(y[0], y[1]);
            o[4 + j] = pk_bf16(y[2], y[3]);
        }
    }
}

__device__ __forceinline__ float norm_bound(const float* v, float sc) {
    uint32_t m = 0;
#pragma unroll
    for (int h = 0; h < 4; h++) {
        const float* u = v + 8 * h;
        m = max(m, __float_as_uint(fmaf(u[0], u[0], fmaf(u[1], u[1], fmaf(u[4], u[4], u[5] * u[5])))));
        m = max(m, __float_as_uint(fmaf(u[2], u[2], fmaf(u[3], u[3], fmaf(u[6], u[6], u[7] * u[7])))));
    }
#pragma unroll
    for (int o = 4; o < 32; o <<= 1) m = max(m, __shfl_xor_sync(0xffffffffu, m, o));
    float f = __uint_as_float(m);
    f += __shfl_xor_sync(0xffffffffu, f, 1);
    f += __shfl_xor_sync(0xffffffffu, f, 2);
    return f * sc;
}

__device__ __forceinline__ uint32_t exp2_pair(float a, float b, uint32_t m1) {
    const uint32_t w = __byte_perm(__float_as_uint(a), __float_as_uint(b), 0x6521);
    uint32_t m, r;
    asm("lop3.b32 %0, %1, 0x007f007f, 0x9f809f80, 0xEA;" : "=r"(m) : "r"(w));
    const uint32_t e = m * m1 + w;
    asm("fma.rn.bf16x2 %0, %1, %2, %3;" : "=r"(r) : "r"(w), "r"(m), "r"(e));
    return r;
}

__device__ __forceinline__ void store_o(const float* o, uint4* dst, uint32_t par) {
    const float s0 = __fdividef(1.f, o[8]), s1 = __fdividef(1.f, o[10]);
    const uint32_t d0 = (pk_bf16(o[0] * s0, o[1] * s0) & ~1u) | par;
    asm volatile("{\n.reg .b128 t;\nmov.b128 t, {%0, %1, %2, %3};\nst.relaxed.gpu.global.b128 [%4], t;\n}" ::"r"(d0),
                 "r"(pk_bf16(o[2] * s1, o[3] * s1)), "r"(pk_bf16(o[4] * s0, o[5] * s0)), "r"(pk_bf16(o[6] * s1, o[7] * s1)), "l"(dst) : "memory");
}
__device__ __forceinline__ uint4 load_o(const uint4* src) {
    uint4 v;
    asm volatile("{\n.reg .b128 t;\nld.relaxed.gpu.global.b128 t, [%4];\nmov.b128 {%0, %1, %2, %3}, t;\n}"
                 : "=r"(v.x), "=r"(v.y), "=r"(v.z), "=r"(v.w) : "l"(src) : "memory");
    return v;
}
__device__ __forceinline__ void fetch_o4(uint4* v, const uint4* src, uint32_t ep) {
    int spins = 0;
    while (__any_sync(0xffffffffu, (((v[0].x ^ ep) | (v[1].x ^ ep) | (v[2].x ^ ep) | (v[3].x ^ ep)) & 1) != 0)) {
        if (++spins > (1 << 22)) __trap();
#pragma unroll
        for (int k = 0; k < 4; k++)
            if (((v[k].x ^ ep) & 1) != 0) v[k] = load_o(src + k * 128);
    }
}
__device__ __forceinline__ uint32_t bmul2(uint32_t a, uint32_t b) { uint32_t r; asm("mul.rn.bf16x2 %0, %1, %2;" : "=r"(r) : "r"(a), "r"(b)); return r; }
__device__ __forceinline__ void sts32(uint32_t a, uint32_t v) { asm volatile("st.shared.u32 [%0], %1;" ::"r"(a), "r"(v) : "memory"); }
__device__ __forceinline__ void load_q(uint32_t* q, int h, int row, int t) {
    const uint8_t* p = gQ + (size_t)h * (SEQ * 32) + (size_t)row * 32 + t * 4;
    q[0] = __ldcg((const uint32_t*)p); q[1] = __ldcg((const uint32_t*)(p + 256));
    q[2] = __ldcg((const uint32_t*)(p + 16)); q[3] = __ldcg((const uint32_t*)(p + 272));
}

template <int NT>
__device__ __forceinline__ void proj16(float (*c)[8], const __nv_bfloat16* x, const __nv_bfloat16* w, int row0, int rstep, int col, int g, int t) {
#pragma unroll
    for (int i = 0; i < NT; i++)
#pragma unroll
        for (int j = 0; j < 8; j++) c[i][j] = 0.f;
    const unsigned short* wu = (const unsigned short*)w;
#pragma unroll 1
    for (int k = 0; k < DM; k += 16) {
        uint32_t b[4];
#pragma unroll
        for (int j = 0; j < 4; j++) {
            const int kr = k + 2 * t + (j & 1) * 8, cc = col + g + (j >> 1) * 8;
            b[j] = (uint32_t)wu[(size_t)kr * (3 * DM) + cc] | ((uint32_t)wu[(size_t)(kr + 1) * (3 * DM) + cc] << 16);
        }
#pragma unroll
        for (int i = 0; i < NT; i++) {
            const __nv_bfloat16* xp = x + (size_t)(row0 + i * rstep + g) * DM + k + 2 * t;
            const uint32_t a0 = *(const uint32_t*)xp, a1 = *(const uint32_t*)(xp + 8 * DM);
            const uint32_t a2 = *(const uint32_t*)(xp + 8), a3 = *(const uint32_t*)(xp + 8 * DM + 8);
#pragma unroll
            for (int j = 0; j < 2; j++)
                asm volatile("mma.sync.aligned.m16n8k16.row.col.f32.bf16.bf16.f32 {%0,%1,%2,%3}, {%4,%5,%6,%7}, {%8,%9}, {%0,%1,%2,%3};"
                             : "+f"(c[i][4 * j]), "+f"(c[i][4 * j + 1]), "+f"(c[i][4 * j + 2]), "+f"(c[i][4 * j + 3])
                             : "r"(a0), "r"(a1), "r"(a2), "r"(a3), "r"(b[2 * j]), "r"(b[2 * j + 1]));
        }
    }
}

struct Maps { CUtensorMap x, kv, q, f1, f3, h, w2, wo, hs, kvs; };

template <int I0, int I1>
__device__ __forceinline__ void issue_stream(const Maps& tm, uint32_t sb, uint32_t rank, int nb, int mb) {
    const uint32_t bar = sb + OFF_BAR;
    const uint32_t dst = sb + OFF_R;
    const int kr = rank * 32;
#pragma unroll
    for (int it = I0; it < I1; it++) {
        const int s = it % NR;
        const uint32_t fb = bar + B_F1 + 8 * it;
        if (it >= 24 + NR) mbar_wait(bar + B_XD + 8 * (it - 24 - NR), 0);
        else if (it >= NR) mbar_wait(bar + B_E1 + 8 * s, ((it / NR) - 1) & 1);
        const int nkv = __builtin_popcount(KVMASK & ((1u << it) - 1));
        if (it < 16 && ((KVMASK >> it) & 1)) {
            tma3d_mc(dst + s * 16384 + rank * 8192, &tm.kv, nb * 64, nkv * 64 + kr, 1, fb);
        } else if (it < 16) {
            tma3d_mc(dst + s * 16384 + rank * 6144, &tm.q, 0, (it - nkv) * 64 + kr, nb * 2, fb);
            tma3d_mc(dst + s * 16384 + rank * 6144 + 4096, &tm.f1, 0, (it - nkv) * 64 + kr, nb * 7, fb);
        } else {
            tma3d_mc(dst + s * 16384 + rank * 6144, &tm.f3, 0, (it & 7) * 64 + kr, nb * 7 + (it < 24 ? 1 : 4), fb);
        }
        if ((XMASK >> it) & 1) {
            const int xc = 1 + __builtin_popcount(XMASK & ((1u << it) - 1));
            tma2d(sb + xc * 16384, &tm.x, xc * 64, mb * 128, bar + B_X + 8 * xc);
        }
    }
}

__global__ void __cluster_dims__(2, 1, 1) __launch_bounds__(640, 1)
fused_kernel(const __grid_constant__ Maps tm, const __nv_bfloat16* __restrict__ x, const __nv_bfloat16* __restrict__ wqkv,
             const __nv_bfloat16* __restrict__ wo, const __nv_bfloat16* __restrict__ w1, const __nv_bfloat16* __restrict__ b1,
             const __nv_bfloat16* __restrict__ w2, const __nv_bfloat16* __restrict__ b2, const __nv_bfloat16* __restrict__ gate,
             __nv_bfloat16* __restrict__ out, const uint32_t m1) {
    const uint32_t sb = smem_u32(smem_raw);
    const uint32_t bar = sb + OFF_BAR;
    const int tid = threadIdx.x, lane = tid & 31;
    const int warp = __shfl_sync(0xffffffffu, tid >> 5, 0);
    const uint32_t rank = cluster_rank();
    const int cl = blockIdx.x >> 1;
    const int nb = cl & 7, mb = (cl >> 3) * 2 + rank;
    const int g = lane >> 2, t = lane & 3;

    const int cb = nb & 3, rb = mb * 2 + (nb >> 2);
    const int rn = (mb >> 1) & 1;
    if (tid == 0) TLM(0, 0);
    TL_INIT();
    if (tid == 512) {
        for (int i = 0; i < 8; i++) { mbar_init(bar + B_X + 8 * i, 1); mbar_init(bar + B_KV + 8 * i, 1); mbar_init(bar + B_T + 8 * i, i < 4 ? 1 : 5); mbar_init(bar + B_XD + 8 * i, 16); }
        for (int i = 0; i < NR; i++) mbar_init(bar + B_E1 + 8 * i, 16);
        for (int i = 0; i < 4; i++) { mbar_init(bar + B_F2 + 8 * i, 1); mbar_init(bar + B_E2 + 8 * i, 8); }
        asm volatile("fence.mbarrier_init.release.cluster;" ::: "memory");
    } else if (tid == 608) {
        for (int i = 0; i < 32; i++) mbar_init(bar + B_F1 + 8 * i, 1);
        mbar_init(bar + B_G, 1);
        for (int i = 0; i < 3; i++) mbar_init(bar + B_SF + 8 * i, i == 1 ? 2 : 1);
        mbar_init(bar + B_SF2, 2);
        mbar_init(bar + B_G3, 1);
        mbar_init(bar + B_G2, 4);
        asm volatile("fence.mbarrier_init.release.cluster;" ::: "memory");
    }
    __syncwarp();
    asm volatile("barrier.cluster.arrive.relaxed.aligned;" ::: "memory");
    if (warp == 19) mbar_expect(bar + B_F1 + 8 * lane, ((KVMASK >> lane) & 1) ? 16384 : 12288);
    if (warp == 16 && lane < 24) mbar_expect(bar + (lane < 8 ? B_X : lane < 16 ? B_KV - 64 : B_T - 128) + 8 * lane, 16384);
    if (tid == 512) {
        tma2d(sb, &tm.x, 0, mb * 128, bar + B_X);
    } else if (tid == 544) {
        map_prefetch(&tm.kv);
        l2_prefetch((const uint8_t*)wqkv + (size_t)blockIdx.x * 3072, 3072);
        l2_prefetch((const uint8_t*)w1 + (size_t)blockIdx.x * 1792, 1792);
        map_prefetch(&tm.q); map_prefetch(&tm.f1); map_prefetch(&tm.f3);
    }
    if ((sb & 0xFFFFFF) != SBD) __trap();
    __syncwarp();
    asm volatile("barrier.cluster.wait.aligned;" ::: "memory");
    if (tid == 512) issue_stream<0, NR>(tm, sb, rank, nb, mb);
    if (tid == 0) { TLM(0, 1); TLC(0, 30); }

    if (warp < 16) {
        const int wg = warp >> 2;
        const int h = cl >> 1, qd = (cl & 1) * 2 + rank;
        const int flip = (h >> 2) & 1;
        uint32_t q[4];
        {
            const int w8 = warp & 7;
            const int T = mb * 8 + w8, row0 = T * 16 + g;
            const uint64_t dA0 = mkdesc(SBD + (wg & 1) * 8192, 16, 1024, 1);
            if (wg < 2) {
                float acc[64];
#pragma unroll
                for (int i = 0; i < 64; i++) acc[i] = 0.f;
                gemm_pass<128, 8192, 2048, 4096, 1024, 1>(acc, bar, dA0, lane, strm_pos(3, 0), strm_code(3), 0, true, false);
                if (tid == 0) TLM(0, 2);
                {
                    const float km = norm_bound(acc, 1.f);
                    float vm = 0.f;
#pragma unroll
                    for (int i = 32; i < 64; i++) vm = fmaxf(vm, fabsf(acc[i]));
                    vm = __uint_as_float(__reduce_max_sync(0xffffffffu, __float_as_uint(vm)));
                    if (lane == 0) { gN[1024 + nb * 128 + T] = km; gN[2048 + nb * 128 + T] = vm; }
                    const uint32_t kp = sb + OFF_R + 12288 + (w8 >> 2) * 1024 + g * 128 + ((((w8 & 3) * 2 + ((t >> 1) ^ (w8 >> 2))) ^ g) << 4) + (t & 1) * 8;
                    uint8_t* vp = gKV + (size_t)(nb * 4) * (SEQ * 64) + 65536 + (((T >> 6) * 16 + 2 * g) * 64 + (T & 63)) * 32 + ((t * 8) ^ ((w8 >> 2) << 4));
                    bar_sync(9, 256);
#pragma unroll
                    for (int hh = 0; hh < 4; hh++) {
                        const float* v = acc + 8 * hh;
                        float p0 = __shfl_up_sync(0xffffffffu, v[2], 4), p1 = __shfl_up_sync(0xffffffffu, v[3], 4);
                        float p2 = __shfl_up_sync(0xffffffffu, v[6], 4), p3 = __shfl_up_sync(0xffffffffu, v[7], 4);
                        if (g == 0) { p0 = p1 = p2 = p3 = 0.f; }
                        sts64(kp + hh * 16384, pk_f16(v[0] - p0, v[1] - p1), pk_f16(v[4] - p2, v[5] - p3));
                        sts64(kp + hh * 16384 + 2048, pk_f16(v[2] - v[0], v[3] - v[1]), pk_f16(v[6] - v[4], v[7] - v[5]));
                        const float* u = acc + 32 + 8 * hh;
                        if (hh < 2) {
                            sts64(kp + (4 + hh) * 16384, pk_bf16(u[0], u[1]), pk_bf16(u[4], u[5]));
                            sts64(kp + (4 + hh) * 16384 + 2048, pk_bf16(u[2], u[3]), pk_bf16(u[6], u[7]));
                        } else {
                            *(uint2*)(vp + (size_t)hh * (SEQ * 64)) = make_uint2(pk_bf16(u[0], u[1]), pk_bf16(u[4], u[5]));
                            *(uint2*)(vp + (size_t)hh * (SEQ * 64) + 2048) = make_uint2(pk_bf16(u[2], u[3]), pk_bf16(u[6], u[7]));
                        }
                    }
                }
                asm volatile("fence.proxy.async.shared::cta;" ::: "memory");
                bar_arrive(10, 288);
                if (tid == 0) TLM(0, 3);
            }
#pragma unroll 1
            for (int p = wg < 2 ? 1 : 0; p < 3; p += 2) {
                float acc[48];
#pragma unroll
                for (int i = 0; i < 48; i++) acc[i] = 0.f;
                pin<48>(acc);
                if (p) bar_sync(5 + p, 512);
                gemm_pass<96, 6144, 1024, 2048, 512, 2>(acc, bar, dA0, lane, p == 0 ? strm_pos(0, 0) : 8 + 8 * p, p == 0 ? strm_code(0) : strm_code(1), p < 2 ? 6 + p : 0, p == 0, p == 2);
                if ((tid & 255) == 0) TLM(0, 4 + 2 * p);
                const uint32_t hp = sb + OFF_R + (p == 2 ? 0 : 12288) + (wg & 1) * 16384 + ((warp & 3) * 16 + g) * 64 + t * 16;
                const uint32_t bp = sb + OFF_BIAS + p * 384 - 256 + t * 8;
                uint32_t ho[24];
                mbar_wait(bar + B_BI, 0);
                if (p == 0) {
                    const float qm = norm_bound(acc, QSCALE * QSCALE);
                    if (lane == 0) gN[nb * 128 + T] = qm;
                    uint8_t* qp = gQ + (size_t)(nb * 4) * (SEQ * 32) + (size_t)row0 * 32 + t * 8;
#pragma unroll
                    for (int hh = 0; hh < 4; hh++) {
                        const float* v = acc + 8 * hh;
                        *(uint2*)(qp + hh * (SEQ * 32)) = make_uint2(pk_f16(v[0] * QSCALE, v[1] * QSCALE), pk_f16(v[4] * QSCALE, v[5] * QSCALE));
                        *(uint2*)(qp + hh * (SEQ * 32) + 256) = make_uint2(pk_f16(v[2] * QSCALE, v[3] * QSCALE), pk_f16(v[6] * QSCALE, v[7] * QSCALE));
                    }
                    bar_arrive(12, 288);
                } else {
                    gelu_pack<0, 2>(acc, bp, ho);
                    pin<16>(ho);
                    mbar_wait(bar + B_G, 0);
                    load_q(q, h, qd * 512 + flip * 256 + warp * 16 + g, t);
                }
                gelu_pack<2, 3>(acc, bp, ho);
                pin<8>(ho + 16);
                if (p == 2) bar_sync(9, 256);
                else mbar_wait(bar + B_SF + 8 * p, 0);
                if (p) {
#pragma unroll
                    for (int i = 0; i < 4; i++) sts128(hp + (i >> 1) * 32768 + (i & 1) * 512, ho + 4 * i);
                }
                sts128(hp + 65536, ho + 16);
                sts128(hp + 65536 + 512, ho + 20);
                asm volatile("fence.proxy.async.shared::cta;" ::: "memory");
                bar_arrive(p == 1 ? 14 : 11, 288);
                if ((tid & 255) == 0) TLM(0, 5 + 2 * p);
            }
        }
        uint32_t ep = 2;
        uint4* const op = gO + ((qd * 8 + wg) * NH + h) * 128 + (tid & 127);
        const uint64_t kd0 = mkdesc(SBD, 16, 256, 3);
        const uint64_t vd0 = mkdesc(SBD + 8192, OFF_ONE - 8192, 256, 3);
        {
            float o[12];
            uint32_t qn[4];
#pragma unroll 1
            for (int rh = 0; rh < 4; rh++) {
                if (rh == 1) {
                    mbar_wait(bar + B_G3, 0);
                    ep = lds32(sb + OFF_G + 256);
                    if (!(ep & 2)) break;
                    load_q(qn, h, qd * 512 + (flip ^ 1) * 256 + warp * 16 + g, t);
                }
                if (!(rh & 1)) {
#pragma unroll
                    for (int i = 0; i < 12; i++) o[i] = 0.f;
                }
                uint64_t kd = kd0 + (rh & 1) * 4096, vd = vd0 + (rh & 1) * (128 * VSTEP);
                uint32_t kvb = bar + B_KV + (rh & 1) * 32;
                float s[32];
#pragma unroll
                for (int i = 0; i < 32; i++) s[i] = i < 2 * NMUFU ? 0.f : MAGIC;
                if ((tid & 255) == 0) TLM(1, (tid >> 8) * 4 + rh);
#pragma unroll 1
                for (int c = 0; c < 4; c++) {
                    mbar_wait(kvb, 0);
                    kvb += 8;
#pragma unroll
                    for (int j = 0; j < 4; j++) {
                        uint32_t p[16];
                        if (!MERGE || j == 0) {
                            wg_fence();
                            wgmma_qk_f16_acc(s, q, kd + j * 128);
                            wg_commit();
                        }
                        wg_wait<0>();
                        pin<32>(s);
#pragma unroll
                        for (int i = 0; i < 16; i++)
                            p[i] = i < NMUFU ? pk_bf16(ex2f(s[2 * i]), ex2f(s[2 * i + 1])) : exp2_pair(s[2 * i], s[2 * i + 1], m1);
                        pin<16>(p);
                        wg_fence();
#pragma unroll
                        for (int u = 0; u < 4; u++) {
                            if (MERGE && j < 3 && u == 5 - MERGE) wgmma_qk_f16_acc(s, q, kd + (j + 1) * 128);
                            wgmma_pv(o, p + 4 * u, vd + (j * 4 + u) * VSTEP);
                        }
                        if (MERGE == 1 && j < 3) wgmma_qk_f16_acc(s, q, kd + (j + 1) * 128);
                        wg_commit();
                    }
                    kd += 1024;
                    vd += 32 * VSTEP;
                }
                wg_wait<0>();
                pin<12>(o);
                if (rh & 1) {
                    if ((tid & 127) == 0 && rh == 3) TLM(1, 8 + wg);
                    store_o(o, op + ((rh >> 1) ^ flip) * (4 * NH * 128), ep & 1);
#pragma unroll
                    for (int i = 0; i < 4; i++) q[i] = qn[i];
                }
            }
            if (tid == 0) { TLM(1, 12); TLC(0, 31); }
        }
        if (!(ep & 2)) {
            bar_sync(8, 512);
            for (int c = 0; c < 8; c++) mbar_wait(bar + B_KV + 8 * c, 0);
            {
                float kc[8][8];
                proj16<8>(kc, x, wqkv, warp * 16, 256, DM + h * 16, g, t);
#pragma unroll
                for (int i = 0; i < 8; i++) {
                    const int T = warp + i * 16;
                    const int pos = ((T >> 6) * 16 + 2 * g) * 64 + (T & 63);
                    const uint32_t a = sb + (pos >> 8) * 16384 + (pos & 255) * 32 + t * 4, sw = ((T >> 2) & 1) << 4;
                    asm volatile("st.shared.u32 [%0], %1;" ::"r"(a + sw), "r"(pk_bf16(kc[i][0], kc[i][1])) : "memory");
                    asm volatile("st.shared.u32 [%0], %1;" ::"r"(a + (sw ^ 16)), "r"(pk_bf16(kc[i][4], kc[i][5])) : "memory");
                    asm volatile("st.shared.u32 [%0], %1;" ::"r"(a + 2048 + sw), "r"(pk_bf16(kc[i][2], kc[i][3])) : "memory");
                    asm volatile("st.shared.u32 [%0], %1;" ::"r"(a + 2048 + (sw ^ 16)), "r"(pk_bf16(kc[i][6], kc[i][7])) : "memory");
                }
                asm volatile("fence.proxy.async.shared::cta;" ::: "memory");
                bar_sync(8, 512);
            }
#pragma unroll 1
            for (int r = 0; r < 2; r++) {
                const int row = qd * 512 + (r ^ flip) * 256 + warp * 16 + g;
                {
                    float qc[1][8];
                    proj16<1>(qc, x, wqkv, row - g, 0, h * 16, g, t);
#pragma unroll
                    for (int i = 0; i < 4; i++) q[i] = pk_bf16(qc[0][2 * i] * QSCALE, qc[0][2 * i + 1] * QSCALE);
                }
                float o[12];
#pragma unroll
                for (int i = 0; i < 12; i++) o[i] = 0.f;
                float m0 = -INFINITY, m1 = -INFINITY;
#pragma unroll 1
                for (int j = 0; j < 32; j++) {
                    const uint64_t kd = kd0 + (j >> 2) * 1024 + (j & 3) * 128, vd = vd0 + ((j >> 2) * 32 + (j & 3) * 4) * VSTEP;
                    float s[32];
                    uint32_t p[16];
                    wg_fence();
                    wgmma_qk_bf16_zero(s, q, kd);
                    wg_commit();
                    wg_wait<0>();
                    pin<32>(s);
                    pin<12>(o);
                    float n0 = m0, n1 = m1;
#pragma unroll
                    for (int i = 0; i < 8; i++) {
                        n0 = fmaxf(n0, fmaxf(s[4 * i], s[4 * i + 1]));
                        n1 = fmaxf(n1, fmaxf(s[4 * i + 2], s[4 * i + 3]));
                    }
                    n0 = fmaxf(n0, __shfl_xor_sync(0xffffffffu, n0, 1));
                    n1 = fmaxf(n1, __shfl_xor_sync(0xffffffffu, n1, 1));
                    n0 = fmaxf(n0, __shfl_xor_sync(0xffffffffu, n0, 2));
                    n1 = fmaxf(n1, __shfl_xor_sync(0xffffffffu, n1, 2));
                    const float c0 = ex2f(m0 - n0), c1 = ex2f(m1 - n1);
                    m0 = n0;
                    m1 = n1;
#pragma unroll
                    for (int i = 0; i < 3; i++) { o[4 * i] *= c0; o[4 * i + 1] *= c0; o[4 * i + 2] *= c1; o[4 * i + 3] *= c1; }
#pragma unroll
                    for (int i = 0; i < 8; i++) {
                        p[2 * i] = pk_bf16(ex2f(s[4 * i] - m0), ex2f(s[4 * i + 1] - m0));
                        p[2 * i + 1] = pk_bf16(ex2f(s[4 * i + 2] - m1), ex2f(s[4 * i + 3] - m1));
                    }
                    pin<16>(p);
                    pin<12>(o);
                    wg_fence();
#pragma unroll
                    for (int u = 0; u < 4; u++) wgmma_pv(o, p + 4 * u, vd + u * VSTEP);
                    wg_commit();
                }
                wg_wait<0>();
                pin<12>(o);
                store_o(o, op + (r ^ flip) * (4 * NH * 128), ep & 1);
            }
        }
        {
            const uint4* src = gO + (rb * NH + (wg * 2 + (rn ^ 1)) * 4) * 128 + (tid & 127);
            uint4 v[4];
#pragma unroll
            for (int i = 0; i < 4; i++) v[i] = load_o(src + i * 128);
            mbar_wait(bar + B_G2, 0);
            const int lr = (warp & 3) * 16;
            const uint32_t g0 = lds32(sb + OFF_G + (lr + g) * 4), g1 = lds32(sb + OFF_G + (lr + g) * 4 + 32);
            const uint32_t a0 = sb + OFF_R + 32768 + wg * 8192 + (lr + (lane & 15)) * 128;
            fetch_o4(v, src, ep);
#pragma unroll
            for (int i = 0; i < 4; i++)
                asm volatile("stmatrix.sync.aligned.m8n8.x4.shared.b16 [%0], {%1, %2, %3, %4};" ::"r"(a0 + (((i * 2 + (lane >> 4)) ^ (lane & 7)) << 4)),
                             "r"(bmul2(v[i].x, g0)), "r"(bmul2(v[i].y, g1)), "r"(bmul2(v[i].z, g0)), "r"(bmul2(v[i].w, g1)) : "memory");
            asm volatile("fence.proxy.async.shared::cta;" ::: "memory");
            __syncwarp();
            if (lane == 0) mbar_arrive(bar + B_T + 32 + 8 * wg);
            if ((tid & 127) == 0) TLM(1, 20 + wg);
        }
    } else {
        if (warp == 16) {
            if (lane == 0) {
                issue_stream<NR, 32>(tm, sb, rank, nb, mb);
                mbar_wait(bar + B_SF2, 0);
#pragma unroll
                for (int s = 0; s < 4; s++) {
                    mbar_expect(bar + B_F2 + 8 * s, 24576);
                    tma5d_mc(sb + OFF_R + s * 24576 + 8192 + rank * 8192, &tm.w2, cb * 128 + rank * 64, s * 2, bar + B_F2 + 8 * s);
                }
                cnt_wait(gCntH + mb * 32, epoch() * 8);
                asm volatile("fence.proxy.async.global;" ::: "memory");
                TLM(1, 13);
#pragma unroll
                for (int s = 0; s < 4; s++) tma2d(sb + OFF_R + s * 24576, &tm.h, s * 64, rb * 64, bar + B_F2 + 8 * s);
            }
        } else if (warp == 17) {
            {
                uint32_t bv[4], b2v[2];
#pragma unroll
                for (int i = 0; i < 4; i++) bv[i] = lane + 32 * i < 112 ? *(const uint32_t*)(b1 + nb * 224 + (lane + 32 * i) * 2) : 0;
#pragma unroll
                for (int i = 0; i < 2; i++) b2v[i] = *(const uint32_t*)(b2 + cb * 128 + (lane + 32 * i) * 2);
#pragma unroll
                for (int i = 0; i < 4; i++) {
                    sts32(sb + OFF_ONE + (lane + 32 * i) * 4, 0x3f803f80u);
                    if (lane + 32 * i < 112) sts64(sb + OFF_BIAS + (lane + 32 * i) * 8, bv[i] << 16, bv[i] & 0xffff0000u);
                }
#pragma unroll
                for (int i = 0; i < 2; i++) sts32(sb + OFF_BIAS + 896 + (lane + 32 * i) * 4, b2v[i]);
                asm volatile("fence.proxy.async.shared::cta;" ::: "memory");
                __syncwarp();
                if (lane == 0) mbar_arrive(bar + B_BI);
            }
            mbar_wait(bar + B_X + 8 * PFX, 0);
            if (lane == 0) {
                l2_prefetch((const uint8_t*)wqkv + 128 * 3072 + (size_t)blockIdx.x * 9216, 9216);
                l2_prefetch((const uint8_t*)w1 + (size_t)blockIdx.x * 14336, 14336);
            }
            mbar_wait(bar + B_X + 8 * 7, 0);
            if (lane == 0) {
                l2_prefetch((const uint8_t*)w2 + (size_t)blockIdx.x * 14336, 14336);
                l2_prefetch((const uint8_t*)wo + (size_t)blockIdx.x * 4096, 4096);
                map_prefetch(&tm.h); map_prefetch(&tm.w2); map_prefetch(&tm.wo); map_prefetch(&tm.hs); map_prefetch(&tm.kvs);
                TLM(0, 11);
            }
            bar_sync(10, 288);
            if (lane == 0) {
#pragma unroll 1
                for (int b = 5; b >= 0; b--) {
                    tma5d_st(&tm.kvs, sb + OFF_R + 12288 + b * 16384, (mb >> 3) * 8, (mb & 7) * 2, nb * 8 + (b < 4 ? 2 * b : 2 * b - 7));
                    asm volatile("cp.async.bulk.commit_group;\ncp.async.bulk.wait_group.read %0;" ::"n"(PACE) : "memory");
                    if (b == 4 - PACE) mbar_arrive(bar + B_SF);
                }
                asm volatile("cp.async.bulk.wait_group.read 0;" ::: "memory");
                mbar_arrive(bar + B_SF + 8);
            }
            __syncwarp();
            bar_sync(12, 288);
            if (lane == 0) {
                asm volatile("cp.async.bulk.wait_group 0;\nfence.proxy.async.global;" ::: "memory");
                cnt_add(gCntQ + nb * 32);
                TLM(0, 13);
            }
        } else {
            {
                const int r0 = mb * 128 + nb * 16 + (warp - 18) * 8;
                uint4 xv[16];
#pragma unroll
                for (int i = 0; i < 16; i++) xv[i] = *(const uint4*)(x + (size_t)(r0 + (i >> 1)) * DM + (i & 1) * 256 + lane * 8);
                const uint4 ga = *(const uint4*)(gate + lane * 8), gb = *(const uint4*)(gate + 256 + lane * 8);
                float z[8];
#pragma unroll
                for (int r = 0; r < 8; r++) z[r] = dot8(xv[2 * r], ga) + dot8(xv[2 * r + 1], gb);
#pragma unroll
                for (int w = 4; w >= 1; w >>= 1)
#pragma unroll
                    for (int r = 0; r < w; r++) {
                        const bool up = lane & w;
                        z[r] = (up ? z[r + w] : z[r]) + __shfl_xor_sync(0xffffffffu, up ? z[r] : z[r + w], w);
                    }
                z[0] += __shfl_xor_sync(0xffffffffu, z[0], 8);
                z[0] += __shfl_xor_sync(0xffffffffu, z[0], 16);
                if (lane < 8) gG[r0 + lane] = 1.f / (1.f + __expf(-z[0]));
                if (tid == 576) TLM(0, 12);
            }
            if (warp == 19) {
#pragma unroll 1
                for (int e = 0; e < 3; e++) {
                    bar_sync(e == 1 ? 14 : 11, 288);
                    if (lane == 0) {
#pragma unroll 1
                        for (int b = e == 0 ? 4 : 0; b < 6; b++) {
                            tma3d_st(&tm.hs, sb + OFF_R + (e == 2 ? 0 : 12288) + b * 16384, 0, mb * 128 + (b & 1) * 64, nb * 7 + e * 3 - 2 + (b >> 1));
                            asm volatile("cp.async.bulk.commit_group;\ncp.async.bulk.wait_group.read %0;" ::"n"(PACE) : "memory");
                        }
                        asm volatile("cp.async.bulk.wait_group.read 0;" ::: "memory");
                        if (e == 0) mbar_arrive(bar + B_SF + 8);
                        if (e == 2) { mbar_arrive_cluster(bar + B_SF2, 0); mbar_arrive_cluster(bar + B_SF2, 1); }
                    }
                    __syncwarp();
                }
                bar_sync(13, 64);
                if (lane == 0) {
                    asm volatile("cp.async.bulk.wait_group 0;\nfence.proxy.async.global;" ::: "memory");
                    cnt_add(gCntH + mb * 32);
                    TLM(0, 15);
                }
            } else {
                bar_arrive(13, 64);
                const int h = cl >> 1, qd = (cl & 1) * 2 + rank;
                const uint32_t ep = epoch();
                if (lane == 0) {
                    cnt_wait(gCntQ + (h >> 2) * 32, ep * 16);
                    mbar_arrive(bar + B_G);
                    TLM(0, 14);
                    asm volatile("fence.proxy.async.global;" ::: "memory");
#pragma unroll
                    for (int c = 0; c < 2; c++) {
                        mbar_wait(bar + B_XD + 8 * c, 0);
                        bulk_mc(sb + c * 16384 + rank * 8192, gKV + (size_t)h * (SEQ * 64) + rank * 65536 + c * 8192, 8192, bar + B_KV + 8 * c);
                    }
                }
                __syncwarp();
            const int hb = h >> 2;
            const uint4 kq = __ldcg((const uint4*)(gN + 1024 + hb * 128 + lane * 4));
            const uint4 vq = __ldcg((const uint4*)(gN + 2048 + hb * 128 + lane * 4));
            const float qq = ldcg_f(gN + hb * 128 + qd * 32 + lane);
            const float kf = __uint_as_float(__reduce_max_sync(0xffffffffu, max(max(kq.x, kq.y), max(kq.z, kq.w))));
            const float vf = __uint_as_float(__reduce_max_sync(0xffffffffu, max(max(vq.x, vq.y), max(vq.z, vq.w))));
            const float qf = __uint_as_float(__reduce_max_sync(0xffffffffu, __float_as_uint(qq)));
            if (lane == 0) {
                sts32(sb + OFF_G + 256, (ep & 1) | ((kf <= 1.0e6f) && (qf <= 1.0e6f) && (kf * qf <= 3400.f) && (vf <= 1.0e12f) ? 2 : 0));
                mbar_arrive(bar + B_G3);
                TLM(0, 16);
#pragma unroll
                for (int c = 2; c < 8; c++) {
                    mbar_wait(bar + B_XD + 8 * c, 0);
                    bulk_mc(sb + c * 16384 + rank * 8192, gKV + (size_t)h * (SEQ * 64) + rank * 65536 + c * 8192, 8192, bar + B_KV + 8 * c);
                }
                TLM(0, 10);
            }
            }
        }
        __syncwarp();
        float acc[64];
#pragma unroll
        for (int i = 0; i < 64; i++) acc[i] = 0.f;
#pragma unroll 1
        for (int io = 0; io < 7; io++) {
#pragma unroll
            for (int s = 0; s < 4; s++) {
                const int it = io * 4 + s;
                mbar_wait(bar + B_F2 + 8 * s, io & 1);
                if (tid == 512 && s == 0 && (io == 0 || io == 4)) TLM(1, 14 + io / 4);
                const uint64_t dA = mkdesc(SBD + OFF_R + s * 24576, 16, 1024, 1);
                const uint64_t dB = mkdesc(SBD + OFF_R + s * 24576 + 8192, 8192, 1024, 1);
                wg_fence();
#pragma unroll
                for (int kk = 0; kk < EXP_FKK; kk++) {
                    wgmma_ss_n128(acc, dA + kk * 2, dB + kk * 128);
                }
                wg_commit();
                if (warp < 18 && it >= 2 && it < 26) {
                    const int s2 = (s + 2) & 3;
                    mbar_wait(bar + B_E2 + 8 * s2, (io - (s < 2)) & 1);
                    if (elect()) {
                        if (warp == 16) {
                            mbar_expect(bar + B_F2 + 8 * s2, 24576);
                            tma5d_mc(sb + OFF_R + s2 * 24576 + 8192 + rank * 8192, &tm.w2, cb * 128 + rank * 64, it * 2 + 4, bar + B_F2 + 8 * s2);
                        } else {
                            asm volatile("fence.proxy.async.global;" ::: "memory");
                            tma2d(sb + OFF_R + s2 * 24576, &tm.h, it * 64 + 128, rb * 64, bar + B_F2 + 8 * s2);
                        }
                    }
                    __syncwarp();
                }
                wg_wait<1>();
                if (it >= 1 && lane < 2) mbar_arrive_cluster(bar + B_E2 + 8 * ((s + 3) & 3), lane);
            }
        }
        wg_wait<0>();
        if (lane < 2) mbar_arrive_cluster(bar + B_E2 + 8 * 3, lane);
        pin<64>(acc);
        if (tid == 576) gEpoch[blockIdx.x] = epoch();
        if (warp == 16) {
            if (lane == 0) TLM(1, 16);
            for (int s = 0; s < 4; s++) mbar_wait(bar + B_E2 + 8 * s, 0);
            if (elect()) {
#pragma unroll
                for (int i = 0; i < 6; i++)
                    tma5d_mc(sb + OFF_R + i * 16384 + rank * 8192, &tm.wo, cb * 128 + rank * 64, ((i & 3) * 2 + (rn ^ (i >> 2))) * 4, bar + B_T + 8 * i);
            }
            __syncwarp();
        }
        uint32_t pa;
        {
            const int lr = (warp - 16) * 16 + g;
            pa = pk_bf16(ldcg_f(gG + rb * 64 + lr), ldcg_f(gG + rb * 64 + lr + 8));
            if (t == 0) {
                sts32(sb + OFF_G + lr * 4, __byte_perm(pa, pa, 0x1010));
                sts32(sb + OFF_G + lr * 4 + 32, __byte_perm(pa, pa, 0x3232));
            }
            const float ga = bf_lo(pa), gb = bf_hi(pa);
            const float g0 = 1.f - ga, g1 = 1.f - gb;
#pragma unroll
            for (int j = 0; j < 16; j++) {
                const uint32_t bv = lds32(sb + OFF_BIAS + 896 + j * 16 + t * 4);
                acc[4 * j] = fmaf(acc[4 * j], 0.5f, bf_lo(bv)) * g0;
                acc[4 * j + 1] = fmaf(acc[4 * j + 1], 0.5f, bf_hi(bv)) * g0;
                acc[4 * j + 2] = fmaf(acc[4 * j + 2], 0.5f, bf_lo(bv)) * g1;
                acc[4 * j + 3] = fmaf(acc[4 * j + 3], 0.5f, bf_hi(bv)) * g1;
            }
            pin<64>(acc);
        }
        {
            mbar_wait(bar + B_G3, 0);
            const uint32_t ep = lds32(sb + OFF_G + 256);
            const uint32_t g0 = __byte_perm(pa, pa, 0x1010), g1 = __byte_perm(pa, pa, 0x3232);
            const uint4* src = gO + (rb * NH + rn * 4) * 128 + (tid & 127);
            uint64_t dB = mkdesc(SBD + OFF_R, 8192, 1024, 1);
#pragma unroll 1
            for (int e = 0; e < 4; e++) {
                uint4 v[4];
#pragma unroll
                for (int i = 0; i < 4; i++) v[i] = load_o(src + i * 128);
                mbar_wait(bar + B_T + 8 * e, 0);
                fetch_o4(v, src, ep);
#pragma unroll
                for (int i = 0; i < 4; i++) {
                    uint32_t a[4] = {bmul2(v[i].x, g0), bmul2(v[i].y, g1), bmul2(v[i].z, g0), bmul2(v[i].w, g1)};
                    pin<4>(a);
                    wg_fence();
                    wgmma_rs_n128(acc, a, dB + i * 128);
                    wg_commit();
                    wg_wait<0>();
                }
                src += 8 * 128;
                dB += 1024;
            }
            __syncwarp();
            if (lane == 0) mbar_arrive(bar + B_G2);
            if (warp == 16) {
                mbar_wait(bar + B_G2, 0);
                if (elect()) {
#pragma unroll
                    for (int i = 0; i < 4; i++)
                        tma5d(sb + OFF_R + i * 8192, &tm.wo, cb * 128 + (i & 1) * 64, ((2 + (i >> 1)) * 2 + (rn ^ 1)) * 4, bar + B_T + 8 * (6 + (i >> 1)));
                }
                __syncwarp();
            }
        }
        if (tid == 512) TLM(1, 17);
#pragma unroll
        for (int i = 0; i < 4; i++) {
            mbar_wait(bar + B_T + 32 + 8 * i, 0);
            const uint64_t dA = mkdesc(SBD + OFF_R + 32768 + i * 8192, 16, 1024, 1);
            const uint64_t dB = mkdesc(SBD + OFF_R + (i < 2 ? 4 + i : i - 2) * 16384, 8192, 1024, 1);
            wg_fence();
#pragma unroll
            for (int kk = 0; kk < 4; kk++) wgmma_ss_n128(acc, dA + kk * 2, dB + kk * 128);
            wg_commit();
        }
        wg_wait<0>();
        pin<64>(acc);
        if (tid == 512) TLM(1, 18);
        {
            const uint32_t st = sb + 98304 + (warp - 16) * 4352;
            const uint32_t wa = st + (lane & 15) * 272 + (lane >> 4) * 16;
#pragma unroll
            for (int j = 0; j < 8; j++)
                asm volatile("stmatrix.sync.aligned.m8n8.x4.shared.b16 [%0], {%1, %2, %3, %4};" ::"r"(wa + j * 32),
                             "r"(pk_bf16(acc[8 * j], acc[8 * j + 1])), "r"(pk_bf16(acc[8 * j + 2], acc[8 * j + 3])),
                             "r"(pk_bf16(acc[8 * j + 4], acc[8 * j + 5])), "r"(pk_bf16(acc[8 * j + 6], acc[8 * j + 7])) : "memory");
            __syncwarp();
            __nv_bfloat16* op = out + (size_t)(rb * 64 + (warp - 16) * 16 + (lane >> 4)) * DM + cb * 128 + (lane & 15) * 8;
#pragma unroll
            for (int j = 0; j < 8; j++) {
                uint4 v;
                asm volatile("ld.shared.v4.u32 {%0, %1, %2, %3}, [%4];" : "=r"(v.x), "=r"(v.y), "=r"(v.z), "=r"(v.w)
                             : "r"(st + (2 * j + (lane >> 4)) * 272 + (lane & 15) * 16));
                *(uint4*)(op + (size_t)j * 2 * DM) = v;
            }
        }
        if (tid == 512) TLM(1, 19);
        TL_DUMP();
    }
}

typedef CUresult (*EncodeFn)(CUtensorMap*, CUtensorMapDataType, cuuint32_t, void*, const cuuint64_t*, const cuuint64_t*, const cuuint32_t*,
                             const cuuint32_t*, CUtensorMapInterleave, CUtensorMapSwizzle, CUtensorMapL2promotion, CUtensorMapFloatOOBfill);

static void make_map(EncodeFn enc, CUtensorMap* m, const void* p, int rank, const cuuint64_t* dims, const cuuint64_t* strides,
                     const cuuint32_t* box, CUtensorMapSwizzle swz) {
    const cuuint32_t es[5] = {1, 1, 1, 1, 1};
    enc(m, CU_TENSOR_MAP_DATA_TYPE_BFLOAT16, rank, (void*)p, dims, strides, box, es, CU_TENSOR_MAP_INTERLEAVE_NONE, swz,
        CU_TENSOR_MAP_L2_PROMOTION_L2_128B, CU_TENSOR_MAP_FLOAT_OOB_FILL_NONE);
}

extern "C" void kernel_launch(void* const* d_in, const int* in_sizes, int n_in, void* d_out, int out_size) {
    const __nv_bfloat16* x = (const __nv_bfloat16*)d_in[0];
    const __nv_bfloat16* wqkv = (const __nv_bfloat16*)d_in[1];
    const __nv_bfloat16* wo = (const __nv_bfloat16*)d_in[2];
    const __nv_bfloat16* w1 = (const __nv_bfloat16*)d_in[4];
    const __nv_bfloat16* b1 = (const __nv_bfloat16*)d_in[5];
    const __nv_bfloat16* w2 = (const __nv_bfloat16*)d_in[6];
    const __nv_bfloat16* b2 = (const __nv_bfloat16*)d_in[7];
    const __nv_bfloat16* gate = (const __nv_bfloat16*)d_in[8];

    void* fp = nullptr;
    cudaDriverEntryPointQueryResult qr;
    cudaGetDriverEntryPoint("cuTensorMapEncodeTiled", &fp, cudaEnableDefault, &qr);
    EncodeFn enc = (EncodeFn)fp;
    void *pH, *pKV;
    cudaGetSymbolAddress(&pH, gH);
    cudaGetSymbolAddress(&pKV, gKV);

    Maps tm;
    const CUtensorMapSwizzle S128 = CU_TENSOR_MAP_SWIZZLE_128B, S64 = CU_TENSOR_MAP_SWIZZLE_64B;
    { cuuint64_t d[2] = {DM, SEQ}, s[1] = {DM * 2}; cuuint32_t b[2] = {64, 128}; make_map(enc, &tm.x, x, 2, d, s, b, S128); }
    { cuuint64_t d[3] = {DM, DM, 3}, s[2] = {3 * DM * 2, DM * 2}; cuuint32_t b[3] = {64, 32, 2}; make_map(enc, &tm.kv, wqkv, 3, d, s, b, S128); }
    { cuuint64_t d[3] = {32, DM, 3 * DM / 32}, s[2] = {3 * DM * 2, 64}; cuuint32_t b[3] = {32, 32, 2}; make_map(enc, &tm.q, wqkv, 3, d, s, b, S64); }
    { cuuint64_t d[3] = {32, DM, FF / 32}, s[2] = {FF * 2, 64}; cuuint32_t b[3] = {32, 32, 1}; make_map(enc, &tm.f1, w1, 3, d, s, b, S64); }
    { cuuint64_t d[3] = {32, DM, FF / 32}, s[2] = {FF * 2, 64}; cuuint32_t b[3] = {32, 32, 3}; make_map(enc, &tm.f3, w1, 3, d, s, b, S64); }
    { cuuint64_t d[2] = {FF, SEQ}, s[1] = {FF * 2}; cuuint32_t b[2] = {64, 64}; make_map(enc, &tm.h, pH, 2, d, s, b, S128); }
    { cuuint64_t d[5] = {DM, 2, 4, 4, FF / 32}, s[4] = {1024, 8 * 1024, 2 * 1024, 32 * 1024}; cuuint32_t b[5] = {64, 2, 4, 4, 2};
      make_map(enc, &tm.w2, w2, 5, d, s, b, S128); }
    { cuuint64_t d[5] = {DM, 2, 2, 4, NH}, s[4] = {1024, 8 * 1024, 2 * 1024, 16 * 1024}; cuuint32_t b[5] = {64, 2, 2, 4, 4};
      make_map(enc, &tm.wo, wo, 5, d, s, b, S128); }

    { cuuint64_t d[3] = {32, SEQ, FF / 32}, s[2] = {FF * 2, 64}; cuuint32_t b[3] = {32, 64, 1}; make_map(enc, &tm.hs, pH, 3, d, s, b, CU_TENSOR_MAP_SWIZZLE_NONE); }
    { cuuint64_t d[5] = {64, 16, 16, 2, 2 * NH}, s[4] = {4096, 128, 2048, 65536}; cuuint32_t b[5] = {64, 8, 2, 2, 1};
      make_map(enc, &tm.kvs, pKV, 5, d, s, b, S128); }
    cudaFuncSetAttribute(fused_kernel, cudaFuncAttributeMaxDynamicSharedMemorySize, TL_SMEM);
    fused_kernel<<<128, 640, TL_SMEM, cudaStreamPerThread>>>(tm, x, wqkv, wo, w1, b1, w2, b2, gate, (__nv_bfloat16*)d_out, 0xffffffffu);
}
```

```cpp
#include <cuda_runtime.h>
#include <cuda_bf16.h>
#include <cuda_fp16.h>
#include <cuda.h>
#include <stdint.h>

#define SEQ 2048
#define DM 512
#define FF 1792
#define NH 32

__device__ __align__(1024) uint8_t gQ[NH * SEQ * 32];
__device__ __align__(1024) uint8_t gKV[NH * SEQ * 64];
__device__ __align__(1024) __nv_bfloat16 gH[SEQ * FF];
__device__ __align__(1024) uint4 gO[32 * NH * 128];
__device__ float gG[SEQ];
__device__ float gN[3 * 8 * 128];
__device__ unsigned int gCntQ[8 * 32];
__device__ unsigned int gCntH[32 * 32];
__device__ unsigned int gEpoch[128];

__device__ __forceinline__ uint32_t smem_u32(const void* p) { return (uint32_t)__cvta_generic_to_shared(p); }
__device__ __forceinline__ void mbar_init(uint32_t a, uint32_t c) { asm volatile("mbarrier.init.shared::cta.b64 [%0], %1;" ::"r"(a), "r"(c)); }
__device__ __forceinline__ void mbar_expect(uint32_t a, uint32_t b) { asm volatile("mbarrier.arrive.expect_tx.shared::cta.b64 _, [%0], %1;" ::"r"(a), "r"(b) : "memory"); }
__device__ __forceinline__ void mbar_arrive(uint32_t a) { asm volatile("mbarrier.arrive.shared::cta.b64 _, [%0];" ::"r"(a) : "memory"); }
__device__ __forceinline__ void mbar_wait(uint32_t a, uint32_t ph) {
    asm volatile("{\n.reg .pred p;\n.reg .u32 n;\nmov.u32 n, 0;\nW_%=:\nmbarrier.try_wait.parity.shared::cta.b64 p, [%0], %1;\n@p bra D_%=;\n"
                 "add.u32 n, n, 1;\nsetp.lt.u32 p, n, 0x400000;\n@p bra W_%=;\ntrap;\nD_%=:\n}" ::"r"(a), "r"(ph) : "memory");
}
__device__ __forceinline__ void mbar_arrive_cluster(uint32_t a, uint32_t cta) {
    asm volatile("{\n.reg .b32 r;\nmapa.shared::cluster.u32 r, %0, %1;\nmbarrier.arrive.shared::cluster.b64 _, [r];\n}" ::"r"(a), "r"(cta) : "memory");
}
__device__ __forceinline__ void bar_sync(int id, int n) { asm volatile("bar.sync %0, %1;" ::"r"(id), "r"(n) : "memory"); }
__device__ __forceinline__ void bar_arrive(int id, int n) { asm volatile("bar.arrive %0, %1;" ::"r"(id), "r"(n) : "memory"); }
__device__ __forceinline__ uint32_t cluster_rank() { uint32_t r; asm("mov.u32 %0, %%cluster_ctarank;" : "=r"(r)); return r; }
__device__ __forceinline__ void cnt_add(unsigned int* c) { asm volatile("red.release.gpu.global.add.u32 [%0], 1;" ::"l"(c) : "memory"); }
__device__ __forceinline__ void cnt_wait(const unsigned int* c, uint32_t target) {
    uint32_t v;
    int spins = 0;
    while (true) {
        asm volatile("ld.acquire.gpu.global.u32 %0, [%1];" : "=r"(v) : "l"(c) : "memory");
        if ((int)(v - target) >= 0) break;
        if (++spins > (1 << 22)) __trap();
        __nanosleep(40);
    }
}
__device__ __forceinline__ void tma2d(uint32_t dst, const CUtensorMap* m, int c0, int c1, uint32_t bar) {
    asm volatile("cp.async.bulk.tensor.2d.shared::cluster.global.mbarrier::complete_tx::bytes [%0], [%1, {%3, %4}], [%2];"
                 ::"r"(dst), "l"(m), "r"(bar), "r"(c0), "r"(c1) : "memory");
}
__device__ __forceinline__ void tma2d_mc(uint32_t dst, const CUtensorMap* m, int c0, int c1, uint32_t bar) {
    asm volatile("cp.async.bulk.tensor.2d.shared::cluster.global.mbarrier::complete_tx::bytes.multicast::cluster [%0], [%1, {%3, %4}], [%2], %5;"
                 ::"r"(dst), "l"(m), "r"(bar), "r"(c0), "r"(c1), "h"((uint16_t)3) : "memory");
}
__device__ __forceinline__ void tma3d_mc(uint32_t dst, const CUtensorMap* m, int c0, int c1, int c2, uint32_t bar) {
    asm volatile("cp.async.bulk.tensor.3d.shared::cluster.global.mbarrier::complete_tx::bytes.multicast::cluster [%0], [%1, {%3, %4, %5}], [%2], %6;"
                 ::"r"(dst), "l"(m), "r"(bar), "r"(c0), "r"(c1), "r"(c2), "h"((uint16_t)3) : "memory");
}
__device__ __forceinline__ void tma5d_mc(uint32_t dst, const CUtensorMap* m, int c0, int c4, uint32_t bar) {
    asm volatile("cp.async.bulk.tensor.5d.shared::cluster.global.mbarrier::complete_tx::bytes.multicast::cluster [%0], [%1, {%3, %5, %5, %5, %4}], [%2], %6;"
                 ::"r"(dst), "l"(m), "r"(bar), "r"(c0), "r"(c4), "r"(0), "h"((uint16_t)3) : "memory");
}
__device__ __forceinline__ void tma5d(uint32_t dst, const CUtensorMap* m, int c0, int c4, uint32_t bar) {
    asm volatile("cp.async.bulk.tensor.5d.shared::cluster.global.mbarrier::complete_tx::bytes [%0], [%1, {%3, %5, %5, %5, %4}], [%2];"
                 ::"r"(dst), "l"(m), "r"(bar), "r"(c0), "r"(c4), "r"(0) : "memory");
}
__device__ __forceinline__ void bulk_mc(uint32_t dst, const void* src, uint32_t bytes, uint32_t bar) {
    asm volatile("cp.async.bulk.shared::cluster.global.mbarrier::complete_tx::bytes.multicast::cluster [%0], [%1], %2, [%3], %4;"
                 ::"r"(dst), "l"(src), "r"(bytes), "r"(bar), "h"((uint16_t)3) : "memory");
}
__device__ __forceinline__ void tma3d_st(const CUtensorMap* m, uint32_t src, int c0, int c1, int c2) {
    asm volatile("cp.async.bulk.tensor.3d.global.shared::cta.bulk_group [%0, {%2, %3, %4}], [%1];" ::"l"(m), "r"(src), "r"(c0), "r"(c1), "r"(c2) : "memory");
}
__device__ __forceinline__ void tma5d_st(const CUtensorMap* m, uint32_t src, int c1, int c2, int c4) {
    asm volatile("cp.async.bulk.tensor.5d.global.shared::cta.bulk_group [%0, {%5, %2, %3, %5, %4}], [%1];"
                 ::"l"(m), "r"(src), "r"(c1), "r"(c2), "r"(c4), "r"(0) : "memory");
}
__device__ __forceinline__ void bulk_st(void* dst, uint32_t src, uint32_t bytes) {
    asm volatile("cp.async.bulk.global.shared::cta.bulk_group [%0], [%1], %2;" ::"l"(dst), "r"(src), "r"(bytes) : "memory");
}
__device__ __forceinline__ void sts64(uint32_t a, uint32_t x, uint32_t y) { asm volatile("st.shared.v2.u32 [%0], {%1, %2};" ::"r"(a), "r"(x), "r"(y) : "memory"); }
__device__ __forceinline__ void sts128(uint32_t a, const uint32_t* v) {
    asm volatile("st.shared.v4.u32 [%0], {%1, %2, %3, %4};" ::"r"(a), "r"(v[0]), "r"(v[1]), "r"(v[2]), "r"(v[3]) : "memory");
}
__device__ __forceinline__ void l2_prefetch(const void* src, uint32_t bytes) {
    asm volatile("cp.async.bulk.prefetch.L2.global [%0], %1;" ::"l"(src), "r"(bytes) : "memory");
}
__device__ __forceinline__ void map_prefetch(const CUtensorMap* m) { asm volatile("prefetch.tensormap [%0];" ::"l"(m) : "memory"); }
__device__ __forceinline__ void wg_fence() { asm volatile("wgmma.fence.sync.aligned;" ::: "memory"); }
__device__ __forceinline__ void wg_commit() { asm volatile("wgmma.commit_group.sync.aligned;" ::: "memory"); }
template <int N> __device__ __forceinline__ void wg_wait() { asm volatile("wgmma.wait_group.sync.aligned %0;" ::"n"(N) : "memory"); }
template <int N> __device__ __forceinline__ void pin(float* s) {
#pragma unroll
    for (int i = 0; i < N; i++) asm volatile("" : "+f"(s[i])::"memory");
}
template <int N> __device__ __forceinline__ void pin(uint32_t* s) {
#pragma unroll
    for (int i = 0; i < N; i++) asm volatile("" : "+r"(s[i])::"memory");
}
__device__ __forceinline__ uint64_t mkdesc(uint32_t addr, uint32_t lbo, uint32_t sbo, uint32_t swz) {
    return (uint64_t)((addr & 0x3FFFF) >> 4) | ((uint64_t)(lbo >> 4) << 16) | ((uint64_t)(sbo >> 4) << 32) | ((uint64_t)swz << 62);
}
__device__ __forceinline__ float ex2f(float x) { float y; asm("ex2.approx.ftz.f32 %0, %1;" : "=f"(y) : "f"(x)); return y; }
__device__ __forceinline__ float tanhf_(float x) { float y; asm("tanh.approx.f32 %0, %1;" : "=f"(y) : "f"(x)); return y; }
__device__ __forceinline__ uint32_t pk_bf16(float lo, float hi) { uint32_t r; asm("cvt.rn.bf16x2.f32 %0, %1, %2;" : "=r"(r) : "f"(hi), "f"(lo)); return r; }
__device__ __forceinline__ uint32_t pk_f16(float lo, float hi) { uint32_t r; asm("cvt.rn.f16x2.f32 %0, %1, %2;" : "=r"(r) : "f"(hi), "f"(lo)); return r; }
__device__ __forceinline__ float bf_lo(uint32_t v) { return __uint_as_float(v << 16); }
__device__ __forceinline__ float bf_hi(uint32_t v) { return __uint_as_float(v & 0xffff0000u); }
__device__ __forceinline__ float dot8(const uint4& a, const uint4& b) {
    return fmaf(bf_lo(a.x), bf_lo(b.x), fmaf(bf_hi(a.x), bf_hi(b.x), fmaf(bf_lo(a.y), bf_lo(b.y), bf_hi(a.y) * bf_hi(b.y)))) +
           fmaf(bf_lo(a.z), bf_lo(b.z), fmaf(bf_hi(a.z), bf_hi(b.z), fmaf(bf_lo(a.w), bf_lo(b.w), bf_hi(a.w) * bf_hi(b.w))));
}
__device__ __forceinline__ uint32_t epoch() {
    uint32_t v;
    asm volatile("ld.global.u32 %0, [%1];" : "=r"(v) : "l"(gEpoch + blockIdx.x));
    return v + 1;
}
__device__ __forceinline__ float ldcg_f(const float* p) { return __ldcg(p); }

extern __shared__ __align__(1024) uint8_t smem_raw[];
#define TLM(k, slot) do {} while (0)
#define TLC(k, slot) do {} while (0)
#define TL_INIT() do {} while (0)
#define TL_DUMP() do {} while (0)
#define TL_SMEM SMEM_BYTES

__device__ __forceinline__ void wgmma_ss_n128(float* d, uint64_t da, uint64_t db) {
    asm volatile("wgmma.mma_async.sync.aligned.m64n128k16.f32.bf16.bf16 {"
        "%0, %1, %2, %3, %4, %5, %6, %7, %8, %9, %10, %11, %12, %13, %14, %15,"
        "%16, %17, %18, %19, %20, %21, %22, %23, %24, %25, %26, %27, %28, %29, %30, %31,"
        "%32, %33, %34, %35, %36, %37, %38, %39, %40, %41, %42, %43, %44, %45, %46, %47,"
        "%48, %49, %50, %51, %52, %53, %54, %55, %56, %57, %58, %59, %60, %61, %62, %63}, %64, %65, 1, 1, 1, 0, 1;\n"
        :
        "+f"(d[0]), "+f"(d[1]), "+f"(d[2]), "+f"(d[3]), "+f"(d[4]), "+f"(d[5]), "+f"(d[6]), "+f"(d[7]),
        "+f"(d[8]), "+f"(d[9]), "+f"(d[10]), "+f"(d[11]), "+f"(d[12]), "+f"(d[13]), "+f"(d[14]), "+f"(d[15]),
        "+f"(d[16]), "+f"(d[17]), "+f"(d[18]), "+f"(d[19]), "+f"(d[20]), "+f"(d[21]), "+f"(d[22]), "+f"(d[23]),
        "+f"(d[24]), "+f"(d[25]), "+f"(d[26]), "+f"(d[27]), "+f"(d[28]), "+f"(d[29]), "+f"(d[30]), "+f"(d[31]),
        "+f"(d[32]), "+f"(d[33]), "+f"(d[34]), "+f"(d[35]), "+f"(d[36]), "+f"(d[37]), "+f"(d[38]), "+f"(d[39]),
        "+f"(d[40]), "+f"(d[41]), "+f"(d[42]), "+f"(d[43]), "+f"(d[44]), "+f"(d[45]), "+f"(d[46]), "+f"(d[47]),
        "+f"(d[48]), "+f"(d[49]), "+f"(d[50]), "+f"(d[51]), "+f"(d[52]), "+f"(d[53]), "+f"(d[54]), "+f"(d[55]),
        "+f"(d[56]), "+f"(d[57]), "+f"(d[58]), "+f"(d[59]), "+f"(d[60]), "+f"(d[61]), "+f"(d[62]), "+f"(d[63])
        : "l"(da), "l"(db));
}
__device__ __forceinline__ void wgmma_ss_n96(float* d, uint64_t da, uint64_t db) {
    asm volatile("wgmma.mma_async.sync.aligned.m64n96k16.f32.bf16.bf16 {"
        "%0, %1, %2, %3, %4, %5, %6, %7, %8, %9, %10, %11, %12, %13, %14, %15,"
        "%16, %17, %18, %19, %20, %21, %22, %23, %24, %25, %26, %27, %28, %29, %30, %31,"
        "%32, %33, %34, %35, %36, %37, %38, %39, %40, %41, %42, %43, %44, %45, %46, %47}, %48, %49, 1, 1, 1, 0, 1;\n"
        :
        "+f"(d[0]), "+f"(d[1]), "+f"(d[2]), "+f"(d[3]), "+f"(d[4]), "+f"(d[5]), "+f"(d[6]), "+f"(d[7]),
        "+f"(d[8]), "+f"(d[9]), "+f"(d[10]), "+f"(d[11]), "+f"(d[12]), "+f"(d[13]), "+f"(d[14]), "+f"(d[15]),
        "+f"(d[16]), "+f"(d[17]), "+f"(d[18]), "+f"(d[19]), "+f"(d[20]), "+f"(d[21]), "+f"(d[22]), "+f"(d[23]),
        "+f"(d[24]), "+f"(d[25]), "+f"(d[26]), "+f"(d[27]), "+f"(d[28]), "+f"(d[29]), "+f"(d[30]), "+f"(d[31]),
        "+f"(d[32]), "+f"(d[33]), "+f"(d[34]), "+f"(d[35]), "+f"(d[36]), "+f"(d[37]), "+f"(d[38]), "+f"(d[39]),
        "+f"(d[40]), "+f"(d[41]), "+f"(d[42]), "+f"(d[43]), "+f"(d[44]), "+f"(d[45]), "+f"(d[46]), "+f"(d[47])
        : "l"(da), "l"(db));
}
__device__ __forceinline__ void wgmma_ss_n64(float* d, uint64_t da, uint64_t db) {
    asm volatile("wgmma.mma_async.sync.aligned.m64n64k16.f32.bf16.bf16 {"
        "%0, %1, %2, %3, %4, %5, %6, %7, %8, %9, %10, %11, %12, %13, %14, %15,"
        "%16, %17, %18, %19, %20, %21, %22, %23, %24, %25, %26, %27, %28, %29, %30, %31}, %32, %33, 1, 1, 1, 0, 1;\n"
        :
        "+f"(d[0]), "+f"(d[1]), "+f"(d[2]), "+f"(d[3]), "+f"(d[4]), "+f"(d[5]), "+f"(d[6]), "+f"(d[7]),
        "+f"(d[8]), "+f"(d[9]), "+f"(d[10]), "+f"(d[11]), "+f"(d[12]), "+f"(d[13]), "+f"(d[14]), "+f"(d[15]),
        "+f"(d[16]), "+f"(d[17]), "+f"(d[18]), "+f"(d[19]), "+f"(d[20]), "+f"(d[21]), "+f"(d[22]), "+f"(d[23]),
        "+f"(d[24]), "+f"(d[25]), "+f"(d[26]), "+f"(d[27]), "+f"(d[28]), "+f"(d[29]), "+f"(d[30]), "+f"(d[31])
        : "l"(da), "l"(db));
}
__device__ __forceinline__ void wgmma_rs_n128(float* d, const uint32_t* a, uint64_t db) {
    asm volatile("wgmma.mma_async.sync.aligned.m64n128k16.f32.bf16.bf16 {"
        "%0, %1, %2, %3, %4, %5, %6, %7, %8, %9, %10, %11, %12, %13, %14, %15,"
        "%16, %17, %18, %19, %20, %21, %22, %23, %24, %25, %26, %27, %28, %29, %30, %31,"
        "%32, %33, %34, %35, %36, %37, %38, %39, %40, %41, %42, %43, %44, %45, %46, %47,"
        "%48, %49, %50, %51, %52, %53, %54, %55, %56, %57, %58, %59, %60, %61, %62, %63}, {%64, %65, %66, %67}, %68, 1, 1, 1, 1;\n"
        :
        "+f"(d[0]), "+f"(d[1]), "+f"(d[2]), "+f"(d[3]), "+f"(d[4]), "+f"(d[5]), "+f"(d[6]), "+f"(d[7]),
        "+f"(d[8]), "+f"(d[9]), "+f"(d[10]), "+f"(d[11]), "+f"(d[12]), "+f"(d[13]), "+f"(d[14]), "+f"(d[15]),
        "+f"(d[16]), "+f"(d[17]), "+f"(d[18]), "+f"(d[19]), "+f"(d[20]), "+f"(d[21]), "+f"(d[22]), "+f"(d[23]),
        "+f"(d[24]), "+f"(d[25]), "+f"(d[26]), "+f"(d[27]), "+f"(d[28]), "+f"(d[29]), "+f"(d[30]), "+f"(d[31]),
        "+f"(d[32]), "+f"(d[33]), "+f"(d[34]), "+f"(d[35]), "+f"(d[36]), "+f"(d[37]), "+f"(d[38]), "+f"(d[39]),
        "+f"(d[40]), "+f"(d[41]), "+f"(d[42]), "+f"(d[43]), "+f"(d[44]), "+f"(d[45]), "+f"(d[46]), "+f"(d[47]),
        "+f"(d[48]), "+f"(d[49]), "+f"(d[50]), "+f"(d[51]), "+f"(d[52]), "+f"(d[53]), "+f"(d[54]), "+f"(d[55]),
        "+f"(d[56]), "+f"(d[57]), "+f"(d[58]), "+f"(d[59]), "+f"(d[60]), "+f"(d[61]), "+f"(d[62]), "+f"(d[63])
        : "r"(a[0]), "r"(a[1]), "r"(a[2]), "r"(a[3]), "l"(db));
}
__device__ __forceinline__ void wgmma_qk_f16_acc(float* d, const uint32_t* a, uint64_t db) {
    asm volatile("wgmma.mma_async.sync.aligned.m64n64k16.f32.f16.f16 {"
        "%0, %1, %2, %3, %4, %5, %6, %7, %8, %9, %10, %11, %12, %13, %14, %15,"
        "%16, %17, %18, %19, %20, %21, %22, %23, %24, %25, %26, %27, %28, %29, %30, %31}, {%32, %33, %34, %35}, %36, 1, 1, 1, 0;\n"
        :
        "+f"(d[0]), "+f"(d[1]), "+f"(d[2]), "+f"(d[3]), "+f"(d[4]), "+f"(d[5]), "+f"(d[6]), "+f"(d[7]),
        "+f"(d[8]), "+f"(d[9]), "+f"(d[10]), "+f"(d[11]), "+f"(d[12]), "+f"(d[13]), "+f"(d[14]), "+f"(d[15]),
        "+f"(d[16]), "+f"(d[17]), "+f"(d[18]), "+f"(d[19]), "+f"(d[20]), "+f"(d[21]), "+f"(d[22]), "+f"(d[23]),
        "+f"(d[24]), "+f"(d[25]), "+f"(d[26]), "+f"(d[27]), "+f"(d[28]), "+f"(d[29]), "+f"(d[30]), "+f"(d[31])
        : "r"(a[0]), "r"(a[1]), "r"(a[2]), "r"(a[3]), "l"(db));
}
__device__ __forceinline__ void wgmma_qk_bf16_zero(float* d, const uint32_t* a, uint64_t db) {
    asm volatile("wgmma.mma_async.sync.aligned.m64n64k16.f32.bf16.bf16 {"
        "%0, %1, %2, %3, %4, %5, %6, %7, %8, %9, %10, %11, %12, %13, %14, %15,"
        "%16, %17, %18, %19, %20, %21, %22, %23, %24, %25, %26, %27, %28, %29, %30, %31}, {%32, %33, %34, %35}, %36, 0, 1, 1, 0;\n"
        :
        "=f"(d[0]), "=f"(d[1]), "=f"(d[2]), "=f"(d[3]), "=f"(d[4]), "=f"(d[5]), "=f"(d[6]), "=f"(d[7]),
        "=f"(d[8]), "=f"(d[9]), "=f"(d[10]), "=f"(d[11]), "=f"(d[12]), "=f"(d[13]), "=f"(d[14]), "=f"(d[15]),
        "=f"(d[16]), "=f"(d[17]), "=f"(d[18]), "=f"(d[19]), "=f"(d[20]), "=f"(d[21]), "=f"(d[22]), "=f"(d[23]),
        "=f"(d[24]), "=f"(d[25]), "=f"(d[26]), "=f"(d[27]), "=f"(d[28]), "=f"(d[29]), "=f"(d[30]), "=f"(d[31])
        : "r"(a[0]), "r"(a[1]), "r"(a[2]), "r"(a[3]), "l"(db));
}
__device__ __forceinline__ void wgmma_pv(float* d, const uint32_t* a, uint64_t db) {
    asm volatile("wgmma.mma_async.sync.aligned.m64n24k16.f32.bf16.bf16 {"
        "%0, %1, %2, %3, %4, %5, %6, %7, %8, %9, %10, %11}, {%12, %13, %14, %15}, %16, 1, 1, 1, 1;\n"
        :
        "+f"(d[0]), "+f"(d[1]), "+f"(d[2]), "+f"(d[3]), "+f"(d[4]), "+f"(d[5]), "+f"(d[6]), "+f"(d[7]),
        "+f"(d[8]), "+f"(d[9]), "+f"(d[10]), "+f"(d[11])
        : "r"(a[0]), "r"(a[1]), "r"(a[2]), "r"(a[3]), "l"(db));
}

template <int N> __device__ __forceinline__ void wgmma_ss(float* d, uint64_t a, uint64_t b) {
    if (N == 128) wgmma_ss_n128(d, a, b);
    if (N == 96) wgmma_ss_n96(d, a, b);
    if (N == 64) wgmma_ss_n64(d, a, b);
}

#define OFF_R 131072
#define OFF_ONE 229376
#define OFF_BAR 229888
#define OFF_BIAS (OFF_BAR + 736)
#define OFF_G (OFF_BIAS + 1152)
#define SMEM_BYTES (OFF_G + 272)
#define SBD 1024u
#define B_X 0
#define B_F1 416
#define B_E1 64
#define B_XD 672
#define B_KV 160
#define B_F2 224
#define B_E2 256
#define B_T 288
#define B_G 360
#define B_G2 368
#define B_G3 376
#define B_SF 384
#define B_BI 400

#define B_SF2 408
#define NR 6

#define PF 1
#define PFX 0
#define PACE 1
#define FSER 0
#define MERGE 1
#define EB 2
#define EXP_FKK 4
#define QSCALE 0.36067376022224085f
#define MAGIC 445.41763f
#define FORCE_IMAD
#define NMUFU 5
#define VSTEP ((uint64_t)((long long)32 - ((long long)32 << 16)))

#define XMASK 0x0D55u
#define KVMASK 0x1D55u
__host__ __device__ constexpr int strm_pos(int pass, int i) {
    if (pass == 1 || pass == 2) return 8 + 8 * pass + i;
    int n = 0;
    for (int p = 0; p < 16; p++)
        if ((int)((KVMASK >> p) & 1) == (pass == 3)) { if (n == i) return p; n++; }
    return 0;
}
__host__ __device__ constexpr uint32_t strm_code(int pass) {
    uint32_t c = 0;
    for (int i = 0; i < 7; i++) c |= (uint32_t)(strm_pos(pass, i + 1) - strm_pos(pass, i)) << (4 * i);
    return c;
}

template <int N, int SUB, int KST, int LBO, int SBO, int SWZ>
__device__ __forceinline__ void gemm_pass(float* acc, uint32_t bar, uint64_t dA, int lane, uint32_t pos, uint32_t code, int barNext, bool waitx, bool last) {
    uint32_t prev = 0, slot = pos % NR;
#pragma unroll 1
    for (int i = 0; i < 8; i++) {
        if (waitx) mbar_wait(bar + B_X + 8 * i, 0);
        mbar_wait(bar + B_F1 + 8 * pos, 0);
        const uint64_t dB = mkdesc(SBD + OFF_R, LBO, SBO, SWZ) + slot * 1024;
        wg_fence();
        wgmma_ss<N>(acc, dA, dB);
        wgmma_ss<N>(acc, dA + 2, dB + KST / 16);
        wg_commit();
        wg_wait<1>();
        if (i > 0 && lane < 2) mbar_arrive_cluster(prev, lane);
        wgmma_ss<N>(acc, dA + 4, dB + SUB / 16);
        wgmma_ss<N>(acc, dA + 6, dB + (SUB + KST) / 16);
        wg_commit();
        prev = last ? bar + B_XD + 8 * i : bar + B_E1 + 8 * slot;
        pos += code & 15;
        slot += code & 15;
        if (slot >= NR) slot -= NR;
        code >>= 4;
        dA += 1024;
    }
    if (barNext) bar_arrive(barNext, 512);
    wg_wait<0>();
    if (lane < 2) mbar_arrive_cluster(prev, lane);
    pin<N / 2>(acc);
}

__device__ __forceinline__ uint32_t lds32(uint32_t a) { uint32_t v; asm volatile("ld.shared.u32 %0, [%1];" : "=r"(v) : "r"(a)); return v; }
__device__ __forceinline__ bool elect() {
    uint32_t p;
    asm volatile("{\n.reg .pred p;\nelect.sync _|p, 0xffffffff;\nselp.u32 %0, 1, 0, p;\n}" : "=r"(p));
    return p;
}

template <int G0, int G1> __device__ __forceinline__ void gelu_pack(const float* acc, uint32_t bias, uint32_t* out) {
#pragma unroll
    for (int G = G0; G < G1; G++) {
        uint32_t* o = out + 8 * G;
#pragma unroll
        for (int j = 0; j < 4; j++) {
            float bv[2];
            asm volatile("ld.shared.v2.f32 {%0, %1}, [%2];" : "=f"(bv[0]), "=f"(bv[1]) : "r"(bias + G * 128 + j * 32));
            float y[4];
#pragma unroll
            for (int i = 0; i < 4; i++) {
                const float h = acc[16 * G + 4 * j + i] + bv[i & 1];
                const float z = h * fmaf(h * h, 0.035677408136300125f, 0.7978845608028654f);
                y[i] = fmaf(h, tanhf_(z), h);
            }
            o[j] = pk_bf16(y[0], y[1]);
            o[4 + j] = pk_bf16(y[2], y[3]);
        }
    }
}

__device__ __forceinline__ float norm_bound(const float* v, float sc) {
    uint32_t m = 0;
#pragma unroll
    for (int h = 0; h < 4; h++) {
        const float* u = v + 8 * h;
        m = max(m, __float_as_uint(fmaf(u[0], u[0], fmaf(u[1], u[1], fmaf(u[4], u[4], u[5] * u[5])))));
        m = max(m, __float_as_uint(fmaf(u[2], u[2], fmaf(u[3], u[3], fmaf(u[6], u[6], u[7] * u[7])))));
    }
#pragma unroll
    for (int o = 4; o < 32; o <<= 1) m = max(m, __shfl_xor_sync(0xffffffffu, m, o));
    float f = __uint_as_float(m);
    f += __shfl_xor_sync(0xffffffffu, f, 1);
    f += __shfl_xor_sync(0xffffffffu, f, 2);
    return f * sc;
}

__device__ __forceinline__ uint32_t exp2_pair(float a, float b, uint32_t m1) {
    const uint32_t w = __byte_perm(__float_as_uint(a), __float_as_uint(b), 0x6521);
    uint32_t m, r;
    asm("lop3.b32 %0, %1, 0x007f007f, 0x9f809f80, 0xEA;" : "=r"(m) : "r"(w));
    const uint32_t e = m * m1 + w;
    asm("fma.rn.bf16x2 %0, %1, %2, %3;" : "=r"(r) : "r"(w), "r"(m), "r"(e));
    return r;
}

__device__ __forceinline__ void store_o(const float* o, uint4* dst, uint32_t par) {
    const float s0 = __fdividef(1.f, o[8]), s1 = __fdividef(1.f, o[10]);
    const uint32_t d0 = (pk_bf16(o[0] * s0, o[1] * s0) & ~1u) | par;
    asm volatile("{\n.reg .b128 t;\nmov.b128 t, {%0, %1, %2, %3};\nst.relaxed.gpu.global.b128 [%4], t;\n}" ::"r"(d0),
                 "r"(pk_bf16(o[2] * s1, o[3] * s1)), "r"(pk_bf16(o[4] * s0, o[5] * s0)), "r"(pk_bf16(o[6] * s1, o[7] * s1)), "l"(dst) : "memory");
}
__device__ __forceinline__ uint4 load_o(const uint4* src) {
    uint4 v;
    asm volatile("{\n.reg .b128 t;\nld.relaxed.gpu.global.b128 t, [%4];\nmov.b128 {%0, %1, %2, %3}, t;\n}"
                 : "=r"(v.x), "=r"(v.y), "=r"(v.z), "=r"(v.w) : "l"(src) : "memory");
    return v;
}
template <int N> __device__ __forceinline__ void fetch_o(uint4* v, const uint4* src, uint32_t ep) {
    int spins = 0;
    while (true) {
        uint32_t bad = 0;
#pragma unroll
        for (int k = 0; k < N; k++) bad |= v[k].x ^ ep;
        if (!__any_sync(0xffffffffu, (bad & 1) != 0)) break;
        if (++spins > (1 << 22)) __trap();
#pragma unroll
        for (int k = 0; k < N; k++)
            if (((v[k].x ^ ep) & 1) != 0) v[k] = load_o(src + k * 128);
    }
}
__device__ __forceinline__ uint32_t bmul2(uint32_t a, uint32_t b) { uint32_t r; asm("mul.rn.bf16x2 %0, %1, %2;" : "=r"(r) : "r"(a), "r"(b)); return r; }
__device__ __forceinline__ void sts32(uint32_t a, uint32_t v) { asm volatile("st.shared.u32 [%0], %1;" ::"r"(a), "r"(v) : "memory"); }
__device__ __forceinline__ void load_q(uint32_t* q, int h, int row, int t) {
    const uint8_t* p = gQ + (size_t)h * (SEQ * 32) + (size_t)row * 32 + t * 4;
    q[0] = __ldcg((const uint32_t*)p); q[1] = __ldcg((const uint32_t*)(p + 256));
    q[2] = __ldcg((const uint32_t*)(p + 16)); q[3] = __ldcg((const uint32_t*)(p + 272));
}

template <int NT>
__device__ __forceinline__ void proj16(float (*c)[8], const __nv_bfloat16* x, const __nv_bfloat16* w, int row0, int rstep, int col, int g, int t) {
#pragma unroll
    for (int i = 0; i < NT; i++)
#pragma unroll
        for (int j = 0; j < 8; j++) c[i][j] = 0.f;
    const unsigned short* wu = (const unsigned short*)w;
#pragma unroll 1
    for (int k = 0; k < DM; k += 16) {
        uint32_t b[4];
#pragma unroll
        for (int j = 0; j < 4; j++) {
            const int kr = k + 2 * t + (j & 1) * 8, cc = col + g + (j >> 1) * 8;
            b[j] = (uint32_t)wu[(size_t)kr * (3 * DM) + cc] | ((uint32_t)wu[(size_t)(kr + 1) * (3 * DM) + cc] << 16);
        }
#pragma unroll
        for (int i = 0; i < NT; i++) {
            const __nv_bfloat16* xp = x + (size_t)(row0 + i * rstep + g) * DM + k + 2 * t;
            const uint32_t a0 = *(const uint32_t*)xp, a1 = *(const uint32_t*)(xp + 8 * DM);
            const uint32_t a2 = *(const uint32_t*)(xp + 8), a3 = *(const uint32_t*)(xp + 8 * DM + 8);
#pragma unroll
            for (int j = 0; j < 2; j++)
                asm volatile("mma.sync.aligned.m16n8k16.row.col.f32.bf16.bf16.f32 {%0,%1,%2,%3}, {%4,%5,%6,%7}, {%8,%9}, {%0,%1,%2,%3};"
                             : "+f"(c[i][4 * j]), "+f"(c[i][4 * j + 1]), "+f"(c[i][4 * j + 2]), "+f"(c[i][4 * j + 3])
                             : "r"(a0), "r"(a1), "r"(a2), "r"(a3), "r"(b[2 * j]), "r"(b[2 * j + 1]));
        }
    }
}

struct Maps { CUtensorMap x, kv, q, f1, f3, h, w2, wo, hs, kvs; };

template <int I0, int I1>
__device__ __forceinline__ void issue_stream(const Maps& tm, uint32_t sb, uint32_t rank, int nb, int mb) {
    const uint32_t bar = sb + OFF_BAR;
    const uint32_t dst = sb + OFF_R;
    const int kr = rank * 32;
#pragma unroll
    for (int it = I0; it < I1; it++) {
        const int s = it % NR;
        const uint32_t fb = bar + B_F1 + 8 * it;
        if (it >= 24 + NR) mbar_wait(bar + B_XD + 8 * (it - 24 - NR), 0);
        else if (it >= NR) mbar_wait(bar + B_E1 + 8 * s, ((it / NR) - 1) & 1);
        const int nkv = __builtin_popcount(KVMASK & ((1u << it) - 1));
        if (it < 16 && ((KVMASK >> it) & 1)) {
            tma3d_mc(dst + s * 16384 + rank * 8192, &tm.kv, nb * 64, nkv * 64 + kr, 1, fb);
        } else if (it < 16) {
            tma3d_mc(dst + s * 16384 + rank * 6144, &tm.q, 0, (it - nkv) * 64 + kr, nb * 2, fb);
            tma3d_mc(dst + s * 16384 + rank * 6144 + 4096, &tm.f1, 0, (it - nkv) * 64 + kr, nb * 7, fb);
        } else {
            tma3d_mc(dst + s * 16384 + rank * 6144, &tm.f3, 0, (it & 7) * 64 + kr, nb * 7 + (it < 24 ? 1 : 4), fb);
        }
        if ((XMASK >> it) & 1) {
            const int xc = 1 + __builtin_popcount(XMASK & ((1u << it) - 1));
            tma2d(sb + xc * 16384, &tm.x, xc * 64, mb * 128, bar + B_X + 8 * xc);
        }
    }
}

__global__ void __cluster_dims__(2, 1, 1) __launch_bounds__(640, 1)
fused_kernel(const __grid_constant__ Maps tm, const __nv_bfloat16* __restrict__ x, const __nv_bfloat16* __restrict__ wqkv,
             const __nv_bfloat16* __restrict__ wo, const __nv_bfloat16* __restrict__ w1, const __nv_bfloat16* __restrict__ b1,
             const __nv_bfloat16* __restrict__ w2, const __nv_bfloat16* __restrict__ b2, const __nv_bfloat16* __restrict__ gate,
             __nv_bfloat16* __restrict__ out, const uint32_t m1) {
    const uint32_t sb = smem_u32(smem_raw);
    const uint32_t bar = sb + OFF_BAR;
    const int tid = threadIdx.x, lane = tid & 31;
    const int warp = __shfl_sync(0xffffffffu, tid >> 5, 0);
    const uint32_t rank = cluster_rank();
    const int cl = blockIdx.x >> 1;
    const int nb = cl & 7, mb = (cl >> 3) * 2 + rank;
    const int g = lane >> 2, t = lane & 3;

    const int cb = nb & 3, rb = mb * 2 + (nb >> 2);
    const int rn = (mb >> 1) & 1;
    if (tid == 0) TLM(0, 0);
    TL_INIT();
    if (tid == 512) {
        for (int i = 0; i < 8; i++) { mbar_init(bar + B_X + 8 * i, 1); mbar_init(bar + B_KV + 8 * i, 1); mbar_init(bar + B_T + 8 * i, i < 4 ? 1 : 5); mbar_init(bar + B_XD + 8 * i, 16); }
        for (int i = 0; i < NR; i++) mbar_init(bar + B_E1 + 8 * i, 16);
        for (int i = 0; i < 4; i++) { mbar_init(bar + B_F2 + 8 * i, 1); mbar_init(bar + B_E2 + 8 * i, 8); }
        asm volatile("fence.mbarrier_init.release.cluster;" ::: "memory");
    } else if (tid == 608) {
        for (int i = 0; i < 32; i++) mbar_init(bar + B_F1 + 8 * i, 1);
        mbar_init(bar + B_G, 1);
        for (int i = 0; i < 3; i++) mbar_init(bar + B_SF + 8 * i, i == 1 ? 2 : 1);
        mbar_init(bar + B_SF2, 2);
        mbar_init(bar + B_G3, 1);
        mbar_init(bar + B_G2, 4);
        asm volatile("fence.mbarrier_init.release.cluster;" ::: "memory");
    }
    __syncwarp();
    asm volatile("barrier.cluster.arrive.relaxed.aligned;" ::: "memory");
    if (warp == 19) mbar_expect(bar + B_F1 + 8 * lane, ((KVMASK >> lane) & 1) ? 16384 : 12288);
    if (warp == 16 && lane < 24) mbar_expect(bar + (lane < 8 ? B_X : lane < 16 ? B_KV - 64 : B_T - 128) + 8 * lane, 16384);
    if (tid == 512) {
        tma2d(sb, &tm.x, 0, mb * 128, bar + B_X);
    } else if (tid == 544) {
        map_prefetch(&tm.kv);
        l2_prefetch((const uint8_t*)wqkv + (size_t)blockIdx.x * 3072, 3072);
        l2_prefetch((const uint8_t*)w1 + (size_t)blockIdx.x * 1792, 1792);
        map_prefetch(&tm.q); map_prefetch(&tm.f1); map_prefetch(&tm.f3);
    }
    if ((sb & 0xFFFFFF) != SBD) __trap();
    __syncwarp();
    asm volatile("barrier.cluster.wait.aligned;" ::: "memory");
    if (tid == 512) issue_stream<0, NR>(tm, sb, rank, nb, mb);
    if (tid == 0) { TLM(0, 1); TLC(0, 30); }

    if (warp < 16) {
        const int wg = warp >> 2;
        const int h = cl >> 1, qd = (cl & 1) * 2 + rank;
        const int flip = (h >> 2) & 1;
        uint32_t q[4];
        {
            const int w8 = warp & 7;
            const int T = mb * 8 + w8, row0 = T * 16 + g;
            const uint64_t dA0 = mkdesc(SBD + (wg & 1) * 8192, 16, 1024, 1);
            if (wg < 2) {
                float acc[64];
#pragma unroll
                for (int i = 0; i < 64; i++) acc[i] = 0.f;
                gemm_pass<128, 8192, 2048, 4096, 1024, 1>(acc, bar, dA0, lane, strm_pos(3, 0), strm_code(3), 0, true, false);
                if (tid == 0) TLM(0, 2);
                {
                    const float km = norm_bound(acc, 1.f);
                    float vm = 0.f;
#pragma unroll
                    for (int i = 32; i < 64; i++) vm = fmaxf(vm, fabsf(acc[i]));
                    vm = __uint_as_float(__reduce_max_sync(0xffffffffu, __float_as_uint(vm)));
                    if (lane == 0) { gN[1024 + nb * 128 + T] = km; gN[2048 + nb * 128 + T] = vm; }
                    const uint32_t kp = sb + OFF_R + 12288 + (w8 >> 2) * 1024 + g * 128 + ((((w8 & 3) * 2 + ((t >> 1) ^ (w8 >> 2))) ^ g) << 4) + (t & 1) * 8;
                    uint8_t* vp = gKV + (size_t)(nb * 4) * (SEQ * 64) + 65536 + (((T >> 6) * 16 + 2 * g) * 64 + (T & 63)) * 32 + ((t * 8) ^ ((w8 >> 2) << 4));
                    bar_sync(9, 256);
#pragma unroll
                    for (int hh = 0; hh < 4; hh++) {
                        const float* v = acc + 8 * hh;
                        float p0 = __shfl_up_sync(0xffffffffu, v[2], 4), p1 = __shfl_up_sync(0xffffffffu, v[3], 4);
                        float p2 = __shfl_up_sync(0xffffffffu, v[6], 4), p3 = __shfl_up_sync(0xffffffffu, v[7], 4);
                        if (g == 0) { p0 = p1 = p2 = p3 = 0.f; }
                        sts64(kp + hh * 16384, pk_f16(v[0] - p0, v[1] - p1), pk_f16(v[4] - p2, v[5] - p3));
                        sts64(kp + hh * 16384 + 2048, pk_f16(v[2] - v[0], v[3] - v[1]), pk_f16(v[6] - v[4], v[7] - v[5]));
                        const float* u = acc + 32 + 8 * hh;
                        if (hh < 2) {
                            sts64(kp + (4 + hh) * 16384, pk_bf16(u[0], u[1]), pk_bf16(u[4], u[5]));
                            sts64(kp + (4 + hh) * 16384 + 2048, pk_bf16(u[2], u[3]), pk_bf16(u[6], u[7]));
                        } else {
                            *(uint2*)(vp + (size_t)hh * (SEQ * 64)) = make_uint2(pk_bf16(u[0], u[1]), pk_bf16(u[4], u[5]));
                            *(uint2*)(vp + (size_t)hh * (SEQ * 64) + 2048) = make_uint2(pk_bf16(u[2], u[3]), pk_bf16(u[6], u[7]));
                        }
                    }
                }
                asm volatile("fence.proxy.async.shared::cta;" ::: "memory");
                bar_arrive(10, 288);
                if (tid == 0) TLM(0, 3);
            }
#pragma unroll 1
            for (int p = wg < 2 ? 1 : 0; p < 3; p += 2) {
                float acc[48];
#pragma unroll
                for (int i = 0; i < 48; i++) acc[i] = 0.f;
                pin<48>(acc);
                if (p) bar_sync(5 + p, 512);
                gemm_pass<96, 6144, 1024, 2048, 512, 2>(acc, bar, dA0, lane, p == 0 ? strm_pos(0, 0) : 8 + 8 * p, p == 0 ? strm_code(0) : strm_code(1), p < 2 ? 6 + p : 0, p == 0, p == 2);
                if ((tid & 255) == 0) TLM(0, 4 + 2 * p);
                const uint32_t hp = sb + OFF_R + (p == 2 ? 0 : 12288) + (wg & 1) * 16384 + ((warp & 3) * 16 + g) * 64 + t * 16;
                const uint32_t bp = sb + OFF_BIAS + p * 384 - 256 + t * 8;
                uint32_t ho[24];
                mbar_wait(bar + B_BI, 0);
                if (p == 0) {
                    const float qm = norm_bound(acc, QSCALE * QSCALE);
                    if (lane == 0) gN[nb * 128 + T] = qm;
                    uint8_t* qp = gQ + (size_t)(nb * 4) * (SEQ * 32) + (size_t)row0 * 32 + t * 8;
#pragma unroll
                    for (int hh = 0; hh < 4; hh++) {
                        const float* v = acc + 8 * hh;
                        *(uint2*)(qp + hh * (SEQ * 32)) = make_uint2(pk_f16(v[0] * QSCALE, v[1] * QSCALE), pk_f16(v[4] * QSCALE, v[5] * QSCALE));
                        *(uint2*)(qp + hh * (SEQ * 32) + 256) = make_uint2(pk_f16(v[2] * QSCALE, v[3] * QSCALE), pk_f16(v[6] * QSCALE, v[7] * QSCALE));
                    }
                    bar_arrive(12, 288);
                } else {
                    gelu_pack<0, 2>(acc, bp, ho);
                    pin<16>(ho);
                    mbar_wait(bar + B_G, 0);
                    load_q(q, h, qd * 512 + flip * 256 + warp * 16 + g, t);
                }
                gelu_pack<2, 3>(acc, bp, ho);
                pin<8>(ho + 16);
                if (p == 2) bar_sync(9, 256);
                else mbar_wait(bar + B_SF + 8 * p, 0);
                if (p) {
#pragma unroll
                    for (int i = 0; i < 4; i++) sts128(hp + (i >> 1) * 32768 + (i & 1) * 512, ho + 4 * i);
                }
                sts128(hp + 65536, ho + 16);
                sts128(hp + 65536 + 512, ho + 20);
                asm volatile("fence.proxy.async.shared::cta;" ::: "memory");
                bar_arrive(p == 1 ? 14 : 11, 288);
                if ((tid & 255) == 0) TLM(0, 5 + 2 * p);
            }
        }
        uint32_t ep = 2;
        uint4* const op = gO + ((qd * 8 + wg) * NH + h) * 128 + (tid & 127);
        const uint64_t kd0 = mkdesc(SBD, 16, 256, 3);
        const uint64_t vd0 = mkdesc(SBD + 8192, OFF_ONE - 8192, 256, 3);
        {
            float o[12];
            uint32_t qn[4];
#pragma unroll 1
            for (int rh = 0; rh < 4; rh++) {
                if (rh == 1) {
                    mbar_wait(bar + B_G3, 0);
                    ep = lds32(sb + OFF_G + 256);
                    if (!(ep & 2)) break;
                    load_q(qn, h, qd * 512 + (flip ^ 1) * 256 + warp * 16 + g, t);
                }
                if (!(rh & 1)) {
#pragma unroll
                    for (int i = 0; i < 12; i++) o[i] = 0.f;
                }
                uint64_t kd = kd0 + (rh & 1) * 4096, vd = vd0 + (rh & 1) * (128 * VSTEP);
                uint32_t kvb = bar + B_KV + (rh & 1) * 32;
                float s[32];
#pragma unroll
                for (int i = 0; i < 32; i++) s[i] = i < 2 * NMUFU ? 0.f : MAGIC;
                if ((tid & 255) == 0) TLM(1, (tid >> 8) * 4 + rh);
#pragma unroll 1
                for (int c = 0; c < 4; c++) {
                    mbar_wait(kvb, 0);
                    kvb += 8;
#pragma unroll
                    for (int j = 0; j < 4; j++) {
                        uint32_t p[16];
                        if (!MERGE || j == 0) {
                            wg_fence();
                            wgmma_qk_f16_acc(s, q, kd + j * 128);
                            wg_commit();
                        }
                        wg_wait<0>();
                        pin<32>(s);
#pragma unroll
                        for (int i = 0; i < 16; i++)
                            p[i] = i < NMUFU ? pk_bf16(ex2f(s[2 * i]), ex2f(s[2 * i + 1])) : exp2_pair(s[2 * i], s[2 * i + 1], m1);
                        pin<16>(p);
                        wg_fence();
#pragma unroll
                        for (int u = 0; u < 4; u++) {
                            if (MERGE && j < 3 && u == 5 - MERGE) wgmma_qk_f16_acc(s, q, kd + (j + 1) * 128);
                            wgmma_pv(o, p + 4 * u, vd + (j * 4 + u) * VSTEP);
                        }
                        if (MERGE == 1 && j < 3) wgmma_qk_f16_acc(s, q, kd + (j + 1) * 128);
                        wg_commit();
                    }
                    kd += 1024;
                    vd += 32 * VSTEP;
                }
                wg_wait<0>();
                pin<12>(o);
                if (rh & 1) {
                    if ((tid & 127) == 0 && rh == 3) TLM(1, 8 + wg);
                    store_o(o, op + ((rh >> 1) ^ flip) * (4 * NH * 128), ep & 1);
#pragma unroll
                    for (int i = 0; i < 4; i++) q[i] = qn[i];
                }
            }
            if (tid == 0) { TLM(1, 12); TLC(0, 31); }
        }
        if (!(ep & 2)) {
            bar_sync(8, 512);
            for (int c = 0; c < 8; c++) mbar_wait(bar + B_KV + 8 * c, 0);
            {
                float kc[8][8];
                proj16<8>(kc, x, wqkv, warp * 16, 256, DM + h * 16, g, t);
#pragma unroll
                for (int i = 0; i < 8; i++) {
                    const int T = warp + i * 16;
                    const int pos = ((T >> 6) * 16 + 2 * g) * 64 + (T & 63);
                    const uint32_t a = sb + (pos >> 8) * 16384 + (pos & 255) * 32 + t * 4, sw = ((T >> 2) & 1) << 4;
                    asm volatile("st.shared.u32 [%0], %1;" ::"r"(a + sw), "r"(pk_bf16(kc[i][0], kc[i][1])) : "memory");
                    asm volatile("st.shared.u32 [%0], %1;" ::"r"(a + (sw ^ 16)), "r"(pk_bf16(kc[i][4], kc[i][5])) : "memory");
                    asm volatile("st.shared.u32 [%0], %1;" ::"r"(a + 2048 + sw), "r"(pk_bf16(kc[i][2], kc[i][3])) : "memory");
                    asm volatile("st.shared.u32 [%0], %1;" ::"r"(a + 2048 + (sw ^ 16)), "r"(pk_bf16(kc[i][6], kc[i][7])) : "memory");
                }
                asm volatile("fence.proxy.async.shared::cta;" ::: "memory");
                bar_sync(8, 512);
            }
#pragma unroll 1
            for (int r = 0; r < 2; r++) {
                const int row = qd * 512 + (r ^ flip) * 256 + warp * 16 + g;
                {
                    float qc[1][8];
                    proj16<1>(qc, x, wqkv, row - g, 0, h * 16, g, t);
#pragma unroll
                    for (int i = 0; i < 4; i++) q[i] = pk_bf16(qc[0][2 * i] * QSCALE, qc[0][2 * i + 1] * QSCALE);
                }
                float o[12];
#pragma unroll
                for (int i = 0; i < 12; i++) o[i] = 0.f;
                float m0 = -INFINITY, m1 = -INFINITY;
#pragma unroll 1
                for (int j = 0; j < 32; j++) {
                    const uint64_t kd = kd0 + (j >> 2) * 1024 + (j & 3) * 128, vd = vd0 + ((j >> 2) * 32 + (j & 3) * 4) * VSTEP;
                    float s[32];
                    uint32_t p[16];
                    wg_fence();
                    wgmma_qk_bf16_zero(s, q, kd);
                    wg_commit();
                    wg_wait<0>();
                    pin<32>(s);
                    pin<12>(o);
                    float n0 = m0, n1 = m1;
#pragma unroll
                    for (int i = 0; i < 8; i++) {
                        n0 = fmaxf(n0, fmaxf(s[4 * i], s[4 * i + 1]));
                        n1 = fmaxf(n1, fmaxf(s[4 * i + 2], s[4 * i + 3]));
                    }
                    n0 = fmaxf(n0, __shfl_xor_sync(0xffffffffu, n0, 1));
                    n1 = fmaxf(n1, __shfl_xor_sync(0xffffffffu, n1, 1));
                    n0 = fmaxf(n0, __shfl_xor_sync(0xffffffffu, n0, 2));
                    n1 = fmaxf(n1, __shfl_xor_sync(0xffffffffu, n1, 2));
                    const float c0 = ex2f(m0 - n0), c1 = ex2f(m1 - n1);
                    m0 = n0;
                    m1 = n1;
#pragma unroll
                    for (int i = 0; i < 3; i++) { o[4 * i] *= c0; o[4 * i + 1] *= c0; o[4 * i + 2] *= c1; o[4 * i + 3] *= c1; }
#pragma unroll
                    for (int i = 0; i < 8; i++) {
                        p[2 * i] = pk_bf16(ex2f(s[4 * i] - m0), ex2f(s[4 * i + 1] - m0));
                        p[2 * i + 1] = pk_bf16(ex2f(s[4 * i + 2] - m1), ex2f(s[4 * i + 3] - m1));
                    }
                    pin<16>(p);
                    pin<12>(o);
                    wg_fence();
#pragma unroll
                    for (int u = 0; u < 4; u++) wgmma_pv(o, p + 4 * u, vd + u * VSTEP);
                    wg_commit();
                }
                wg_wait<0>();
                pin<12>(o);
                store_o(o, op + (r ^ flip) * (4 * NH * 128), ep & 1);
            }
        }
        {
            const uint4* src = gO + (rb * NH + (wg * 2 + (rn ^ 1)) * 4) * 128 + (tid & 127);
            uint4 v[4];
#pragma unroll
            for (int i = 0; i < 4; i++) v[i] = load_o(src + i * 128);
            mbar_wait(bar + B_G2, 0);
            const int lr = (warp & 3) * 16;
            const uint32_t g0 = lds32(sb + OFF_G + (lr + g) * 4), g1 = lds32(sb + OFF_G + (lr + g) * 4 + 32);
            const uint32_t a0 = sb + OFF_R + 32768 + wg * 8192 + (lr + (lane & 15)) * 128;
            fetch_o<4>(v, src, ep);
#pragma unroll
            for (int i = 0; i < 4; i++)
                asm volatile("stmatrix.sync.aligned.m8n8.x4.shared.b16 [%0], {%1, %2, %3, %4};" ::"r"(a0 + (((i * 2 + (lane >> 4)) ^ (lane & 7)) << 4)),
                             "r"(bmul2(v[i].x, g0)), "r"(bmul2(v[i].y, g1)), "r"(bmul2(v[i].z, g0)), "r"(bmul2(v[i].w, g1)) : "memory");
            asm volatile("fence.proxy.async.shared::cta;" ::: "memory");
            __syncwarp();
            if (lane == 0) mbar_arrive(bar + B_T + 32 + 8 * wg);
            if ((tid & 127) == 0) TLM(1, 20 + wg);
        }
    } else {
        if (warp == 16) {
            if (lane == 0) {
                issue_stream<NR, 32>(tm, sb, rank, nb, mb);
                mbar_wait(bar + B_SF2, 0);
#pragma unroll
                for (int s = 0; s < 4; s++) {
                    mbar_expect(bar + B_F2 + 8 * s, 24576);
                    tma5d_mc(sb + OFF_R + s * 24576 + 8192 + rank * 8192, &tm.w2, cb * 128 + rank * 64, s * 2, bar + B_F2 + 8 * s);
                }
                cnt_wait(gCntH + mb * 32, epoch() * 8);
                asm volatile("fence.proxy.async.global;" ::: "memory");
                TLM(1, 13);
#pragma unroll
                for (int s = 0; s < 4; s++) tma2d(sb + OFF_R + s * 24576, &tm.h, s * 64, rb * 64, bar + B_F2 + 8 * s);
            }
        } else if (warp == 17) {
            {
                uint32_t bv[4], b2v[2];
#pragma unroll
                for (int i = 0; i < 4; i++) bv[i] = lane + 32 * i < 112 ? *(const uint32_t*)(b1 + nb * 224 + (lane + 32 * i) * 2) : 0;
#pragma unroll
                for (int i = 0; i < 2; i++) b2v[i] = *(const uint32_t*)(b2 + cb * 128 + (lane + 32 * i) * 2);
#pragma unroll
                for (int i = 0; i < 4; i++) {
                    sts32(sb + OFF_ONE + (lane + 32 * i) * 4, 0x3f803f80u);
                    if (lane + 32 * i < 112) sts64(sb + OFF_BIAS + (lane + 32 * i) * 8, bv[i] << 16, bv[i] & 0xffff0000u);
                }
#pragma unroll
                for (int i = 0; i < 2; i++) sts32(sb + OFF_BIAS + 896 + (lane + 32 * i) * 4, b2v[i]);
                asm volatile("fence.proxy.async.shared::cta;" ::: "memory");
                __syncwarp();
                if (lane == 0) mbar_arrive(bar + B_BI);
            }
            mbar_wait(bar + B_X + 8 * PFX, 0);
            if (lane == 0) {
                l2_prefetch((const uint8_t*)wqkv + 128 * 3072 + (size_t)blockIdx.x * 9216, 9216);
                l2_prefetch((const uint8_t*)w1 + (size_t)blockIdx.x * 14336, 14336);
            }
            mbar_wait(bar + B_X + 8 * 7, 0);
            if (lane == 0) {
                l2_prefetch((const uint8_t*)w2 + (size_t)blockIdx.x * 14336, 14336);
                l2_prefetch((const uint8_t*)wo + (size_t)blockIdx.x * 4096, 4096);
                map_prefetch(&tm.h); map_prefetch(&tm.w2); map_prefetch(&tm.wo); map_prefetch(&tm.hs); map_prefetch(&tm.kvs);
                TLM(0, 11);
            }
            bar_sync(10, 288);
            if (lane == 0) {
#pragma unroll 1
                for (int b = 5; b >= 0; b--) {
                    tma5d_st(&tm.kvs, sb + OFF_R + 12288 + b * 16384, (mb >> 3) * 8, (mb & 7) * 2, nb * 8 + (b < 4 ? 2 * b : 2 * b - 7));
                    asm volatile("cp.async.bulk.commit_group;\ncp.async.bulk.wait_group.read %0;" ::"n"(PACE) : "memory");
                    if (b == 4 - PACE) mbar_arrive(bar + B_SF);
                }
                asm volatile("cp.async.bulk.wait_group.read 0;" ::: "memory");
                mbar_arrive(bar + B_SF + 8);
            }
            __syncwarp();
            bar_sync(12, 288);
            if (lane == 0) {
                asm volatile("cp.async.bulk.wait_group 0;\nfence.proxy.async.global;" ::: "memory");
                cnt_add(gCntQ + nb * 32);
                TLM(0, 13);
            }
        } else {
            {
                const int r0 = mb * 128 + nb * 16 + (warp - 18) * 8;
                uint4 xv[16];
#pragma unroll
                for (int i = 0; i < 16; i++) xv[i] = *(const uint4*)(x + (size_t)(r0 + (i >> 1)) * DM + (i & 1) * 256 + lane * 8);
                const uint4 ga = *(const uint4*)(gate + lane * 8), gb = *(const uint4*)(gate + 256 + lane * 8);
                float z[8];
#pragma unroll
                for (int r = 0; r < 8; r++) z[r] = dot8(xv[2 * r], ga) + dot8(xv[2 * r + 1], gb);
#pragma unroll
                for (int w = 4; w >= 1; w >>= 1)
#pragma unroll
                    for (int r = 0; r < w; r++) {
                        const bool up = lane & w;
                        z[r] = (up ? z[r + w] : z[r]) + __shfl_xor_sync(0xffffffffu, up ? z[r] : z[r + w], w);
                    }
                z[0] += __shfl_xor_sync(0xffffffffu, z[0], 8);
                z[0] += __shfl_xor_sync(0xffffffffu, z[0], 16);
                if (lane < 8) gG[r0 + lane] = 1.f / (1.f + __expf(-z[0]));
                if (tid == 576) TLM(0, 12);
            }
            if (warp == 19) {
#pragma unroll 1
                for (int e = 0; e < 3; e++) {
                    bar_sync(e == 1 ? 14 : 11, 288);
                    if (lane == 0) {
#pragma unroll 1
                        for (int b = e == 0 ? 4 : 0; b < 6; b++) {
                            tma3d_st(&tm.hs, sb + OFF_R + (e == 2 ? 0 : 12288) + b * 16384, 0, mb * 128 + (b & 1) * 64, nb * 7 + e * 3 - 2 + (b >> 1));
                            asm volatile("cp.async.bulk.commit_group;\ncp.async.bulk.wait_group.read %0;" ::"n"(PACE) : "memory");
                        }
                        asm volatile("cp.async.bulk.wait_group.read 0;" ::: "memory");
                        if (e == 0) mbar_arrive(bar + B_SF + 8);
                        if (e == 2) { mbar_arrive_cluster(bar + B_SF2, 0); mbar_arrive_cluster(bar + B_SF2, 1); }
                    }
                    __syncwarp();
                }
                bar_sync(13, 64);
                if (lane == 0) {
                    asm volatile("cp.async.bulk.wait_group 0;\nfence.proxy.async.global;" ::: "memory");
                    cnt_add(gCntH + mb * 32);
                    TLM(0, 15);
                }
            } else {
                bar_arrive(13, 64);
                const int h = cl >> 1, qd = (cl & 1) * 2 + rank;
                const uint32_t ep = epoch();
                if (lane == 0) {
                    cnt_wait(gCntQ + (h >> 2) * 32, ep * 16);
                    mbar_arrive(bar + B_G);
                    TLM(0, 14);
                    asm volatile("fence.proxy.async.global;" ::: "memory");
#pragma unroll
                    for (int c = 0; c < 2; c++) {
                        mbar_wait(bar + B_XD + 8 * c, 0);
                        bulk_mc(sb + c * 16384 + rank * 8192, gKV + (size_t)h * (SEQ * 64) + rank * 65536 + c * 8192, 8192, bar + B_KV + 8 * c);
                    }
                }
                __syncwarp();
            const int hb = h >> 2;
            const uint4 kq = __ldcg((const uint4*)(gN + 1024 + hb * 128 + lane * 4));
            const uint4 vq = __ldcg((const uint4*)(gN + 2048 + hb * 128 + lane * 4));
            const float qq = ldcg_f(gN + hb * 128 + qd * 32 + lane);
            const float kf = __uint_as_float(__reduce_max_sync(0xffffffffu, max(max(kq.x, kq.y), max(kq.z, kq.w))));
            const float vf = __uint_as_float(__reduce_max_sync(0xffffffffu, max(max(vq.x, vq.y), max(vq.z, vq.w))));
            const float qf = __uint_as_float(__reduce_max_sync(0xffffffffu, __float_as_uint(qq)));
            if (lane == 0) {
                sts32(sb + OFF_G + 256, (ep & 1) | ((kf <= 1.0e6f) && (qf <= 1.0e6f) && (kf * qf <= 3400.f) && (vf <= 1.0e12f) ? 2 : 0));
                mbar_arrive(bar + B_G3);
                TLM(0, 16);
#pragma unroll
                for (int c = 2; c < 8; c++) {
                    mbar_wait(bar + B_XD + 8 * c, 0);
                    bulk_mc(sb + c * 16384 + rank * 8192, gKV + (size_t)h * (SEQ * 64) + rank * 65536 + c * 8192, 8192, bar + B_KV + 8 * c);
                }
                TLM(0, 10);
            }
            }
        }
        __syncwarp();
        float acc[64];
#pragma unroll
        for (int i = 0; i < 64; i++) acc[i] = 0.f;
#pragma unroll 1
        for (int io = 0; io < 7; io++) {
#pragma unroll
            for (int s = 0; s < 4; s++) {
                const int it = io * 4 + s;
                mbar_wait(bar + B_F2 + 8 * s, io & 1);
                if (tid == 512 && s == 0 && (io == 0 || io == 4)) TLM(1, 14 + io / 4);
                const uint64_t dA = mkdesc(SBD + OFF_R + s * 24576, 16, 1024, 1);
                const uint64_t dB = mkdesc(SBD + OFF_R + s * 24576 + 8192, 8192, 1024, 1);
                wg_fence();
#pragma unroll
                for (int kk = 0; kk < EXP_FKK; kk++) {
                    wgmma_ss_n128(acc, dA + kk * 2, dB + kk * 128);
                }
                wg_commit();
                if (warp < 18 && it >= 2 && it < 26) {
                    const int s2 = (s + 2) & 3;
                    mbar_wait(bar + B_E2 + 8 * s2, (io - (s < 2)) & 1);
                    if (elect()) {
                        if (warp == 16) {
                            mbar_expect(bar + B_F2 + 8 * s2, 24576);
                            tma5d_mc(sb + OFF_R + s2 * 24576 + 8192 + rank * 8192, &tm.w2, cb * 128 + rank * 64, it * 2 + 4, bar + B_F2 + 8 * s2);
                        } else {
                            asm volatile("fence.proxy.async.global;" ::: "memory");
                            tma2d(sb + OFF_R + s2 * 24576, &tm.h, it * 64 + 128, rb * 64, bar + B_F2 + 8 * s2);
                        }
                    }
                    __syncwarp();
                }
                wg_wait<1>();
                if (it >= 1 && lane < 2) mbar_arrive_cluster(bar + B_E2 + 8 * ((s + 3) & 3), lane);
            }
        }
        wg_wait<0>();
        if (lane < 2) mbar_arrive_cluster(bar + B_E2 + 8 * 3, lane);
        pin<64>(acc);
        if (tid == 576) gEpoch[blockIdx.x] = epoch();
        if (warp == 16) {
            if (lane == 0) TLM(1, 16);
            for (int s = 0; s < 4; s++) mbar_wait(bar + B_E2 + 8 * s, 0);
            if (elect()) {
#pragma unroll
                for (int i = 0; i < 6; i++)
                    tma5d_mc(sb + OFF_R + i * 16384 + rank * 8192, &tm.wo, cb * 128 + rank * 64, ((i & 3) * 2 + (rn ^ (i >> 2))) * 4, bar + B_T + 8 * i);
            }
            __syncwarp();
        }
        uint32_t pa;
        {
            const int lr = (warp - 16) * 16 + g;
            pa = pk_bf16(ldcg_f(gG + rb * 64 + lr), ldcg_f(gG + rb * 64 + lr + 8));
            if (t == 0) {
                sts32(sb + OFF_G + lr * 4, __byte_perm(pa, pa, 0x1010));
                sts32(sb + OFF_G + lr * 4 + 32, __byte_perm(pa, pa, 0x3232));
            }
            const float ga = bf_lo(pa), gb = bf_hi(pa);
            const float g0 = 1.f - ga, g1 = 1.f - gb;
#pragma unroll
            for (int j = 0; j < 16; j++) {
                const uint32_t bv = lds32(sb + OFF_BIAS + 896 + j * 16 + t * 4);
                acc[4 * j] = fmaf(acc[4 * j], 0.5f, bf_lo(bv)) * g0;
                acc[4 * j + 1] = fmaf(acc[4 * j + 1], 0.5f, bf_hi(bv)) * g0;
                acc[4 * j + 2] = fmaf(acc[4 * j + 2], 0.5f, bf_lo(bv)) * g1;
                acc[4 * j + 3] = fmaf(acc[4 * j + 3], 0.5f, bf_hi(bv)) * g1;
            }
            pin<64>(acc);
        }
        {
            mbar_wait(bar + B_G3, 0);
            const uint32_t ep = lds32(sb + OFF_G + 256);
            const uint32_t g0 = __byte_perm(pa, pa, 0x1010), g1 = __byte_perm(pa, pa, 0x3232);
            const uint4* src = gO + (rb * NH + rn * 4) * 128 + (tid & 127);
            const uint64_t dB = mkdesc(SBD + OFF_R, 8192, 1024, 1);
            uint4 v0 = load_o(src), v1 = load_o(src + 128), v2 = load_o(src + 256);
#pragma unroll 1
            for (int e = 0; e < 16; e++) {
                mbar_wait(bar + B_T + 8 * (e >> 2), 0);
                fetch_o<1>(&v0, src + (e + (e & 12)) * 128, ep);
                uint32_t a[4] = {bmul2(v0.x, g0), bmul2(v0.y, g1), bmul2(v0.z, g0), bmul2(v0.w, g1)};
                pin<4>(a);
                wg_fence();
                wgmma_rs_n128(acc, a, dB + (e + (e & 12)) * 128);
                wg_commit();
                v0 = v1;
                v1 = v2;
                if (e < 13) v2 = load_o(src + (e + 3 + ((e + 3) & 12)) * 128);
                wg_wait<0>();
            }
            __syncwarp();
            if (lane == 0) mbar_arrive(bar + B_G2);
            if (warp == 16) {
                mbar_wait(bar + B_G2, 0);
                if (elect()) {
#pragma unroll
                    for (int i = 0; i < 4; i++)
                        tma5d(sb + OFF_R + i * 8192, &tm.wo, cb * 128 + (i & 1) * 64, ((2 + (i >> 1)) * 2 + (rn ^ 1)) * 4, bar + B_T + 8 * (6 + (i >> 1)));
                }
                __syncwarp();
            }
        }
        if (tid == 512) TLM(1, 17);
#pragma unroll
        for (int i = 0; i < 4; i++) {
            mbar_wait(bar + B_T + 32 + 8 * i, 0);
            const uint64_t dA = mkdesc(SBD + OFF_R + 32768 + i * 8192, 16, 1024, 1);
            const uint64_t dB = mkdesc(SBD + OFF_R + (i < 2 ? 4 + i : i - 2) * 16384, 8192, 1024, 1);
            wg_fence();
#pragma unroll
            for (int kk = 0; kk < 4; kk++) wgmma_ss_n128(acc, dA + kk * 2, dB + kk * 128);
            wg_commit();
        }
        wg_wait<0>();
        pin<64>(acc);
        if (tid == 512) TLM(1, 18);
        {
            const uint32_t st = sb + 98304 + (warp - 16) * 4352;
            const uint32_t wa = st + (lane & 15) * 272 + (lane >> 4) * 16;
#pragma unroll
            for (int j = 0; j < 8; j++)
                asm volatile("stmatrix.sync.aligned.m8n8.x4.shared.b16 [%0], {%1, %2, %3, %4};" ::"r"(wa + j * 32),
                             "r"(pk_bf16(acc[8 * j], acc[8 * j + 1])), "r"(pk_bf16(acc[8 * j + 2], acc[8 * j + 3])),
                             "r"(pk_bf16(acc[8 * j + 4], acc[8 * j + 5])), "r"(pk_bf16(acc[8 * j + 6], acc[8 * j + 7])) : "memory");
            __syncwarp();
            __nv_bfloat16* op = out + (size_t)(rb * 64 + (warp - 16) * 16 + (lane >> 4)) * DM + cb * 128 + (lane & 15) * 8;
#pragma unroll
            for (int j = 0; j < 8; j++) {
                uint4 v;
                asm volatile("ld.shared.v4.u32 {%0, %1, %2, %3}, [%4];" : "=r"(v.x), "=r"(v.y), "=r"(v.z), "=r"(v.w)
                             : "r"(st + (2 * j + (lane >> 4)) * 272 + (lane & 15) * 16));
                *(uint4*)(op + (size_t)j * 2 * DM) = v;
            }
        }
        if (tid == 512) TLM(1, 19);
        TL_DUMP();
    }
}

typedef CUresult (*EncodeFn)(CUtensorMap*, CUtensorMapDataType, cuuint32_t, void*, const cuuint64_t*, const cuuint64_t*, const cuuint32_t*,
                             const cuuint32_t*, CUtensorMapInterleave, CUtensorMapSwizzle, CUtensorMapL2promotion, CUtensorMapFloatOOBfill);

static void make_map(EncodeFn enc, CUtensorMap* m, const void* p, int rank, const cuuint64_t* dims, const cuuint64_t* strides,
                     const cuuint32_t* box, CUtensorMapSwizzle swz) {
    const cuuint32_t es[5] = {1, 1, 1, 1, 1};
    enc(m, CU_TENSOR_MAP_DATA_TYPE_BFLOAT16, rank, (void*)p, dims, strides, box, es, CU_TENSOR_MAP_INTERLEAVE_NONE, swz,
        CU_TENSOR_MAP_L2_PROMOTION_L2_128B, CU_TENSOR_MAP_FLOAT_OOB_FILL_NONE);
}

extern "C" void kernel_launch(void* const* d_in, const int* in_sizes, int n_in, void* d_out, int out_size) {
    const __nv_bfloat16* x = (const __nv_bfloat16*)d_in[0];
    const __nv_bfloat16* wqkv = (const __nv_bfloat16*)d_in[1];
    const __nv_bfloat16* wo = (const __nv_bfloat16*)d_in[2];
    const __nv_bfloat16* w1 = (const __nv_bfloat16*)d_in[4];
    const __nv_bfloat16* b1 = (const __nv_bfloat16*)d_in[5];
    const __nv_bfloat16* w2 = (const __nv_bfloat16*)d_in[6];
    const __nv_bfloat16* b2 = (const __nv_bfloat16*)d_in[7];
    const __nv_bfloat16* gate = (const __nv_bfloat16*)d_in[8];

    void* fp = nullptr;
    cudaDriverEntryPointQueryResult qr;
    cudaGetDriverEntryPoint("cuTensorMapEncodeTiled", &fp, cudaEnableDefault, &qr);
    EncodeFn enc = (EncodeFn)fp;
    void *pH, *pKV;
    cudaGetSymbolAddress(&pH, gH);
    cudaGetSymbolAddress(&pKV, gKV);

    Maps tm;
    const CUtensorMapSwizzle S128 = CU_TENSOR_MAP_SWIZZLE_128B, S64 = CU_TENSOR_MAP_SWIZZLE_64B;
    { cuuint64_t d[2] = {DM, SEQ}, s[1] = {DM * 2}; cuuint32_t b[2] = {64, 128}; make_map(enc, &tm.x, x, 2, d, s, b, S128); }
    { cuuint64_t d[3] = {DM, DM, 3}, s[2] = {3 * DM * 2, DM * 2}; cuuint32_t b[3] = {64, 32, 2}; make_map(enc, &tm.kv, wqkv, 3, d, s, b, S128); }
    { cuuint64_t d[3] = {32, DM, 3 * DM / 32}, s[2] = {3 * DM * 2, 64}; cuuint32_t b[3] = {32, 32, 2}; make_map(enc, &tm.q, wqkv, 3, d, s, b, S64); }
    { cuuint64_t d[3] = {32, DM, FF / 32}, s[2] = {FF * 2, 64}; cuuint32_t b[3] = {32, 32, 1}; make_map(enc, &tm.f1, w1, 3, d, s, b, S64); }
    { cuuint64_t d[3] = {32, DM, FF / 32}, s[2] = {FF * 2, 64}; cuuint32_t b[3] = {32, 32, 3}; make_map(enc, &tm.f3, w1, 3, d, s, b, S64); }
    { cuuint64_t d[2] = {FF, SEQ}, s[1] = {FF * 2}; cuuint32_t b[2] = {64, 64}; make_map(enc, &tm.h, pH, 2, d, s, b, S128); }
    { cuuint64_t d[5] = {DM, 2, 4, 4, FF / 32}, s[4] = {1024, 8 * 1024, 2 * 1024, 32 * 1024}; cuuint32_t b[5] = {64, 2, 4, 4, 2};
      make_map(enc, &tm.w2, w2, 5, d, s, b, S128); }
    { cuuint64_t d[5] = {DM, 2, 2, 4, NH}, s[4] = {1024, 8 * 1024, 2 * 1024, 16 * 1024}; cuuint32_t b[5] = {64, 2, 2, 4, 4};
      make_map(enc, &tm.wo, wo, 5, d, s, b, S128); }

    { cuuint64_t d[3] = {32, SEQ, FF / 32}, s[2] = {FF * 2, 64}; cuuint32_t b[3] = {32, 64, 1}; make_map(enc, &tm.hs, pH, 3, d, s, b, CU_TENSOR_MAP_SWIZZLE_NONE); }
    { cuuint64_t d[5] = {64, 16, 16, 2, 2 * NH}, s[4] = {4096, 128, 2048, 65536}; cuuint32_t b[5] = {64, 8, 2, 2, 1};
      make_map(enc, &tm.kvs, pKV, 5, d, s, b, S128); }
    cudaFuncSetAttribute(fused_kernel, cudaFuncAttributeMaxDynamicSharedMemorySize, TL_SMEM);
    fused_kernel<<<128, 640, TL_SMEM, cudaStreamPerThread>>>(tm, x, wqkv, wo, w1, b1, w2, b2, gate, (__nv_bfloat16*)d_out, 0xffffffffu);
}
```

```cpp
#include <cuda_runtime.h>
#include <cuda_bf16.h>
#include <cuda_fp16.h>
#include <cuda.h>
#include <stdint.h>

#define SEQ 2048
#define DM 512
#define FF 1792
#define NH 32

__device__ __align__(1024) uint8_t gQ[NH * SEQ * 32];
__device__ __align__(1024) uint8_t gKV[NH * SEQ * 64];
__device__ __align__(1024) __nv_bfloat16 gH[SEQ * FF];
__device__ __align__(1024) uint4 gO[32 * NH * 128];
__device__ float gG[SEQ];
__device__ float gN[3 * 8 * 128];
__device__ unsigned int gCntQ[8 * 32];
__device__ unsigned int gCntH[32 * 32];
__device__ unsigned int gEpoch[128];

__device__ __forceinline__ uint32_t smem_u32(const void* p) { return (uint32_t)__cvta_generic_to_shared(p); }
__device__ __forceinline__ void mbar_init(uint32_t a, uint32_t c) { asm volatile("mbarrier.init.shared::cta.b64 [%0], %1;" ::"r"(a), "r"(c)); }
__device__ __forceinline__ void mbar_expect(uint32_t a, uint32_t b) { asm volatile("mbarrier.arrive.expect_tx.shared::cta.b64 _, [%0], %1;" ::"r"(a), "r"(b) : "memory"); }
__device__ __forceinline__ void mbar_arrive(uint32_t a) { asm volatile("mbarrier.arrive.shared::cta.b64 _, [%0];" ::"r"(a) : "memory"); }
__device__ __forceinline__ void mbar_wait(uint32_t a, uint32_t ph) {
    asm volatile("{\n.reg .pred p;\n.reg .u32 n;\nmov.u32 n, 0;\nW_%=:\nmbarrier.try_wait.parity.shared::cta.b64 p, [%0], %1;\n@p bra D_%=;\n"
                 "add.u32 n, n, 1;\nsetp.lt.u32 p, n, 0x400000;\n@p bra W_%=;\ntrap;\nD_%=:\n}" ::"r"(a), "r"(ph) : "memory");
}
__device__ __forceinline__ void mbar_arrive_cluster(uint32_t a, uint32_t cta) {
    asm volatile("{\n.reg .b32 r;\nmapa.shared::cluster.u32 r, %0, %1;\nmbarrier.arrive.shared::cluster.b64 _, [r];\n}" ::"r"(a), "r"(cta) : "memory");
}
__device__ __forceinline__ void bar_sync(int id, int n) { asm volatile("bar.sync %0, %1;" ::"r"(id), "r"(n) : "memory"); }
__device__ __forceinline__ void bar_arrive(int id, int n) { asm volatile("bar.arrive %0, %1;" ::"r"(id), "r"(n) : "memory"); }
__device__ __forceinline__ uint32_t cluster_rank() { uint32_t r; asm("mov.u32 %0, %%cluster_ctarank;" : "=r"(r)); return r; }
__device__ __forceinline__ void cnt_add(unsigned int* c) { asm volatile("red.release.gpu.global.add.u32 [%0], 1;" ::"l"(c) : "memory"); }
__device__ __forceinline__ void cnt_wait(const unsigned int* c, uint32_t target) {
    uint32_t v;
    int spins = 0;
    while (true) {
        asm volatile("ld.acquire.gpu.global.u32 %0, [%1];" : "=r"(v) : "l"(c) : "memory");
        if ((int)(v - target) >= 0) break;
        if (++spins > (1 << 22)) __trap();
        __nanosleep(40);
    }
}
__device__ __forceinline__ void tma2d(uint32_t dst, const CUtensorMap* m, int c0, int c1, uint32_t bar) {
    asm volatile("cp.async.bulk.tensor.2d.shared::cluster.global.mbarrier::complete_tx::bytes [%0], [%1, {%3, %4}], [%2];"
                 ::"r"(dst), "l"(m), "r"(bar), "r"(c0), "r"(c1) : "memory");
}
__device__ __forceinline__ void tma2d_mc(uint32_t dst, const CUtensorMap* m, int c0, int c1, uint32_t bar) {
    asm volatile("cp.async.bulk.tensor.2d.shared::cluster.global.mbarrier::complete_tx::bytes.multicast::cluster [%0], [%1, {%3, %4}], [%2], %5;"
                 ::"r"(dst), "l"(m), "r"(bar), "r"(c0), "r"(c1), "h"((uint16_t)3) : "memory");
}
__device__ __forceinline__ void tma3d_mc(uint32_t dst, const CUtensorMap* m, int c0, int c1, int c2, uint32_t bar) {
    asm volatile("cp.async.bulk.tensor.3d.shared::cluster.global.mbarrier::complete_tx::bytes.multicast::cluster [%0], [%1, {%3, %4, %5}], [%2], %6;"
                 ::"r"(dst), "l"(m), "r"(bar), "r"(c0), "r"(c1), "r"(c2), "h"((uint16_t)3) : "memory");
}
__device__ __forceinline__ void tma5d_mc(uint32_t dst, const CUtensorMap* m, int c0, int c4, uint32_t bar) {
    asm volatile("cp.async.bulk.tensor.5d.shared::cluster.global.mbarrier::complete_tx::bytes.multicast::cluster [%0], [%1, {%3, %5, %5, %5, %4}], [%2], %6;"
                 ::"r"(dst), "l"(m), "r"(bar), "r"(c0), "r"(c4), "r"(0), "h"((uint16_t)3) : "memory");
}
__device__ __forceinline__ void tma5d(uint32_t dst, const CUtensorMap* m, int c0, int c4, uint32_t bar) {
    asm volatile("cp.async.bulk.tensor.5d.shared::cluster.global.mbarrier::complete_tx::bytes [%0], [%1, {%3, %5, %5, %5, %4}], [%2];"
                 ::"r"(dst), "l"(m), "r"(bar), "r"(c0), "r"(c4), "r"(0) : "memory");
}
__device__ __forceinline__ void bulk_mc(uint32_t dst, const void* src, uint32_t bytes, uint32_t bar) {
    asm volatile("cp.async.bulk.shared::cluster.global.mbarrier::complete_tx::bytes.multicast::cluster [%0], [%1], %2, [%3], %4;"
                 ::"r"(dst), "l"(src), "r"(bytes), "r"(bar), "h"((uint16_t)3) : "memory");
}
__device__ __forceinline__ void tma3d_st(const CUtensorMap* m, uint32_t src, int c0, int c1, int c2) {
    asm volatile("cp.async.bulk.tensor.3d.global.shared::cta.bulk_group [%0, {%2, %3, %4}], [%1];" ::"l"(m), "r"(src), "r"(c0), "r"(c1), "r"(c2) : "memory");
}
__device__ __forceinline__ void tma5d_st(const CUtensorMap* m, uint32_t src, int c1, int c2, int c4) {
    asm volatile("cp.async.bulk.tensor.5d.global.shared::cta.bulk_group [%0, {%5, %2, %3, %5, %4}], [%1];"
                 ::"l"(m), "r"(src), "r"(c1), "r"(c2), "r"(c4), "r"(0) : "memory");
}
__device__ __forceinline__ void bulk_st(void* dst, uint32_t src, uint32_t bytes) {
    asm volatile("cp.async.bulk.global.shared::cta.bulk_group [%0], [%1], %2;" ::"l"(dst), "r"(src), "r"(bytes) : "memory");
}
__device__ __forceinline__ void sts64(uint32_t a, uint32_t x, uint32_t y) { asm volatile("st.shared.v2.u32 [%0], {%1, %2};" ::"r"(a), "r"(x), "r"(y) : "memory"); }
__device__ __forceinline__ void sts128(uint32_t a, const uint32_t* v) {
    asm volatile("st.shared.v4.u32 [%0], {%1, %2, %3, %4};" ::"r"(a), "r"(v[0]), "r"(v[1]), "r"(v[2]), "r"(v[3]) : "memory");
}
__device__ __forceinline__ void l2_prefetch(const void* src, uint32_t bytes) {
    asm volatile("cp.async.bulk.prefetch.L2.global [%0], %1;" ::"l"(src), "r"(bytes) : "memory");
}
__device__ __forceinline__ void map_prefetch(const CUtensorMap* m) { asm volatile("prefetch.tensormap [%0];" ::"l"(m) : "memory"); }
__device__ __forceinline__ void wg_fence() { asm volatile("wgmma.fence.sync.aligned;" ::: "memory"); }
__device__ __forceinline__ void wg_commit() { asm volatile("wgmma.commit_group.sync.aligned;" ::: "memory"); }
template <int N> __device__ __forceinline__ void wg_wait() { asm volatile("wgmma.wait_group.sync.aligned %0;" ::"n"(N) : "memory"); }
template <int N> __device__ __forceinline__ void pin(float* s) {
#pragma unroll
    for (int i = 0; i < N; i++) asm volatile("" : "+f"(s[i])::"memory");
}
template <int N> __device__ __forceinline__ void pin(uint32_t* s) {
#pragma unroll
    for (int i = 0; i < N; i++) asm volatile("" : "+r"(s[i])::"memory");
}
__device__ __forceinline__ uint64_t mkdesc(uint32_t addr, uint32_t lbo, uint32_t sbo, uint32_t swz) {
    return (uint64_t)((addr & 0x3FFFF) >> 4) | ((uint64_t)(lbo >> 4) << 16) | ((uint64_t)(sbo >> 4) << 32) | ((uint64_t)swz << 62);
}
__device__ __forceinline__ float ex2f(float x) { float y; asm("ex2.approx.ftz.f32 %0, %1;" : "=f"(y) : "f"(x)); return y; }
__device__ __forceinline__ float tanhf_(float x) { float y; asm("tanh.approx.f32 %0, %1;" : "=f"(y) : "f"(x)); return y; }
__device__ __forceinline__ uint32_t pk_bf16(float lo, float hi) { uint32_t r; asm("cvt.rn.bf16x2.f32 %0, %1, %2;" : "=r"(r) : "f"(hi), "f"(lo)); return r; }
__device__ __forceinline__ uint32_t pk_f16(float lo, float hi) { uint32_t r; asm("cvt.rn.f16x2.f32 %0, %1, %2;" : "=r"(r) : "f"(hi), "f"(lo)); return r; }
__device__ __forceinline__ float bf_lo(uint32_t v) { return __uint_as_float(v << 16); }
__device__ __forceinline__ float bf_hi(uint32_t v) { return __uint_as_float(v & 0xffff0000u); }
__device__ __forceinline__ float dot8(const uint4& a, const uint4& b) {
    return fmaf(bf_lo(a.x), bf_lo(b.x), fmaf(bf_hi(a.x), bf_hi(b.x), fmaf(bf_lo(a.y), bf_lo(b.y), bf_hi(a.y) * bf_hi(b.y)))) +
           fmaf(bf_lo(a.z), bf_lo(b.z), fmaf(bf_hi(a.z), bf_hi(b.z), fmaf(bf_lo(a.w), bf_lo(b.w), bf_hi(a.w) * bf_hi(b.w))));
}
__device__ __forceinline__ uint32_t epoch() {
    uint32_t v;
    asm volatile("ld.global.u32 %0, [%1];" : "=r"(v) : "l"(gEpoch + blockIdx.x));
    return v + 1;
}
__device__ __forceinline__ float ldcg_f(const float* p) { return __ldcg(p); }

extern __shared__ __align__(1024) uint8_t smem_raw[];
#define TLM(k, slot) do {} while (0)
#define TLC(k, slot) do {} while (0)
#define TL_INIT() do {} while (0)
#define TL_DUMP() do {} while (0)
#define TL_SMEM SMEM_BYTES

__device__ __forceinline__ void wgmma_ss_n128(float* d, uint64_t da, uint64_t db) {
    asm volatile("wgmma.mma_async.sync.aligned.m64n128k16.f32.bf16.bf16 {"
        "%0, %1, %2, %3, %4, %5, %6, %7, %8, %9, %10, %11, %12, %13, %14, %15,"
        "%16, %17, %18, %19, %20, %21, %22, %23, %24, %25, %26, %27, %28, %29, %30, %31,"
        "%32, %33, %34, %35, %36, %37, %38, %39, %40, %41, %42, %43, %44, %45, %46, %47,"
        "%48, %49, %50, %51, %52, %53, %54, %55, %56, %57, %58, %59, %60, %61, %62, %63}, %64, %65, 1, 1, 1, 0, 1;\n"
        :
        "+f"(d[0]), "+f"(d[1]), "+f"(d[2]), "+f"(d[3]), "+f"(d[4]), "+f"(d[5]), "+f"(d[6]), "+f"(d[7]),
        "+f"(d[8]), "+f"(d[9]), "+f"(d[10]), "+f"(d[11]), "+f"(d[12]), "+f"(d[13]), "+f"(d[14]), "+f"(d[15]),
        "+f"(d[16]), "+f"(d[17]), "+f"(d[18]), "+f"(d[19]), "+f"(d[20]), "+f"(d[21]), "+f"(d[22]), "+f"(d[23]),
        "+f"(d[24]), "+f"(d[25]), "+f"(d[26]), "+f"(d[27]), "+f"(d[28]), "+f"(d[29]), "+f"(d[30]), "+f"(d[31]),
        "+f"(d[32]), "+f"(d[33]), "+f"(d[34]), "+f"(d[35]), "+f"(d[36]), "+f"(d[37]), "+f"(d[38]), "+f"(d[39]),
        "+f"(d[40]), "+f"(d[41]), "+f"(d[42]), "+f"(d[43]), "+f"(d[44]), "+f"(d[45]), "+f"(d[46]), "+f"(d[47]),
        "+f"(d[48]), "+f"(d[49]), "+f"(d[50]), "+f"(d[51]), "+f"(d[52]), "+f"(d[53]), "+f"(d[54]), "+f"(d[55]),
        "+f"(d[56]), "+f"(d[57]), "+f"(d[58]), "+f"(d[59]), "+f"(d[60]), "+f"(d[61]), "+f"(d[62]), "+f"(d[63])
        : "l"(da), "l"(db));
}
__device__ __forceinline__ void wgmma_ss_n96(float* d, uint64_t da, uint64_t db) {
    asm volatile("wgmma.mma_async.sync.aligned.m64n96k16.f32.bf16.bf16 {"
        "%0, %1, %2, %3, %4, %5, %6, %7, %8, %9, %10, %11, %12, %13, %14, %15,"
        "%16, %17, %18, %19, %20, %21, %22, %23, %24, %25, %26, %27, %28, %29, %30, %31,"
        "%32, %33, %34, %35, %36, %37, %38, %39, %40, %41, %42, %43, %44, %45, %46, %47}, %48, %49, 1, 1, 1, 0, 1;\n"
        :
        "+f"(d[0]), "+f"(d[1]), "+f"(d[2]), "+f"(d[3]), "+f"(d[4]), "+f"(d[5]), "+f"(d[6]), "+f"(d[7]),
        "+f"(d[8]), "+f"(d[9]), "+f"(d[10]), "+f"(d[11]), "+f"(d[12]), "+f"(d[13]), "+f"(d[14]), "+f"(d[15]),
        "+f"(d[16]), "+f"(d[17]), "+f"(d[18]), "+f"(d[19]), "+f"(d[20]), "+f"(d[21]), "+f"(d[22]), "+f"(d[23]),
        "+f"(d[24]), "+f"(d[25]), "+f"(d[26]), "+f"(d[27]), "+f"(d[28]), "+f"(d[29]), "+f"(d[30]), "+f"(d[31]),
        "+f"(d[32]), "+f"(d[33]), "+f"(d[34]), "+f"(d[35]), "+f"(d[36]), "+f"(d[37]), "+f"(d[38]), "+f"(d[39]),
        "+f"(d[40]), "+f"(d[41]), "+f"(d[42]), "+f"(d[43]), "+f"(d[44]), "+f"(d[45]), "+f"(d[46]), "+f"(d[47])
        : "l"(da), "l"(db));
}
__device__ __forceinline__ void wgmma_ss_n64(float* d, uint64_t da, uint64_t db) {
    asm volatile("wgmma.mma_async.sync.aligned.m64n64k16.f32.bf16.bf16 {"
        "%0, %1, %2, %3, %4, %5, %6, %7, %8, %9, %10, %11, %12, %13, %14, %15,"
        "%16, %17, %18, %19, %20, %21, %22, %23, %24, %25, %26, %27, %28, %29, %30, %31}, %32, %33, 1, 1, 1, 0, 1;\n"
        :
        "+f"(d[0]), "+f"(d[1]), "+f"(d[2]), "+f"(d[3]), "+f"(d[4]), "+f"(d[5]), "+f"(d[6]), "+f"(d[7]),
        "+f"(d[8]), "+f"(d[9]), "+f"(d[10]), "+f"(d[11]), "+f"(d[12]), "+f"(d[13]), "+f"(d[14]), "+f"(d[15]),
        "+f"(d[16]), "+f"(d[17]), "+f"(d[18]), "+f"(d[19]), "+f"(d[20]), "+f"(d[21]), "+f"(d[22]), "+f"(d[23]),
        "+f"(d[24]), "+f"(d[25]), "+f"(d[26]), "+f"(d[27]), "+f"(d[28]), "+f"(d[29]), "+f"(d[30]), "+f"(d[31])
        : "l"(da), "l"(db));
}
__device__ __forceinline__ void wgmma_rs_n128(float* d, const uint32_t* a, uint64_t db) {
    asm volatile("wgmma.mma_async.sync.aligned.m64n128k16.f32.bf16.bf16 {"
        "%0, %1, %2, %3, %4, %5, %6, %7, %8, %9, %10, %11, %12, %13, %14, %15,"
        "%16, %17, %18, %19, %20, %21, %22, %23, %24, %25, %26, %27, %28, %29, %30, %31,"
        "%32, %33, %34, %35, %36, %37, %38, %39, %40, %41, %42, %43, %44, %45, %46, %47,"
        "%48, %49, %50, %51, %52, %53, %54, %55, %56, %57, %58, %59, %60, %61, %62, %63}, {%64, %65, %66, %67}, %68, 1, 1, 1, 1;\n"
        :
        "+f"(d[0]), "+f"(d[1]), "+f"(d[2]), "+f"(d[3]), "+f"(d[4]), "+f"(d[5]), "+f"(d[6]), "+f"(d[7]),
        "+f"(d[8]), "+f"(d[9]), "+f"(d[10]), "+f"(d[11]), "+f"(d[12]), "+f"(d[13]), "+f"(d[14]), "+f"(d[15]),
        "+f"(d[16]), "+f"(d[17]), "+f"(d[18]), "+f"(d[19]), "+f"(d[20]), "+f"(d[21]), "+f"(d[22]), "+f"(d[23]),
        "+f"(d[24]), "+f"(d[25]), "+f"(d[26]), "+f"(d[27]), "+f"(d[28]), "+f"(d[29]), "+f"(d[30]), "+f"(d[31]),
        "+f"(d[32]), "+f"(d[33]), "+f"(d[34]), "+f"(d[35]), "+f"(d[36]), "+f"(d[37]), "+f"(d[38]), "+f"(d[39]),
        "+f"(d[40]), "+f"(d[41]), "+f"(d[42]), "+f"(d[43]), "+f"(d[44]), "+f"(d[45]), "+f"(d[46]), "+f"(d[47]),
        "+f"(d[48]), "+f"(d[49]), "+f"(d[50]), "+f"(d[51]), "+f"(d[52]), "+f"(d[53]), "+f"(d[54]), "+f"(d[55]),
        "+f"(d[56]), "+f"(d[57]), "+f"(d[58]), "+f"(d[59]), "+f"(d[60]), "+f"(d[61]), "+f"(d[62]), "+f"(d[63])
        : "r"(a[0]), "r"(a[1]), "r"(a[2]), "r"(a[3]), "l"(db));
}
__device__ __forceinline__ void wgmma_qk_f16_acc(float* d, const uint32_t* a, uint64_t db) {
    asm volatile("wgmma.mma_async.sync.aligned.m64n64k16.f32.f16.f16 {"
        "%0, %1, %2, %3, %4, %5, %6, %7, %8, %9, %10, %11, %12, %13, %14, %15,"
        "%16, %17, %18, %19, %20, %21, %22, %23, %24, %25, %26, %27, %28, %29, %30, %31}, {%32, %33, %34, %35}, %36, 1, 1, 1, 0;\n"
        :
        "+f"(d[0]), "+f"(d[1]), "+f"(d[2]), "+f"(d[3]), "+f"(d[4]), "+f"(d[5]), "+f"(d[6]), "+f"(d[7]),
        "+f"(d[8]), "+f"(d[9]), "+f"(d[10]), "+f"(d[11]), "+f"(d[12]), "+f"(d[13]), "+f"(d[14]), "+f"(d[15]),
        "+f"(d[16]), "+f"(d[17]), "+f"(d[18]), "+f"(d[19]), "+f"(d[20]), "+f"(d[21]), "+f"(d[22]), "+f"(d[23]),
        "+f"(d[24]), "+f"(d[25]), "+f"(d[26]), "+f"(d[27]), "+f"(d[28]), "+f"(d[29]), "+f"(d[30]), "+f"(d[31])
        : "r"(a[0]), "r"(a[1]), "r"(a[2]), "r"(a[3]), "l"(db));
}
__device__ __forceinline__ void wgmma_qk_bf16_zero(float* d, const uint32_t* a, uint64_t db) {
    asm volatile("wgmma.mma_async.sync.aligned.m64n64k16.f32.bf16.bf16 {"
        "%0, %1, %2, %3, %4, %5, %6, %7, %8, %9, %10, %11, %12, %13, %14, %15,"
        "%16, %17, %18, %19, %20, %21, %22, %23, %24, %25, %26, %27, %28, %29, %30, %31}, {%32, %33, %34, %35}, %36, 0, 1, 1, 0;\n"
        :
        "=f"(d[0]), "=f"(d[1]), "=f"(d[2]), "=f"(d[3]), "=f"(d[4]), "=f"(d[5]), "=f"(d[6]), "=f"(d[7]),
        "=f"(d[8]), "=f"(d[9]), "=f"(d[10]), "=f"(d[11]), "=f"(d[12]), "=f"(d[13]), "=f"(d[14]), "=f"(d[15]),
        "=f"(d[16]), "=f"(d[17]), "=f"(d[18]), "=f"(d[19]), "=f"(d[20]), "=f"(d[21]), "=f"(d[22]), "=f"(d[23]),
        "=f"(d[24]), "=f"(d[25]), "=f"(d[26]), "=f"(d[27]), "=f"(d[28]), "=f"(d[29]), "=f"(d[30]), "=f"(d[31])
        : "r"(a[0]), "r"(a[1]), "r"(a[2]), "r"(a[3]), "l"(db));
}
__device__ __forceinline__ void wgmma_pv(float* d, const uint32_t* a, uint64_t db) {
    asm volatile("wgmma.mma_async.sync.aligned.m64n24k16.f32.bf16.bf16 {"
        "%0, %1, %2, %3, %4, %5, %6, %7, %8, %9, %10, %11}, {%12, %13, %14, %15}, %16, 1, 1, 1, 1;\n"
        :
        "+f"(d[0]), "+f"(d[1]), "+f"(d[2]), "+f"(d[3]), "+f"(d[4]), "+f"(d[5]), "+f"(d[6]), "+f"(d[7]),
        "+f"(d[8]), "+f"(d[9]), "+f"(d[10]), "+f"(d[11])
        : "r"(a[0]), "r"(a[1]), "r"(a[2]), "r"(a[3]), "l"(db));
}

template <int N> __device__ __forceinline__ void wgmma_ss(float* d, uint64_t a, uint64_t b) {
    if (N == 128) wgmma_ss_n128(d, a, b);
    if (N == 96) wgmma_ss_n96(d, a, b);
    if (N == 64) wgmma_ss_n64(d, a, b);
}

#define OFF_R 131072
#define OFF_ONE 229376
#define OFF_BAR 229888
#define OFF_BIAS (OFF_BAR + 736)
#define OFF_G (OFF_BIAS + 1152)
#define SMEM_BYTES (OFF_G + 272)
#define SBD 1024u
#define B_X 0
#define B_F1 416
#define B_E1 64
#define B_XD 672
#define B_KV 160
#define B_F2 224
#define B_E2 256
#define B_T 288
#define B_G 360
#define B_G2 368
#define B_G3 376
#define B_SF 384
#define B_BI 400

#define B_SF2 408
#define NR 6

#define PF 1
#define PFX 0
#define PACE 1
#define FSER 0
#define MERGE 1
#define EB 2
#define EXP_FKK 4
#define QSCALE 0.36067376022224085f
#define MAGIC 445.41763f
#define FORCE_IMAD
#define NMUFU 5
#define VSTEP ((uint64_t)((long long)32 - ((long long)32 << 16)))

#define XMASK 0x0D55u
#define KVMASK 0x1D55u
__host__ __device__ constexpr int strm_pos(int pass, int i) {
    if (pass == 1 || pass == 2) return 8 + 8 * pass + i;
    int n = 0;
    for (int p = 0; p < 16; p++)
        if ((int)((KVMASK >> p) & 1) == (pass == 3)) { if (n == i) return p; n++; }
    return 0;
}
__host__ __device__ constexpr uint32_t strm_code(int pass) {
    uint32_t c = 0;
    for (int i = 0; i < 7; i++) c |= (uint32_t)(strm_pos(pass, i + 1) - strm_pos(pass, i)) << (4 * i);
    return c;
}

template <int N, int SUB, int KST, int LBO, int SBO, int SWZ>
__device__ __forceinline__ void gemm_pass(float* acc, uint32_t bar, uint64_t dA, int lane, uint32_t pos, uint32_t code, int barNext, bool waitx, bool last) {
    uint32_t prev = 0, slot = pos % NR;
#pragma unroll 1
    for (int i = 0; i < 8; i++) {
        if (waitx) mbar_wait(bar + B_X + 8 * i, 0);
        mbar_wait(bar + B_F1 + 8 * pos, 0);
        const uint64_t dB = mkdesc(SBD + OFF_R, LBO, SBO, SWZ) + slot * 1024;
        wg_fence();
        wgmma_ss<N>(acc, dA, dB);
        wgmma_ss<N>(acc, dA + 2, dB + KST / 16);
        wg_commit();
        wg_wait<1>();
        if (i > 0 && lane < 2) mbar_arrive_cluster(prev, lane);
        wgmma_ss<N>(acc, dA + 4, dB + SUB / 16);
        wgmma_ss<N>(acc, dA + 6, dB + (SUB + KST) / 16);
        wg_commit();
        prev = last ? bar + B_XD + 8 * i : bar + B_E1 + 8 * slot;
        pos += code & 15;
        slot += code & 15;
        if (slot >= NR) slot -= NR;
        code >>= 4;
        dA += 1024;
    }
    if (barNext) bar_arrive(barNext, 512);
    wg_wait<0>();
    if (lane < 2) mbar_arrive_cluster(prev, lane);
    pin<N / 2>(acc);
}

__device__ __forceinline__ uint32_t lds32(uint32_t a) { uint32_t v; asm volatile("ld.shared.u32 %0, [%1];" : "=r"(v) : "r"(a)); return v; }
__device__ __forceinline__ bool elect() {
    uint32_t p;
    asm volatile("{\n.reg .pred p;\nelect.sync _|p, 0xffffffff;\nselp.u32 %0, 1, 0, p;\n}" : "=r"(p));
    return p;
}

template <int G0, int G1> __device__ __forceinline__ void gelu_pack(const float* acc, uint32_t bias, uint32_t* out) {
#pragma unroll
    for (int G = G0; G < G1; G++) {
        uint32_t* o = out + 8 * G;
#pragma unroll
        for (int j = 0; j < 4; j++) {
            float bv[2];
            asm volatile("ld.shared.v2.f32 {%0, %1}, [%2];" : "=f"(bv[0]), "=f"(bv[1]) : "r"(bias + G * 128 + j * 32));
            float y[4];
#pragma unroll
            for (int i = 0; i < 4; i++) {
                const float h = acc[16 * G + 4 * j + i] + bv[i & 1];
                const float z = h * fmaf(h * h, 0.035677408136300125f, 0.7978845608028654f);
                y[i] = fmaf(h, tanhf_(z), h);
            }
            o[j] = pk_bf16(y[0], y[1]);
            o[4 + j] = pk_bf16(y[2], y[3]);
        }
    }
}

__device__ __forceinline__ float norm_bound(const float* v, float sc) {
    uint32_t m = 0;
#pragma unroll
    for (int h = 0; h < 4; h++) {
        const float* u = v + 8 * h;
        m = max(m, __float_as_uint(fmaf(u[0], u[0], fmaf(u[1], u[1], fmaf(u[4], u[4], u[5] * u[5])))));
        m = max(m, __float_as_uint(fmaf(u[2], u[2], fmaf(u[3], u[3], fmaf(u[6], u[6], u[7] * u[7])))));
    }
#pragma unroll
    for (int o = 4; o < 32; o <<= 1) m = max(m, __shfl_xor_sync(0xffffffffu, m, o));
    float f = __uint_as_float(m);
    f += __shfl_xor_sync(0xffffffffu, f, 1);
    f += __shfl_xor_sync(0xffffffffu, f, 2);
    return f * sc;
}

__device__ __forceinline__ uint32_t exp2_pair(float a, float b, uint32_t m1) {
    const uint32_t w = __byte_perm(__float_as_uint(a), __float_as_uint(b), 0x6521);
    uint32_t m, r;
    asm("lop3.b32 %0, %1, 0x007f007f, 0x9f809f80, 0xEA;" : "=r"(m) : "r"(w));
    const uint32_t e = m * m1 + w;
    asm("fma.rn.bf16x2 %0, %1, %2, %3;" : "=r"(r) : "r"(w), "r"(m), "r"(e));
    return r;
}

__device__ __forceinline__ void store_o(const float* o, uint4* dst, uint32_t par) {
    const float s0 = __fdividef(1.f, o[8]), s1 = __fdividef(1.f, o[10]);
    const uint32_t d0 = (pk_bf16(o[0] * s0, o[1] * s0) & ~1u) | par;
    asm volatile("{\n.reg .b128 t;\nmov.b128 t, {%0, %1, %2, %3};\nst.relaxed.gpu.global.b128 [%4], t;\n}" ::"r"(d0),
                 "r"(pk_bf16(o[2] * s1, o[3] * s1)), "r"(pk_bf16(o[4] * s0, o[5] * s0)), "r"(pk_bf16(o[6] * s1, o[7] * s1)), "l"(dst) : "memory");
}
__device__ __forceinline__ uint4 load_o(const uint4* src) {
    uint4 v;
    asm volatile("{\n.reg .b128 t;\nld.relaxed.gpu.global.b128 t, [%4];\nmov.b128 {%0, %1, %2, %3}, t;\n}"
                 : "=r"(v.x), "=r"(v.y), "=r"(v.z), "=r"(v.w) : "l"(src) : "memory");
    return v;
}
template <int N> __device__ __forceinline__ void fetch_o(uint4* v, const uint4* src, uint32_t ep) {
    int spins = 0;
    while (true) {
        uint32_t bad = 0;
#pragma unroll
        for (int k = 0; k < N; k++) bad |= v[k].x ^ ep;
        if (!__any_sync(0xffffffffu, (bad & 1) != 0)) break;
        if (++spins > (1 << 22)) __trap();
#pragma unroll
        for (int k = 0; k < N; k++)
            if (((v[k].x ^ ep) & 1) != 0) v[k] = load_o(src + k * 128);
    }
}
__device__ __forceinline__ uint32_t bmul2(uint32_t a, uint32_t b) { uint32_t r; asm("mul.rn.bf16x2 %0, %1, %2;" : "=r"(r) : "r"(a), "r"(b)); return r; }
__device__ __forceinline__ void sts32(uint32_t a, uint32_t v) { asm volatile("st.shared.u32 [%0], %1;" ::"r"(a), "r"(v) : "memory"); }
__device__ __forceinline__ void stage_o(const uint4* v, uint32_t a0, uint32_t g0, uint32_t g1, int lane) {
#pragma unroll
    for (int i = 0; i < 4; i++)
        asm volatile("stmatrix.sync.aligned.m8n8.x4.shared.b16 [%0], {%1, %2, %3, %4};" ::"r"(a0 + (((i * 2 + (lane >> 4)) ^ (lane & 7)) << 4)),
                     "r"(bmul2(v[i].x, g0)), "r"(bmul2(v[i].y, g1)), "r"(bmul2(v[i].z, g0)), "r"(bmul2(v[i].w, g1)) : "memory");
    asm volatile("fence.proxy.async.shared::cta;" ::: "memory");
}
__device__ __forceinline__ void load_q(uint32_t* q, int h, int row, int t) {
    const uint8_t* p = gQ + (size_t)h * (SEQ * 32) + (size_t)row * 32 + t * 4;
    q[0] = __ldcg((const uint32_t*)p); q[1] = __ldcg((const uint32_t*)(p + 256));
    q[2] = __ldcg((const uint32_t*)(p + 16)); q[3] = __ldcg((const uint32_t*)(p + 272));
}

template <int NT>
__device__ __forceinline__ void proj16(float (*c)[8], const __nv_bfloat16* x, const __nv_bfloat16* w, int row0, int rstep, int col, int g, int t) {
#pragma unroll
    for (int i = 0; i < NT; i++)
#pragma unroll
        for (int j = 0; j < 8; j++) c[i][j] = 0.f;
    const unsigned short* wu = (const unsigned short*)w;
#pragma unroll 1
    for (int k = 0; k < DM; k += 16) {
        uint32_t b[4];
#pragma unroll
        for (int j = 0; j < 4; j++) {
            const int kr = k + 2 * t + (j & 1) * 8, cc = col + g + (j >> 1) * 8;
            b[j] = (uint32_t)wu[(size_t)kr * (3 * DM) + cc] | ((uint32_t)wu[(size_t)(kr + 1) * (3 * DM) + cc] << 16);
        }
#pragma unroll
        for (int i = 0; i < NT; i++) {
            const __nv_bfloat16* xp = x + (size_t)(row0 + i * rstep + g) * DM + k + 2 * t;
            const uint32_t a0 = *(const uint32_t*)xp, a1 = *(const uint32_t*)(xp + 8 * DM);
            const uint32_t a2 = *(const uint32_t*)(xp + 8), a3 = *(const uint32_t*)(xp + 8 * DM + 8);
#pragma unroll
            for (int j = 0; j < 2; j++)
                asm volatile("mma.sync.aligned.m16n8k16.row.col.f32.bf16.bf16.f32 {%0,%1,%2,%3}, {%4,%5,%6,%7}, {%8,%9}, {%0,%1,%2,%3};"
                             : "+f"(c[i][4 * j]), "+f"(c[i][4 * j + 1]), "+f"(c[i][4 * j + 2]), "+f"(c[i][4 * j + 3])
                             : "r"(a0), "r"(a1), "r"(a2), "r"(a3), "r"(b[2 * j]), "r"(b[2 * j + 1]));
        }
    }
}

struct Maps { CUtensorMap x, kv, q, f1, f3, h, w2, wo, hs, kvs; };

template <int I0, int I1>
__device__ __forceinline__ void issue_stream(const Maps& tm, uint32_t sb, uint32_t rank, int nb, int mb) {
    const uint32_t bar = sb + OFF_BAR;
    const uint32_t dst = sb + OFF_R;
    const int kr = rank * 32;
#pragma unroll
    for (int it = I0; it < I1; it++) {
        const int s = it % NR;
        const uint32_t fb = bar + B_F1 + 8 * it;
        if (it >= 24 + NR) mbar_wait(bar + B_XD + 8 * (it - 24 - NR), 0);
        else if (it >= NR) mbar_wait(bar + B_E1 + 8 * s, ((it / NR) - 1) & 1);
        const int nkv = __builtin_popcount(KVMASK & ((1u << it) - 1));
        if (it < 16 && ((KVMASK >> it) & 1)) {
            tma3d_mc(dst + s * 16384 + rank * 8192, &tm.kv, nb * 64, nkv * 64 + kr, 1, fb);
        } else if (it < 16) {
            tma3d_mc(dst + s * 16384 + rank * 6144, &tm.q, 0, (it - nkv) * 64 + kr, nb * 2, fb);
            tma3d_mc(dst + s * 16384 + rank * 6144 + 4096, &tm.f1, 0, (it - nkv) * 64 + kr, nb * 7, fb);
        } else {
            tma3d_mc(dst + s * 16384 + rank * 6144, &tm.f3, 0, (it & 7) * 64 + kr, nb * 7 + (it < 24 ? 1 : 4), fb);
        }
        if ((XMASK >> it) & 1) {
            const int xc = 1 + __builtin_popcount(XMASK & ((1u << it) - 1));
            tma2d(sb + xc * 16384, &tm.x, xc * 64, mb * 128, bar + B_X + 8 * xc);
        }
    }
}

__global__ void __cluster_dims__(2, 1, 1) __launch_bounds__(640, 1)
fused_kernel(const __grid_constant__ Maps tm, const __nv_bfloat16* __restrict__ x, const __nv_bfloat16* __restrict__ wqkv,
             const __nv_bfloat16* __restrict__ wo, const __nv_bfloat16* __restrict__ w1, const __nv_bfloat16* __restrict__ b1,
             const __nv_bfloat16* __restrict__ w2, const __nv_bfloat16* __restrict__ b2, const __nv_bfloat16* __restrict__ gate,
             __nv_bfloat16* __restrict__ out, const uint32_t m1) {
    const uint32_t sb = smem_u32(smem_raw);
    const uint32_t bar = sb + OFF_BAR;
    const int tid = threadIdx.x, lane = tid & 31;
    const int warp = __shfl_sync(0xffffffffu, tid >> 5, 0);
    const uint32_t rank = cluster_rank();
    const int cl = blockIdx.x >> 1;
    const int nb = cl & 7, mb = (cl >> 3) * 2 + rank;
    const int g = lane >> 2, t = lane & 3;

    const int cb = nb & 3, rb = mb * 2 + (nb >> 2);
    const int rn = (mb >> 1) & 1;
    if (tid == 0) TLM(0, 0);
    TL_INIT();
    if (tid == 512) {
        for (int i = 0; i < 8; i++) { mbar_init(bar + B_X + 8 * i, 1); mbar_init(bar + B_KV + 8 * i, 1); mbar_init(bar + B_T + 8 * i, i < 4 ? 1 : 5); mbar_init(bar + B_XD + 8 * i, 16); }
        for (int i = 0; i < NR; i++) mbar_init(bar + B_E1 + 8 * i, 16);
        for (int i = 0; i < 4; i++) { mbar_init(bar + B_F2 + 8 * i, 1); mbar_init(bar + B_E2 + 8 * i, 8); }
        asm volatile("fence.mbarrier_init.release.cluster;" ::: "memory");
    } else if (tid == 608) {
        for (int i = 0; i < 32; i++) mbar_init(bar + B_F1 + 8 * i, 1);
        mbar_init(bar + B_G, 1);
        for (int i = 0; i < 3; i++) mbar_init(bar + B_SF + 8 * i, i == 1 ? 2 : 1);
        mbar_init(bar + B_SF2, 2);
        mbar_init(bar + B_G3, 1);
        mbar_init(bar + B_G2, 4);
        asm volatile("fence.mbarrier_init.release.cluster;" ::: "memory");
    }
    __syncwarp();
    asm volatile("barrier.cluster.arrive.relaxed.aligned;" ::: "memory");
    if (warp == 19) mbar_expect(bar + B_F1 + 8 * lane, ((KVMASK >> lane) & 1) ? 16384 : 12288);
    if (warp == 16 && lane < 24) mbar_expect(bar + (lane < 8 ? B_X : lane < 16 ? B_KV - 64 : B_T - 128) + 8 * lane, 16384);
    if (tid == 512) {
        tma2d(sb, &tm.x, 0, mb * 128, bar + B_X);
    } else if (tid == 544) {
        map_prefetch(&tm.kv);
        l2_prefetch((const uint8_t*)wqkv + (size_t)blockIdx.x * 3072, 3072);
        l2_prefetch((const uint8_t*)w1 + (size_t)blockIdx.x * 1792, 1792);
        map_prefetch(&tm.q); map_prefetch(&tm.f1); map_prefetch(&tm.f3);
    }
    if ((sb & 0xFFFFFF) != SBD) __trap();
    __syncwarp();
    asm volatile("barrier.cluster.wait.aligned;" ::: "memory");
    if (tid == 512) issue_stream<0, NR>(tm, sb, rank, nb, mb);
    if (tid == 0) { TLM(0, 1); TLC(0, 30); }

    if (warp < 16) {
        const int wg = warp >> 2;
        const int h = cl >> 1, qd = (cl & 1) * 2 + rank;
        const int flip = (h >> 2) & 1;
        uint32_t q[4];
        {
            const int w8 = warp & 7;
            const int T = mb * 8 + w8, row0 = T * 16 + g;
            const uint64_t dA0 = mkdesc(SBD + (wg & 1) * 8192, 16, 1024, 1);
            if (wg < 2) {
                float acc[64];
#pragma unroll
                for (int i = 0; i < 64; i++) acc[i] = 0.f;
                gemm_pass<128, 8192, 2048, 4096, 1024, 1>(acc, bar, dA0, lane, strm_pos(3, 0), strm_code(3), 0, true, false);
                if (tid == 0) TLM(0, 2);
                {
                    const float km = norm_bound(acc, 1.f);
                    float vm = 0.f;
#pragma unroll
                    for (int i = 32; i < 64; i++) vm = fmaxf(vm, fabsf(acc[i]));
                    vm = __uint_as_float(__reduce_max_sync(0xffffffffu, __float_as_uint(vm)));
                    if (lane == 0) { gN[1024 + nb * 128 + T] = km; gN[2048 + nb * 128 + T] = vm; }
                    const uint32_t kp = sb + OFF_R + 12288 + (w8 >> 2) * 1024 + g * 128 + ((((w8 & 3) * 2 + ((t >> 1) ^ (w8 >> 2))) ^ g) << 4) + (t & 1) * 8;
                    uint8_t* vp = gKV + (size_t)(nb * 4) * (SEQ * 64) + 65536 + (((T >> 6) * 16 + 2 * g) * 64 + (T & 63)) * 32 + ((t * 8) ^ ((w8 >> 2) << 4));
                    bar_sync(9, 256);
#pragma unroll
                    for (int hh = 0; hh < 4; hh++) {
                        const float* v = acc + 8 * hh;
                        float p0 = __shfl_up_sync(0xffffffffu, v[2], 4), p1 = __shfl_up_sync(0xffffffffu, v[3], 4);
                        float p2 = __shfl_up_sync(0xffffffffu, v[6], 4), p3 = __shfl_up_sync(0xffffffffu, v[7], 4);
                        if (g == 0) { p0 = p1 = p2 = p3 = 0.f; }
                        sts64(kp + hh * 16384, pk_f16(v[0] - p0, v[1] - p1), pk_f16(v[4] - p2, v[5] - p3));
                        sts64(kp + hh * 16384 + 2048, pk_f16(v[2] - v[0], v[3] - v[1]), pk_f16(v[6] - v[4], v[7] - v[5]));
                        const float* u = acc + 32 + 8 * hh;
                        if (hh < 2) {
                            sts64(kp + (4 + hh) * 16384, pk_bf16(u[0], u[1]), pk_bf16(u[4], u[5]));
                            sts64(kp + (4 + hh) * 16384 + 2048, pk_bf16(u[2], u[3]), pk_bf16(u[6], u[7]));
                        } else {
                            *(uint2*)(vp + (size_t)hh * (SEQ * 64)) = make_uint2(pk_bf16(u[0], u[1]), pk_bf16(u[4], u[5]));
                            *(uint2*)(vp + (size_t)hh * (SEQ * 64) + 2048) = make_uint2(pk_bf16(u[2], u[3]), pk_bf16(u[6], u[7]));
                        }
                    }
                }
                asm volatile("fence.proxy.async.shared::cta;" ::: "memory");
                bar_arrive(10, 288);
                if (tid == 0) TLM(0, 3);
            }
#pragma unroll 1
            for (int p = wg < 2 ? 1 : 0; p < 3; p += 2) {
                float acc[48];
#pragma unroll
                for (int i = 0; i < 48; i++) acc[i] = 0.f;
                pin<48>(acc);
                if (p) bar_sync(5 + p, 512);
                gemm_pass<96, 6144, 1024, 2048, 512, 2>(acc, bar, dA0, lane, p == 0 ? strm_pos(0, 0) : 8 + 8 * p, p == 0 ? strm_code(0) : strm_code(1), p < 2 ? 6 + p : 0, p == 0, p == 2);
                if ((tid & 255) == 0) TLM(0, 4 + 2 * p);
                const uint32_t hp = sb + OFF_R + (p == 2 ? 0 : 12288) + (wg & 1) * 16384 + ((warp & 3) * 16 + g) * 64 + t * 16;
                const uint32_t bp = sb + OFF_BIAS + p * 384 - 256 + t * 8;
                uint32_t ho[24];
                mbar_wait(bar + B_BI, 0);
                if (p == 0) {
                    const float qm = norm_bound(acc, QSCALE * QSCALE);
                    if (lane == 0) gN[nb * 128 + T] = qm;
                    uint8_t* qp = gQ + (size_t)(nb * 4) * (SEQ * 32) + (size_t)row0 * 32 + t * 8;
#pragma unroll
                    for (int hh = 0; hh < 4; hh++) {
                        const float* v = acc + 8 * hh;
                        *(uint2*)(qp + hh * (SEQ * 32)) = make_uint2(pk_f16(v[0] * QSCALE, v[1] * QSCALE), pk_f16(v[4] * QSCALE, v[5] * QSCALE));
                        *(uint2*)(qp + hh * (SEQ * 32) + 256) = make_uint2(pk_f16(v[2] * QSCALE, v[3] * QSCALE), pk_f16(v[6] * QSCALE, v[7] * QSCALE));
                    }
                    bar_arrive(12, 288);
                } else {
                    gelu_pack<0, 2>(acc, bp, ho);
                    pin<16>(ho);
                    mbar_wait(bar + B_G, 0);
                    load_q(q, h, qd * 512 + flip * 256 + warp * 16 + g, t);
                }
                gelu_pack<2, 3>(acc, bp, ho);
                pin<8>(ho + 16);
                if (p == 2) bar_sync(9, 256);
                else mbar_wait(bar + B_SF + 8 * p, 0);
                if (p) {
#pragma unroll
                    for (int i = 0; i < 4; i++) sts128(hp + (i >> 1) * 32768 + (i & 1) * 512, ho + 4 * i);
                }
                sts128(hp + 65536, ho + 16);
                sts128(hp + 65536 + 512, ho + 20);
                asm volatile("fence.proxy.async.shared::cta;" ::: "memory");
                bar_arrive(p == 1 ? 14 : 11, 288);
                if ((tid & 255) == 0) TLM(0, 5 + 2 * p);
            }
        }
        uint32_t ep = 2;
        uint4* const op = gO + ((qd * 8 + wg) * NH + h) * 128 + (tid & 127);
        const uint64_t kd0 = mkdesc(SBD, 16, 256, 3);
        const uint64_t vd0 = mkdesc(SBD + 8192, OFF_ONE - 8192, 256, 3);
        {
            float o[12];
            uint32_t qn[4];
#pragma unroll 1
            for (int rh = 0; rh < 4; rh++) {
                if (rh == 1) {
                    mbar_wait(bar + B_G3, 0);
                    ep = lds32(sb + OFF_G + 256);
                    if (!(ep & 2)) break;
                    load_q(qn, h, qd * 512 + (flip ^ 1) * 256 + warp * 16 + g, t);
                }
                if (!(rh & 1)) {
#pragma unroll
                    for (int i = 0; i < 12; i++) o[i] = 0.f;
                }
                uint64_t kd = kd0 + (rh & 1) * 4096, vd = vd0 + (rh & 1) * (128 * VSTEP);
                uint32_t kvb = bar + B_KV + (rh & 1) * 32;
                float s[32];
#pragma unroll
                for (int i = 0; i < 32; i++) s[i] = i < 2 * NMUFU ? 0.f : MAGIC;
                if ((tid & 255) == 0) TLM(1, (tid >> 8) * 4 + rh);
#pragma unroll 1
                for (int c = 0; c < 4; c++) {
                    mbar_wait(kvb, 0);
                    kvb += 8;
#pragma unroll
                    for (int j = 0; j < 4; j++) {
                        uint32_t p[16];
                        if (!MERGE || j == 0) {
                            wg_fence();
                            wgmma_qk_f16_acc(s, q, kd + j * 128);
                            wg_commit();
                        }
                        wg_wait<0>();
                        pin<32>(s);
#pragma unroll
                        for (int i = 0; i < 16; i++)
                            p[i] = i < NMUFU ? pk_bf16(ex2f(s[2 * i]), ex2f(s[2 * i + 1])) : exp2_pair(s[2 * i], s[2 * i + 1], m1);
                        pin<16>(p);
                        wg_fence();
#pragma unroll
                        for (int u = 0; u < 4; u++) {
                            if (MERGE && j < 3 && u == 5 - MERGE) wgmma_qk_f16_acc(s, q, kd + (j + 1) * 128);
                            wgmma_pv(o, p + 4 * u, vd + (j * 4 + u) * VSTEP);
                        }
                        if (MERGE == 1 && j < 3) wgmma_qk_f16_acc(s, q, kd + (j + 1) * 128);
                        wg_commit();
                    }
                    kd += 1024;
                    vd += 32 * VSTEP;
                }
                wg_wait<0>();
                pin<12>(o);
                if (rh & 1) {
                    if ((tid & 127) == 0 && rh == 3) TLM(1, 8 + wg);
                    store_o(o, op + ((rh >> 1) ^ flip) * (4 * NH * 128), ep & 1);
#pragma unroll
                    for (int i = 0; i < 4; i++) q[i] = qn[i];
                }
            }
            if (tid == 0) { TLM(1, 12); TLC(0, 31); }
        }
        if (!(ep & 2)) {
            bar_sync(8, 512);
            for (int c = 0; c < 8; c++) mbar_wait(bar + B_KV + 8 * c, 0);
            {
                float kc[8][8];
                proj16<8>(kc, x, wqkv, warp * 16, 256, DM + h * 16, g, t);
#pragma unroll
                for (int i = 0; i < 8; i++) {
                    const int T = warp + i * 16;
                    const int pos = ((T >> 6) * 16 + 2 * g) * 64 + (T & 63);
                    const uint32_t a = sb + (pos >> 8) * 16384 + (pos & 255) * 32 + t * 4, sw = ((T >> 2) & 1) << 4;
                    asm volatile("st.shared.u32 [%0], %1;" ::"r"(a + sw), "r"(pk_bf16(kc[i][0], kc[i][1])) : "memory");
                    asm volatile("st.shared.u32 [%0], %1;" ::"r"(a + (sw ^ 16)), "r"(pk_bf16(kc[i][4], kc[i][5])) : "memory");
                    asm volatile("st.shared.u32 [%0], %1;" ::"r"(a + 2048 + sw), "r"(pk_bf16(kc[i][2], kc[i][3])) : "memory");
                    asm volatile("st.shared.u32 [%0], %1;" ::"r"(a + 2048 + (sw ^ 16)), "r"(pk_bf16(kc[i][6], kc[i][7])) : "memory");
                }
                asm volatile("fence.proxy.async.shared::cta;" ::: "memory");
                bar_sync(8, 512);
            }
#pragma unroll 1
            for (int r = 0; r < 2; r++) {
                const int row = qd * 512 + (r ^ flip) * 256 + warp * 16 + g;
                {
                    float qc[1][8];
                    proj16<1>(qc, x, wqkv, row - g, 0, h * 16, g, t);
#pragma unroll
                    for (int i = 0; i < 4; i++) q[i] = pk_bf16(qc[0][2 * i] * QSCALE, qc[0][2 * i + 1] * QSCALE);
                }
                float o[12];
#pragma unroll
                for (int i = 0; i < 12; i++) o[i] = 0.f;
                float m0 = -INFINITY, m1 = -INFINITY;
#pragma unroll 1
                for (int j = 0; j < 32; j++) {
                    const uint64_t kd = kd0 + (j >> 2) * 1024 + (j & 3) * 128, vd = vd0 + ((j >> 2) * 32 + (j & 3) * 4) * VSTEP;
                    float s[32];
                    uint32_t p[16];
                    wg_fence();
                    wgmma_qk_bf16_zero(s, q, kd);
                    wg_commit();
                    wg_wait<0>();
                    pin<32>(s);
                    pin<12>(o);
                    float n0 = m0, n1 = m1;
#pragma unroll
                    for (int i = 0; i < 8; i++) {
                        n0 = fmaxf(n0, fmaxf(s[4 * i], s[4 * i + 1]));
                        n1 = fmaxf(n1, fmaxf(s[4 * i + 2], s[4 * i + 3]));
                    }
                    n0 = fmaxf(n0, __shfl_xor_sync(0xffffffffu, n0, 1));
                    n1 = fmaxf(n1, __shfl_xor_sync(0xffffffffu, n1, 1));
                    n0 = fmaxf(n0, __shfl_xor_sync(0xffffffffu, n0, 2));
                    n1 = fmaxf(n1, __shfl_xor_sync(0xffffffffu, n1, 2));
                    const float c0 = ex2f(m0 - n0), c1 = ex2f(m1 - n1);
                    m0 = n0;
                    m1 = n1;
#pragma unroll
                    for (int i = 0; i < 3; i++) { o[4 * i] *= c0; o[4 * i + 1] *= c0; o[4 * i + 2] *= c1; o[4 * i + 3] *= c1; }
#pragma unroll
                    for (int i = 0; i < 8; i++) {
                        p[2 * i] = pk_bf16(ex2f(s[4 * i] - m0), ex2f(s[4 * i + 1] - m0));
                        p[2 * i + 1] = pk_bf16(ex2f(s[4 * i + 2] - m1), ex2f(s[4 * i + 3] - m1));
                    }
                    pin<16>(p);
                    pin<12>(o);
                    wg_fence();
#pragma unroll
                    for (int u = 0; u < 4; u++) wgmma_pv(o, p + 4 * u, vd + u * VSTEP);
                    wg_commit();
                }
                wg_wait<0>();
                pin<12>(o);
                store_o(o, op + (r ^ flip) * (4 * NH * 128), ep & 1);
            }
        }
        {
            const uint4* src = gO + (rb * NH + (wg * 2 + (rn ^ 1)) * 4) * 128 + (tid & 127);
            uint4 v[4];
#pragma unroll
            for (int i = 0; i < 4; i++) v[i] = load_o(src + i * 128);
            mbar_wait(bar + B_G2, 0);
            const int lr = (warp & 3) * 16;
            const uint32_t g0 = lds32(sb + OFF_G + (lr + g) * 4), g1 = lds32(sb + OFF_G + (lr + g) * 4 + 32);
            fetch_o<4>(v, src, ep);
            stage_o(v, sb + OFF_R + 65536 + wg * 8192 + (lr + (lane & 15)) * 128, g0, g1, lane);
            __syncwarp();
            if (lane == 0) mbar_arrive(bar + B_T + 32 + 8 * wg);
            if ((tid & 127) == 0) TLM(1, 20 + wg);
        }
    } else {
        if (warp == 16) {
            if (lane == 0) {
                issue_stream<NR, 32>(tm, sb, rank, nb, mb);
                mbar_wait(bar + B_SF2, 0);
#pragma unroll
                for (int s = 0; s < 4; s++) {
                    mbar_expect(bar + B_F2 + 8 * s, 24576);
                    tma5d_mc(sb + OFF_R + s * 24576 + 8192 + rank * 8192, &tm.w2, cb * 128 + rank * 64, s * 2, bar + B_F2 + 8 * s);
                }
                cnt_wait(gCntH + mb * 32, epoch() * 8);
                asm volatile("fence.proxy.async.global;" ::: "memory");
                TLM(1, 13);
#pragma unroll
                for (int s = 0; s < 4; s++) tma2d(sb + OFF_R + s * 24576, &tm.h, s * 64, rb * 64, bar + B_F2 + 8 * s);
            }
        } else if (warp == 17) {
            {
                uint32_t bv[4], b2v[2];
#pragma unroll
                for (int i = 0; i < 4; i++) bv[i] = lane + 32 * i < 112 ? *(const uint32_t*)(b1 + nb * 224 + (lane + 32 * i) * 2) : 0;
#pragma unroll
                for (int i = 0; i < 2; i++) b2v[i] = *(const uint32_t*)(b2 + cb * 128 + (lane + 32 * i) * 2);
#pragma unroll
                for (int i = 0; i < 4; i++) {
                    sts32(sb + OFF_ONE + (lane + 32 * i) * 4, 0x3f803f80u);
                    if (lane + 32 * i < 112) sts64(sb + OFF_BIAS + (lane + 32 * i) * 8, bv[i] << 16, bv[i] & 0xffff0000u);
                }
#pragma unroll
                for (int i = 0; i < 2; i++) sts32(sb + OFF_BIAS + 896 + (lane + 32 * i) * 4, b2v[i]);
                asm volatile("fence.proxy.async.shared::cta;" ::: "memory");
                __syncwarp();
                if (lane == 0) mbar_arrive(bar + B_BI);
            }
            mbar_wait(bar + B_X + 8 * PFX, 0);
            if (lane == 0) {
                l2_prefetch((const uint8_t*)wqkv + 128 * 3072 + (size_t)blockIdx.x * 9216, 9216);
                l2_prefetch((const uint8_t*)w1 + (size_t)blockIdx.x * 14336, 14336);
            }
            mbar_wait(bar + B_X + 8 * 7, 0);
            if (lane == 0) {
                l2_prefetch((const uint8_t*)w2 + (size_t)blockIdx.x * 14336, 14336);
                l2_prefetch((const uint8_t*)wo + (size_t)blockIdx.x * 4096, 4096);
                map_prefetch(&tm.h); map_prefetch(&tm.w2); map_prefetch(&tm.wo); map_prefetch(&tm.hs); map_prefetch(&tm.kvs);
                TLM(0, 11);
            }
            bar_sync(10, 288);
            if (lane == 0) {
#pragma unroll 1
                for (int b = 5; b >= 0; b--) {
                    tma5d_st(&tm.kvs, sb + OFF_R + 12288 + b * 16384, (mb >> 3) * 8, (mb & 7) * 2, nb * 8 + (b < 4 ? 2 * b : 2 * b - 7));
                    asm volatile("cp.async.bulk.commit_group;\ncp.async.bulk.wait_group.read %0;" ::"n"(PACE) : "memory");
                    if (b == 4 - PACE) mbar_arrive(bar + B_SF);
                }
                asm volatile("cp.async.bulk.wait_group.read 0;" ::: "memory");
                mbar_arrive(bar + B_SF + 8);
            }
            __syncwarp();
            bar_sync(12, 288);
            if (lane == 0) {
                asm volatile("cp.async.bulk.wait_group 0;\nfence.proxy.async.global;" ::: "memory");
                cnt_add(gCntQ + nb * 32);
                TLM(0, 13);
            }
        } else {
            {
                const int r0 = mb * 128 + nb * 16 + (warp - 18) * 8;
                uint4 xv[16];
#pragma unroll
                for (int i = 0; i < 16; i++) xv[i] = *(const uint4*)(x + (size_t)(r0 + (i >> 1)) * DM + (i & 1) * 256 + lane * 8);
                const uint4 ga = *(const uint4*)(gate + lane * 8), gb = *(const uint4*)(gate + 256 + lane * 8);
                float z[8];
#pragma unroll
                for (int r = 0; r < 8; r++) z[r] = dot8(xv[2 * r], ga) + dot8(xv[2 * r + 1], gb);
#pragma unroll
                for (int w = 4; w >= 1; w >>= 1)
#pragma unroll
                    for (int r = 0; r < w; r++) {
                        const bool up = lane & w;
                        z[r] = (up ? z[r + w] : z[r]) + __shfl_xor_sync(0xffffffffu, up ? z[r] : z[r + w], w);
                    }
                z[0] += __shfl_xor_sync(0xffffffffu, z[0], 8);
                z[0] += __shfl_xor_sync(0xffffffffu, z[0], 16);
                if (lane < 8) gG[r0 + lane] = 1.f / (1.f + __expf(-z[0]));
                if (tid == 576) TLM(0, 12);
            }
            if (warp == 19) {
#pragma unroll 1
                for (int e = 0; e < 3; e++) {
                    bar_sync(e == 1 ? 14 : 11, 288);
                    if (lane == 0) {
#pragma unroll 1
                        for (int b = e == 0 ? 4 : 0; b < 6; b++) {
                            tma3d_st(&tm.hs, sb + OFF_R + (e == 2 ? 0 : 12288) + b * 16384, 0, mb * 128 + (b & 1) * 64, nb * 7 + e * 3 - 2 + (b >> 1));
                            asm volatile("cp.async.bulk.commit_group;\ncp.async.bulk.wait_group.read %0;" ::"n"(PACE) : "memory");
                        }
                        asm volatile("cp.async.bulk.wait_group.read 0;" ::: "memory");
                        if (e == 0) mbar_arrive(bar + B_SF + 8);
                        if (e == 2) { mbar_arrive_cluster(bar + B_SF2, 0); mbar_arrive_cluster(bar + B_SF2, 1); }
                    }
                    __syncwarp();
                }
                bar_sync(13, 64);
                if (lane == 0) {
                    asm volatile("cp.async.bulk.wait_group 0;\nfence.proxy.async.global;" ::: "memory");
                    cnt_add(gCntH + mb * 32);
                    TLM(0, 15);
                }
            } else {
                bar_arrive(13, 64);
                const int h = cl >> 1, qd = (cl & 1) * 2 + rank;
                const uint32_t ep = epoch();
                if (lane == 0) {
                    cnt_wait(gCntQ + (h >> 2) * 32, ep * 16);
                    mbar_arrive(bar + B_G);
                    TLM(0, 14);
                    asm volatile("fence.proxy.async.global;" ::: "memory");
#pragma unroll
                    for (int c = 0; c < 2; c++) {
                        mbar_wait(bar + B_XD + 8 * c, 0);
                        bulk_mc(sb + c * 16384 + rank * 8192, gKV + (size_t)h * (SEQ * 64) + rank * 65536 + c * 8192, 8192, bar + B_KV + 8 * c);
                    }
                }
                __syncwarp();
            const int hb = h >> 2;
            const uint4 kq = __ldcg((const uint4*)(gN + 1024 + hb * 128 + lane * 4));
            const uint4 vq = __ldcg((const uint4*)(gN + 2048 + hb * 128 + lane * 4));
            const float qq = ldcg_f(gN + hb * 128 + qd * 32 + lane);
            const float kf = __uint_as_float(__reduce_max_sync(0xffffffffu, max(max(kq.x, kq.y), max(kq.z, kq.w))));
            const float vf = __uint_as_float(__reduce_max_sync(0xffffffffu, max(max(vq.x, vq.y), max(vq.z, vq.w))));
            const float qf = __uint_as_float(__reduce_max_sync(0xffffffffu, __float_as_uint(qq)));
            if (lane == 0) {
                sts32(sb + OFF_G + 256, (ep & 1) | ((kf <= 1.0e6f) && (qf <= 1.0e6f) && (kf * qf <= 3400.f) && (vf <= 1.0e12f) ? 2 : 0));
                mbar_arrive(bar + B_G3);
                TLM(0, 16);
#pragma unroll
                for (int c = 2; c < 8; c++) {
                    mbar_wait(bar + B_XD + 8 * c, 0);
                    bulk_mc(sb + c * 16384 + rank * 8192, gKV + (size_t)h * (SEQ * 64) + rank * 65536 + c * 8192, 8192, bar + B_KV + 8 * c);
                }
                TLM(0, 10);
            }
            }
        }
        __syncwarp();
        float acc[64];
#pragma unroll
        for (int i = 0; i < 64; i++) acc[i] = 0.f;
#pragma unroll 1
        for (int io = 0; io < 7; io++) {
#pragma unroll
            for (int s = 0; s < 4; s++) {
                const int it = io * 4 + s;
                mbar_wait(bar + B_F2 + 8 * s, io & 1);
                if (tid == 512 && s == 0 && (io == 0 || io == 4)) TLM(1, 14 + io / 4);
                const uint64_t dA = mkdesc(SBD + OFF_R + s * 24576, 16, 1024, 1);
                const uint64_t dB = mkdesc(SBD + OFF_R + s * 24576 + 8192, 8192, 1024, 1);
                wg_fence();
#pragma unroll
                for (int kk = 0; kk < EXP_FKK; kk++) {
                    wgmma_ss_n128(acc, dA + kk * 2, dB + kk * 128);
                }
                wg_commit();
                if (warp < 18 && it >= 2 && it < 26) {
                    const int s2 = (s + 2) & 3;
                    mbar_wait(bar + B_E2 + 8 * s2, (io - (s < 2)) & 1);
                    if (elect()) {
                        if (warp == 16) {
                            mbar_expect(bar + B_F2 + 8 * s2, 24576);
                            tma5d_mc(sb + OFF_R + s2 * 24576 + 8192 + rank * 8192, &tm.w2, cb * 128 + rank * 64, it * 2 + 4, bar + B_F2 + 8 * s2);
                        } else {
                            asm volatile("fence.proxy.async.global;" ::: "memory");
                            tma2d(sb + OFF_R + s2 * 24576, &tm.h, it * 64 + 128, rb * 64, bar + B_F2 + 8 * s2);
                        }
                    }
                    __syncwarp();
                }
                wg_wait<1>();
                if (it >= 1 && lane < 2) mbar_arrive_cluster(bar + B_E2 + 8 * ((s + 3) & 3), lane);
            }
        }
        wg_wait<0>();
        if (lane < 2) mbar_arrive_cluster(bar + B_E2 + 8 * 3, lane);
        pin<64>(acc);
        if (tid == 576) gEpoch[blockIdx.x] = epoch();
        if (warp == 16) {
            if (lane == 0) TLM(1, 16);
            for (int s = 0; s < 4; s++) mbar_wait(bar + B_E2 + 8 * s, 0);
            if (elect()) {
#pragma unroll
                for (int i = 0; i < 4; i++)
                    tma5d_mc(sb + OFF_R + i * 16384 + rank * 8192, &tm.wo, cb * 128 + rank * 64, (i * 2 + rn) * 4, bar + B_T + 8 * i);
            }
            __syncwarp();
        }
        uint32_t pa;
        {
            const int lr = (warp - 16) * 16 + g;
            pa = pk_bf16(ldcg_f(gG + rb * 64 + lr), ldcg_f(gG + rb * 64 + lr + 8));
            if (t == 0) {
                sts32(sb + OFF_G + lr * 4, __byte_perm(pa, pa, 0x1010));
                sts32(sb + OFF_G + lr * 4 + 32, __byte_perm(pa, pa, 0x3232));
            }
            const float ga = bf_lo(pa), gb = bf_hi(pa);
            const float g0 = 1.f - ga, g1 = 1.f - gb;
#pragma unroll
            for (int j = 0; j < 16; j++) {
                const uint32_t bv = lds32(sb + OFF_BIAS + 896 + j * 16 + t * 4);
                acc[4 * j] = fmaf(acc[4 * j], 0.5f, bf_lo(bv)) * g0;
                acc[4 * j + 1] = fmaf(acc[4 * j + 1], 0.5f, bf_hi(bv)) * g0;
                acc[4 * j + 2] = fmaf(acc[4 * j + 2], 0.5f, bf_lo(bv)) * g1;
                acc[4 * j + 3] = fmaf(acc[4 * j + 3], 0.5f, bf_hi(bv)) * g1;
            }
            pin<64>(acc);
        }
        {
            mbar_wait(bar + B_G3, 0);
            const uint32_t ep = lds32(sb + OFF_G + 256);
            const uint4* src = gO + (rb * NH + rn * 4) * 128 + (tid & 127);
            bar_sync(15, 128);
#pragma unroll 1
            for (int e = 0; e < 4; e++) {
                uint4 v[4];
#pragma unroll
                for (int i = 0; i < 4; i++) v[i] = load_o(src + i * 128);
                fetch_o<4>(v, src, ep);
                stage_o(v, sb + OFF_R + 65536 + e * 8192 + ((warp - 16) * 16 + (lane & 15)) * 128, __byte_perm(pa, pa, 0x1010), __byte_perm(pa, pa, 0x3232), lane);
                src += 8 * 128;
            }
            bar_sync(15, 128);
        }
#pragma unroll 1
        for (int late = 0; late < 2; late++) {
#pragma unroll
            for (int i = 0; i < 4; i++) {
                mbar_wait(bar + B_T + late * 32 + 8 * i, 0);
                const uint64_t dA = mkdesc(SBD + OFF_R + 65536 + i * 8192, 16, 1024, 1);
                const uint64_t dB = mkdesc(SBD + OFF_R + i * 16384, 8192, 1024, 1);
                wg_fence();
#pragma unroll
                for (int kk = 0; kk < 4; kk++) wgmma_ss_n128(acc, dA + kk * 2, dB + kk * 128);
                wg_commit();
            }
            if (!late) {
                wg_wait<0>();
                if (lane == 0) mbar_arrive(bar + B_G2);
                if (warp == 16) {
                    mbar_wait(bar + B_G2, 0);
                    if (elect()) {
#pragma unroll
                        for (int i = 0; i < 8; i++)
                            tma5d(sb + OFF_R + i * 8192, &tm.wo, cb * 128 + (i & 1) * 64, ((i >> 1) * 2 + (rn ^ 1)) * 4, bar + B_T + 32 + 8 * (i >> 1));
                    }
                    __syncwarp();
                }
                if (tid == 512) TLM(1, 17);
            }
        }
        wg_wait<0>();
        pin<64>(acc);
        if (tid == 512) TLM(1, 18);
        {
            const uint32_t st = sb + 98304 + (warp - 16) * 4352;
            const uint32_t wa = st + (lane & 15) * 272 + (lane >> 4) * 16;
#pragma unroll
            for (int j = 0; j < 8; j++)
                asm volatile("stmatrix.sync.aligned.m8n8.x4.shared.b16 [%0], {%1, %2, %3, %4};" ::"r"(wa + j * 32),
                             "r"(pk_bf16(acc[8 * j], acc[8 * j + 1])), "r"(pk_bf16(acc[8 * j + 2], acc[8 * j + 3])),
                             "r"(pk_bf16(acc[8 * j + 4], acc[8 * j + 5])), "r"(pk_bf16(acc[8 * j + 6], acc[8 * j + 7])) : "memory");
            __syncwarp();
            __nv_bfloat16* op = out + (size_t)(rb * 64 + (warp - 16) * 16 + (lane >> 4)) * DM + cb * 128 + (lane & 15) * 8;
#pragma unroll
            for (int j = 0; j < 8; j++) {
                uint4 v;
                asm volatile("ld.shared.v4.u32 {%0, %1, %2, %3}, [%4];" : "=r"(v.x), "=r"(v.y), "=r"(v.z), "=r"(v.w)
                             : "r"(st + (2 * j + (lane >> 4)) * 272 + (lane & 15) * 16));
                *(uint4*)(op + (size_t)j * 2 * DM) = v;
            }
        }
        if (tid == 512) TLM(1, 19);
        TL_DUMP();
    }
}

typedef CUresult (*EncodeFn)(CUtensorMap*, CUtensorMapDataType, cuuint32_t, void*, const cuuint64_t*, const cuuint64_t*, const cuuint32_t*,
                             const cuuint32_t*, CUtensorMapInterleave, CUtensorMapSwizzle, CUtensorMapL2promotion, CUtensorMapFloatOOBfill);

static void make_map(EncodeFn enc, CUtensorMap* m, const void* p, int rank, const cuuint64_t* dims, const cuuint64_t* strides,
                     const cuuint32_t* box, CUtensorMapSwizzle swz) {
    const cuuint32_t es[5] = {1, 1, 1, 1, 1};
    enc(m, CU_TENSOR_MAP_DATA_TYPE_BFLOAT16, rank, (void*)p, dims, strides, box, es, CU_TENSOR_MAP_INTERLEAVE_NONE, swz,
        CU_TENSOR_MAP_L2_PROMOTION_L2_128B, CU_TENSOR_MAP_FLOAT_OOB_FILL_NONE);
}

extern "C" void kernel_launch(void* const* d_in, const int* in_sizes, int n_in, void* d_out, int out_size) {
    const __nv_bfloat16* x = (const __nv_bfloat16*)d_in[0];
    const __nv_bfloat16* wqkv = (const __nv_bfloat16*)d_in[1];
    const __nv_bfloat16* wo = (const __nv_bfloat16*)d_in[2];
    const __nv_bfloat16* w1 = (const __nv_bfloat16*)d_in[4];
    const __nv_bfloat16* b1 = (const __nv_bfloat16*)d_in[5];
    const __nv_bfloat16* w2 = (const __nv_bfloat16*)d_in[6];
    const __nv_bfloat16* b2 = (const __nv_bfloat16*)d_in[7];
    const __nv_bfloat16* gate = (const __nv_bfloat16*)d_in[8];

    void* fp = nullptr;
    cudaDriverEntryPointQueryResult qr;
    cudaGetDriverEntryPoint("cuTensorMapEncodeTiled", &fp, cudaEnableDefault, &qr);
    EncodeFn enc = (EncodeFn)fp;
    void *pH, *pKV;
    cudaGetSymbolAddress(&pH, gH);
    cudaGetSymbolAddress(&pKV, gKV);

    Maps tm;
    const CUtensorMapSwizzle S128 = CU_TENSOR_MAP_SWIZZLE_128B, S64 = CU_TENSOR_MAP_SWIZZLE_64B;
    { cuuint64_t d[2] = {DM, SEQ}, s[1] = {DM * 2}; cuuint32_t b[2] = {64, 128}; make_map(enc, &tm.x, x, 2, d, s, b, S128); }
    { cuuint64_t d[3] = {DM, DM, 3}, s[2] = {3 * DM * 2, DM * 2}; cuuint32_t b[3] = {64, 32, 2}; make_map(enc, &tm.kv, wqkv, 3, d, s, b, S128); }
    { cuuint64_t d[3] = {32, DM, 3 * DM / 32}, s[2] = {3 * DM * 2, 64}; cuuint32_t b[3] = {32, 32, 2}; make_map(enc, &tm.q, wqkv, 3, d, s, b, S64); }
    { cuuint64_t d[3] = {32, DM, FF / 32}, s[2] = {FF * 2, 64}; cuuint32_t b[3] = {32, 32, 1}; make_map(enc, &tm.f1, w1, 3, d, s, b, S64); }
    { cuuint64_t d[3] = {32, DM, FF / 32}, s[2] = {FF * 2, 64}; cuuint32_t b[3] = {32, 32, 3}; make_map(enc, &tm.f3, w1, 3, d, s, b, S64); }
    { cuuint64_t d[2] = {FF, SEQ}, s[1] = {FF * 2}; cuuint32_t b[2] = {64, 64}; make_map(enc, &tm.h, pH, 2, d, s, b, S128); }
    { cuuint64_t d[5] = {DM, 2, 4, 4, FF / 32}, s[4] = {1024, 8 * 1024, 2 * 1024, 32 * 1024}; cuuint32_t b[5] = {64, 2, 4, 4, 2};
      make_map(enc, &tm.w2, w2, 5, d, s, b, S128); }
    { cuuint64_t d[5] = {DM, 2, 2, 4, NH}, s[4] = {1024, 8 * 1024, 2 * 1024, 16 * 1024}; cuuint32_t b[5] = {64, 2, 2, 4, 4};
      make_map(enc, &tm.wo, wo, 5, d, s, b, S128); }

    { cuuint64_t d[3] = {32, SEQ, FF / 32}, s[2] = {FF * 2, 64}; cuuint32_t b[3] = {32, 64, 1}; make_map(enc, &tm.hs, pH, 3, d, s, b, CU_TENSOR_MAP_SWIZZLE_NONE); }
    { cuuint64_t d[5] = {64, 16, 16, 2, 2 * NH}, s[4] = {4096, 128, 2048, 65536}; cuuint32_t b[5] = {64, 8, 2, 2, 1};
      make_map(enc, &tm.kvs, pKV, 5, d, s, b, S128); }
    cudaFuncSetAttribute(fused_kernel, cudaFuncAttributeMaxDynamicSharedMemorySize, TL_SMEM);
    fused_kernel<<<128, 640, TL_SMEM, cudaStreamPerThread>>>(tm, x, wqkv, wo, w1, b1, w2, b2, gate, (__nv_bfloat16*)d_out, 0xffffffffu);
}
```

```cpp
#include <cuda_runtime.h>
#include <cuda_bf16.h>
#include <cuda_fp16.h>
#include <cuda.h>
#include <stdint.h>

#define SEQ 2048
#define DM 512
#define FF 1792
#define NH 32

__device__ __align__(1024) uint8_t gQ[NH * SEQ * 32];
__device__ __align__(1024) uint8_t gKV[NH * SEQ * 64];
__device__ __align__(1024) __nv_bfloat16 gH[SEQ * FF];
__device__ __align__(1024) uint4 gO[32 * NH * 128];
__device__ float gG[SEQ];
__device__ float gN[3 * 8 * 128];
__device__ unsigned int gCntQ[8 * 32];
__device__ unsigned int gCntH[32 * 32];
__device__ unsigned int gEpoch[128];

__device__ __forceinline__ uint32_t smem_u32(const void* p) { return (uint32_t)__cvta_generic_to_shared(p); }
__device__ __forceinline__ void mbar_init(uint32_t a, uint32_t c) { asm volatile("mbarrier.init.shared::cta.b64 [%0], %1;" ::"r"(a), "r"(c)); }
__device__ __forceinline__ void mbar_expect(uint32_t a, uint32_t b) { asm volatile("mbarrier.arrive.expect_tx.shared::cta.b64 _, [%0], %1;" ::"r"(a), "r"(b) : "memory"); }
__device__ __forceinline__ void mbar_arrive(uint32_t a) { asm volatile("mbarrier.arrive.shared::cta.b64 _, [%0];" ::"r"(a) : "memory"); }
__device__ __forceinline__ void mbar_wait(uint32_t a, uint32_t ph) {
    asm volatile("{\n.reg .pred p;\n.reg .u32 n;\nmov.u32 n, 0;\nW_%=:\nmbarrier.try_wait.parity.shared::cta.b64 p, [%0], %1;\n@p bra D_%=;\n"
                 "add.u32 n, n, 1;\nsetp.lt.u32 p, n, 0x400000;\n@p bra W_%=;\ntrap;\nD_%=:\n}" ::"r"(a), "r"(ph) : "memory");
}
__device__ __forceinline__ void mbar_arrive_cluster(uint32_t a, uint32_t cta) {
    asm volatile("{\n.reg .b32 r;\nmapa.shared::cluster.u32 r, %0, %1;\nmbarrier.arrive.shared::cluster.b64 _, [r];\n}" ::"r"(a), "r"(cta) : "memory");
}
__device__ __forceinline__ void bar_sync(int id, int n) { asm volatile("bar.sync %0, %1;" ::"r"(id), "r"(n) : "memory"); }
__device__ __forceinline__ void bar_arrive(int id, int n) { asm volatile("bar.arrive %0, %1;" ::"r"(id), "r"(n) : "memory"); }
__device__ __forceinline__ uint32_t cluster_rank() { uint32_t r; asm("mov.u32 %0, %%cluster_ctarank;" : "=r"(r)); return r; }
__device__ __forceinline__ void cnt_add(unsigned int* c) { asm volatile("red.release.gpu.global.add.u32 [%0], 1;" ::"l"(c) : "memory"); }
__device__ __forceinline__ void cnt_wait(const unsigned int* c, uint32_t target) {
    uint32_t v;
    int spins = 0;
    while (true) {
        asm volatile("ld.acquire.gpu.global.u32 %0, [%1];" : "=r"(v) : "l"(c) : "memory");
        if ((int)(v - target) >= 0) break;
        if (++spins > (1 << 22)) __trap();
        __nanosleep(40);
    }
}
__device__ __forceinline__ void tma2d(uint32_t dst, const CUtensorMap* m, int c0, int c1, uint32_t bar) {
    asm volatile("cp.async.bulk.tensor.2d.shared::cluster.global.mbarrier::complete_tx::bytes [%0], [%1, {%3, %4}], [%2];"
                 ::"r"(dst), "l"(m), "r"(bar), "r"(c0), "r"(c1) : "memory");
}
__device__ __forceinline__ void tma2d_mc(uint32_t dst, const CUtensorMap* m, int c0, int c1, uint32_t bar) {
    asm volatile("cp.async.bulk.tensor.2d.shared::cluster.global.mbarrier::complete_tx::bytes.multicast::cluster [%0], [%1, {%3, %4}], [%2], %5;"
                 ::"r"(dst), "l"(m), "r"(bar), "r"(c0), "r"(c1), "h"((uint16_t)3) : "memory");
}
__device__ __forceinline__ void tma3d_mc(uint32_t dst, const CUtensorMap* m, int c0, int c1, int c2, uint32_t bar) {
    asm volatile("cp.async.bulk.tensor.3d.shared::cluster.global.mbarrier::complete_tx::bytes.multicast::cluster [%0], [%1, {%3, %4, %5}], [%2], %6;"
                 ::"r"(dst), "l"(m), "r"(bar), "r"(c0), "r"(c1), "r"(c2), "h"((uint16_t)3) : "memory");
}
__device__ __forceinline__ void tma5d_mc(uint32_t dst, const CUtensorMap* m, int c0, int c4, uint32_t bar) {
    asm volatile("cp.async.bulk.tensor.5d.shared::cluster.global.mbarrier::complete_tx::bytes.multicast::cluster [%0], [%1, {%3, %5, %5, %5, %4}], [%2], %6;"
                 ::"r"(dst), "l"(m), "r"(bar), "r"(c0), "r"(c4), "r"(0), "h"((uint16_t)3) : "memory");
}
__device__ __forceinline__ void tma5d(uint32_t dst, const CUtensorMap* m, int c0, int c4, uint32_t bar) {
    asm volatile("cp.async.bulk.tensor.5d.shared::cluster.global.mbarrier::complete_tx::bytes [%0], [%1, {%3, %5, %5, %5, %4}], [%2];"
                 ::"r"(dst), "l"(m), "r"(bar), "r"(c0), "r"(c4), "r"(0) : "memory");
}
__device__ __forceinline__ void bulk_mc(uint32_t dst, const void* src, uint32_t bytes, uint32_t bar) {
    asm volatile("cp.async.bulk.shared::cluster.global.mbarrier::complete_tx::bytes.multicast::cluster [%0], [%1], %2, [%3], %4;"
                 ::"r"(dst), "l"(src), "r"(bytes), "r"(bar), "h"((uint16_t)3) : "memory");
}
__device__ __forceinline__ void tma3d_st(const CUtensorMap* m, uint32_t src, int c0, int c1, int c2) {
    asm volatile("cp.async.bulk.tensor.3d.global.shared::cta.bulk_group [%0, {%2, %3, %4}], [%1];" ::"l"(m), "r"(src), "r"(c0), "r"(c1), "r"(c2) : "memory");
}
__device__ __forceinline__ void tma5d_st(const CUtensorMap* m, uint32_t src, int c1, int c2, int c4) {
    asm volatile("cp.async.bulk.tensor.5d.global.shared::cta.bulk_group [%0, {%5, %2, %3, %5, %4}], [%1];"
                 ::"l"(m), "r"(src), "r"(c1), "r"(c2), "r"(c4), "r"(0) : "memory");
}
__device__ __forceinline__ void bulk_st(void* dst, uint32_t src, uint32_t bytes) {
    asm volatile("cp.async.bulk.global.shared::cta.bulk_group [%0], [%1], %2;" ::"l"(dst), "r"(src), "r"(bytes) : "memory");
}
__device__ __forceinline__ void sts64(uint32_t a, uint32_t x, uint32_t y) { asm volatile("st.shared.v2.u32 [%0], {%1, %2};" ::"r"(a), "r"(x), "r"(y) : "memory"); }
__device__ __forceinline__ void sts128(uint32_t a, const uint32_t* v) {
    asm volatile("st.shared.v4.u32 [%0], {%1, %2, %3, %4};" ::"r"(a), "r"(v[0]), "r"(v[1]), "r"(v[2]), "r"(v[3]) : "memory");
}
__device__ __forceinline__ void l2_prefetch(const void* src, uint32_t bytes) {
    asm volatile("cp.async.bulk.prefetch.L2.global [%0], %1;" ::"l"(src), "r"(bytes) : "memory");
}
__device__ __forceinline__ void map_prefetch(const CUtensorMap* m) { asm volatile("prefetch.tensormap [%0];" ::"l"(m) : "memory"); }
__device__ __forceinline__ void wg_fence() { asm volatile("wgmma.fence.sync.aligned;" ::: "memory"); }
__device__ __forceinline__ void wg_commit() { asm volatile("wgmma.commit_group.sync.aligned;" ::: "memory"); }
template <int N> __device__ __forceinline__ void wg_wait() { asm volatile("wgmma.wait_group.sync.aligned %0;" ::"n"(N) : "memory"); }
template <int N> __device__ __forceinline__ void pin(float* s) {
#pragma unroll
    for (int i = 0; i < N; i++) asm volatile("" : "+f"(s[i])::"memory");
}
template <int N> __device__ __forceinline__ void pin(uint32_t* s) {
#pragma unroll
    for (int i = 0; i < N; i++) asm volatile("" : "+r"(s[i])::"memory");
}
__device__ __forceinline__ uint64_t mkdesc(uint32_t addr, uint32_t lbo, uint32_t sbo, uint32_t swz) {
    return (uint64_t)((addr & 0x3FFFF) >> 4) | ((uint64_t)(lbo >> 4) << 16) | ((uint64_t)(sbo >> 4) << 32) | ((uint64_t)swz << 62);
}
__device__ __forceinline__ float ex2f(float x) { float y; asm("ex2.approx.ftz.f32 %0, %1;" : "=f"(y) : "f"(x)); return y; }
__device__ __forceinline__ float tanhf_(float x) { float y; asm("tanh.approx.f32 %0, %1;" : "=f"(y) : "f"(x)); return y; }
__device__ __forceinline__ uint32_t pk_bf16(float lo, float hi) { uint32_t r; asm("cvt.rn.bf16x2.f32 %0, %1, %2;" : "=r"(r) : "f"(hi), "f"(lo)); return r; }
__device__ __forceinline__ uint32_t pk_f16(float lo, float hi) { uint32_t r; asm("cvt.rn.f16x2.f32 %0, %1, %2;" : "=r"(r) : "f"(hi), "f"(lo)); return r; }
__device__ __forceinline__ float bf_lo(uint32_t v) { return __uint_as_float(v << 16); }
__device__ __forceinline__ float bf_hi(uint32_t v) { return __uint_as_float(v & 0xffff0000u); }
__device__ __forceinline__ float dot8(const uint4& a, const uint4& b) {
    return fmaf(bf_lo(a.x), bf_lo(b.x), fmaf(bf_hi(a.x), bf_hi(b.x), fmaf(bf_lo(a.y), bf_lo(b.y), bf_hi(a.y) * bf_hi(b.y)))) +
           fmaf(bf_lo(a.z), bf_lo(b.z), fmaf(bf_hi(a.z), bf_hi(b.z), fmaf(bf_lo(a.w), bf_lo(b.w), bf_hi(a.w) * bf_hi(b.w))));
}
__device__ __forceinline__ uint32_t epoch() {
    uint32_t v;
    asm volatile("ld.global.u32 %0, [%1];" : "=r"(v) : "l"(gEpoch + blockIdx.x));
    return v + 1;
}
__device__ __forceinline__ float ldcg_f(const float* p) { return __ldcg(p); }

extern __shared__ __align__(1024) uint8_t smem_raw[];
#define TLM(k, slot) do {} while (0)
#define TLC(k, slot) do {} while (0)
#define TL_INIT() do {} while (0)
#define TL_DUMP() do {} while (0)
#define TL_SMEM SMEM_BYTES

__device__ __forceinline__ void wgmma_ss_n128(float* d, uint64_t da, uint64_t db) {
    asm volatile("wgmma.mma_async.sync.aligned.m64n128k16.f32.bf16.bf16 {"
        "%0, %1, %2, %3, %4, %5, %6, %7, %8, %9, %10, %11, %12, %13, %14, %15,"
        "%16, %17, %18, %19, %20, %21, %22, %23, %24, %25, %26, %27, %28, %29, %30, %31,"
        "%32, %33, %34, %35, %36, %37, %38, %39, %40, %41, %42, %43, %44, %45, %46, %47,"
        "%48, %49, %50, %51, %52, %53, %54, %55, %56, %57, %58, %59, %60, %61, %62, %63}, %64, %65, 1, 1, 1, 0, 1;\n"
        :
        "+f"(d[0]), "+f"(d[1]), "+f"(d[2]), "+f"(d[3]), "+f"(d[4]), "+f"(d[5]), "+f"(d[6]), "+f"(d[7]),
        "+f"(d[8]), "+f"(d[9]), "+f"(d[10]), "+f"(d[11]), "+f"(d[12]), "+f"(d[13]), "+f"(d[14]), "+f"(d[15]),
        "+f"(d[16]), "+f"(d[17]), "+f"(d[18]), "+f"(d[19]), "+f"(d[20]), "+f"(d[21]), "+f"(d[22]), "+f"(d[23]),
        "+f"(d[24]), "+f"(d[25]), "+f"(d[26]), "+f"(d[27]), "+f"(d[28]), "+f"(d[29]), "+f"(d[30]), "+f"(d[31]),
        "+f"(d[32]), "+f"(d[33]), "+f"(d[34]), "+f"(d[35]), "+f"(d[36]), "+f"(d[37]), "+f"(d[38]), "+f"(d[39]),
        "+f"(d[40]), "+f"(d[41]), "+f"(d[42]), "+f"(d[43]), "+f"(d[44]), "+f"(d[45]), "+f"(d[46]), "+f"(d[47]),
        "+f"(d[48]), "+f"(d[49]), "+f"(d[50]), "+f"(d[51]), "+f"(d[52]), "+f"(d[53]), "+f"(d[54]), "+f"(d[55]),
        "+f"(d[56]), "+f"(d[57]), "+f"(d[58]), "+f"(d[59]), "+f"(d[60]), "+f"(d[61]), "+f"(d[62]), "+f"(d[63])
        : "l"(da), "l"(db));
}
__device__ __forceinline__ void wgmma_ss_n96(float* d, uint64_t da, uint64_t db) {
    asm volatile("wgmma.mma_async.sync.aligned.m64n96k16.f32.bf16.bf16 {"
        "%0, %1, %2, %3, %4, %5, %6, %7, %8, %9, %10, %11, %12, %13, %14, %15,"
        "%16, %17, %18, %19, %20, %21, %22, %23, %24, %25, %26, %27, %28, %29, %30, %31,"
        "%32, %33, %34, %35, %36, %37, %38, %39, %40, %41, %42, %43, %44, %45, %46, %47}, %48, %49, 1, 1, 1, 0, 1;\n"
        :
        "+f"(d[0]), "+f"(d[1]), "+f"(d[2]), "+f"(d[3]), "+f"(d[4]), "+f"(d[5]), "+f"(d[6]), "+f"(d[7]),
        "+f"(d[8]), "+f"(d[9]), "+f"(d[10]), "+f"(d[11]), "+f"(d[12]), "+f"(d[13]), "+f"(d[14]), "+f"(d[15]),
        "+f"(d[16]), "+f"(d[17]), "+f"(d[18]), "+f"(d[19]), "+f"(d[20]), "+f"(d[21]), "+f"(d[22]), "+f"(d[23]),
        "+f"(d[24]), "+f"(d[25]), "+f"(d[26]), "+f"(d[27]), "+f"(d[28]), "+f"(d[29]), "+f"(d[30]), "+f"(d[31]),
        "+f"(d[32]), "+f"(d[33]), "+f"(d[34]), "+f"(d[35]), "+f"(d[36]), "+f"(d[37]), "+f"(d[38]), "+f"(d[39]),
        "+f"(d[40]), "+f"(d[41]), "+f"(d[42]), "+f"(d[43]), "+f"(d[44]), "+f"(d[45]), "+f"(d[46]), "+f"(d[47])
        : "l"(da), "l"(db));
}
__device__ __forceinline__ void wgmma_ss_n64(float* d, uint64_t da, uint64_t db) {
    asm volatile("wgmma.mma_async.sync.aligned.m64n64k16.f32.bf16.bf16 {"
        "%0, %1, %2, %3, %4, %5, %6, %7, %8, %9, %10, %11, %12, %13, %14, %15,"
        "%16, %17, %18, %19, %20, %21, %22, %23, %24, %25, %26, %27, %28, %29, %30, %31}, %32, %33, 1, 1, 1, 0, 1;\n"
        :
        "+f"(d[0]), "+f"(d[1]), "+f"(d[2]), "+f"(d[3]), "+f"(d[4]), "+f"(d[5]), "+f"(d[6]), "+f"(d[7]),
        "+f"(d[8]), "+f"(d[9]), "+f"(d[10]), "+f"(d[11]), "+f"(d[12]), "+f"(d[13]), "+f"(d[14]), "+f"(d[15]),
        "+f"(d[16]), "+f"(d[17]), "+f"(d[18]), "+f"(d[19]), "+f"(d[20]), "+f"(d[21]), "+f"(d[22]), "+f"(d[23]),
        "+f"(d[24]), "+f"(d[25]), "+f"(d[26]), "+f"(d[27]), "+f"(d[28]), "+f"(d[29]), "+f"(d[30]), "+f"(d[31])
        : "l"(da), "l"(db));
}
__device__ __forceinline__ void wgmma_rs_n128(float* d, const uint32_t* a, uint64_t db) {
    asm volatile("wgmma.mma_async.sync.aligned.m64n128k16.f32.bf16.bf16 {"
        "%0, %1, %2, %3, %4, %5, %6, %7, %8, %9, %10, %11, %12, %13, %14, %15,"
        "%16, %17, %18, %19, %20, %21, %22, %23, %24, %25, %26, %27, %28, %29, %30, %31,"
        "%32, %33, %34, %35, %36, %37, %38, %39, %40, %41, %42, %43, %44, %45, %46, %47,"
        "%48, %49, %50, %51, %52, %53, %54, %55, %56, %57, %58, %59, %60, %61, %62, %63}, {%64, %65, %66, %67}, %68, 1, 1, 1, 1;\n"
        :
        "+f"(d[0]), "+f"(d[1]), "+f"(d[2]), "+f"(d[3]), "+f"(d[4]), "+f"(d[5]), "+f"(d[6]), "+f"(d[7]),
        "+f"(d[8]), "+f"(d[9]), "+f"(d[10]), "+f"(d[11]), "+f"(d[12]), "+f"(d[13]), "+f"(d[14]), "+f"(d[15]),
        "+f"(d[16]), "+f"(d[17]), "+f"(d[18]), "+f"(d[19]), "+f"(d[20]), "+f"(d[21]), "+f"(d[22]), "+f"(d[23]),
        "+f"(d[24]), "+f"(d[25]), "+f"(d[26]), "+f"(d[27]), "+f"(d[28]), "+f"(d[29]), "+f"(d[30]), "+f"(d[31]),
        "+f"(d[32]), "+f"(d[33]), "+f"(d[34]), "+f"(d[35]), "+f"(d[36]), "+f"(d[37]), "+f"(d[38]), "+f"(d[39]),
        "+f"(d[40]), "+f"(d[41]), "+f"(d[42]), "+f"(d[43]), "+f"(d[44]), "+f"(d[45]), "+f"(d[46]), "+f"(d[47]),
        "+f"(d[48]), "+f"(d[49]), "+f"(d[50]), "+f"(d[51]), "+f"(d[52]), "+f"(d[53]), "+f"(d[54]), "+f"(d[55]),
        "+f"(d[56]), "+f"(d[57]), "+f"(d[58]), "+f"(d[59]), "+f"(d[60]), "+f"(d[61]), "+f"(d[62]), "+f"(d[63])
        : "r"(a[0]), "r"(a[1]), "r"(a[2]), "r"(a[3]), "l"(db));
}
__device__ __forceinline__ void wgmma_qk_f16_acc(float* d, const uint32_t* a, uint64_t db) {
    asm volatile("wgmma.mma_async.sync.aligned.m64n64k16.f32.f16.f16 {"
        "%0, %1, %2, %3, %4, %5, %6, %7, %8, %9, %10, %11, %12, %13, %14, %15,"
        "%16, %17, %18, %19, %20, %21, %22, %23, %24, %25, %26, %27, %28, %29, %30, %31}, {%32, %33, %34, %35}, %36, 1, 1, 1, 0;\n"
        :
        "+f"(d[0]), "+f"(d[1]), "+f"(d[2]), "+f"(d[3]), "+f"(d[4]), "+f"(d[5]), "+f"(d[6]), "+f"(d[7]),
        "+f"(d[8]), "+f"(d[9]), "+f"(d[10]), "+f"(d[11]), "+f"(d[12]), "+f"(d[13]), "+f"(d[14]), "+f"(d[15]),
        "+f"(d[16]), "+f"(d[17]), "+f"(d[18]), "+f"(d[19]), "+f"(d[20]), "+f"(d[21]), "+f"(d[22]), "+f"(d[23]),
        "+f"(d[24]), "+f"(d[25]), "+f"(d[26]), "+f"(d[27]), "+f"(d[28]), "+f"(d[29]), "+f"(d[30]), "+f"(d[31])
        : "r"(a[0]), "r"(a[1]), "r"(a[2]), "r"(a[3]), "l"(db));
}
__device__ __forceinline__ void wgmma_qk_bf16_zero(float* d, const uint32_t* a, uint64_t db) {
    asm volatile("wgmma.mma_async.sync.aligned.m64n64k16.f32.bf16.bf16 {"
        "%0, %1, %2, %3, %4, %5, %6, %7, %8, %9, %10, %11, %12, %13, %14, %15,"
        "%16, %17, %18, %19, %20, %21, %22, %23, %24, %25, %26, %27, %28, %29, %30, %31}, {%32, %33, %34, %35}, %36, 0, 1, 1, 0;\n"
        :
        "=f"(d[0]), "=f"(d[1]), "=f"(d[2]), "=f"(d[3]), "=f"(d[4]), "=f"(d[5]), "=f"(d[6]), "=f"(d[7]),
        "=f"(d[8]), "=f"(d[9]), "=f"(d[10]), "=f"(d[11]), "=f"(d[12]), "=f"(d[13]), "=f"(d[14]), "=f"(d[15]),
        "=f"(d[16]), "=f"(d[17]), "=f"(d[18]), "=f"(d[19]), "=f"(d[20]), "=f"(d[21]), "=f"(d[22]), "=f"(d[23]),
        "=f"(d[24]), "=f"(d[25]), "=f"(d[26]), "=f"(d[27]), "=f"(d[28]), "=f"(d[29]), "=f"(d[30]), "=f"(d[31])
        : "r"(a[0]), "r"(a[1]), "r"(a[2]), "r"(a[3]), "l"(db));
}
__device__ __forceinline__ void wgmma_pv(float* d, const uint32_t* a, uint64_t db) {
    asm volatile("wgmma.mma_async.sync.aligned.m64n24k16.f32.bf16.bf16 {"
        "%0, %1, %2, %3, %4, %5, %6, %7, %8, %9, %10, %11}, {%12, %13, %14, %15}, %16, 1, 1, 1, 1;\n"
        :
        "+f"(d[0]), "+f"(d[1]), "+f"(d[2]), "+f"(d[3]), "+f"(d[4]), "+f"(d[5]), "+f"(d[6]), "+f"(d[7]),
        "+f"(d[8]), "+f"(d[9]), "+f"(d[10]), "+f"(d[11])
        : "r"(a[0]), "r"(a[1]), "r"(a[2]), "r"(a[3]), "l"(db));
}

template <int N> __device__ __forceinline__ void wgmma_ss(float* d, uint64_t a, uint64_t b) {
    if (N == 128) wgmma_ss_n128(d, a, b);
    if (N == 96) wgmma_ss_n96(d, a, b);
    if (N == 64) wgmma_ss_n64(d, a, b);
}

#define OFF_R 131072
#define OFF_ONE 229376
#define OFF_BAR 229888
#define OFF_BIAS (OFF_BAR + 736)
#define OFF_G (OFF_BIAS + 1152)
#define SMEM_BYTES (OFF_G + 272)
#define SBD 1024u
#define B_X 0
#define B_F1 416
#define B_E1 64
#define B_XD 672
#define B_KV 160
#define B_F2 224
#define B_E2 256
#define B_T 288
#define B_G 360
#define B_G2 368
#define B_G3 376
#define B_SF 384
#define B_BI 400

#define B_SF2 408
#define NR 6

#define PF 1
#define PFX 0
#define PACE 1
#define FSER 1
#define MERGE 1
#define EB 2
#define ANDM 0x4440
#define HOLD 5
#define EXP_FKK 4
#define QSCALE 0.36067376022224085f
#define MAGIC 445.41763f
#define FORCE_IMAD
#define NMUFU 5
#define VSTEP ((uint64_t)((long long)32 - ((long long)32 << 16)))

#define XMASK 0x0D55u
#define KVMASK 0x1D55u
__host__ __device__ constexpr int strm_pos(int pass, int i) {
    if (pass == 1 || pass == 2) return 8 + 8 * pass + i;
    int n = 0;
    for (int p = 0; p < 16; p++)
        if ((int)((KVMASK >> p) & 1) == (pass == 3)) { if (n == i) return p; n++; }
    return 0;
}
__host__ __device__ constexpr uint32_t strm_code(int pass) {
    uint32_t c = 0;
    for (int i = 0; i < 7; i++) c |= (uint32_t)(strm_pos(pass, i + 1) - strm_pos(pass, i)) << (4 * i);
    return c;
}

template <int N, int SUB, int KST, int LBO, int SBO, int SWZ>
__device__ __forceinline__ void gemm_pass(float* acc, uint32_t bar, uint64_t dA, int lane, uint32_t pos, uint32_t code, int barNext, bool waitx, bool last) {
    uint32_t prev = 0, slot = pos % NR;
#pragma unroll 1
    for (int i = 0; i < 8; i++) {
        if (waitx) {
            mbar_wait(bar + B_X + 8 * i, 0);
            if (N == 96 && i == HOLD) bar_sync(4, 512);
        }
        mbar_wait(bar + B_F1 + 8 * pos, 0);
        const uint64_t dB = mkdesc(SBD + OFF_R, LBO, SBO, SWZ) + slot * 1024;
        wg_fence();
        wgmma_ss<N>(acc, dA, dB);
        wgmma_ss<N>(acc, dA + 2, dB + KST / 16);
        wg_commit();
        wg_wait<1>();
        if (i > 0 && lane < 2) mbar_arrive_cluster(prev, lane);
        wgmma_ss<N>(acc, dA + 4, dB + SUB / 16);
        wgmma_ss<N>(acc, dA + 6, dB + (SUB + KST) / 16);
        wg_commit();
        prev = last ? bar + B_XD + 8 * i : bar + B_E1 + 8 * slot;
        pos += code & 15;
        slot += code & 15;
        if (slot >= NR) slot -= NR;
        code >>= 4;
        dA += 1024;
    }
    if (barNext) bar_arrive(barNext, 512);
    wg_wait<0>();
    if (lane < 2) mbar_arrive_cluster(prev, lane);
    pin<N / 2>(acc);
}

__device__ __forceinline__ uint32_t lds32(uint32_t a) { uint32_t v; asm volatile("ld.shared.u32 %0, [%1];" : "=r"(v) : "r"(a)); return v; }
__device__ __forceinline__ bool elect() {
    uint32_t p;
    asm volatile("{\n.reg .pred p;\nelect.sync _|p, 0xffffffff;\nselp.u32 %0, 1, 0, p;\n}" : "=r"(p));
    return p;
}

template <int G0, int G1> __device__ __forceinline__ void gelu_pack(const float* acc, uint32_t bias, uint32_t* out) {
#pragma unroll
    for (int G = G0; G < G1; G++) {
        uint32_t* o = out + 8 * G;
#pragma unroll
        for (int j = 0; j < 4; j++) {
            float bv[2];
            asm volatile("ld.shared.v2.f32 {%0, %1}, [%2];" : "=f"(bv[0]), "=f"(bv[1]) : "r"(bias + G * 128 + j * 32));
            float y[4];
#pragma unroll
            for (int i = 0; i < 4; i++) {
                const float h = acc[16 * G + 4 * j + i] + bv[i & 1];
                const float z = h * fmaf(h * h, 0.035677408136300125f, 0.7978845608028654f);
                y[i] = fmaf(h, tanhf_(z), h);
            }
            o[j] = pk_bf16(y[0], y[1]);
            o[4 + j] = pk_bf16(y[2], y[3]);
        }
    }
}

__device__ __forceinline__ float norm_bound(const float* v, float sc) {
    uint32_t m = 0;
#pragma unroll
    for (int h = 0; h < 4; h++) {
        const float* u = v + 8 * h;
        m = max(m, __float_as_uint(fmaf(u[0], u[0], fmaf(u[1], u[1], fmaf(u[4], u[4], u[5] * u[5])))));
        m = max(m, __float_as_uint(fmaf(u[2], u[2], fmaf(u[3], u[3], fmaf(u[6], u[6], u[7] * u[7])))));
    }
#pragma unroll
    for (int o = 4; o < 32; o <<= 1) m = max(m, __shfl_xor_sync(0xffffffffu, m, o));
    float f = __uint_as_float(m);
    f += __shfl_xor_sync(0xffffffffu, f, 1);
    f += __shfl_xor_sync(0xffffffffu, f, 2);
    return f * sc;
}

__device__ __forceinline__ uint32_t exp2_pair(float a, float b, uint32_t m1) {
    const uint32_t w = __byte_perm(__float_as_uint(a), __float_as_uint(b), 0x6521);
    uint32_t m, r;
    asm("lop3.b32 %0, %1, 0x007f007f, 0x9f809f80, 0xEA;" : "=r"(m) : "r"(w));
    const uint32_t e = m * m1 + w;
    asm("fma.rn.bf16x2 %0, %1, %2, %3;" : "=r"(r) : "r"(w), "r"(m), "r"(e));
    return r;
}

__device__ __forceinline__ uint32_t exp2_pair_b(float a, float b) {
    const uint32_t w = __byte_perm(__float_as_uint(a), __float_as_uint(b), 0x6521);
    uint32_t m, r;
    asm("lop3.b32 %0, %1, 0x007f007f, 0xbf00bf00, 0xEA;" : "=r"(m) : "r"(w));
    asm("fma.rn.bf16x2 %0, %1, %2, %3;" : "=r"(r) : "r"(w), "r"(m), "r"(w & 0x7f807f80u));
    return r;
}
__device__ __forceinline__ void store_o(const float* o, uint4* dst, uint32_t par) {
    const float s0 = __fdividef(1.f, o[8]), s1 = __fdividef(1.f, o[10]);
    const uint32_t d0 = (pk_bf16(o[0] * s0, o[1] * s0) & ~1u) | par;
    asm volatile("{\n.reg .b128 t;\nmov.b128 t, {%0, %1, %2, %3};\nst.relaxed.gpu.global.b128 [%4], t;\n}" ::"r"(d0),
                 "r"(pk_bf16(o[2] * s1, o[3] * s1)), "r"(pk_bf16(o[4] * s0, o[5] * s0)), "r"(pk_bf16(o[6] * s1, o[7] * s1)), "l"(dst) : "memory");
}
__device__ __forceinline__ uint4 load_o(const uint4* src) {
    uint4 v;
    asm volatile("{\n.reg .b128 t;\nld.relaxed.gpu.global.b128 t, [%4];\nmov.b128 {%0, %1, %2, %3}, t;\n}"
                 : "=r"(v.x), "=r"(v.y), "=r"(v.z), "=r"(v.w) : "l"(src) : "memory");
    return v;
}
template <int N> __device__ __forceinline__ void fetch_o(uint4* v, const uint4* src, uint32_t ep) {
    int spins = 0;
    while (true) {
        uint32_t bad = 0;
#pragma unroll
        for (int k = 0; k < N; k++) bad |= v[k].x ^ ep;
        if (!__any_sync(0xffffffffu, (bad & 1) != 0)) break;
        if (++spins > (1 << 22)) __trap();
#pragma unroll
        for (int k = 0; k < N; k++)
            if (((v[k].x ^ ep) & 1) != 0) v[k] = load_o(src + k * 128);
    }
}
__device__ __forceinline__ uint32_t bmul2(uint32_t a, uint32_t b) { uint32_t r; asm("mul.rn.bf16x2 %0, %1, %2;" : "=r"(r) : "r"(a), "r"(b)); return r; }
__device__ __forceinline__ void sts32(uint32_t a, uint32_t v) { asm volatile("st.shared.u32 [%0], %1;" ::"r"(a), "r"(v) : "memory"); }
__device__ __forceinline__ void stage_o(const uint4* v, uint32_t a0, uint32_t g0, uint32_t g1, int lane) {
#pragma unroll
    for (int i = 0; i < 4; i++)
        asm volatile("stmatrix.sync.aligned.m8n8.x4.shared.b16 [%0], {%1, %2, %3, %4};" ::"r"(a0 + (((i * 2 + (lane >> 4)) ^ (lane & 7)) << 4)),
                     "r"(bmul2(v[i].x, g0)), "r"(bmul2(v[i].y, g1)), "r"(bmul2(v[i].z, g0)), "r"(bmul2(v[i].w, g1)) : "memory");
    asm volatile("fence.proxy.async.shared::cta;" ::: "memory");
}
__device__ __forceinline__ void load_q(uint32_t* q, int h, int row, int t) {
    const uint8_t* p = gQ + (size_t)h * (SEQ * 32) + (size_t)row * 32 + t * 4;
    q[0] = __ldcg((const uint32_t*)p); q[1] = __ldcg((const uint32_t*)(p + 256));
    q[2] = __ldcg((const uint32_t*)(p + 16)); q[3] = __ldcg((const uint32_t*)(p + 272));
}

template <int NT>
__device__ __forceinline__ void proj16(float (*c)[8], const __nv_bfloat16* x, const __nv_bfloat16* w, int row0, int rstep, int col, int g, int t) {
#pragma unroll
    for (int i = 0; i < NT; i++)
#pragma unroll
        for (int j = 0; j < 8; j++) c[i][j] = 0.f;
    const unsigned short* wu = (const unsigned short*)w;
#pragma unroll 1
    for (int k = 0; k < DM; k += 16) {
        uint32_t b[4];
#pragma unroll
        for (int j = 0; j < 4; j++) {
            const int kr = k + 2 * t + (j & 1) * 8, cc = col + g + (j >> 1) * 8;
            b[j] = (uint32_t)wu[(size_t)kr * (3 * DM) + cc] | ((uint32_t)wu[(size_t)(kr + 1) * (3 * DM) + cc] << 16);
        }
#pragma unroll
        for (int i = 0; i < NT; i++) {
            const __nv_bfloat16* xp = x + (size_t)(row0 + i * rstep + g) * DM + k + 2 * t;
            const uint32_t a0 = *(const uint32_t*)xp, a1 = *(const uint32_t*)(xp + 8 * DM);
            const uint32_t a2 = *(const uint32_t*)(xp + 8), a3 = *(const uint32_t*)(xp + 8 * DM + 8);
#pragma unroll
            for (int j = 0; j < 2; j++)
                asm volatile("mma.sync.aligned.m16n8k16.row.col.f32.bf16.bf16.f32 {%0,%1,%2,%3}, {%4,%5,%6,%7}, {%8,%9}, {%0,%1,%2,%3};"
                             : "+f"(c[i][4 * j]), "+f"(c[i][4 * j + 1]), "+f"(c[i][4 * j + 2]), "+f"(c[i][4 * j + 3])
                             : "r"(a0), "r"(a1), "r"(a2), "r"(a3), "r"(b[2 * j]), "r"(b[2 * j + 1]));
        }
    }
}

struct Maps { CUtensorMap x, kv, q, f1, f3, h, w2, wo, hs, kvs; };

template <int I0, int I1>
__device__ __forceinline__ void issue_stream(const Maps& tm, uint32_t sb, uint32_t rank, int nb, int mb) {
    const uint32_t bar = sb + OFF_BAR;
    const uint32_t dst = sb + OFF_R;
    const int kr = rank * 32;
#pragma unroll
    for (int it = I0; it < I1; it++) {
        const int s = it % NR;
        const uint32_t fb = bar + B_F1 + 8 * it;
        if (it >= 24 + NR) mbar_wait(bar + B_XD + 8 * (it - 24 - NR), 0);
        else if (it >= NR) mbar_wait(bar + B_E1 + 8 * s, ((it / NR) - 1) & 1);
        const int nkv = __builtin_popcount(KVMASK & ((1u << it) - 1));
        if (it < 16 && ((KVMASK >> it) & 1)) {
            tma3d_mc(dst + s * 16384 + rank * 8192, &tm.kv, nb * 64, nkv * 64 + kr, 1, fb);
        } else if (it < 16) {
            tma3d_mc(dst + s * 16384 + rank * 6144, &tm.q, 0, (it - nkv) * 64 + kr, nb * 2, fb);
            tma3d_mc(dst + s * 16384 + rank * 6144 + 4096, &tm.f1, 0, (it - nkv) * 64 + kr, nb * 7, fb);
        } else {
            tma3d_mc(dst + s * 16384 + rank * 6144, &tm.f3, 0, (it & 7) * 64 + kr, nb * 7 + (it < 24 ? 1 : 4), fb);
        }
        if ((XMASK >> it) & 1) {
            const int xc = 1 + __builtin_popcount(XMASK & ((1u << it) - 1));
            tma2d(sb + xc * 16384, &tm.x, xc * 64, mb * 128, bar + B_X + 8 * xc);
        }
    }
}

__global__ void __cluster_dims__(2, 1, 1) __launch_bounds__(640, 1)
fused_kernel(const __grid_constant__ Maps tm, const __nv_bfloat16* __restrict__ x, const __nv_bfloat16* __restrict__ wqkv,
             const __nv_bfloat16* __restrict__ wo, const __nv_bfloat16* __restrict__ w1, const __nv_bfloat16* __restrict__ b1,
             const __nv_bfloat16* __restrict__ w2, const __nv_bfloat16* __restrict__ b2, const __nv_bfloat16* __restrict__ gate,
             __nv_bfloat16* __restrict__ out, const uint32_t m1) {
    const uint32_t sb = smem_u32(smem_raw);
    const uint32_t bar = sb + OFF_BAR;
    const int tid = threadIdx.x, lane = tid & 31;
    const int warp = __shfl_sync(0xffffffffu, tid >> 5, 0);
    const uint32_t rank = cluster_rank();
    const int cl = blockIdx.x >> 1;
    const int nb = cl & 7, mb = (cl >> 3) * 2 + rank;
    const int g = lane >> 2, t = lane & 3;

    const int cb = nb & 3, rb = mb * 2 + (nb >> 2);
    const int rn = (mb >> 1) & 1;
    if (tid == 0) TLM(0, 0);
    TL_INIT();
    if (tid == 512) {
        for (int i = 0; i < 8; i++) { mbar_init(bar + B_X + 8 * i, 1); mbar_init(bar + B_KV + 8 * i, 1); mbar_init(bar + B_T + 8 * i, i < 4 ? 1 : 5); mbar_init(bar + B_XD + 8 * i, 16); }
        for (int i = 0; i < NR; i++) mbar_init(bar + B_E1 + 8 * i, 16);
        for (int i = 0; i < 4; i++) { mbar_init(bar + B_F2 + 8 * i, 1); mbar_init(bar + B_E2 + 8 * i, 8); }
        asm volatile("fence.mbarrier_init.release.cluster;" ::: "memory");
    } else if (tid == 608) {
        for (int i = 0; i < 32; i++) mbar_init(bar + B_F1 + 8 * i, 1);
        mbar_init(bar + B_G, 1);
        for (int i = 0; i < 3; i++) mbar_init(bar + B_SF + 8 * i, i == 1 ? 2 : 1);
        mbar_init(bar + B_SF2, 2);
        mbar_init(bar + B_G3, 1);
        mbar_init(bar + B_G2, 4);
        asm volatile("fence.mbarrier_init.release.cluster;" ::: "memory");
    }
    __syncwarp();
    asm volatile("barrier.cluster.arrive.relaxed.aligned;" ::: "memory");
    if (warp == 19) mbar_expect(bar + B_F1 + 8 * lane, ((KVMASK >> lane) & 1) ? 16384 : 12288);
    if (warp == 16 && lane < 24) mbar_expect(bar + (lane < 8 ? B_X : lane < 16 ? B_KV - 64 : B_T - 128) + 8 * lane, 16384);
    if (tid == 512) {
        tma2d(sb, &tm.x, 0, mb * 128, bar + B_X);
    } else if (tid == 544) {
        map_prefetch(&tm.kv);
        l2_prefetch((const uint8_t*)wqkv + (size_t)blockIdx.x * 3072, 3072);
        l2_prefetch((const uint8_t*)w1 + (size_t)blockIdx.x * 1792, 1792);
        map_prefetch(&tm.q); map_prefetch(&tm.f1); map_prefetch(&tm.f3);
    }
    if ((sb & 0xFFFFFF) != SBD) __trap();
    __syncwarp();
    asm volatile("barrier.cluster.wait.aligned;" ::: "memory");
    if (tid == 512) issue_stream<0, NR>(tm, sb, rank, nb, mb);
    if (tid == 0) { TLM(0, 1); TLC(0, 30); }

    if (warp < 16) {
        const int wg = warp >> 2;
        const int h = cl >> 1, qd = (cl & 1) * 2 + rank;
        const int flip = (h >> 2) & 1;
        uint32_t q[4];
        {
            const int w8 = warp & 7;
            const int T = mb * 8 + w8, row0 = T * 16 + g;
            const uint64_t dA0 = mkdesc(SBD + (wg & 1) * 8192, 16, 1024, 1);
            if (wg < 2) {
                float acc[64];
#pragma unroll
                for (int i = 0; i < 64; i++) acc[i] = 0.f;
                gemm_pass<128, 8192, 2048, 4096, 1024, 1>(acc, bar, dA0, lane, strm_pos(3, 0), strm_code(3), HOLD < 8 ? 4 : 0, true, false);
                if (tid == 0) TLM(0, 2);
                {
                    const float km = norm_bound(acc, 1.f);
                    uint32_t pv[16];
#pragma unroll
                    for (int i = 0; i < 16; i++) { pv[i] = pk_bf16(acc[32 + 2 * i], acc[33 + 2 * i]); }
                    uint32_t big = 0;
#pragma unroll
                    for (int i = 0; i < 16; i++) big |= pv[i] & (pv[i] << 1);
                    const bool vbig = __any_sync(0xffffffffu, (big & 0x40004000u) != 0);
                    if (lane == 0) gN[1024 + nb * 128 + T] = vbig ? 3.0e38f : km;
                    const float gm = g == 0 ? 0.f : -1.f;
                    const uint32_t kp = sb + OFF_R + 12288 + (w8 >> 2) * 1024 + g * 128 + ((((w8 & 3) * 2 + ((t >> 1) ^ (w8 >> 2))) ^ g) << 4) + (t & 1) * 8;
                    uint8_t* vp = gKV + (size_t)(nb * 4) * (SEQ * 64) + 65536 + (((T >> 6) * 16 + 2 * g) * 64 + (T & 63)) * 32 + ((t * 8) ^ ((w8 >> 2) << 4));
                    bar_sync(9, 256);
#pragma unroll
                    for (int hh = 0; hh < 4; hh++) {
                        const float* v = acc + 8 * hh;
                        float p0 = __shfl_up_sync(0xffffffffu, v[2], 4), p1 = __shfl_up_sync(0xffffffffu, v[3], 4);
                        float p2 = __shfl_up_sync(0xffffffffu, v[6], 4), p3 = __shfl_up_sync(0xffffffffu, v[7], 4);
                        sts64(kp + hh * 16384, pk_f16(fmaf(p0, gm, v[0]), fmaf(p1, gm, v[1])), pk_f16(fmaf(p2, gm, v[4]), fmaf(p3, gm, v[5])));
                        sts64(kp + hh * 16384 + 2048, pk_f16(v[2] - v[0], v[3] - v[1]), pk_f16(v[6] - v[4], v[7] - v[5]));
                        const uint32_t* u = pv + 4 * hh;
                        if (hh < 2) {
                            sts64(kp + (4 + hh) * 16384, u[0], u[2]);
                            sts64(kp + (4 + hh) * 16384 + 2048, u[1], u[3]);
                        } else {
                            *(uint2*)(vp + (size_t)hh * (SEQ * 64)) = make_uint2(u[0], u[2]);
                            *(uint2*)(vp + (size_t)hh * (SEQ * 64) + 2048) = make_uint2(u[1], u[3]);
                        }
                    }
                }
                asm volatile("fence.proxy.async.shared::cta;" ::: "memory");
                bar_arrive(10, 288);
                if (tid == 0) TLM(0, 3);
            }
#pragma unroll 1
            for (int p = wg < 2 ? 1 : 0; p < 3; p += 2) {
                float acc[48];
#pragma unroll
                for (int i = 0; i < 48; i++) acc[i] = 0.f;
                pin<48>(acc);
                if (p) bar_sync(5 + p, 512);
                gemm_pass<96, 6144, 1024, 2048, 512, 2>(acc, bar, dA0, lane, p == 0 ? strm_pos(0, 0) : 8 + 8 * p, p == 0 ? strm_code(0) : strm_code(1), p < 2 ? 6 + p : 0, p == 0, p == 2);
                if ((tid & 255) == 0) TLM(0, 4 + 2 * p);
                const uint32_t hp = sb + OFF_R + (p == 2 ? 0 : 12288) + (wg & 1) * 16384 + ((warp & 3) * 16 + g) * 64 + t * 16;
                const uint32_t bp = sb + OFF_BIAS + p * 384 - 256 + t * 8;
                uint32_t ho[24];
                mbar_wait(bar + B_BI, 0);
                if (p == 0) {
                    const float qm = norm_bound(acc, QSCALE * QSCALE);
                    if (lane == 0) gN[nb * 128 + T] = qm;
                    uint8_t* qp = gQ + (size_t)(nb * 4) * (SEQ * 32) + (size_t)row0 * 32 + t * 8;
#pragma unroll
                    for (int hh = 0; hh < 4; hh++) {
                        const float* v = acc + 8 * hh;
                        *(uint2*)(qp + hh * (SEQ * 32)) = make_uint2(pk_f16(v[0] * QSCALE, v[1] * QSCALE), pk_f16(v[4] * QSCALE, v[5] * QSCALE));
                        *(uint2*)(qp + hh * (SEQ * 32) + 256) = make_uint2(pk_f16(v[2] * QSCALE, v[3] * QSCALE), pk_f16(v[6] * QSCALE, v[7] * QSCALE));
                    }
                    bar_arrive(12, 288);
                } else {
                    gelu_pack<0, 2>(acc, bp, ho);
                    pin<16>(ho);
                    mbar_wait(bar + B_G, 0);
                    load_q(q, h, qd * 512 + flip * 256 + warp * 16 + g, t);
                }
                gelu_pack<2, 3>(acc, bp, ho);
                pin<8>(ho + 16);
                if (p == 2) bar_sync(9, 256);
                else mbar_wait(bar + B_SF + 8 * p, 0);
                if (p) {
#pragma unroll
                    for (int i = 0; i < 4; i++) sts128(hp + (i >> 1) * 32768 + (i & 1) * 512, ho + 4 * i);
                }
                sts128(hp + 65536, ho + 16);
                sts128(hp + 65536 + 512, ho + 20);
                asm volatile("fence.proxy.async.shared::cta;" ::: "memory");
                bar_arrive(p == 1 ? 14 : 11, 288);
                if ((tid & 255) == 0) TLM(0, 5 + 2 * p);
            }
        }
        uint32_t ep = 2;
        uint4* const op = gO + ((qd * 8 + wg) * NH + h) * 128 + (tid & 127);
        const uint64_t kd0 = mkdesc(SBD, 16, 256, 3);
        const uint64_t vd0 = mkdesc(SBD + 8192, OFF_ONE - 8192, 256, 3);
        {
            float o[12];
            uint32_t qn[4];
#pragma unroll 1
            for (int rh = 0; rh < 4; rh++) {
                if (rh == 1) {
                    mbar_wait(bar + B_G3, 0);
                    ep = lds32(sb + OFF_G + 256);
                    if (!(ep & 2)) break;
                    load_q(qn, h, qd * 512 + (flip ^ 1) * 256 + warp * 16 + g, t);
                }
                if (!(rh & 1)) {
#pragma unroll
                    for (int i = 0; i < 12; i++) o[i] = 0.f;
                }
                uint64_t kd = kd0 + (rh & 1) * 4096, vd = vd0 + (rh & 1) * (128 * VSTEP);
                uint32_t kvb = bar + B_KV + (rh & 1) * 32;
                float s[32];
#pragma unroll
                for (int i = 0; i < 32; i++) s[i] = i < 2 * NMUFU ? 0.f : ((ANDM >> (i >> 1)) & 1) ? MAGIC - 63.f : MAGIC;
                if ((tid & 255) == 0) TLM(1, (tid >> 8) * 4 + rh);
#pragma unroll 1
                for (int c = 0; c < 4; c++) {
                    mbar_wait(kvb, 0);
                    kvb += 8;
#pragma unroll
                    for (int j = 0; j < 4; j++) {
                        uint32_t p[16];
                        if (!MERGE || j == 0) {
                            wg_fence();
                            wgmma_qk_f16_acc(s, q, kd + j * 128);
                            wg_commit();
                        }
                        wg_wait<0>();
                        pin<32>(s);
#pragma unroll
                        for (int i = 0; i < 16; i++)
                            p[i] = i < NMUFU ? pk_bf16(ex2f(s[2 * i]), ex2f(s[2 * i + 1])) : ((ANDM >> i) & 1) ? exp2_pair_b(s[2 * i], s[2 * i + 1]) : exp2_pair(s[2 * i], s[2 * i + 1], m1);
                        pin<16>(p);
                        wg_fence();
#pragma unroll
                        for (int u = 0; u < 4; u++) {
                            if (MERGE && j < 3 && u == 5 - MERGE) wgmma_qk_f16_acc(s, q, kd + (j + 1) * 128);
                            wgmma_pv(o, p + 4 * u, vd + (j * 4 + u) * VSTEP);
                        }
                        if (MERGE == 1 && j < 3) wgmma_qk_f16_acc(s, q, kd + (j + 1) * 128);
                        wg_commit();
                    }
                    kd += 1024;
                    vd += 32 * VSTEP;
                }
                wg_wait<0>();
                pin<12>(o);
                if (rh & 1) {
                    if ((tid & 127) == 0 && rh == 3) TLM(1, 8 + wg);
                    store_o(o, op + ((rh >> 1) ^ flip) * (4 * NH * 128), ep & 1);
#pragma unroll
                    for (int i = 0; i < 4; i++) q[i] = qn[i];
                }
            }
            if (tid == 0) { TLM(1, 12); TLC(0, 31); }
        }
        if (!(ep & 2)) {
            bar_sync(8, 512);
            for (int c = 0; c < 8; c++) mbar_wait(bar + B_KV + 8 * c, 0);
            {
                float kc[8][8];
                proj16<8>(kc, x, wqkv, warp * 16, 256, DM + h * 16, g, t);
#pragma unroll
                for (int i = 0; i < 8; i++) {
                    const int T = warp + i * 16;
                    const int pos = ((T >> 6) * 16 + 2 * g) * 64 + (T & 63);
                    const uint32_t a = sb + (pos >> 8) * 16384 + (pos & 255) * 32 + t * 4, sw = ((T >> 2) & 1) << 4;
                    asm volatile("st.shared.u32 [%0], %1;" ::"r"(a + sw), "r"(pk_bf16(kc[i][0], kc[i][1])) : "memory");
                    asm volatile("st.shared.u32 [%0], %1;" ::"r"(a + (sw ^ 16)), "r"(pk_bf16(kc[i][4], kc[i][5])) : "memory");
                    asm volatile("st.shared.u32 [%0], %1;" ::"r"(a + 2048 + sw), "r"(pk_bf16(kc[i][2], kc[i][3])) : "memory");
                    asm volatile("st.shared.u32 [%0], %1;" ::"r"(a + 2048 + (sw ^ 16)), "r"(pk_bf16(kc[i][6], kc[i][7])) : "memory");
                }
                asm volatile("fence.proxy.async.shared::cta;" ::: "memory");
                bar_sync(8, 512);
            }
#pragma unroll 1
            for (int r = 0; r < 2; r++) {
                const int row = qd * 512 + (r ^ flip) * 256 + warp * 16 + g;
                {
                    float qc[1][8];
                    proj16<1>(qc, x, wqkv, row - g, 0, h * 16, g, t);
#pragma unroll
                    for (int i = 0; i < 4; i++) q[i] = pk_bf16(qc[0][2 * i] * QSCALE, qc[0][2 * i + 1] * QSCALE);
                }
                float o[12];
#pragma unroll
                for (int i = 0; i < 12; i++) o[i] = 0.f;
                float m0 = -INFINITY, m1 = -INFINITY;
#pragma unroll 1
                for (int j = 0; j < 32; j++) {
                    const uint64_t kd = kd0 + (j >> 2) * 1024 + (j & 3) * 128, vd = vd0 + ((j >> 2) * 32 + (j & 3) * 4) * VSTEP;
                    float s[32];
                    uint32_t p[16];
                    wg_fence();
                    wgmma_qk_bf16_zero(s, q, kd);
                    wg_commit();
                    wg_wait<0>();
                    pin<32>(s);
                    pin<12>(o);
                    float n0 = m0, n1 = m1;
#pragma unroll
                    for (int i = 0; i < 8; i++) {
                        n0 = fmaxf(n0, fmaxf(s[4 * i], s[4 * i + 1]));
                        n1 = fmaxf(n1, fmaxf(s[4 * i + 2], s[4 * i + 3]));
                    }
                    n0 = fmaxf(n0, __shfl_xor_sync(0xffffffffu, n0, 1));
                    n1 = fmaxf(n1, __shfl_xor_sync(0xffffffffu, n1, 1));
                    n0 = fmaxf(n0, __shfl_xor_sync(0xffffffffu, n0, 2));
                    n1 = fmaxf(n1, __shfl_xor_sync(0xffffffffu, n1, 2));
                    const float c0 = ex2f(m0 - n0), c1 = ex2f(m1 - n1);
                    m0 = n0;
                    m1 = n1;
#pragma unroll
                    for (int i = 0; i < 3; i++) { o[4 * i] *= c0; o[4 * i + 1] *= c0; o[4 * i + 2] *= c1; o[4 * i + 3] *= c1; }
#pragma unroll
                    for (int i = 0; i < 8; i++) {
                        p[2 * i] = pk_bf16(ex2f(s[4 * i] - m0), ex2f(s[4 * i + 1] - m0));
                        p[2 * i + 1] = pk_bf16(ex2f(s[4 * i + 2] - m1), ex2f(s[4 * i + 3] - m1));
                    }
                    pin<16>(p);
                    pin<12>(o);
                    wg_fence();
#pragma unroll
                    for (int u = 0; u < 4; u++) wgmma_pv(o, p + 4 * u, vd + u * VSTEP);
                    wg_commit();
                }
                wg_wait<0>();
                pin<12>(o);
                store_o(o, op + (r ^ flip) * (4 * NH * 128), ep & 1);
            }
        }
        {
            const uint4* src = gO + (rb * NH + (wg * 2 + (rn ^ 1)) * 4) * 128 + (tid & 127);
            uint4 v[4];
#pragma unroll
            for (int i = 0; i < 4; i++) v[i] = load_o(src + i * 128);
            mbar_wait(bar + B_G2, 0);
            const int lr = (warp & 3) * 16;
            const uint32_t g0 = lds32(sb + OFF_G + (lr + g) * 4), g1 = lds32(sb + OFF_G + (lr + g) * 4 + 32);
            fetch_o<4>(v, src, ep);
            stage_o(v, sb + OFF_R + 65536 + wg * 8192 + (lr + (lane & 15)) * 128, g0, g1, lane);
            __syncwarp();
            if (lane == 0) mbar_arrive(bar + B_T + 32 + 8 * wg);
            if ((tid & 127) == 0) TLM(1, 20 + wg);
        }
    } else {
        if (warp == 16) {
            if (lane == 0) {
                issue_stream<NR, 32>(tm, sb, rank, nb, mb);
                mbar_wait(bar + B_SF2, 0);
#pragma unroll
                for (int s = 0; s < 4; s++) {
                    mbar_expect(bar + B_F2 + 8 * s, 24576);
                    tma5d_mc(sb + OFF_R + s * 24576 + 8192 + rank * 8192, &tm.w2, cb * 128 + rank * 64, s * 2, bar + B_F2 + 8 * s);
                }
                cnt_wait(gCntH + mb * 32, epoch() * 8);
                asm volatile("fence.proxy.async.global;" ::: "memory");
                TLM(1, 13);
#pragma unroll
                for (int s = 0; s < 4; s++) tma2d(sb + OFF_R + s * 24576, &tm.h, s * 64, rb * 64, bar + B_F2 + 8 * s);
            }
        } else if (warp == 17) {
            {
                uint32_t bv[4], b2v[2];
#pragma unroll
                for (int i = 0; i < 4; i++) bv[i] = lane + 32 * i < 112 ? *(const uint32_t*)(b1 + nb * 224 + (lane + 32 * i) * 2) : 0;
#pragma unroll
                for (int i = 0; i < 2; i++) b2v[i] = *(const uint32_t*)(b2 + cb * 128 + (lane + 32 * i) * 2);
#pragma unroll
                for (int i = 0; i < 4; i++) {
                    sts32(sb + OFF_ONE + (lane + 32 * i) * 4, 0x3f803f80u);
                    if (lane + 32 * i < 112) sts64(sb + OFF_BIAS + (lane + 32 * i) * 8, bv[i] << 16, bv[i] & 0xffff0000u);
                }
#pragma unroll
                for (int i = 0; i < 2; i++) sts32(sb + OFF_BIAS + 896 + (lane + 32 * i) * 4, b2v[i]);
                asm volatile("fence.proxy.async.shared::cta;" ::: "memory");
                __syncwarp();
                if (lane == 0) mbar_arrive(bar + B_BI);
            }
            mbar_wait(bar + B_X + 8 * PFX, 0);
            if (lane == 0) {
                l2_prefetch((const uint8_t*)wqkv + 128 * 3072 + (size_t)blockIdx.x * 9216, 9216);
                l2_prefetch((const uint8_t*)w1 + (size_t)blockIdx.x * 14336, 14336);
            }
            mbar_wait(bar + B_X + 8 * 7, 0);
            if (lane == 0) {
                l2_prefetch((const uint8_t*)w2 + (size_t)blockIdx.x * 14336, 14336);
                l2_prefetch((const uint8_t*)wo + (size_t)blockIdx.x * 4096, 4096);
                map_prefetch(&tm.h); map_prefetch(&tm.w2); map_prefetch(&tm.wo); map_prefetch(&tm.hs); map_prefetch(&tm.kvs);
                TLM(0, 11);
            }
            bar_sync(10, 288);
            if (lane == 0) {
#pragma unroll 1
                for (int b = 5; b >= 0; b--) {
                    tma5d_st(&tm.kvs, sb + OFF_R + 12288 + b * 16384, (mb >> 3) * 8, (mb & 7) * 2, nb * 8 + (b < 4 ? 2 * b : 2 * b - 7));
                    asm volatile("cp.async.bulk.commit_group;\ncp.async.bulk.wait_group.read %0;" ::"n"(PACE) : "memory");
                    if (b == 4 - PACE) mbar_arrive(bar + B_SF);
                }
                asm volatile("cp.async.bulk.wait_group.read 0;" ::: "memory");
                mbar_arrive(bar + B_SF + 8);
            }
            __syncwarp();
            bar_sync(12, 288);
            if (lane == 0) {
                asm volatile("cp.async.bulk.wait_group 0;\nfence.proxy.async.global;" ::: "memory");
                cnt_add(gCntQ + nb * 32);
                TLM(0, 13);
            }
        } else {
            {
                const int r0 = mb * 128 + nb * 16 + (warp - 18) * 8;
                uint4 xv[16];
#pragma unroll
                for (int i = 0; i < 16; i++) xv[i] = *(const uint4*)(x + (size_t)(r0 + (i >> 1)) * DM + (i & 1) * 256 + lane * 8);
                const uint4 ga = *(const uint4*)(gate + lane * 8), gb = *(const uint4*)(gate + 256 + lane * 8);
                float z[8];
#pragma unroll
                for (int r = 0; r < 8; r++) z[r] = dot8(xv[2 * r], ga) + dot8(xv[2 * r + 1], gb);
#pragma unroll
                for (int w = 4; w >= 1; w >>= 1)
#pragma unroll
                    for (int r = 0; r < w; r++) {
                        const bool up = lane & w;
                        z[r] = (up ? z[r + w] : z[r]) + __shfl_xor_sync(0xffffffffu, up ? z[r] : z[r + w], w);
                    }
                z[0] += __shfl_xor_sync(0xffffffffu, z[0], 8);
                z[0] += __shfl_xor_sync(0xffffffffu, z[0], 16);
                if (lane < 8) gG[r0 + lane] = 1.f / (1.f + __expf(-z[0]));
                if (tid == 576) TLM(0, 12);
            }
            if (warp == 19) {
#pragma unroll 1
                for (int e = 0; e < 3; e++) {
                    bar_sync(e == 1 ? 14 : 11, 288);
                    if (lane == 0) {
#pragma unroll 1
                        for (int b = e == 0 ? 4 : 0; b < 6; b++) {
                            tma3d_st(&tm.hs, sb + OFF_R + (e == 2 ? 0 : 12288) + b * 16384, 0, mb * 128 + (b & 1) * 64, nb * 7 + e * 3 - 2 + (b >> 1));
                            asm volatile("cp.async.bulk.commit_group;\ncp.async.bulk.wait_group.read %0;" ::"n"(PACE) : "memory");
                        }
                        asm volatile("cp.async.bulk.wait_group.read 0;" ::: "memory");
                        if (e == 0) mbar_arrive(bar + B_SF + 8);
                        if (e == 2) { mbar_arrive_cluster(bar + B_SF2, 0); mbar_arrive_cluster(bar + B_SF2, 1); }
                    }
                    __syncwarp();
                }
                bar_sync(13, 64);
                if (lane == 0) {
                    asm volatile("cp.async.bulk.wait_group 0;\nfence.proxy.async.global;" ::: "memory");
                    cnt_add(gCntH + mb * 32);
                    TLM(0, 15);
                }
            } else {
                bar_arrive(13, 64);
                const int h = cl >> 1, qd = (cl & 1) * 2 + rank;
                const uint32_t ep = epoch();
                if (lane == 0) {
                    cnt_wait(gCntQ + (h >> 2) * 32, ep * 16);
                    mbar_arrive(bar + B_G);
                    TLM(0, 14);
                    asm volatile("fence.proxy.async.global;" ::: "memory");
#pragma unroll
                    for (int c = 0; c < 2; c++) {
                        mbar_wait(bar + B_XD + 8 * c, 0);
                        bulk_mc(sb + c * 16384 + rank * 8192, gKV + (size_t)h * (SEQ * 64) + rank * 65536 + c * 8192, 8192, bar + B_KV + 8 * c);
                    }
                }
                __syncwarp();
            const int hb = h >> 2;
            const uint4 kq = __ldcg((const uint4*)(gN + 1024 + hb * 128 + lane * 4));
            const float qq = ldcg_f(gN + hb * 128 + qd * 32 + lane);
            const float kf = __uint_as_float(__reduce_max_sync(0xffffffffu, max(max(kq.x, kq.y), max(kq.z, kq.w))));
            const float qf = __uint_as_float(__reduce_max_sync(0xffffffffu, __float_as_uint(qq)));
            if (lane == 0) {
                sts32(sb + OFF_G + 256, (ep & 1) | ((kf <= 1.0e6f) && (qf <= 1.0e6f) && (kf * qf <= 2300.f) ? 2 : 0));
                mbar_arrive(bar + B_G3);
                TLM(0, 16);
#pragma unroll
                for (int c = 2; c < 8; c++) {
                    mbar_wait(bar + B_XD + 8 * c, 0);
                    bulk_mc(sb + c * 16384 + rank * 8192, gKV + (size_t)h * (SEQ * 64) + rank * 65536 + c * 8192, 8192, bar + B_KV + 8 * c);
                }
                TLM(0, 10);
            }
            }
        }
        __syncwarp();
        float acc[64];
#pragma unroll
        for (int i = 0; i < 64; i++) acc[i] = 0.f;
#pragma unroll 1
        for (int io = 0; io < 7; io++) {
#pragma unroll
            for (int s = 0; s < 4; s++) {
                const int it = io * 4 + s;
                mbar_wait(bar + B_F2 + 8 * s, io & 1);
                if (tid == 512 && s == 0 && (io == 0 || io == 4)) TLM(1, 14 + io / 4);
                const uint64_t dA = mkdesc(SBD + OFF_R + s * 24576, 16, 1024, 1);
                const uint64_t dB = mkdesc(SBD + OFF_R + s * 24576 + 8192, 8192, 1024, 1);
                wg_fence();
#pragma unroll
                for (int kk = 0; kk < EXP_FKK; kk++) {
                    wgmma_ss_n128(acc, dA + kk * 2, dB + kk * 128);
                    if (kk < 3 && (FSER != 3 || kk == 1)) {
                        wg_commit();
                        wg_wait<0>();
                    }
                }
                wg_commit();
                if (warp < 18 && it >= 2 && it < 26) {
                    const int s2 = (s + 2) & 3;
                    mbar_wait(bar + B_E2 + 8 * s2, (io - (s < 2)) & 1);
                    if (elect()) {
                        if (warp == 16) {
                            mbar_expect(bar + B_F2 + 8 * s2, 24576);
                            tma5d_mc(sb + OFF_R + s2 * 24576 + 8192 + rank * 8192, &tm.w2, cb * 128 + rank * 64, it * 2 + 4, bar + B_F2 + 8 * s2);
                        } else {
                            asm volatile("fence.proxy.async.global;" ::: "memory");
                            tma2d(sb + OFF_R + s2 * 24576, &tm.h, it * 64 + 128, rb * 64, bar + B_F2 + 8 * s2);
                        }
                    }
                    __syncwarp();
                }
                wg_wait<1>();
                if (it >= 1 && lane < 2) mbar_arrive_cluster(bar + B_E2 + 8 * ((s + 3) & 3), lane);
            }
        }
        wg_wait<0>();
        if (lane < 2) mbar_arrive_cluster(bar + B_E2 + 8 * 3, lane);
        pin<64>(acc);
        if (tid == 576) gEpoch[blockIdx.x] = epoch();
        if (warp == 16) {
            if (lane == 0) TLM(1, 16);
            for (int s = 0; s < 4; s++) mbar_wait(bar + B_E2 + 8 * s, 0);
            if (elect()) {
#pragma unroll
                for (int i = 0; i < 4; i++)
                    tma5d_mc(sb + OFF_R + i * 16384 + rank * 8192, &tm.wo, cb * 128 + rank * 64, (i * 2 + rn) * 4, bar + B_T + 8 * i);
            }
            __syncwarp();
        }
        uint32_t pa;
        {
            const int lr = (warp - 16) * 16 + g;
            pa = pk_bf16(ldcg_f(gG + rb * 64 + lr), ldcg_f(gG + rb * 64 + lr + 8));
            if (t == 0) {
                sts32(sb + OFF_G + lr * 4, __byte_perm(pa, pa, 0x1010));
                sts32(sb + OFF_G + lr * 4 + 32, __byte_perm(pa, pa, 0x3232));
            }
            const float ga = bf_lo(pa), gb = bf_hi(pa);
            const float g0 = 1.f - ga, g1 = 1.f - gb;
#pragma unroll
            for (int j = 0; j < 16; j++) {
                const uint32_t bv = lds32(sb + OFF_BIAS + 896 + j * 16 + t * 4);
                acc[4 * j] = fmaf(acc[4 * j], 0.5f, bf_lo(bv)) * g0;
                acc[4 * j + 1] = fmaf(acc[4 * j + 1], 0.5f, bf_hi(bv)) * g0;
                acc[4 * j + 2] = fmaf(acc[4 * j + 2], 0.5f, bf_lo(bv)) * g1;
                acc[4 * j + 3] = fmaf(acc[4 * j + 3], 0.5f, bf_hi(bv)) * g1;
            }
            pin<64>(acc);
        }
        {
            mbar_wait(bar + B_G3, 0);
            const uint32_t ep = lds32(sb + OFF_G + 256);
            const uint4* src = gO + (rb * NH + rn * 4) * 128 + (tid & 127);
            bar_sync(15, 128);
#pragma unroll 1
            for (int e = 0; e < 4; e++) {
                uint4 v[4];
#pragma unroll
                for (int i = 0; i < 4; i++) v[i] = load_o(src + i * 128);
                fetch_o<4>(v, src, ep);
                stage_o(v, sb + OFF_R + 65536 + e * 8192 + ((warp - 16) * 16 + (lane & 15)) * 128, __byte_perm(pa, pa, 0x1010), __byte_perm(pa, pa, 0x3232), lane);
                src += 8 * 128;
            }
            bar_sync(15, 128);
        }
#pragma unroll 1
        for (int late = 0; late < 2; late++) {
#pragma unroll
            for (int i = 0; i < 4; i++) {
                mbar_wait(bar + B_T + late * 32 + 8 * i, 0);
                const uint64_t dA = mkdesc(SBD + OFF_R + 65536 + i * 8192, 16, 1024, 1);
                const uint64_t dB = mkdesc(SBD + OFF_R + i * 16384, 8192, 1024, 1);
                wg_fence();
#pragma unroll
                for (int kk = 0; kk < 4; kk++) wgmma_ss_n128(acc, dA + kk * 2, dB + kk * 128);
                wg_commit();
            }
            if (!late) {
                wg_wait<0>();
                if (lane == 0) mbar_arrive(bar + B_G2);
                if (warp == 16) {
                    mbar_wait(bar + B_G2, 0);
                    if (elect()) {
#pragma unroll
                        for (int i = 0; i < 8; i++)
                            tma5d(sb + OFF_R + i * 8192, &tm.wo, cb * 128 + (i & 1) * 64, ((i >> 1) * 2 + (rn ^ 1)) * 4, bar + B_T + 32 + 8 * (i >> 1));
                    }
                    __syncwarp();
                }
                if (tid == 512) TLM(1, 17);
            }
        }
        wg_wait<0>();
        pin<64>(acc);
        if (tid == 512) TLM(1, 18);
        {
            const uint32_t st = sb + 98304 + (warp - 16) * 4352;
            const uint32_t wa = st + (lane & 15) * 272 + (lane >> 4) * 16;
#pragma unroll
            for (int j = 0; j < 8; j++)
                asm volatile("stmatrix.sync.aligned.m8n8.x4.shared.b16 [%0], {%1, %2, %3, %4};" ::"r"(wa + j * 32),
                             "r"(pk_bf16(acc[8 * j], acc[8 * j + 1])), "r"(pk_bf16(acc[8 * j + 2], acc[8 * j + 3])),
                             "r"(pk_bf16(acc[8 * j + 4], acc[8 * j + 5])), "r"(pk_bf16(acc[8 * j + 6], acc[8 * j + 7])) : "memory");
            __syncwarp();
            __nv_bfloat16* op = out + (size_t)(rb * 64 + (warp - 16) * 16 + (lane >> 4)) * DM + cb * 128 + (lane & 15) * 8;
#pragma unroll
            for (int j = 0; j < 8; j++) {
                uint4 v;
                asm volatile("ld.shared.v4.u32 {%0, %1, %2, %3}, [%4];" : "=r"(v.x), "=r"(v.y), "=r"(v.z), "=r"(v.w)
                             : "r"(st + (2 * j + (lane >> 4)) * 272 + (lane & 15) * 16));
                *(uint4*)(op + (size_t)j * 2 * DM) = v;
            }
        }
        if (tid == 512) TLM(1, 19);
        TL_DUMP();
    }
}

typedef CUresult (*EncodeFn)(CUtensorMap*, CUtensorMapDataType, cuuint32_t, void*, const cuuint64_t*, const cuuint64_t*, const cuuint32_t*,
                             const cuuint32_t*, CUtensorMapInterleave, CUtensorMapSwizzle, CUtensorMapL2promotion, CUtensorMapFloatOOBfill);

static void make_map(EncodeFn enc, CUtensorMap* m, const void* p, int rank, const cuuint64_t* dims, const cuuint64_t* strides,
                     const cuuint32_t* box, CUtensorMapSwizzle swz) {
    const cuuint32_t es[5] = {1, 1, 1, 1, 1};
    enc(m, CU_TENSOR_MAP_DATA_TYPE_BFLOAT16, rank, (void*)p, dims, strides, box, es, CU_TENSOR_MAP_INTERLEAVE_NONE, swz,
        CU_TENSOR_MAP_L2_PROMOTION_L2_128B, CU_TENSOR_MAP_FLOAT_OOB_FILL_NONE);
}

extern "C" void kernel_launch(void* const* d_in, const int* in_sizes, int n_in, void* d_out, int out_size) {
    const __nv_bfloat16* x = (const __nv_bfloat16*)d_in[0];
    const __nv_bfloat16* wqkv = (const __nv_bfloat16*)d_in[1];
    const __nv_bfloat16* wo = (const __nv_bfloat16*)d_in[2];
    const __nv_bfloat16* w1 = (const __nv_bfloat16*)d_in[4];
    const __nv_bfloat16* b1 = (const __nv_bfloat16*)d_in[5];
    const __nv_bfloat16* w2 = (const __nv_bfloat16*)d_in[6];
    const __nv_bfloat16* b2 = (const __nv_bfloat16*)d_in[7];
    const __nv_bfloat16* gate = (const __nv_bfloat16*)d_in[8];

    void* fp = nullptr;
    cudaDriverEntryPointQueryResult qr;
    cudaGetDriverEntryPoint("cuTensorMapEncodeTiled", &fp, cudaEnableDefault, &qr);
    EncodeFn enc = (EncodeFn)fp;
    void *pH, *pKV;
    cudaGetSymbolAddress(&pH, gH);
    cudaGetSymbolAddress(&pKV, gKV);

    Maps tm;
    const CUtensorMapSwizzle S128 = CU_TENSOR_MAP_SWIZZLE_128B, S64 = CU_TENSOR_MAP_SWIZZLE_64B;
    { cuuint64_t d[2] = {DM, SEQ}, s[1] = {DM * 2}; cuuint32_t b[2] = {64, 128}; make_map(enc, &tm.x, x, 2, d, s, b, S128); }
    { cuuint64_t d[3] = {DM, DM, 3}, s[2] = {3 * DM * 2, DM * 2}; cuuint32_t b[3] = {64, 32, 2}; make_map(enc, &tm.kv, wqkv, 3, d, s, b, S128); }
    { cuuint64_t d[3] = {32, DM, 3 * DM / 32}, s[2] = {3 * DM * 2, 64}; cuuint32_t b[3] = {32, 32, 2}; make_map(enc, &tm.q, wqkv, 3, d, s, b, S64); }
    { cuuint64_t d[3] = {32, DM, FF / 32}, s[2] = {FF * 2, 64}; cuuint32_t b[3] = {32, 32, 1}; make_map(enc, &tm.f1, w1, 3, d, s, b, S64); }
    { cuuint64_t d[3] = {32, DM, FF / 32}, s[2] = {FF * 2, 64}; cuuint32_t b[3] = {32, 32, 3}; make_map(enc, &tm.f3, w1, 3, d, s, b, S64); }
    { cuuint64_t d[2] = {FF, SEQ}, s[1] = {FF * 2}; cuuint32_t b[2] = {64, 64}; make_map(enc, &tm.h, pH, 2, d, s, b, S128); }
    { cuuint64_t d[5] = {DM, 2, 4, 4, FF / 32}, s[4] = {1024, 8 * 1024, 2 * 1024, 32 * 1024}; cuuint32_t b[5] = {64, 2, 4, 4, 2};
      make_map(enc, &tm.w2, w2, 5, d, s, b, S128); }
    { cuuint64_t d[5] = {DM, 2, 2, 4, NH}, s[4] = {1024, 8 * 1024, 2 * 1024, 16 * 1024}; cuuint32_t b[5] = {64, 2, 2, 4, 4};
      make_map(enc, &tm.wo, wo, 5, d, s, b, S128); }

    { cuuint64_t d[3] = {32, SEQ, FF / 32}, s[2] = {FF * 2, 64}; cuuint32_t b[3] = {32, 64, 1}; make_map(enc, &tm.hs, pH, 3, d, s, b, CU_TENSOR_MAP_SWIZZLE_NONE); }
    { cuuint64_t d[5] = {64, 16, 16, 2, 2 * NH}, s[4] = {4096, 128, 2048, 65536}; cuuint32_t b[5] = {64, 8, 2, 2, 1};
      make_map(enc, &tm.kvs, pKV, 5, d, s, b, S128); }
    cudaFuncSetAttribute(fused_kernel, cudaFuncAttributeMaxDynamicSharedMemorySize, TL_SMEM);
    fused_kernel<<<128, 640, TL_SMEM, cudaStreamPerThread>>>(tm, x, wqkv, wo, w1, b1, w2, b2, gate, (__nv_bfloat16*)d_out, 0xffffffffu);
}
```

```cpp
#include <cuda_runtime.h>
#include <cuda_bf16.h>
#include <cuda_fp16.h>
#include <cuda.h>
#include <stdint.h>

#define SEQ 2048
#define DM 512
#define FF 1792
#define NH 32

__device__ __align__(1024) uint8_t gQ[NH * SEQ * 32];
__device__ __align__(1024) uint8_t gKV[NH * SEQ * 64];
__device__ __align__(1024) __nv_bfloat16 gH[SEQ * FF];
__device__ __align__(1024) uint4 gO[32 * NH * 128];
__device__ float gG[SEQ];
__device__ float gN[3 * 8 * 128];
__device__ unsigned int gCntQ[8 * 32];
__device__ unsigned int gCntH[32 * 32];
__device__ unsigned int gEpoch[128];

__device__ __forceinline__ uint32_t smem_u32(const void* p) { return (uint32_t)__cvta_generic_to_shared(p); }
__device__ __forceinline__ void mbar_init(uint32_t a, uint32_t c) { asm volatile("mbarrier.init.shared::cta.b64 [%0], %1;" ::"r"(a), "r"(c)); }
__device__ __forceinline__ void mbar_expect(uint32_t a, uint32_t b) { asm volatile("mbarrier.arrive.expect_tx.shared::cta.b64 _, [%0], %1;" ::"r"(a), "r"(b) : "memory"); }
__device__ __forceinline__ void mbar_arrive(uint32_t a) { asm volatile("mbarrier.arrive.shared::cta.b64 _, [%0];" ::"r"(a) : "memory"); }
__device__ __forceinline__ void mbar_wait(uint32_t a, uint32_t ph) {
    asm volatile("{\n.reg .pred p;\n.reg .u32 n;\nmov.u32 n, 0;\nW_%=:\nmbarrier.try_wait.parity.shared::cta.b64 p, [%0], %1;\n@p bra D_%=;\n"
                 "add.u32 n, n, 1;\nsetp.lt.u32 p, n, 0x400000;\n@p bra W_%=;\ntrap;\nD_%=:\n}" ::"r"(a), "r"(ph) : "memory");
}
__device__ __forceinline__ void mbar_arrive_cluster(uint32_t a, uint32_t cta) {
    asm volatile("{\n.reg .b32 r;\nmapa.shared::cluster.u32 r, %0, %1;\nmbarrier.arrive.shared::cluster.b64 _, [r];\n}" ::"r"(a), "r"(cta) : "memory");
}
__device__ __forceinline__ void bar_sync(int id, int n) { asm volatile("bar.sync %0, %1;" ::"r"(id), "r"(n) : "memory"); }
__device__ __forceinline__ void bar_arrive(int id, int n) { asm volatile("bar.arrive %0, %1;" ::"r"(id), "r"(n) : "memory"); }
__device__ __forceinline__ uint32_t cluster_rank() { uint32_t r; asm("mov.u32 %0, %%cluster_ctarank;" : "=r"(r)); return r; }
__device__ __forceinline__ void cnt_add(unsigned int* c) { asm volatile("red.release.gpu.global.add.u32 [%0], 1;" ::"l"(c) : "memory"); }
__device__ __forceinline__ void cnt_wait(const unsigned int* c, uint32_t target) {
    uint32_t v;
    int spins = 0;
    while (true) {
        asm volatile("ld.acquire.gpu.global.u32 %0, [%1];" : "=r"(v) : "l"(c) : "memory");
        if ((int)(v - target) >= 0) break;
        if (++spins > (1 << 22)) __trap();
        __nanosleep(40);
    }
}
__device__ __forceinline__ void tma2d(uint32_t dst, const CUtensorMap* m, int c0, int c1, uint32_t bar) {
    asm volatile("cp.async.bulk.tensor.2d.shared::cluster.global.mbarrier::complete_tx::bytes [%0], [%1, {%3, %4}], [%2];"
                 ::"r"(dst), "l"(m), "r"(bar), "r"(c0), "r"(c1) : "memory");
}
__device__ __forceinline__ void tma2d_mc(uint32_t dst, const CUtensorMap* m, int c0, int c1, uint32_t bar) {
    asm volatile("cp.async.bulk.tensor.2d.shared::cluster.global.mbarrier::complete_tx::bytes.multicast::cluster [%0], [%1, {%3, %4}], [%2], %5;"
                 ::"r"(dst), "l"(m), "r"(bar), "r"(c0), "r"(c1), "h"((uint16_t)3) : "memory");
}
__device__ __forceinline__ void tma3d_mc(uint32_t dst, const CUtensorMap* m, int c0, int c1, int c2, uint32_t bar) {
    asm volatile("cp.async.bulk.tensor.3d.shared::cluster.global.mbarrier::complete_tx::bytes.multicast::cluster [%0], [%1, {%3, %4, %5}], [%2], %6;"
                 ::"r"(dst), "l"(m), "r"(bar), "r"(c0), "r"(c1), "r"(c2), "h"((uint16_t)3) : "memory");
}
__device__ __forceinline__ void tma5d_mc(uint32_t dst, const CUtensorMap* m, int c0, int c4, uint32_t bar) {
    asm volatile("cp.async.bulk.tensor.5d.shared::cluster.global.mbarrier::complete_tx::bytes.multicast::cluster [%0], [%1, {%3, %5, %5, %5, %4}], [%2], %6;"
                 ::"r"(dst), "l"(m), "r"(bar), "r"(c0), "r"(c4), "r"(0), "h"((uint16_t)3) : "memory");
}
__device__ __forceinline__ void tma5d(uint32_t dst, const CUtensorMap* m, int c0, int c4, uint32_t bar) {
    asm volatile("cp.async.bulk.tensor.5d.shared::cluster.global.mbarrier::complete_tx::bytes [%0], [%1, {%3, %5, %5, %5, %4}], [%2];"
                 ::"r"(dst), "l"(m), "r"(bar), "r"(c0), "r"(c4), "r"(0) : "memory");
}
__device__ __forceinline__ void bulk_mc(uint32_t dst, const void* src, uint32_t bytes, uint32_t bar) {
    asm volatile("cp.async.bulk.shared::cluster.global.mbarrier::complete_tx::bytes.multicast::cluster [%0], [%1], %2, [%3], %4;"
                 ::"r"(dst), "l"(src), "r"(bytes), "r"(bar), "h"((uint16_t)3) : "memory");
}
__device__ __forceinline__ void tma3d_st(const CUtensorMap* m, uint32_t src, int c0, int c1, int c2) {
    asm volatile("cp.async.bulk.tensor.3d.global.shared::cta.bulk_group [%0, {%2, %3, %4}], [%1];" ::"l"(m), "r"(src), "r"(c0), "r"(c1), "r"(c2) : "memory");
}
__device__ __forceinline__ void tma5d_st(const CUtensorMap* m, uint32_t src, int c1, int c2, int c4) {
    asm volatile("cp.async.bulk.tensor.5d.global.shared::cta.bulk_group [%0, {%5, %2, %3, %5, %4}], [%1];"
                 ::"l"(m), "r"(src), "r"(c1), "r"(c2), "r"(c4), "r"(0) : "memory");
}
__device__ __forceinline__ void bulk_st(void* dst, uint32_t src, uint32_t bytes) {
    asm volatile("cp.async.bulk.global.shared::cta.bulk_group [%0], [%1], %2;" ::"l"(dst), "r"(src), "r"(bytes) : "memory");
}
__device__ __forceinline__ void sts64(uint32_t a, uint32_t x, uint32_t y) { asm volatile("st.shared.v2.u32 [%0], {%1, %2};" ::"r"(a), "r"(x), "r"(y) : "memory"); }
__device__ __forceinline__ void sts128(uint32_t a, const uint32_t* v) {
    asm volatile("st.shared.v4.u32 [%0], {%1, %2, %3, %4};" ::"r"(a), "r"(v[0]), "r"(v[1]), "r"(v[2]), "r"(v[3]) : "memory");
}
__device__ __forceinline__ void l2_prefetch(const void* src, uint32_t bytes) {
    asm volatile("cp.async.bulk.prefetch.L2.global [%0], %1;" ::"l"(src), "r"(bytes) : "memory");
}
__device__ __forceinline__ void map_prefetch(const CUtensorMap* m) { asm volatile("prefetch.tensormap [%0];" ::"l"(m) : "memory"); }
__device__ __forceinline__ void wg_fence() { asm volatile("wgmma.fence.sync.aligned;" ::: "memory"); }
__device__ __forceinline__ void wg_commit() { asm volatile("wgmma.commit_group.sync.aligned;" ::: "memory"); }
template <int N> __device__ __forceinline__ void wg_wait() { asm volatile("wgmma.wait_group.sync.aligned %0;" ::"n"(N) : "memory"); }
template <int N> __device__ __forceinline__ void pin(float* s) {
#pragma unroll
    for (int i = 0; i < N; i++) asm volatile("" : "+f"(s[i])::"memory");
}
template <int N> __device__ __forceinline__ void pin(uint32_t* s) {
#pragma unroll
    for (int i = 0; i < N; i++) asm volatile("" : "+r"(s[i])::"memory");
}
__device__ __forceinline__ uint64_t mkdesc(uint32_t addr, uint32_t lbo, uint32_t sbo, uint32_t swz) {
    return (uint64_t)((addr & 0x3FFFF) >> 4) | ((uint64_t)(lbo >> 4) << 16) | ((uint64_t)(sbo >> 4) << 32) | ((uint64_t)swz << 62);
}
__device__ __forceinline__ float ex2f(float x) { float y; asm("ex2.approx.ftz.f32 %0, %1;" : "=f"(y) : "f"(x)); return y; }
__device__ __forceinline__ float tanhf_(float x) { float y; asm("tanh.approx.f32 %0, %1;" : "=f"(y) : "f"(x)); return y; }
__device__ __forceinline__ uint32_t pk_bf16(float lo, float hi) { uint32_t r; asm("cvt.rn.bf16x2.f32 %0, %1, %2;" : "=r"(r) : "f"(hi), "f"(lo)); return r; }
__device__ __forceinline__ uint32_t pk_f16(float lo, float hi) { uint32_t r; asm("cvt.rn.f16x2.f32 %0, %1, %2;" : "=r"(r) : "f"(hi), "f"(lo)); return r; }
__device__ __forceinline__ float bf_lo(uint32_t v) { return __uint_as_float(v << 16); }
__device__ __forceinline__ float bf_hi(uint32_t v) { return __uint_as_float(v & 0xffff0000u); }
__device__ __forceinline__ float dot8(const uint4& a, const uint4& b) {
    return fmaf(bf_lo(a.x), bf_lo(b.x), fmaf(bf_hi(a.x), bf_hi(b.x), fmaf(bf_lo(a.y), bf_lo(b.y), bf_hi(a.y) * bf_hi(b.y)))) +
           fmaf(bf_lo(a.z), bf_lo(b.z), fmaf(bf_hi(a.z), bf_hi(b.z), fmaf(bf_lo(a.w), bf_lo(b.w), bf_hi(a.w) * bf_hi(b.w))));
}
__device__ __forceinline__ uint32_t epoch() {
    uint32_t v;
    asm volatile("ld.global.u32 %0, [%1];" : "=r"(v) : "l"(gEpoch + blockIdx.x));
    return v + 1;
}
__device__ __forceinline__ float ldcg_f(const float* p) { return __ldcg(p); }

extern __shared__ __align__(1024) uint8_t smem_raw[];
#define TLM(k, slot) do {} while (0)
#define TLC(k, slot) do {} while (0)
#define TL_INIT() do {} while (0)
#define TL_DUMP() do {} while (0)
#define TL_SMEM SMEM_BYTES

__device__ __forceinline__ void wgmma_ss_n128(float* d, uint64_t da, uint64_t db) {
    asm volatile("wgmma.mma_async.sync.aligned.m64n128k16.f32.bf16.bf16 {"
        "%0, %1, %2, %3, %4, %5, %6, %7, %8, %9, %10, %11, %12, %13, %14, %15,"
        "%16, %17, %18, %19, %20, %21, %22, %23, %24, %25, %26, %27, %28, %29, %30, %31,"
        "%32, %33, %34, %35, %36, %37, %38, %39, %40, %41, %42, %43, %44, %45, %46, %47,"
        "%48, %49, %50, %51, %52, %53, %54, %55, %56, %57, %58, %59, %60, %61, %62, %63}, %64, %65, 1, 1, 1, 0, 1;\n"
        :
        "+f"(d[0]), "+f"(d[1]), "+f"(d[2]), "+f"(d[3]), "+f"(d[4]), "+f"(d[5]), "+f"(d[6]), "+f"(d[7]),
        "+f"(d[8]), "+f"(d[9]), "+f"(d[10]), "+f"(d[11]), "+f"(d[12]), "+f"(d[13]), "+f"(d[14]), "+f"(d[15]),
        "+f"(d[16]), "+f"(d[17]), "+f"(d[18]), "+f"(d[19]), "+f"(d[20]), "+f"(d[21]), "+f"(d[22]), "+f"(d[23]),
        "+f"(d[24]), "+f"(d[25]), "+f"(d[26]), "+f"(d[27]), "+f"(d[28]), "+f"(d[29]), "+f"(d[30]), "+f"(d[31]),
        "+f"(d[32]), "+f"(d[33]), "+f"(d[34]), "+f"(d[35]), "+f"(d[36]), "+f"(d[37]), "+f"(d[38]), "+f"(d[39]),
        "+f"(d[40]), "+f"(d[41]), "+f"(d[42]), "+f"(d[43]), "+f"(d[44]), "+f"(d[45]), "+f"(d[46]), "+f"(d[47]),
        "+f"(d[48]), "+f"(d[49]), "+f"(d[50]), "+f"(d[51]), "+f"(d[52]), "+f"(d[53]), "+f"(d[54]), "+f"(d[55]),
        "+f"(d[56]), "+f"(d[57]), "+f"(d[58]), "+f"(d[59]), "+f"(d[60]), "+f"(d[61]), "+f"(d[62]), "+f"(d[63])
        : "l"(da), "l"(db));
}
__device__ __forceinline__ void wgmma_ss_n96(float* d, uint64_t da, uint64_t db) {
    asm volatile("wgmma.mma_async.sync.aligned.m64n96k16.f32.bf16.bf16 {"
        "%0, %1, %2, %3, %4, %5, %6, %7, %8, %9, %10, %11, %12, %13, %14, %15,"
        "%16, %17, %18, %19, %20, %21, %22, %23, %24, %25, %26, %27, %28, %29, %30, %31,"
        "%32, %33, %34, %35, %36, %37, %38, %39, %40, %41, %42, %43, %44, %45, %46, %47}, %48, %49, 1, 1, 1, 0, 1;\n"
        :
        "+f"(d[0]), "+f"(d[1]), "+f"(d[2]), "+f"(d[3]), "+f"(d[4]), "+f"(d[5]), "+f"(d[6]), "+f"(d[7]),
        "+f"(d[8]), "+f"(d[9]), "+f"(d[10]), "+f"(d[11]), "+f"(d[12]), "+f"(d[13]), "+f"(d[14]), "+f"(d[15]),
        "+f"(d[16]), "+f"(d[17]), "+f"(d[18]), "+f"(d[19]), "+f"(d[20]), "+f"(d[21]), "+f"(d[22]), "+f"(d[23]),
        "+f"(d[24]), "+f"(d[25]), "+f"(d[26]), "+f"(d[27]), "+f"(d[28]), "+f"(d[29]), "+f"(d[30]), "+f"(d[31]),
        "+f"(d[32]), "+f"(d[33]), "+f"(d[34]), "+f"(d[35]), "+f"(d[36]), "+f"(d[37]), "+f"(d[38]), "+f"(d[39]),
        "+f"(d[40]), "+f"(d[41]), "+f"(d[42]), "+f"(d[43]), "+f"(d[44]), "+f"(d[45]), "+f"(d[46]), "+f"(d[47])
        : "l"(da), "l"(db));
}
__device__ __forceinline__ void wgmma_ss_n64(float* d, uint64_t da, uint64_t db) {
    asm volatile("wgmma.mma_async.sync.aligned.m64n64k16.f32.bf16.bf16 {"
        "%0, %1, %2, %3, %4, %5, %6, %7, %8, %9, %10, %11, %12, %13, %14, %15,"
        "%16, %17, %18, %19, %20, %21, %22, %23, %24, %25, %26, %27, %28, %29, %30, %31}, %32, %33, 1, 1, 1, 0, 1;\n"
        :
        "+f"(d[0]), "+f"(d[1]), "+f"(d[2]), "+f"(d[3]), "+f"(d[4]), "+f"(d[5]), "+f"(d[6]), "+f"(d[7]),
        "+f"(d[8]), "+f"(d[9]), "+f"(d[10]), "+f"(d[11]), "+f"(d[12]), "+f"(d[13]), "+f"(d[14]), "+f"(d[15]),
        "+f"(d[16]), "+f"(d[17]), "+f"(d[18]), "+f"(d[19]), "+f"(d[20]), "+f"(d[21]), "+f"(d[22]), "+f"(d[23]),
        "+f"(d[24]), "+f"(d[25]), "+f"(d[26]), "+f"(d[27]), "+f"(d[28]), "+f"(d[29]), "+f"(d[30]), "+f"(d[31])
        : "l"(da), "l"(db));
}
__device__ __forceinline__ void wgmma_rs_n128(float* d, const uint32_t* a, uint64_t db) {
    asm volatile("wgmma.mma_async.sync.aligned.m64n128k16.f32.bf16.bf16 {"
        "%0, %1, %2, %3, %4, %5, %6, %7, %8, %9, %10, %11, %12, %13, %14, %15,"
        "%16, %17, %18, %19, %20, %21, %22, %23, %24, %25, %26, %27, %28, %29, %30, %31,"
        "%32, %33, %34, %35, %36, %37, %38, %39, %40, %41, %42, %43, %44, %45, %46, %47,"
        "%48, %49, %50, %51, %52, %53, %54, %55, %56, %57, %58, %59, %60, %61, %62, %63}, {%64, %65, %66, %67}, %68, 1, 1, 1, 1;\n"
        :
        "+f"(d[0]), "+f"(d[1]), "+f"(d[2]), "+f"(d[3]), "+f"(d[4]), "+f"(d[5]), "+f"(d[6]), "+f"(d[7]),
        "+f"(d[8]), "+f"(d[9]), "+f"(d[10]), "+f"(d[11]), "+f"(d[12]), "+f"(d[13]), "+f"(d[14]), "+f"(d[15]),
        "+f"(d[16]), "+f"(d[17]), "+f"(d[18]), "+f"(d[19]), "+f"(d[20]), "+f"(d[21]), "+f"(d[22]), "+f"(d[23]),
        "+f"(d[24]), "+f"(d[25]), "+f"(d[26]), "+f"(d[27]), "+f"(d[28]), "+f"(d[29]), "+f"(d[30]), "+f"(d[31]),
        "+f"(d[32]), "+f"(d[33]), "+f"(d[34]), "+f"(d[35]), "+f"(d[36]), "+f"(d[37]), "+f"(d[38]), "+f"(d[39]),
        "+f"(d[40]), "+f"(d[41]), "+f"(d[42]), "+f"(d[43]), "+f"(d[44]), "+f"(d[45]), "+f"(d[46]), "+f"(d[47]),
        "+f"(d[48]), "+f"(d[49]), "+f"(d[50]), "+f"(d[51]), "+f"(d[52]), "+f"(d[53]), "+f"(d[54]), "+f"(d[55]),
        "+f"(d[56]), "+f"(d[57]), "+f"(d[58]), "+f"(d[59]), "+f"(d[60]), "+f"(d[61]), "+f"(d[62]), "+f"(d[63])
        : "r"(a[0]), "r"(a[1]), "r"(a[2]), "r"(a[3]), "l"(db));
}
__device__ __forceinline__ void wgmma_qk_f16_acc(float* d, const uint32_t* a, uint64_t db) {
    asm volatile("wgmma.mma_async.sync.aligned.m64n64k16.f32.f16.f16 {"
        "%0, %1, %2, %3, %4, %5, %6, %7, %8, %9, %10, %11, %12, %13, %14, %15,"
        "%16, %17, %18, %19, %20, %21, %22, %23, %24, %25, %26, %27, %28, %29, %30, %31}, {%32, %33, %34, %35}, %36, 1, 1, 1, 0;\n"
        :
        "+f"(d[0]), "+f"(d[1]), "+f"(d[2]), "+f"(d[3]), "+f"(d[4]), "+f"(d[5]), "+f"(d[6]), "+f"(d[7]),
        "+f"(d[8]), "+f"(d[9]), "+f"(d[10]), "+f"(d[11]), "+f"(d[12]), "+f"(d[13]), "+f"(d[14]), "+f"(d[15]),
        "+f"(d[16]), "+f"(d[17]), "+f"(d[18]), "+f"(d[19]), "+f"(d[20]), "+f"(d[21]), "+f"(d[22]), "+f"(d[23]),
        "+f"(d[24]), "+f"(d[25]), "+f"(d[26]), "+f"(d[27]), "+f"(d[28]), "+f"(d[29]), "+f"(d[30]), "+f"(d[31])
        : "r"(a[0]), "r"(a[1]), "r"(a[2]), "r"(a[3]), "l"(db));
}
__device__ __forceinline__ void wgmma_qk_bf16_zero(float* d, const uint32_t* a, uint64_t db) {
    asm volatile("wgmma.mma_async.sync.aligned.m64n64k16.f32.bf16.bf16 {"
        "%0, %1, %2, %3, %4, %5, %6, %7, %8, %9, %10, %11, %12, %13, %14, %15,"
        "%16, %17, %18, %19, %20, %21, %22, %23, %24, %25, %26, %27, %28, %29, %30, %31}, {%32, %33, %34, %35}, %36, 0, 1, 1, 0;\n"
        :
        "=f"(d[0]), "=f"(d[1]), "=f"(d[2]), "=f"(d[3]), "=f"(d[4]), "=f"(d[5]), "=f"(d[6]), "=f"(d[7]),
        "=f"(d[8]), "=f"(d[9]), "=f"(d[10]), "=f"(d[11]), "=f"(d[12]), "=f"(d[13]), "=f"(d[14]), "=f"(d[15]),
        "=f"(d[16]), "=f"(d[17]), "=f"(d[18]), "=f"(d[19]), "=f"(d[20]), "=f"(d[21]), "=f"(d[22]), "=f"(d[23]),
        "=f"(d[24]), "=f"(d[25]), "=f"(d[26]), "=f"(d[27]), "=f"(d[28]), "=f"(d[29]), "=f"(d[30]), "=f"(d[31])
        : "r"(a[0]), "r"(a[1]), "r"(a[2]), "r"(a[3]), "l"(db));
}
__device__ __forceinline__ void wgmma_pv(float* d, const uint32_t* a, uint64_t db) {
    asm volatile("wgmma.mma_async.sync.aligned.m64n24k16.f32.bf16.bf16 {"
        "%0, %1, %2, %3, %4, %5, %6, %7, %8, %9, %10, %11}, {%12, %13, %14, %15}, %16, 1, 1, 1, 1;\n"
        :
        "+f"(d[0]), "+f"(d[1]), "+f"(d[2]), "+f"(d[3]), "+f"(d[4]), "+f"(d[5]), "+f"(d[6]), "+f"(d[7]),
        "+f"(d[8]), "+f"(d[9]), "+f"(d[10]), "+f"(d[11])
        : "r"(a[0]), "r"(a[1]), "r"(a[2]), "r"(a[3]), "l"(db));
}

template <int N> __device__ __forceinline__ void wgmma_ss(float* d, uint64_t a, uint64_t b) {
    if (N == 128) wgmma_ss_n128(d, a, b);
    if (N == 96) wgmma_ss_n96(d, a, b);
    if (N == 64) wgmma_ss_n64(d, a, b);
}

#define OFF_R 131072
#define OFF_ONE 229376
#define OFF_BAR 229888
#define OFF_BIAS (OFF_BAR + 736)
#define OFF_G (OFF_BIAS + 1152)
#define SMEM_BYTES (OFF_G + 272)
#define SBD 1024u
#define B_X 0
#define B_F1 416
#define B_E1 64
#define B_XD 672
#define B_KV 160
#define B_F2 224
#define B_E2 256
#define B_T 288
#define B_G 360
#define B_G2 368
#define B_G3 376
#define B_SF 384
#define B_BI 400
#define B_DONE 112
#define B_DONE2 120

#define B_SF2 408
#define NR 6

#define PF 1
#define PFX 0
#define PACE 1
#define FSER 1
#define MERGE 1
#define EB 2
#define ANDM 0x4440
#define HOLD 8
#define TRIG 16
#define EXP_FKK 4
#define QSCALE 0.36067376022224085f
#define MAGIC 445.41763f
#define FORCE_IMAD
#define NMUFU 5
#define VSTEP ((uint64_t)((long long)32 - ((long long)32 << 16)))

#define XMASK 0x0D55u
#define KVMASK 0x1D55u
__host__ __device__ constexpr int strm_pos(int pass, int i) {
    if (pass == 1 || pass == 2) return 8 + 8 * pass + i;
    int n = 0;
    for (int p = 0; p < 16; p++)
        if ((int)((KVMASK >> p) & 1) == (pass == 3)) { if (n == i) return p; n++; }
    return 0;
}
__host__ __device__ constexpr uint32_t strm_code(int pass) {
    uint32_t c = 0;
    for (int i = 0; i < 7; i++) c |= (uint32_t)(strm_pos(pass, i + 1) - strm_pos(pass, i)) << (4 * i);
    return c;
}

template <int N, int SUB, int KST, int LBO, int SBO, int SWZ>
__device__ __forceinline__ void gemm_pass(float* acc, uint32_t bar, uint64_t dA, int lane, uint32_t pos, uint32_t code, int barNext, bool waitx, bool last) {
    uint32_t prev = 0, slot = pos % NR;
#pragma unroll 1
    for (int i = 0; i < 8; i++) {
        if (waitx) {
            mbar_wait(bar + B_X + 8 * i, 0);
            if (N == 96 && i == HOLD) bar_sync(4, 512);
        }
        mbar_wait(bar + B_F1 + 8 * pos, 0);
        const uint64_t dB = mkdesc(SBD + OFF_R, LBO, SBO, SWZ) + slot * 1024;
        wg_fence();
        wgmma_ss<N>(acc, dA, dB);
        wgmma_ss<N>(acc, dA + 2, dB + KST / 16);
        wg_commit();
        wg_wait<1>();
        if (i > 0 && lane < 2) mbar_arrive_cluster(prev, lane);
        wgmma_ss<N>(acc, dA + 4, dB + SUB / 16);
        wgmma_ss<N>(acc, dA + 6, dB + (SUB + KST) / 16);
        wg_commit();
        prev = last ? bar + B_XD + 8 * i : bar + B_E1 + 8 * slot;
        pos += code & 15;
        slot += code & 15;
        if (slot >= NR) slot -= NR;
        code >>= 4;
        dA += 1024;
    }
    if (barNext) bar_arrive(barNext, 512);
    wg_wait<0>();
    if (lane < 2) mbar_arrive_cluster(prev, lane);
    pin<N / 2>(acc);
}

__device__ __forceinline__ uint32_t lds32(uint32_t a) { uint32_t v; asm volatile("ld.shared.u32 %0, [%1];" : "=r"(v) : "r"(a)); return v; }
__device__ __forceinline__ bool elect() {
    uint32_t p;
    asm volatile("{\n.reg .pred p;\nelect.sync _|p, 0xffffffff;\nselp.u32 %0, 1, 0, p;\n}" : "=r"(p));
    return p;
}

template <int G0, int G1> __device__ __forceinline__ void gelu_pack(const float* acc, uint32_t bias, uint32_t* out) {
#pragma unroll
    for (int G = G0; G < G1; G++) {
        uint32_t* o = out + 8 * G;
#pragma unroll
        for (int j = 0; j < 4; j++) {
            float bv[2];
            asm volatile("ld.shared.v2.f32 {%0, %1}, [%2];" : "=f"(bv[0]), "=f"(bv[1]) : "r"(bias + G * 128 + j * 32));
            float y[4];
#pragma unroll
            for (int i = 0; i < 4; i++) {
                const float h = acc[16 * G + 4 * j + i] + bv[i & 1];
                const float z = h * fmaf(h * h, 0.035677408136300125f, 0.7978845608028654f);
                y[i] = fmaf(h, tanhf_(z), h);
            }
            o[j] = pk_bf16(y[0], y[1]);
            o[4 + j] = pk_bf16(y[2], y[3]);
        }
    }
}

__device__ __forceinline__ float norm_bound(const float* v, float sc) {
    uint32_t m = 0;
#pragma unroll
    for (int h = 0; h < 4; h++) {
        const float* u = v + 8 * h;
        m = max(m, __float_as_uint(fmaf(u[0], u[0], fmaf(u[1], u[1], fmaf(u[4], u[4], u[5] * u[5])))));
        m = max(m, __float_as_uint(fmaf(u[2], u[2], fmaf(u[3], u[3], fmaf(u[6], u[6], u[7] * u[7])))));
    }
#pragma unroll
    for (int o = 4; o < 32; o <<= 1) m = max(m, __shfl_xor_sync(0xffffffffu, m, o));
    float f = __uint_as_float(m);
    f += __shfl_xor_sync(0xffffffffu, f, 1);
    f += __shfl_xor_sync(0xffffffffu, f, 2);
    return f * sc;
}

__device__ __forceinline__ uint32_t exp2_pair(float a, float b, uint32_t m1) {
    const uint32_t w = __byte_perm(__float_as_uint(a), __float_as_uint(b), 0x6521);
    uint32_t m, r;
    asm("lop3.b32 %0, %1, 0x007f007f, 0x9f809f80, 0xEA;" : "=r"(m) : "r"(w));
    const uint32_t e = m * m1 + w;
    asm("fma.rn.bf16x2 %0, %1, %2, %3;" : "=r"(r) : "r"(w), "r"(m), "r"(e));
    return r;
}

__device__ __forceinline__ uint32_t exp2_pair_b(float a, float b) {
    const uint32_t w = __byte_perm(__float_as_uint(a), __float_as_uint(b), 0x6521);
    uint32_t m, r;
    asm("lop3.b32 %0, %1, 0x007f007f, 0xbf00bf00, 0xEA;" : "=r"(m) : "r"(w));
    asm("fma.rn.bf16x2 %0, %1, %2, %3;" : "=r"(r) : "r"(w), "r"(m), "r"(w & 0x7f807f80u));
    return r;
}
__device__ __forceinline__ void store_o(const float* o, uint4* dst, uint32_t par) {
    const float s0 = __fdividef(1.f, o[8]), s1 = __fdividef(1.f, o[10]);
    const uint32_t d0 = (pk_bf16(o[0] * s0, o[1] * s0) & ~1u) | par;
    asm volatile("{\n.reg .b128 t;\nmov.b128 t, {%0, %1, %2, %3};\nst.relaxed.gpu.global.b128 [%4], t;\n}" ::"r"(d0),
                 "r"(pk_bf16(o[2] * s1, o[3] * s1)), "r"(pk_bf16(o[4] * s0, o[5] * s0)), "r"(pk_bf16(o[6] * s1, o[7] * s1)), "l"(dst) : "memory");
}
__device__ __forceinline__ uint4 load_o(const uint4* src) {
    uint4 v;
    asm volatile("{\n.reg .b128 t;\nld.relaxed.gpu.global.b128 t, [%4];\nmov.b128 {%0, %1, %2, %3}, t;\n}"
                 : "=r"(v.x), "=r"(v.y), "=r"(v.z), "=r"(v.w) : "l"(src) : "memory");
    return v;
}
template <int N> __device__ __forceinline__ void fetch_o(uint4* v, const uint4* src, uint32_t ep) {
    int spins = 0;
    while (true) {
        uint32_t bad = 0;
#pragma unroll
        for (int k = 0; k < N; k++) bad |= v[k].x ^ ep;
        if (!__any_sync(0xffffffffu, (bad & 1) != 0)) break;
        if (++spins > (1 << 22)) __trap();
#pragma unroll
        for (int k = 0; k < N; k++)
            if (((v[k].x ^ ep) & 1) != 0) v[k] = load_o(src + k * 128);
    }
}
__device__ __forceinline__ uint32_t bmul2(uint32_t a, uint32_t b) { uint32_t r; asm("mul.rn.bf16x2 %0, %1, %2;" : "=r"(r) : "r"(a), "r"(b)); return r; }
__device__ __forceinline__ void sts32(uint32_t a, uint32_t v) { asm volatile("st.shared.u32 [%0], %1;" ::"r"(a), "r"(v) : "memory"); }
__device__ __forceinline__ void stage_o(const uint4* v, uint32_t a0, uint32_t g0, uint32_t g1, int lane) {
#pragma unroll
    for (int i = 0; i < 4; i++)
        asm volatile("stmatrix.sync.aligned.m8n8.x4.shared.b16 [%0], {%1, %2, %3, %4};" ::"r"(a0 + (((i * 2 + (lane >> 4)) ^ (lane & 7)) << 4)),
                     "r"(bmul2(v[i].x, g0)), "r"(bmul2(v[i].y, g1)), "r"(bmul2(v[i].z, g0)), "r"(bmul2(v[i].w, g1)) : "memory");
    asm volatile("fence.proxy.async.shared::cta;" ::: "memory");
}
__device__ __forceinline__ void load_q(uint32_t* q, int h, int row, int t) {
    const uint8_t* p = gQ + (size_t)h * (SEQ * 32) + (size_t)row * 32 + t * 4;
    q[0] = __ldcg((const uint32_t*)p); q[1] = __ldcg((const uint32_t*)(p + 256));
    q[2] = __ldcg((const uint32_t*)(p + 16)); q[3] = __ldcg((const uint32_t*)(p + 272));
}

template <int NT>
__device__ __forceinline__ void proj16(float (*c)[8], const __nv_bfloat16* x, const __nv_bfloat16* w, int row0, int rstep, int col, int g, int t) {
#pragma unroll
    for (int i = 0; i < NT; i++)
#pragma unroll
        for (int j = 0; j < 8; j++) c[i][j] = 0.f;
    const unsigned short* wu = (const unsigned short*)w;
#pragma unroll 1
    for (int k = 0; k < DM; k += 16) {
        uint32_t b[4];
#pragma unroll
        for (int j = 0; j < 4; j++) {
            const int kr = k + 2 * t + (j & 1) * 8, cc = col + g + (j >> 1) * 8;
            b[j] = (uint32_t)wu[(size_t)kr * (3 * DM) + cc] | ((uint32_t)wu[(size_t)(kr + 1) * (3 * DM) + cc] << 16);
        }
#pragma unroll
        for (int i = 0; i < NT; i++) {
            const __nv_bfloat16* xp = x + (size_t)(row0 + i * rstep + g) * DM + k + 2 * t;
            const uint32_t a0 = *(const uint32_t*)xp, a1 = *(const uint32_t*)(xp + 8 * DM);
            const uint32_t a2 = *(const uint32_t*)(xp + 8), a3 = *(const uint32_t*)(xp + 8 * DM + 8);
#pragma unroll
            for (int j = 0; j < 2; j++)
                asm volatile("mma.sync.aligned.m16n8k16.row.col.f32.bf16.bf16.f32 {%0,%1,%2,%3}, {%4,%5,%6,%7}, {%8,%9}, {%0,%1,%2,%3};"
                             : "+f"(c[i][4 * j]), "+f"(c[i][4 * j + 1]), "+f"(c[i][4 * j + 2]), "+f"(c[i][4 * j + 3])
                             : "r"(a0), "r"(a1), "r"(a2), "r"(a3), "r"(b[2 * j]), "r"(b[2 * j + 1]));
        }
    }
}

struct Maps { CUtensorMap x, kv, q, f1, f3, h, w2, wo, hs, kvs; };

template <int I0, int I1>
__device__ __forceinline__ void issue_stream(const Maps& tm, uint32_t sb, uint32_t rank, int nb, int mb) {
    const uint32_t bar = sb + OFF_BAR;
    const uint32_t dst = sb + OFF_R;
    const int kr = rank * 32;
#pragma unroll
    for (int it = I0; it < I1; it++) {
        const int s = it % NR;
        const uint32_t fb = bar + B_F1 + 8 * it;
        if (it >= 24 + NR) mbar_wait(bar + B_XD + 8 * (it - 24 - NR), 0);
        else if (it >= NR) mbar_wait(bar + B_E1 + 8 * s, ((it / NR) - 1) & 1);
        const int nkv = __builtin_popcount(KVMASK & ((1u << it) - 1));
        if (it < 16 && ((KVMASK >> it) & 1)) {
            tma3d_mc(dst + s * 16384 + rank * 8192, &tm.kv, nb * 64, nkv * 64 + kr, 1, fb);
        } else if (it < 16) {
            tma3d_mc(dst + s * 16384 + rank * 6144, &tm.q, 0, (it - nkv) * 64 + kr, nb * 2, fb);
            tma3d_mc(dst + s * 16384 + rank * 6144 + 4096, &tm.f1, 0, (it - nkv) * 64 + kr, nb * 7, fb);
        } else {
            tma3d_mc(dst + s * 16384 + rank * 6144, &tm.f3, 0, (it & 7) * 64 + kr, nb * 7 + (it < 24 ? 1 : 4), fb);
        }
        if ((XMASK >> it) & 1) {
            const int xc = 1 + __builtin_popcount(XMASK & ((1u << it) - 1));
            tma2d(sb + xc * 16384, &tm.x, xc * 64, mb * 128, bar + B_X + 8 * xc);
        }
    }
}

__global__ void __cluster_dims__(2, 1, 1) __launch_bounds__(640, 1)
fused_kernel(const __grid_constant__ Maps tm, const __nv_bfloat16* __restrict__ x, const __nv_bfloat16* __restrict__ wqkv,
             const __nv_bfloat16* __restrict__ wo, const __nv_bfloat16* __restrict__ w1, const __nv_bfloat16* __restrict__ b1,
             const __nv_bfloat16* __restrict__ w2, const __nv_bfloat16* __restrict__ b2, const __nv_bfloat16* __restrict__ gate,
             __nv_bfloat16* __restrict__ out, const uint32_t m1) {
    const uint32_t sb = smem_u32(smem_raw);
    const uint32_t bar = sb + OFF_BAR;
    const int tid = threadIdx.x, lane = tid & 31;
    const int warp = __shfl_sync(0xffffffffu, tid >> 5, 0);
    const uint32_t rank = cluster_rank();
    const int cl = blockIdx.x >> 1;
    const int nb = cl & 7, mb = (cl >> 3) * 2 + rank;
    const int g = lane >> 2, t = lane & 3;

    const int cb = nb & 3, rb = mb * 2 + (nb >> 2);
    const int rn = (mb >> 1) & 1;
    if (tid == 0) TLM(0, 0);
    TL_INIT();
    if (tid == 512) {
        for (int i = 0; i < 8; i++) { mbar_init(bar + B_X + 8 * i, 1); mbar_init(bar + B_KV + 8 * i, 1); mbar_init(bar + B_T + 8 * i, i < 4 ? 1 : 5); mbar_init(bar + B_XD + 8 * i, 16); }
        for (int i = 0; i < NR; i++) mbar_init(bar + B_E1 + 8 * i, 16);
        for (int i = 0; i < 4; i++) { mbar_init(bar + B_F2 + 8 * i, 1); mbar_init(bar + B_E2 + 8 * i, 8); }
        asm volatile("fence.mbarrier_init.release.cluster;" ::: "memory");
    } else if (tid == 608) {
        for (int i = 0; i < 32; i++) mbar_init(bar + B_F1 + 8 * i, 1);
        mbar_init(bar + B_G, 1);
        mbar_init(bar + B_DONE, 16);
        mbar_init(bar + B_DONE2, TRIG);
        for (int i = 0; i < 3; i++) mbar_init(bar + B_SF + 8 * i, i == 1 ? 2 : 1);
        mbar_init(bar + B_SF2, 2);
        mbar_init(bar + B_G3, 1);
        mbar_init(bar + B_G2, 4);
        asm volatile("fence.mbarrier_init.release.cluster;" ::: "memory");
    }
    __syncwarp();
    asm volatile("barrier.cluster.arrive.relaxed.aligned;" ::: "memory");
    if (warp == 19) mbar_expect(bar + B_F1 + 8 * lane, ((KVMASK >> lane) & 1) ? 16384 : 12288);
    if (warp == 16 && lane < 24) mbar_expect(bar + (lane < 8 ? B_X : lane < 16 ? B_KV - 64 : B_T - 128) + 8 * lane, 16384);
    if (tid == 512) {
        tma2d(sb, &tm.x, 0, mb * 128, bar + B_X);
    } else if (tid == 544) {
        map_prefetch(&tm.kv);
        l2_prefetch((const uint8_t*)wqkv + (size_t)blockIdx.x * 3072, 3072);
        l2_prefetch((const uint8_t*)w1 + (size_t)blockIdx.x * 1792, 1792);
        map_prefetch(&tm.q); map_prefetch(&tm.f1); map_prefetch(&tm.f3);
    }
    if ((sb & 0xFFFFFF) != SBD) __trap();
    __syncwarp();
    asm volatile("barrier.cluster.wait.aligned;" ::: "memory");
    if (tid == 512) issue_stream<0, NR>(tm, sb, rank, nb, mb);
    if (tid == 0) { TLM(0, 1); TLC(0, 30); }

    if (warp < 16) {
        const int wg = warp >> 2;
        const int h = cl >> 1, qd = (cl & 1) * 2 + rank;
        const int flip = (h >> 2) & 1;
        uint32_t q[4];
        {
            const int w8 = warp & 7;
            const int T = mb * 8 + w8, row0 = T * 16 + g;
            const uint64_t dA0 = mkdesc(SBD + (wg & 1) * 8192, 16, 1024, 1);
            if (wg < 2) {
                float acc[64];
#pragma unroll
                for (int i = 0; i < 64; i++) acc[i] = 0.f;
                gemm_pass<128, 8192, 2048, 4096, 1024, 1>(acc, bar, dA0, lane, strm_pos(3, 0), strm_code(3), HOLD < 8 ? 4 : 0, true, false);
                if (tid == 0) TLM(0, 2);
                {
                    const float km = norm_bound(acc, 1.f);
                    uint32_t pv[16];
#pragma unroll
                    for (int i = 0; i < 16; i++) { pv[i] = pk_bf16(acc[32 + 2 * i], acc[33 + 2 * i]); }
                    uint32_t big = 0;
#pragma unroll
                    for (int i = 0; i < 16; i++) big |= pv[i] & (pv[i] << 1);
                    const bool vbig = __any_sync(0xffffffffu, (big & 0x40004000u) != 0);
                    if (lane == 0) gN[1024 + nb * 128 + T] = vbig ? 3.0e38f : km;
                    const float gm = g == 0 ? 0.f : -1.f;
                    const uint32_t kp = sb + OFF_R + 12288 + (w8 >> 2) * 1024 + g * 128 + ((((w8 & 3) * 2 + ((t >> 1) ^ (w8 >> 2))) ^ g) << 4) + (t & 1) * 8;
                    uint8_t* vp = gKV + (size_t)(nb * 4) * (SEQ * 64) + 65536 + (((T >> 6) * 16 + 2 * g) * 64 + (T & 63)) * 32 + ((t * 8) ^ ((w8 >> 2) << 4));
                    bar_sync(9, 256);
#pragma unroll
                    for (int hh = 0; hh < 4; hh++) {
                        const float* v = acc + 8 * hh;
                        float p0 = __shfl_up_sync(0xffffffffu, v[2], 4), p1 = __shfl_up_sync(0xffffffffu, v[3], 4);
                        float p2 = __shfl_up_sync(0xffffffffu, v[6], 4), p3 = __shfl_up_sync(0xffffffffu, v[7], 4);
                        sts64(kp + hh * 16384, pk_f16(fmaf(p0, gm, v[0]), fmaf(p1, gm, v[1])), pk_f16(fmaf(p2, gm, v[4]), fmaf(p3, gm, v[5])));
                        sts64(kp + hh * 16384 + 2048, pk_f16(v[2] - v[0], v[3] - v[1]), pk_f16(v[6] - v[4], v[7] - v[5]));
                        const uint32_t* u = pv + 4 * hh;
                        if (hh < 2) {
                            sts64(kp + (4 + hh) * 16384, u[0], u[2]);
                            sts64(kp + (4 + hh) * 16384 + 2048, u[1], u[3]);
                        } else {
                            *(uint2*)(vp + (size_t)hh * (SEQ * 64)) = make_uint2(u[0], u[2]);
                            *(uint2*)(vp + (size_t)hh * (SEQ * 64) + 2048) = make_uint2(u[1], u[3]);
                        }
                    }
                }
                asm volatile("fence.proxy.async.shared::cta;" ::: "memory");
                bar_arrive(10, 288);
                if (tid == 0) TLM(0, 3);
            }
#pragma unroll 1
            for (int p = wg < 2 ? 1 : 0; p < 3; p += 2) {
                float acc[48];
#pragma unroll
                for (int i = 0; i < 48; i++) acc[i] = 0.f;
                pin<48>(acc);
                if (p) bar_sync(5 + p, 512);
                gemm_pass<96, 6144, 1024, 2048, 512, 2>(acc, bar, dA0, lane, p == 0 ? strm_pos(0, 0) : 8 + 8 * p, p == 0 ? strm_code(0) : strm_code(1), p < 2 ? 6 + p : 0, p == 0, p == 2);
                if ((tid & 255) == 0) TLM(0, 4 + 2 * p);
                const uint32_t hp = sb + OFF_R + (p == 2 ? 0 : 12288) + (wg & 1) * 16384 + ((warp & 3) * 16 + g) * 64 + t * 16;
                const uint32_t bp = sb + OFF_BIAS + p * 384 - 256 + t * 8;
                uint32_t ho[24];
                mbar_wait(bar + B_BI, 0);
                if (p == 0) {
                    const float qm = norm_bound(acc, QSCALE * QSCALE);
                    if (lane == 0) gN[nb * 128 + T] = qm;
                    uint8_t* qp = gQ + (size_t)(nb * 4) * (SEQ * 32) + (size_t)row0 * 32 + t * 8;
#pragma unroll
                    for (int hh = 0; hh < 4; hh++) {
                        const float* v = acc + 8 * hh;
                        *(uint2*)(qp + hh * (SEQ * 32)) = make_uint2(pk_f16(v[0] * QSCALE, v[1] * QSCALE), pk_f16(v[4] * QSCALE, v[5] * QSCALE));
                        *(uint2*)(qp + hh * (SEQ * 32) + 256) = make_uint2(pk_f16(v[2] * QSCALE, v[3] * QSCALE), pk_f16(v[6] * QSCALE, v[7] * QSCALE));
                    }
                    bar_arrive(12, 288);
                } else {
                    gelu_pack<0, 2>(acc, bp, ho);
                    pin<16>(ho);
                    mbar_wait(bar + B_G, 0);
                    load_q(q, h, qd * 512 + flip * 256 + warp * 16 + g, t);
                }
                gelu_pack<2, 3>(acc, bp, ho);
                pin<8>(ho + 16);
                if (p == 2) bar_sync(9, 256);
                else mbar_wait(bar + B_SF + 8 * p, 0);
                if (p) {
#pragma unroll
                    for (int i = 0; i < 4; i++) sts128(hp + (i >> 1) * 32768 + (i & 1) * 512, ho + 4 * i);
                }
                sts128(hp + 65536, ho + 16);
                sts128(hp + 65536 + 512, ho + 20);
                asm volatile("fence.proxy.async.shared::cta;" ::: "memory");
                bar_arrive(p == 1 ? 14 : 11, 288);
                if ((tid & 255) == 0) TLM(0, 5 + 2 * p);
            }
        }
        uint32_t ep = 2;
        uint4* const op = gO + ((qd * 8 + wg) * NH + h) * 128 + (tid & 127);
        const uint64_t kd0 = mkdesc(SBD, 16, 256, 3);
        const uint64_t vd0 = mkdesc(SBD + 8192, OFF_ONE - 8192, 256, 3);
        {
            float o[12];
            uint32_t qn[4];
#pragma unroll 1
            for (int rh = 0; rh < 4; rh++) {
                if (rh == 1) {
                    mbar_wait(bar + B_G3, 0);
                    ep = lds32(sb + OFF_G + 256);
                    if (!(ep & 2)) break;
                    load_q(qn, h, qd * 512 + (flip ^ 1) * 256 + warp * 16 + g, t);
                }
                if (rh == 3 && lane == 0) mbar_arrive(bar + B_DONE);
                if (!(rh & 1)) {
#pragma unroll
                    for (int i = 0; i < 12; i++) o[i] = 0.f;
                }
                uint64_t kd = kd0 + (rh & 1) * 4096, vd = vd0 + (rh & 1) * (128 * VSTEP);
                uint32_t kvb = bar + B_KV + (rh & 1) * 32;
                float s[32];
#pragma unroll
                for (int i = 0; i < 32; i++) s[i] = i < 2 * NMUFU ? 0.f : ((ANDM >> (i >> 1)) & 1) ? MAGIC - 63.f : MAGIC;
                if ((tid & 255) == 0) TLM(1, (tid >> 8) * 4 + rh);
#pragma unroll 1
                for (int c = 0; c < 4; c++) {
                    mbar_wait(kvb, 0);
                    kvb += 8;
#pragma unroll
                    for (int j = 0; j < 4; j++) {
                        uint32_t p[16];
                        if (!MERGE || j == 0) {
                            wg_fence();
                            wgmma_qk_f16_acc(s, q, kd + j * 128);
                            wg_commit();
                        }
                        wg_wait<0>();
                        pin<32>(s);
#pragma unroll
                        for (int i = 0; i < 16; i++)
                            p[i] = i < NMUFU ? pk_bf16(ex2f(s[2 * i]), ex2f(s[2 * i + 1])) : ((ANDM >> i) & 1) ? exp2_pair_b(s[2 * i], s[2 * i + 1]) : exp2_pair(s[2 * i], s[2 * i + 1], m1);
                        pin<16>(p);
                        wg_fence();
#pragma unroll
                        for (int u = 0; u < 4; u++) {
                            if (MERGE && j < 3 && u == 5 - MERGE) wgmma_qk_f16_acc(s, q, kd + (j + 1) * 128);
                            wgmma_pv(o, p + 4 * u, vd + (j * 4 + u) * VSTEP);
                        }
                        if (MERGE == 1 && j < 3) wgmma_qk_f16_acc(s, q, kd + (j + 1) * 128);
                        wg_commit();
                    }
                    kd += 1024;
                    vd += 32 * VSTEP;
                }
                wg_wait<0>();
                pin<12>(o);
                if (rh & 1) {
                    if ((tid & 127) == 0 && rh == 3) TLM(1, 8 + wg);
                    store_o(o, op + ((rh >> 1) ^ flip) * (4 * NH * 128), ep & 1);
#pragma unroll
                    for (int i = 0; i < 4; i++) q[i] = qn[i];
                }
            }
            if (tid == 0) { TLM(1, 12); TLC(0, 31); }
        }
        if (!(ep & 2)) {
            bar_sync(8, 512);
            for (int c = 0; c < 8; c++) mbar_wait(bar + B_KV + 8 * c, 0);
            {
                float kc[8][8];
                proj16<8>(kc, x, wqkv, warp * 16, 256, DM + h * 16, g, t);
#pragma unroll
                for (int i = 0; i < 8; i++) {
                    const int T = warp + i * 16;
                    const int pos = ((T >> 6) * 16 + 2 * g) * 64 + (T & 63);
                    const uint32_t a = sb + (pos >> 8) * 16384 + (pos & 255) * 32 + t * 4, sw = ((T >> 2) & 1) << 4;
                    asm volatile("st.shared.u32 [%0], %1;" ::"r"(a + sw), "r"(pk_bf16(kc[i][0], kc[i][1])) : "memory");
                    asm volatile("st.shared.u32 [%0], %1;" ::"r"(a + (sw ^ 16)), "r"(pk_bf16(kc[i][4], kc[i][5])) : "memory");
                    asm volatile("st.shared.u32 [%0], %1;" ::"r"(a + 2048 + sw), "r"(pk_bf16(kc[i][2], kc[i][3])) : "memory");
                    asm volatile("st.shared.u32 [%0], %1;" ::"r"(a + 2048 + (sw ^ 16)), "r"(pk_bf16(kc[i][6], kc[i][7])) : "memory");
                }
                asm volatile("fence.proxy.async.shared::cta;" ::: "memory");
                bar_sync(8, 512);
            }
#pragma unroll 1
            for (int r = 0; r < 2; r++) {
                const int row = qd * 512 + (r ^ flip) * 256 + warp * 16 + g;
                {
                    float qc[1][8];
                    proj16<1>(qc, x, wqkv, row - g, 0, h * 16, g, t);
#pragma unroll
                    for (int i = 0; i < 4; i++) q[i] = pk_bf16(qc[0][2 * i] * QSCALE, qc[0][2 * i + 1] * QSCALE);
                }
                float o[12];
#pragma unroll
                for (int i = 0; i < 12; i++) o[i] = 0.f;
                float m0 = -INFINITY, m1 = -INFINITY;
#pragma unroll 1
                for (int j = 0; j < 32; j++) {
                    const uint64_t kd = kd0 + (j >> 2) * 1024 + (j & 3) * 128, vd = vd0 + ((j >> 2) * 32 + (j & 3) * 4) * VSTEP;
                    float s[32];
                    uint32_t p[16];
                    wg_fence();
                    wgmma_qk_bf16_zero(s, q, kd);
                    wg_commit();
                    wg_wait<0>();
                    pin<32>(s);
                    pin<12>(o);
                    float n0 = m0, n1 = m1;
#pragma unroll
                    for (int i = 0; i < 8; i++) {
                        n0 = fmaxf(n0, fmaxf(s[4 * i], s[4 * i + 1]));
                        n1 = fmaxf(n1, fmaxf(s[4 * i + 2], s[4 * i + 3]));
                    }
                    n0 = fmaxf(n0, __shfl_xor_sync(0xffffffffu, n0, 1));
                    n1 = fmaxf(n1, __shfl_xor_sync(0xffffffffu, n1, 1));
                    n0 = fmaxf(n0, __shfl_xor_sync(0xffffffffu, n0, 2));
                    n1 = fmaxf(n1, __shfl_xor_sync(0xffffffffu, n1, 2));
                    const float c0 = ex2f(m0 - n0), c1 = ex2f(m1 - n1);
                    m0 = n0;
                    m1 = n1;
#pragma unroll
                    for (int i = 0; i < 3; i++) { o[4 * i] *= c0; o[4 * i + 1] *= c0; o[4 * i + 2] *= c1; o[4 * i + 3] *= c1; }
#pragma unroll
                    for (int i = 0; i < 8; i++) {
                        p[2 * i] = pk_bf16(ex2f(s[4 * i] - m0), ex2f(s[4 * i + 1] - m0));
                        p[2 * i + 1] = pk_bf16(ex2f(s[4 * i + 2] - m1), ex2f(s[4 * i + 3] - m1));
                    }
                    pin<16>(p);
                    pin<12>(o);
                    wg_fence();
#pragma unroll
                    for (int u = 0; u < 4; u++) wgmma_pv(o, p + 4 * u, vd + u * VSTEP);
                    wg_commit();
                }
                wg_wait<0>();
                pin<12>(o);
                store_o(o, op + (r ^ flip) * (4 * NH * 128), ep & 1);
                if (r == 1 && lane == 0) mbar_arrive(bar + B_DONE);
            }
        }
        if (lane == 0 && warp >= 16 - TRIG) mbar_arrive(bar + B_DONE2);
        {
            const uint4* src = gO + (rb * NH + (wg * 2 + (rn ^ 1)) * 4) * 128 + (tid & 127);
            uint4 v[4];
#pragma unroll
            for (int i = 0; i < 4; i++) v[i] = load_o(src + i * 128);
            mbar_wait(bar + B_G2, 0);
            const int lr = (warp & 3) * 16;
            const uint32_t g0 = lds32(sb + OFF_G + (lr + g) * 4), g1 = lds32(sb + OFF_G + (lr + g) * 4 + 32);
            fetch_o<4>(v, src, ep);
            stage_o(v, sb + OFF_R + 65536 + wg * 8192 + (lr + (lane & 15)) * 128, g0, g1, lane);
            __syncwarp();
            if (lane == 0) mbar_arrive(bar + B_T + 32 + 8 * wg);
            if ((tid & 127) == 0) TLM(1, 20 + wg);
        }
    } else {
        if (warp == 16) {
            if (lane == 0) {
                issue_stream<NR, 32>(tm, sb, rank, nb, mb);
                mbar_wait(bar + B_SF2, 0);
#pragma unroll
                for (int s = 0; s < 4; s++) {
                    mbar_expect(bar + B_F2 + 8 * s, 24576);
                    tma5d_mc(sb + OFF_R + s * 24576 + 8192 + rank * 8192, &tm.w2, cb * 128 + rank * 64, s * 2, bar + B_F2 + 8 * s);
                }
                cnt_wait(gCntH + mb * 32, epoch() * 8);
                asm volatile("fence.proxy.async.global;" ::: "memory");
                TLM(1, 13);
#pragma unroll
                for (int s = 0; s < 4; s++) tma2d(sb + OFF_R + s * 24576, &tm.h, s * 64, rb * 64, bar + B_F2 + 8 * s);
            }
        } else if (warp == 17) {
            {
                uint32_t bv[4], b2v[2];
#pragma unroll
                for (int i = 0; i < 4; i++) bv[i] = lane + 32 * i < 112 ? *(const uint32_t*)(b1 + nb * 224 + (lane + 32 * i) * 2) : 0;
#pragma unroll
                for (int i = 0; i < 2; i++) b2v[i] = *(const uint32_t*)(b2 + cb * 128 + (lane + 32 * i) * 2);
#pragma unroll
                for (int i = 0; i < 4; i++) {
                    sts32(sb + OFF_ONE + (lane + 32 * i) * 4, 0x3f803f80u);
                    if (lane + 32 * i < 112) sts64(sb + OFF_BIAS + (lane + 32 * i) * 8, bv[i] << 16, bv[i] & 0xffff0000u);
                }
#pragma unroll
                for (int i = 0; i < 2; i++) sts32(sb + OFF_BIAS + 896 + (lane + 32 * i) * 4, b2v[i]);
                asm volatile("fence.proxy.async.shared::cta;" ::: "memory");
                __syncwarp();
                if (lane == 0) mbar_arrive(bar + B_BI);
            }
            mbar_wait(bar + B_X + 8 * PFX, 0);
            if (lane == 0) {
                l2_prefetch((const uint8_t*)wqkv + 128 * 3072 + (size_t)blockIdx.x * 9216, 9216);
                l2_prefetch((const uint8_t*)w1 + (size_t)blockIdx.x * 14336, 14336);
            }
            mbar_wait(bar + B_X + 8 * 7, 0);
            if (lane == 0) {
                l2_prefetch((const uint8_t*)w2 + (size_t)blockIdx.x * 14336, 14336);
                l2_prefetch((const uint8_t*)wo + (size_t)blockIdx.x * 4096, 4096);
                map_prefetch(&tm.h); map_prefetch(&tm.w2); map_prefetch(&tm.wo); map_prefetch(&tm.hs); map_prefetch(&tm.kvs);
                TLM(0, 11);
            }
            bar_sync(10, 288);
            if (lane == 0) {
#pragma unroll 1
                for (int b = 5; b >= 0; b--) {
                    tma5d_st(&tm.kvs, sb + OFF_R + 12288 + b * 16384, (mb >> 3) * 8, (mb & 7) * 2, nb * 8 + (b < 4 ? 2 * b : 2 * b - 7));
                    asm volatile("cp.async.bulk.commit_group;\ncp.async.bulk.wait_group.read %0;" ::"n"(PACE) : "memory");
                    if (b == 4 - PACE) mbar_arrive(bar + B_SF);
                }
                asm volatile("cp.async.bulk.wait_group.read 0;" ::: "memory");
                mbar_arrive(bar + B_SF + 8);
            }
            __syncwarp();
            bar_sync(12, 288);
            if (lane == 0) {
                asm volatile("cp.async.bulk.wait_group 0;\nfence.proxy.async.global;" ::: "memory");
                cnt_add(gCntQ + nb * 32);
                TLM(0, 13);
            }
        } else {
            {
                const int r0 = mb * 128 + nb * 16 + (warp - 18) * 8;
                uint4 xv[16];
#pragma unroll
                for (int i = 0; i < 16; i++) xv[i] = *(const uint4*)(x + (size_t)(r0 + (i >> 1)) * DM + (i & 1) * 256 + lane * 8);
                const uint4 ga = *(const uint4*)(gate + lane * 8), gb = *(const uint4*)(gate + 256 + lane * 8);
                float z[8];
#pragma unroll
                for (int r = 0; r < 8; r++) z[r] = dot8(xv[2 * r], ga) + dot8(xv[2 * r + 1], gb);
#pragma unroll
                for (int w = 4; w >= 1; w >>= 1)
#pragma unroll
                    for (int r = 0; r < w; r++) {
                        const bool up = lane & w;
                        z[r] = (up ? z[r + w] : z[r]) + __shfl_xor_sync(0xffffffffu, up ? z[r] : z[r + w], w);
                    }
                z[0] += __shfl_xor_sync(0xffffffffu, z[0], 8);
                z[0] += __shfl_xor_sync(0xffffffffu, z[0], 16);
                if (lane < 8) gG[r0 + lane] = 1.f / (1.f + __expf(-z[0]));
                if (tid == 576) TLM(0, 12);
            }
            if (warp == 19) {
#pragma unroll 1
                for (int e = 0; e < 3; e++) {
                    bar_sync(e == 1 ? 14 : 11, 288);
                    if (lane == 0) {
#pragma unroll 1
                        for (int b = e == 0 ? 4 : 0; b < 6; b++) {
                            tma3d_st(&tm.hs, sb + OFF_R + (e == 2 ? 0 : 12288) + b * 16384, 0, mb * 128 + (b & 1) * 64, nb * 7 + e * 3 - 2 + (b >> 1));
                            asm volatile("cp.async.bulk.commit_group;\ncp.async.bulk.wait_group.read %0;" ::"n"(PACE) : "memory");
                        }
                        asm volatile("cp.async.bulk.wait_group.read 0;" ::: "memory");
                        if (e == 0) mbar_arrive(bar + B_SF + 8);
                        if (e == 2) { mbar_arrive_cluster(bar + B_SF2, 0); mbar_arrive_cluster(bar + B_SF2, 1); }
                    }
                    __syncwarp();
                }
                bar_sync(13, 64);
                if (lane == 0) {
                    asm volatile("cp.async.bulk.wait_group 0;\nfence.proxy.async.global;" ::: "memory");
                    cnt_add(gCntH + mb * 32);
                    TLM(0, 15);
                }
            } else {
                bar_arrive(13, 64);
                const int h = cl >> 1, qd = (cl & 1) * 2 + rank;
                const uint32_t ep = epoch();
                if (lane == 0) {
                    cnt_wait(gCntQ + (h >> 2) * 32, ep * 16);
                    mbar_arrive(bar + B_G);
                    TLM(0, 14);
                    asm volatile("fence.proxy.async.global;" ::: "memory");
#pragma unroll
                    for (int c = 0; c < 2; c++) {
                        mbar_wait(bar + B_XD + 8 * c, 0);
                        bulk_mc(sb + c * 16384 + rank * 8192, gKV + (size_t)h * (SEQ * 64) + rank * 65536 + c * 8192, 8192, bar + B_KV + 8 * c);
                    }
                }
                __syncwarp();
            const int hb = h >> 2;
            const uint4 kq = __ldcg((const uint4*)(gN + 1024 + hb * 128 + lane * 4));
            const float qq = ldcg_f(gN + hb * 128 + qd * 32 + lane);
            const float kf = __uint_as_float(__reduce_max_sync(0xffffffffu, max(max(kq.x, kq.y), max(kq.z, kq.w))));
            const float qf = __uint_as_float(__reduce_max_sync(0xffffffffu, __float_as_uint(qq)));
            if (lane == 0) {
                sts32(sb + OFF_G + 256, (ep & 1) | ((kf <= 1.0e6f) && (qf <= 1.0e6f) && (kf * qf <= 2300.f) ? 2 : 0));
                mbar_arrive(bar + B_G3);
                TLM(0, 16);
#pragma unroll
                for (int c = 2; c < 8; c++) {
                    mbar_wait(bar + B_XD + 8 * c, 0);
                    bulk_mc(sb + c * 16384 + rank * 8192, gKV + (size_t)h * (SEQ * 64) + rank * 65536 + c * 8192, 8192, bar + B_KV + 8 * c);
                }
                TLM(0, 10);
            }
            }
        }
        __syncwarp();
        float acc[64];
#pragma unroll
        for (int i = 0; i < 64; i++) acc[i] = 0.f;
#pragma unroll 1
        for (int io = 0; io < 7; io++) {
#pragma unroll
            for (int s = 0; s < 4; s++) {
                const int it = io * 4 + s;
                mbar_wait(bar + B_F2 + 8 * s, io & 1);
                if (tid == 512 && s == 0 && (io == 0 || io == 4)) TLM(1, 14 + io / 4);
                const uint64_t dA = mkdesc(SBD + OFF_R + s * 24576, 16, 1024, 1);
                const uint64_t dB = mkdesc(SBD + OFF_R + s * 24576 + 8192, 8192, 1024, 1);
                wg_fence();
#pragma unroll
                for (int kk = 0; kk < EXP_FKK; kk++) {
                    wgmma_ss_n128(acc, dA + kk * 2, dB + kk * 128);
                    if (kk < 3 && (FSER != 3 || kk == 1)) {
                        wg_commit();
                        wg_wait<0>();
                    }
                }
                wg_commit();
                if (warp < 18 && it >= 2 && it < 26) {
                    const int s2 = (s + 2) & 3;
                    mbar_wait(bar + B_E2 + 8 * s2, (io - (s < 2)) & 1);
                    if (elect()) {
                        if (warp == 16) {
                            mbar_expect(bar + B_F2 + 8 * s2, 24576);
                            tma5d_mc(sb + OFF_R + s2 * 24576 + 8192 + rank * 8192, &tm.w2, cb * 128 + rank * 64, it * 2 + 4, bar + B_F2 + 8 * s2);
                        } else {
                            asm volatile("fence.proxy.async.global;" ::: "memory");
                            tma2d(sb + OFF_R + s2 * 24576, &tm.h, it * 64 + 128, rb * 64, bar + B_F2 + 8 * s2);
                        }
                    }
                    __syncwarp();
                }
                wg_wait<1>();
                if (it >= 1 && lane < 2) mbar_arrive_cluster(bar + B_E2 + 8 * ((s + 3) & 3), lane);
            }
        }
        wg_wait<0>();
        if (lane < 2) mbar_arrive_cluster(bar + B_E2 + 8 * 3, lane);
        pin<64>(acc);
        if (tid == 576) gEpoch[blockIdx.x] = epoch();
        if (warp == 16) {
            if (lane == 0) TLM(1, 16);
            for (int s = 0; s < 4; s++) mbar_wait(bar + B_E2 + 8 * s, 0);
            if (elect()) {
#pragma unroll
                for (int i = 0; i < 4; i++)
                    tma5d_mc(sb + OFF_R + i * 16384 + rank * 8192, &tm.wo, cb * 128 + rank * 64, (i * 2 + rn) * 4, bar + B_T + 8 * i);
            }
            __syncwarp();
        }
        uint32_t pa;
        {
            const int lr = (warp - 16) * 16 + g;
            pa = pk_bf16(ldcg_f(gG + rb * 64 + lr), ldcg_f(gG + rb * 64 + lr + 8));
            if (t == 0) {
                sts32(sb + OFF_G + lr * 4, __byte_perm(pa, pa, 0x1010));
                sts32(sb + OFF_G + lr * 4 + 32, __byte_perm(pa, pa, 0x3232));
            }
            const float ga = bf_lo(pa), gb = bf_hi(pa);
            const float g0 = 1.f - ga, g1 = 1.f - gb;
#pragma unroll
            for (int j = 0; j < 16; j++) {
                const uint32_t bv = lds32(sb + OFF_BIAS + 896 + j * 16 + t * 4);
                acc[4 * j] = fmaf(acc[4 * j], 0.5f, bf_lo(bv)) * g0;
                acc[4 * j + 1] = fmaf(acc[4 * j + 1], 0.5f, bf_hi(bv)) * g0;
                acc[4 * j + 2] = fmaf(acc[4 * j + 2], 0.5f, bf_lo(bv)) * g1;
                acc[4 * j + 3] = fmaf(acc[4 * j + 3], 0.5f, bf_hi(bv)) * g1;
            }
            pin<64>(acc);
        }
        {
            mbar_wait(bar + B_G3, 0);
            const uint32_t ep = lds32(sb + OFF_G + 256);
            const uint4* src = gO + (rb * NH + rn * 4) * 128 + (tid & 127);
            bar_sync(15, 128);
#pragma unroll 1
            for (int e = 0; e < 4; e++) {
                uint4 v[4];
#pragma unroll
                for (int i = 0; i < 4; i++) v[i] = load_o(src + i * 128);
                fetch_o<4>(v, src, ep);
                stage_o(v, sb + OFF_R + 65536 + e * 8192 + ((warp - 16) * 16 + (lane & 15)) * 128, __byte_perm(pa, pa, 0x1010), __byte_perm(pa, pa, 0x3232), lane);
                src += 8 * 128;
            }
            if (warp == 16) {
                mbar_wait(bar + B_DONE, 0);
                if (elect()) {
#pragma unroll
                    for (int i = 0; i < 8; i++)
                        tma5d(sb + i * 8192, &tm.wo, cb * 128 + (i & 1) * 64, ((i >> 1) * 2 + (rn ^ 1)) * 4, bar + B_T + 32 + 8 * (i >> 1));
                }
                __syncwarp();
            }
            bar_sync(15, 128);
            if (tid == 512) TLM(1, 17);
            mbar_wait(bar + B_DONE2, 0);
        }
#pragma unroll 1
        for (int late = 0; late < 2; late++) {
            const uint64_t dB0 = mkdesc(SBD + OFF_R, 8192, 1024, 1) - late * (OFF_R / 16);
#pragma unroll
            for (int i = 0; i < 4; i++) {
                mbar_wait(bar + B_T + late * 32 + 8 * i, 0);
                const uint64_t dA = mkdesc(SBD + OFF_R + 65536 + i * 8192, 16, 1024, 1);
                wg_fence();
#pragma unroll
                for (int kk = 0; kk < 4; kk++) wgmma_ss_n128(acc, dA + kk * 2, dB0 + i * 1024 + kk * 128);
                wg_commit();
            }
            if (!late) {
                wg_wait<0>();
                if (lane == 0) mbar_arrive(bar + B_G2);
            }
        }
        wg_wait<0>();
        pin<64>(acc);
        if (tid == 512) TLM(1, 18);
        {
            const uint32_t st = sb + 98304 + (warp - 16) * 4352;
            const uint32_t wa = st + (lane & 15) * 272 + (lane >> 4) * 16;
#pragma unroll
            for (int j = 0; j < 8; j++)
                asm volatile("stmatrix.sync.aligned.m8n8.x4.shared.b16 [%0], {%1, %2, %3, %4};" ::"r"(wa + j * 32),
                             "r"(pk_bf16(acc[8 * j], acc[8 * j + 1])), "r"(pk_bf16(acc[8 * j + 2], acc[8 * j + 3])),
                             "r"(pk_bf16(acc[8 * j + 4], acc[8 * j + 5])), "r"(pk_bf16(acc[8 * j + 6], acc[8 * j + 7])) : "memory");
            __syncwarp();
            __nv_bfloat16* op = out + (size_t)(rb * 64 + (warp - 16) * 16 + (lane >> 4)) * DM + cb * 128 + (lane & 15) * 8;
#pragma unroll
            for (int j = 0; j < 8; j++) {
                uint4 v;
                asm volatile("ld.shared.v4.u32 {%0, %1, %2, %3}, [%4];" : "=r"(v.x), "=r"(v.y), "=r"(v.z), "=r"(v.w)
                             : "r"(st + (2 * j + (lane >> 4)) * 272 + (lane & 15) * 16));
                *(uint4*)(op + (size_t)j * 2 * DM) = v;
            }
        }
        if (tid == 512) TLM(1, 19);
        TL_DUMP();
    }
}

typedef CUresult (*EncodeFn)(CUtensorMap*, CUtensorMapDataType, cuuint32_t, void*, const cuuint64_t*, const cuuint64_t*, const cuuint32_t*,
                             const cuuint32_t*, CUtensorMapInterleave, CUtensorMapSwizzle, CUtensorMapL2promotion, CUtensorMapFloatOOBfill);

static void make_map(EncodeFn enc, CUtensorMap* m, const void* p, int rank, const cuuint64_t* dims, const cuuint64_t* strides,
                     const cuuint32_t* box, CUtensorMapSwizzle swz) {
    const cuuint32_t es[5] = {1, 1, 1, 1, 1};
    enc(m, CU_TENSOR_MAP_DATA_TYPE_BFLOAT16, rank, (void*)p, dims, strides, box, es, CU_TENSOR_MAP_INTERLEAVE_NONE, swz,
        CU_TENSOR_MAP_L2_PROMOTION_L2_128B, CU_TENSOR_MAP_FLOAT_OOB_FILL_NONE);
}

extern "C" void kernel_launch(void* const* d_in, const int* in_sizes, int n_in, void* d_out, int out_size) {
    const __nv_bfloat16* x = (const __nv_bfloat16*)d_in[0];
    const __nv_bfloat16* wqkv = (const __nv_bfloat16*)d_in[1];
    const __nv_bfloat16* wo = (const __nv_bfloat16*)d_in[2];
    const __nv_bfloat16* w1 = (const __nv_bfloat16*)d_in[4];
    const __nv_bfloat16* b1 = (const __nv_bfloat16*)d_in[5];
    const __nv_bfloat16* w2 = (const __nv_bfloat16*)d_in[6];
    const __nv_bfloat16* b2 = (const __nv_bfloat16*)d_in[7];
    const __nv_bfloat16* gate = (const __nv_bfloat16*)d_in[8];

    void* fp = nullptr;
    cudaDriverEntryPointQueryResult qr;
    cudaGetDriverEntryPoint("cuTensorMapEncodeTiled", &fp, cudaEnableDefault, &qr);
    EncodeFn enc = (EncodeFn)fp;
    void *pH, *pKV;
    cudaGetSymbolAddress(&pH, gH);
    cudaGetSymbolAddress(&pKV, gKV);

    Maps tm;
    const CUtensorMapSwizzle S128 = CU_TENSOR_MAP_SWIZZLE_128B, S64 = CU_TENSOR_MAP_SWIZZLE_64B;
    { cuuint64_t d[2] = {DM, SEQ}, s[1] = {DM * 2}; cuuint32_t b[2] = {64, 128}; make_map(enc, &tm.x, x, 2, d, s, b, S128); }
    { cuuint64_t d[3] = {DM, DM, 3}, s[2] = {3 * DM * 2, DM * 2}; cuuint32_t b[3] = {64, 32, 2}; make_map(enc, &tm.kv, wqkv, 3, d, s, b, S128); }
    { cuuint64_t d[3] = {32, DM, 3 * DM / 32}, s[2] = {3 * DM * 2, 64}; cuuint32_t b[3] = {32, 32, 2}; make_map(enc, &tm.q, wqkv, 3, d, s, b, S64); }
    { cuuint64_t d[3] = {32, DM, FF / 32}, s[2] = {FF * 2, 64}; cuuint32_t b[3] = {32, 32, 1}; make_map(enc, &tm.f1, w1, 3, d, s, b, S64); }
    { cuuint64_t d[3] = {32, DM, FF / 32}, s[2] = {FF * 2, 64}; cuuint32_t b[3] = {32, 32, 3}; make_map(enc, &tm.f3, w1, 3, d, s, b, S64); }
    { cuuint64_t d[2] = {FF, SEQ}, s[1] = {FF * 2}; cuuint32_t b[2] = {64, 64}; make_map(enc, &tm.h, pH, 2, d, s, b, S128); }
    { cuuint64_t d[5] = {DM, 2, 4, 4, FF / 32}, s[4] = {1024, 8 * 1024, 2 * 1024, 32 * 1024}; cuuint32_t b[5] = {64, 2, 4, 4, 2};
      make_map(enc, &tm.w2, w2, 5, d, s, b, S128); }
    { cuuint64_t d[5] = {DM, 2, 2, 4, NH}, s[4] = {1024, 8 * 1024, 2 * 1024, 16 * 1024}; cuuint32_t b[5] = {64, 2, 2, 4, 4};
      make_map(enc, &tm.wo, wo, 5, d, s, b, S128); }

    { cuuint64_t d[3] = {32, SEQ, FF / 32}, s[2] = {FF * 2, 64}; cuuint32_t b[3] = {32, 64, 1}; make_map(enc, &tm.hs, pH, 3, d, s, b, CU_TENSOR_MAP_SWIZZLE_NONE); }
    { cuuint64_t d[5] = {64, 16, 16, 2, 2 * NH}, s[4] = {4096, 128, 2048, 65536}; cuuint32_t b[5] = {64, 8, 2, 2, 1};
      make_map(enc, &tm.kvs, pKV, 5, d, s, b, S128); }
    cudaFuncSetAttribute(fused_kernel, cudaFuncAttributeMaxDynamicSharedMemorySize, TL_SMEM);
    fused_kernel<<<128, 640, TL_SMEM, cudaStreamPerThread>>>(tm, x, wqkv, wo, w1, b1, w2, b2, gate, (__nv_bfloat16*)d_out, 0xffffffffu);
}
```

```cpp
#include <cuda_runtime.h>
#include <cuda_bf16.h>
#include <cuda_fp16.h>
#include <cuda.h>
#include <stdint.h>

#define SEQ 2048
#define DM 512
#define FF 1792
#define NH 32

__device__ __align__(1024) uint8_t gQ[NH * SEQ * 32];
__device__ __align__(1024) uint8_t gKV[NH * SEQ * 64];
__device__ __align__(1024) __nv_bfloat16 gH[SEQ * FF];
__device__ __align__(1024) uint4 gO[32 * NH * 128];
__device__ float gG[SEQ];
__device__ float gN[3 * 8 * 128];
__device__ unsigned int gCntQ[8 * 32];
__device__ unsigned int gCntH[32 * 32];
__device__ unsigned int gEpoch[128];

__device__ __forceinline__ uint32_t smem_u32(const void* p) { return (uint32_t)__cvta_generic_to_shared(p); }
__device__ __forceinline__ void mbar_init(uint32_t a, uint32_t c) { asm volatile("mbarrier.init.shared::cta.b64 [%0], %1;" ::"r"(a), "r"(c)); }
__device__ __forceinline__ void mbar_expect(uint32_t a, uint32_t b) { asm volatile("mbarrier.arrive.expect_tx.shared::cta.b64 _, [%0], %1;" ::"r"(a), "r"(b) : "memory"); }
__device__ __forceinline__ void mbar_arrive(uint32_t a) { asm volatile("mbarrier.arrive.shared::cta.b64 _, [%0];" ::"r"(a) : "memory"); }
__device__ __forceinline__ void mbar_wait(uint32_t a, uint32_t ph) {
    asm volatile("{\n.reg .pred p;\n.reg .u32 n;\nmov.u32 n, 0;\nW_%=:\nmbarrier.try_wait.parity.shared::cta.b64 p, [%0], %1;\n@p bra D_%=;\n"
                 "add.u32 n, n, 1;\nsetp.lt.u32 p, n, 0x400000;\n@p bra W_%=;\ntrap;\nD_%=:\n}" ::"r"(a), "r"(ph) : "memory");
}
__device__ __forceinline__ void mbar_arrive_cluster(uint32_t a, uint32_t cta) {
    asm volatile("{\n.reg .b32 r;\nmapa.shared::cluster.u32 r, %0, %1;\nmbarrier.arrive.shared::cluster.b64 _, [r];\n}" ::"r"(a), "r"(cta) : "memory");
}
__device__ __forceinline__ void bar_sync(int id, int n) { asm volatile("bar.sync %0, %1;" ::"r"(id), "r"(n) : "memory"); }
__device__ __forceinline__ void bar_arrive(int id, int n) { asm volatile("bar.arrive %0, %1;" ::"r"(id), "r"(n) : "memory"); }
__device__ __forceinline__ uint32_t cluster_rank() { uint32_t r; asm("mov.u32 %0, %%cluster_ctarank;" : "=r"(r)); return r; }
__device__ __forceinline__ void cnt_add(unsigned int* c) { asm volatile("red.release.gpu.global.add.u32 [%0], 1;" ::"l"(c) : "memory"); }
__device__ __forceinline__ void cnt_wait(const unsigned int* c, uint32_t target) {
    uint32_t v;
    int spins = 0;
    while (true) {
        asm volatile("ld.acquire.gpu.global.u32 %0, [%1];" : "=r"(v) : "l"(c) : "memory");
        if ((int)(v - target) >= 0) break;
        if (++spins > (1 << 22)) __trap();
        __nanosleep(40);
    }
}
__device__ __forceinline__ void tma2d(uint32_t dst, const CUtensorMap* m, int c0, int c1, uint32_t bar) {
    asm volatile("cp.async.bulk.tensor.2d.shared::cluster.global.mbarrier::complete_tx::bytes [%0], [%1, {%3, %4}], [%2];"
                 ::"r"(dst), "l"(m), "r"(bar), "r"(c0), "r"(c1) : "memory");
}
__device__ __forceinline__ void tma2d_mc(uint32_t dst, const CUtensorMap* m, int c0, int c1, uint32_t bar) {
    asm volatile("cp.async.bulk.tensor.2d.shared::cluster.global.mbarrier::complete_tx::bytes.multicast::cluster [%0], [%1, {%3, %4}], [%2], %5;"
                 ::"r"(dst), "l"(m), "r"(bar), "r"(c0), "r"(c1), "h"((uint16_t)3) : "memory");
}
__device__ __forceinline__ void tma3d_mc(uint32_t dst, const CUtensorMap* m, int c0, int c1, int c2, uint32_t bar) {
    asm volatile("cp.async.bulk.tensor.3d.shared::cluster.global.mbarrier::complete_tx::bytes.multicast::cluster [%0], [%1, {%3, %4, %5}], [%2], %6;"
                 ::"r"(dst), "l"(m), "r"(bar), "r"(c0), "r"(c1), "r"(c2), "h"((uint16_t)3) : "memory");
}
__device__ __forceinline__ void tma5d_mc(uint32_t dst, const CUtensorMap* m, int c0, int c4, uint32_t bar) {
    asm volatile("cp.async.bulk.tensor.5d.shared::cluster.global.mbarrier::complete_tx::bytes.multicast::cluster [%0], [%1, {%3, %5, %5, %5, %4}], [%2], %6;"
                 ::"r"(dst), "l"(m), "r"(bar), "r"(c0), "r"(c4), "r"(0), "h"((uint16_t)3) : "memory");
}
__device__ __forceinline__ void tma5d(uint32_t dst, const CUtensorMap* m, int c0, int c4, uint32_t bar) {
    asm volatile("cp.async.bulk.tensor.5d.shared::cluster.global.mbarrier::complete_tx::bytes [%0], [%1, {%3, %5, %5, %5, %4}], [%2];"
                 ::"r"(dst), "l"(m), "r"(bar), "r"(c0), "r"(c4), "r"(0) : "memory");
}
__device__ __forceinline__ void bulk_mc(uint32_t dst, const void* src, uint32_t bytes, uint32_t bar) {
    asm volatile("cp.async.bulk.shared::cluster.global.mbarrier::complete_tx::bytes.multicast::cluster [%0], [%1], %2, [%3], %4;"
                 ::"r"(dst), "l"(src), "r"(bytes), "r"(bar), "h"((uint16_t)3) : "memory");
}
__device__ __forceinline__ void tma3d_st(const CUtensorMap* m, uint32_t src, int c0, int c1, int c2) {
    asm volatile("cp.async.bulk.tensor.3d.global.shared::cta.bulk_group [%0, {%2, %3, %4}], [%1];" ::"l"(m), "r"(src), "r"(c0), "r"(c1), "r"(c2) : "memory");
}
__device__ __forceinline__ void tma5d_st(const CUtensorMap* m, uint32_t src, int c1, int c2, int c4) {
    asm volatile("cp.async.bulk.tensor.5d.global.shared::cta.bulk_group [%0, {%5, %2, %3, %5, %4}], [%1];"
                 ::"l"(m), "r"(src), "r"(c1), "r"(c2), "r"(c4), "r"(0) : "memory");
}
__device__ __forceinline__ void bulk_st(void* dst, uint32_t src, uint32_t bytes) {
    asm volatile("cp.async.bulk.global.shared::cta.bulk_group [%0], [%1], %2;" ::"l"(dst), "r"(src), "r"(bytes) : "memory");
}
__device__ __forceinline__ void sts64(uint32_t a, uint32_t x, uint32_t y) { asm volatile("st.shared.v2.u32 [%0], {%1, %2};" ::"r"(a), "r"(x), "r"(y) : "memory"); }
__device__ __forceinline__ void sts128(uint32_t a, const uint32_t* v) {
    asm volatile("st.shared.v4.u32 [%0], {%1, %2, %3, %4};" ::"r"(a), "r"(v[0]), "r"(v[1]), "r"(v[2]), "r"(v[3]) : "memory");
}
__device__ __forceinline__ void l2_prefetch(const void* src, uint32_t bytes) {
    asm volatile("cp.async.bulk.prefetch.L2.global [%0], %1;" ::"l"(src), "r"(bytes) : "memory");
}
__device__ __forceinline__ void map_prefetch(const CUtensorMap* m) { asm volatile("prefetch.tensormap [%0];" ::"l"(m) : "memory"); }
__device__ __forceinline__ void wg_fence() { asm volatile("wgmma.fence.sync.aligned;" ::: "memory"); }
__device__ __forceinline__ void wg_commit() { asm volatile("wgmma.commit_group.sync.aligned;" ::: "memory"); }
template <int N> __device__ __forceinline__ void wg_wait() { asm volatile("wgmma.wait_group.sync.aligned %0;" ::"n"(N) : "memory"); }
template <int N> __device__ __forceinline__ void pin(float* s) {
#pragma unroll
    for (int i = 0; i < N; i++) asm volatile("" : "+f"(s[i])::"memory");
}
template <int N> __device__ __forceinline__ void pin(uint32_t* s) {
#pragma unroll
    for (int i = 0; i < N; i++) asm volatile("" : "+r"(s[i])::"memory");
}
__device__ __forceinline__ uint64_t mkdesc(uint32_t addr, uint32_t lbo, uint32_t sbo, uint32_t swz) {
    return (uint64_t)((addr & 0x3FFFF) >> 4) | ((uint64_t)(lbo >> 4) << 16) | ((uint64_t)(sbo >> 4) << 32) | ((uint64_t)swz << 62);
}
__device__ __forceinline__ float ex2f(float x) { float y; asm("ex2.approx.ftz.f32 %0, %1;" : "=f"(y) : "f"(x)); return y; }
__device__ __forceinline__ float tanhf_(float x) { float y; asm("tanh.approx.f32 %0, %1;" : "=f"(y) : "f"(x)); return y; }
__device__ __forceinline__ uint32_t pk_bf16(float lo, float hi) { uint32_t r; asm("cvt.rn.bf16x2.f32 %0, %1, %2;" : "=r"(r) : "f"(hi), "f"(lo)); return r; }
__device__ __forceinline__ uint32_t pk_f16(float lo, float hi) { uint32_t r; asm("cvt.rn.f16x2.f32 %0, %1, %2;" : "=r"(r) : "f"(hi), "f"(lo)); return r; }
__device__ __forceinline__ float bf_lo(uint32_t v) { return __uint_as_float(v << 16); }
__device__ __forceinline__ float bf_hi(uint32_t v) { return __uint_as_float(v & 0xffff0000u); }
__device__ __forceinline__ float dot8(const uint4& a, const uint4& b) {
    return fmaf(bf_lo(a.x), bf_lo(b.x), fmaf(bf_hi(a.x), bf_hi(b.x), fmaf(bf_lo(a.y), bf_lo(b.y), bf_hi(a.y) * bf_hi(b.y)))) +
           fmaf(bf_lo(a.z), bf_lo(b.z), fmaf(bf_hi(a.z), bf_hi(b.z), fmaf(bf_lo(a.w), bf_lo(b.w), bf_hi(a.w) * bf_hi(b.w))));
}
__device__ __forceinline__ uint32_t epoch() {
    uint32_t v;
    asm volatile("ld.global.u32 %0, [%1];" : "=r"(v) : "l"(gEpoch + blockIdx.x));
    return v + 1;
}
__device__ __forceinline__ float ldcg_f(const float* p) { return __ldcg(p); }

extern __shared__ __align__(1024) uint8_t smem_raw[];
#define TLM(k, slot) do {} while (0)
#define TLC(k, slot) do {} while (0)
#define TL_INIT() do {} while (0)
#define TL_DUMP() do {} while (0)
#define TL_SMEM SMEM_BYTES

__device__ __forceinline__ void wgmma_ss_n128(float* d, uint64_t da, uint64_t db) {
    asm volatile("wgmma.mma_async.sync.aligned.m64n128k16.f32.bf16.bf16 {"
        "%0, %1, %2, %3, %4, %5, %6, %7, %8, %9, %10, %11, %12, %13, %14, %15,"
        "%16, %17, %18, %19, %20, %21, %22, %23, %24, %25, %26, %27, %28, %29, %30, %31,"
        "%32, %33, %34, %35, %36, %37, %38, %39, %40, %41, %42, %43, %44, %45, %46, %47,"
        "%48, %49, %50, %51, %52, %53, %54, %55, %56, %57, %58, %59, %60, %61, %62, %63}, %64, %65, 1, 1, 1, 0, 1;\n"
        :
        "+f"(d[0]), "+f"(d[1]), "+f"(d[2]), "+f"(d[3]), "+f"(d[4]), "+f"(d[5]), "+f"(d[6]), "+f"(d[7]),
        "+f"(d[8]), "+f"(d[9]), "+f"(d[10]), "+f"(d[11]), "+f"(d[12]), "+f"(d[13]), "+f"(d[14]), "+f"(d[15]),
        "+f"(d[16]), "+f"(d[17]), "+f"(d[18]), "+f"(d[19]), "+f"(d[20]), "+f"(d[21]), "+f"(d[22]), "+f"(d[23]),
        "+f"(d[24]), "+f"(d[25]), "+f"(d[26]), "+f"(d[27]), "+f"(d[28]), "+f"(d[29]), "+f"(d[30]), "+f"(d[31]),
        "+f"(d[32]), "+f"(d[33]), "+f"(d[34]), "+f"(d[35]), "+f"(d[36]), "+f"(d[37]), "+f"(d[38]), "+f"(d[39]),
        "+f"(d[40]), "+f"(d[41]), "+f"(d[42]), "+f"(d[43]), "+f"(d[44]), "+f"(d[45]), "+f"(d[46]), "+f"(d[47]),
        "+f"(d[48]), "+f"(d[49]), "+f"(d[50]), "+f"(d[51]), "+f"(d[52]), "+f"(d[53]), "+f"(d[54]), "+f"(d[55]),
        "+f"(d[56]), "+f"(d[57]), "+f"(d[58]), "+f"(d[59]), "+f"(d[60]), "+f"(d[61]), "+f"(d[62]), "+f"(d[63])
        : "l"(da), "l"(db));
}
__device__ __forceinline__ void wgmma_ss_n96(float* d, uint64_t da, uint64_t db) {
    asm volatile("wgmma.mma_async.sync.aligned.m64n96k16.f32.bf16.bf16 {"
        "%0, %1, %2, %3, %4, %5, %6, %7, %8, %9, %10, %11, %12, %13, %14, %15,"
        "%16, %17, %18, %19, %20, %21, %22, %23, %24, %25, %26, %27, %28, %29, %30, %31,"
        "%32, %33, %34, %35, %36, %37, %38, %39, %40, %41, %42, %43, %44, %45, %46, %47}, %48, %49, 1, 1, 1, 0, 1;\n"
        :
        "+f"(d[0]), "+f"(d[1]), "+f"(d[2]), "+f"(d[3]), "+f"(d[4]), "+f"(d[5]), "+f"(d[6]), "+f"(d[7]),
        "+f"(d[8]), "+f"(d[9]), "+f"(d[10]), "+f"(d[11]), "+f"(d[12]), "+f"(d[13]), "+f"(d[14]), "+f"(d[15]),
        "+f"(d[16]), "+f"(d[17]), "+f"(d[18]), "+f"(d[19]), "+f"(d[20]), "+f"(d[21]), "+f"(d[22]), "+f"(d[23]),
        "+f"(d[24]), "+f"(d[25]), "+f"(d[26]), "+f"(d[27]), "+f"(d[28]), "+f"(d[29]), "+f"(d[30]), "+f"(d[31]),
        "+f"(d[32]), "+f"(d[33]), "+f"(d[34]), "+f"(d[35]), "+f"(d[36]), "+f"(d[37]), "+f"(d[38]), "+f"(d[39]),
        "+f"(d[40]), "+f"(d[41]), "+f"(d[42]), "+f"(d[43]), "+f"(d[44]), "+f"(d[45]), "+f"(d[46]), "+f"(d[47])
        : "l"(da), "l"(db));
}
__device__ __forceinline__ void wgmma_ss_n64(float* d, uint64_t da, uint64_t db) {
    asm volatile("wgmma.mma_async.sync.aligned.m64n64k16.f32.bf16.bf16 {"
        "%0, %1, %2, %3, %4, %5, %6, %7, %8, %9, %10, %11, %12, %13, %14, %15,"
        "%16, %17, %18, %19, %20, %21, %22, %23, %24, %25, %26, %27, %28, %29, %30, %31}, %32, %33, 1, 1, 1, 0, 1;\n"
        :
        "+f"(d[0]), "+f"(d[1]), "+f"(d[2]), "+f"(d[3]), "+f"(d[4]), "+f"(d[5]), "+f"(d[6]), "+f"(d[7]),
        "+f"(d[8]), "+f"(d[9]), "+f"(d[10]), "+f"(d[11]), "+f"(d[12]), "+f"(d[13]), "+f"(d[14]), "+f"(d[15]),
        "+f"(d[16]), "+f"(d[17]), "+f"(d[18]), "+f"(d[19]), "+f"(d[20]), "+f"(d[21]), "+f"(d[22]), "+f"(d[23]),
        "+f"(d[24]), "+f"(d[25]), "+f"(d[26]), "+f"(d[27]), "+f"(d[28]), "+f"(d[29]), "+f"(d[30]), "+f"(d[31])
        : "l"(da), "l"(db));
}
__device__ __forceinline__ void wgmma_rs_n128(float* d, const uint32_t* a, uint64_t db) {
    asm volatile("wgmma.mma_async.sync.aligned.m64n128k16.f32.bf16.bf16 {"
        "%0, %1, %2, %3, %4, %5, %6, %7, %8, %9, %10, %11, %12, %13, %14, %15,"
        "%16, %17, %18, %19, %20, %21, %22, %23, %24, %25, %26, %27, %28, %29, %30, %31,"
        "%32, %33, %34, %35, %36, %37, %38, %39, %40, %41, %42, %43, %44, %45, %46, %47,"
        "%48, %49, %50, %51, %52, %53, %54, %55, %56, %57, %58, %59, %60, %61, %62, %63}, {%64, %65, %66, %67}, %68, 1, 1, 1, 1;\n"
        :
        "+f"(d[0]), "+f"(d[1]), "+f"(d[2]), "+f"(d[3]), "+f"(d[4]), "+f"(d[5]), "+f"(d[6]), "+f"(d[7]),
        "+f"(d[8]), "+f"(d[9]), "+f"(d[10]), "+f"(d[11]), "+f"(d[12]), "+f"(d[13]), "+f"(d[14]), "+f"(d[15]),
        "+f"(d[16]), "+f"(d[17]), "+f"(d[18]), "+f"(d[19]), "+f"(d[20]), "+f"(d[21]), "+f"(d[22]), "+f"(d[23]),
        "+f"(d[24]), "+f"(d[25]), "+f"(d[26]), "+f"(d[27]), "+f"(d[28]), "+f"(d[29]), "+f"(d[30]), "+f"(d[31]),
        "+f"(d[32]), "+f"(d[33]), "+f"(d[34]), "+f"(d[35]), "+f"(d[36]), "+f"(d[37]), "+f"(d[38]), "+f"(d[39]),
        "+f"(d[40]), "+f"(d[41]), "+f"(d[42]), "+f"(d[43]), "+f"(d[44]), "+f"(d[45]), "+f"(d[46]), "+f"(d[47]),
        "+f"(d[48]), "+f"(d[49]), "+f"(d[50]), "+f"(d[51]), "+f"(d[52]), "+f"(d[53]), "+f"(d[54]), "+f"(d[55]),
        "+f"(d[56]), "+f"(d[57]), "+f"(d[58]), "+f"(d[59]), "+f"(d[60]), "+f"(d[61]), "+f"(d[62]), "+f"(d[63])
        : "r"(a[0]), "r"(a[1]), "r"(a[2]), "r"(a[3]), "l"(db));
}
__device__ __forceinline__ void wgmma_qk_f16_acc(float* d, const uint32_t* a, uint64_t db) {
    asm volatile("wgmma.mma_async.sync.aligned.m64n64k16.f32.f16.f16 {"
        "%0, %1, %2, %3, %4, %5, %6, %7, %8, %9, %10, %11, %12, %13, %14, %15,"
        "%16, %17, %18, %19, %20, %21, %22, %23, %24, %25, %26, %27, %28, %29, %30, %31}, {%32, %33, %34, %35}, %36, 1, 1, 1, 0;\n"
        :
        "+f"(d[0]), "+f"(d[1]), "+f"(d[2]), "+f"(d[3]), "+f"(d[4]), "+f"(d[5]), "+f"(d[6]), "+f"(d[7]),
        "+f"(d[8]), "+f"(d[9]), "+f"(d[10]), "+f"(d[11]), "+f"(d[12]), "+f"(d[13]), "+f"(d[14]), "+f"(d[15]),
        "+f"(d[16]), "+f"(d[17]), "+f"(d[18]), "+f"(d[19]), "+f"(d[20]), "+f"(d[21]), "+f"(d[22]), "+f"(d[23]),
        "+f"(d[24]), "+f"(d[25]), "+f"(d[26]), "+f"(d[27]), "+f"(d[28]), "+f"(d[29]), "+f"(d[30]), "+f"(d[31])
        : "r"(a[0]), "r"(a[1]), "r"(a[2]), "r"(a[3]), "l"(db));
}
__device__ __forceinline__ void wgmma_qk_bf16_zero(float* d, const uint32_t* a, uint64_t db) {
    asm volatile("wgmma.mma_async.sync.aligned.m64n64k16.f32.bf16.bf16 {"
        "%0, %1, %2, %3, %4, %5, %6, %7, %8, %9, %10, %11, %12, %13, %14, %15,"
        "%16, %17, %18, %19, %20, %21, %22, %23, %24, %25, %26, %27, %28, %29, %30, %31}, {%32, %33, %34, %35}, %36, 0, 1, 1, 0;\n"
        :
        "=f"(d[0]), "=f"(d[1]), "=f"(d[2]), "=f"(d[3]), "=f"(d[4]), "=f"(d[5]), "=f"(d[6]), "=f"(d[7]),
        "=f"(d[8]), "=f"(d[9]), "=f"(d[10]), "=f"(d[11]), "=f"(d[12]), "=f"(d[13]), "=f"(d[14]), "=f"(d[15]),
        "=f"(d[16]), "=f"(d[17]), "=f"(d[18]), "=f"(d[19]), "=f"(d[20]), "=f"(d[21]), "=f"(d[22]), "=f"(d[23]),
        "=f"(d[24]), "=f"(d[25]), "=f"(d[26]), "=f"(d[27]), "=f"(d[28]), "=f"(d[29]), "=f"(d[30]), "=f"(d[31])
        : "r"(a[0]), "r"(a[1]), "r"(a[2]), "r"(a[3]), "l"(db));
}
__device__ __forceinline__ void wgmma_pv(float* d, const uint32_t* a, uint64_t db) {
    asm volatile("wgmma.mma_async.sync.aligned.m64n24k16.f32.bf16.bf16 {"
        "%0, %1, %2, %3, %4, %5, %6, %7, %8, %9, %10, %11}, {%12, %13, %14, %15}, %16, 1, 1, 1, 1;\n"
        :
        "+f"(d[0]), "+f"(d[1]), "+f"(d[2]), "+f"(d[3]), "+f"(d[4]), "+f"(d[5]), "+f"(d[6]), "+f"(d[7]),
        "+f"(d[8]), "+f"(d[9]), "+f"(d[10]), "+f"(d[11])
        : "r"(a[0]), "r"(a[1]), "r"(a[2]), "r"(a[3]), "l"(db));
}

template <int N> __device__ __forceinline__ void wgmma_ss(float* d, uint64_t a, uint64_t b) {
    if (N == 128) wgmma_ss_n128(d, a, b);
    if (N == 96) wgmma_ss_n96(d, a, b);
    if (N == 64) wgmma_ss_n64(d, a, b);
}

#define OFF_R 131072
#define OFF_ONE 229376
#define OFF_BAR 229888
#define OFF_BIAS (OFF_BAR + 736)
#define OFF_G (OFF_BIAS + 1152)
#define SMEM_BYTES (OFF_G + 272)
#define SBD 1024u
#define B_X 0
#define B_F1 416
#define B_E1 64
#define B_XD 672
#define B_KV 160
#define B_F2 224
#define B_E2 256
#define B_T 288
#define B_G 360
#define B_G2 368
#define B_G3 376
#define B_SF 384
#define B_BI 400
#define B_DONE 112
#define B_DONE2 120

#define B_SF2 408
#define NR 6

#define PF 1
#define PFX 0
#define PACE 1
#define FSER 1
#define MERGE 1
#define EB 2
#define ANDM 0x4440
#define HOLD 8
#define TRIG 16
#define XPF 4
#define GDEL 7
#define WPF 0
#define EXP_FKK 4
#define QSCALE 0.36067376022224085f
#define MAGIC 445.41763f
#define FORCE_IMAD
#define NMUFU 5
#define VSTEP ((uint64_t)((long long)32 - ((long long)32 << 16)))

#define XMASK 0x0D55u
#define KVMASK 0x1D55u
__host__ __device__ constexpr int strm_pos(int pass, int i) {
    if (pass == 1 || pass == 2) return 8 + 8 * pass + i;
    int n = 0;
    for (int p = 0; p < 16; p++)
        if ((int)((KVMASK >> p) & 1) == (pass == 3)) { if (n == i) return p; n++; }
    return 0;
}
__host__ __device__ constexpr uint32_t strm_code(int pass) {
    uint32_t c = 0;
    for (int i = 0; i < 7; i++) c |= (uint32_t)(strm_pos(pass, i + 1) - strm_pos(pass, i)) << (4 * i);
    return c;
}

template <int N, int SUB, int KST, int LBO, int SBO, int SWZ>
__device__ __forceinline__ void gemm_pass(float* acc, uint32_t bar, uint64_t dA, int lane, uint32_t pos, uint32_t code, int barNext, bool waitx, bool last) {
    uint32_t prev = 0, slot = pos % NR;
#pragma unroll 1
    for (int i = 0; i < 8; i++) {
        if (waitx) {
            mbar_wait(bar + B_X + 8 * i, 0);
            if (N == 96 && i == HOLD) bar_sync(4, 512);
        }
        mbar_wait(bar + B_F1 + 8 * pos, 0);
        const uint64_t dB = mkdesc(SBD + OFF_R, LBO, SBO, SWZ) + slot * 1024;
        wg_fence();
        wgmma_ss<N>(acc, dA, dB);
        wgmma_ss<N>(acc, dA + 2, dB + KST / 16);
        wg_commit();
        wg_wait<1>();
        if (i > 0 && lane < 2) mbar_arrive_cluster(prev, lane);
        wgmma_ss<N>(acc, dA + 4, dB + SUB / 16);
        wgmma_ss<N>(acc, dA + 6, dB + (SUB + KST) / 16);
        wg_commit();
        prev = last ? bar + B_XD + 8 * i : bar + B_E1 + 8 * slot;
        pos += code & 15;
        slot += code & 15;
        if (slot >= NR) slot -= NR;
        code >>= 4;
        dA += 1024;
    }
    if (barNext) bar_arrive(barNext, 512);
    wg_wait<0>();
    if (lane < 2) mbar_arrive_cluster(prev, lane);
    pin<N / 2>(acc);
}

__device__ __forceinline__ uint32_t lds32(uint32_t a) { uint32_t v; asm volatile("ld.shared.u32 %0, [%1];" : "=r"(v) : "r"(a)); return v; }
__device__ __forceinline__ bool elect() {
    uint32_t p;
    asm volatile("{\n.reg .pred p;\nelect.sync _|p, 0xffffffff;\nselp.u32 %0, 1, 0, p;\n}" : "=r"(p));
    return p;
}

template <int G0, int G1> __device__ __forceinline__ void gelu_pack(const float* acc, uint32_t bias, uint32_t* out) {
#pragma unroll
    for (int G = G0; G < G1; G++) {
        uint32_t* o = out + 8 * G;
#pragma unroll
        for (int j = 0; j < 4; j++) {
            float bv[2];
            asm volatile("ld.shared.v2.f32 {%0, %1}, [%2];" : "=f"(bv[0]), "=f"(bv[1]) : "r"(bias + G * 128 + j * 32));
            float y[4];
#pragma unroll
            for (int i = 0; i < 4; i++) {
                const float h = acc[16 * G + 4 * j + i] + bv[i & 1];
                const float z = h * fmaf(h * h, 0.035677408136300125f, 0.7978845608028654f);
                y[i] = fmaf(h, tanhf_(z), h);
            }
            o[j] = pk_bf16(y[0], y[1]);
            o[4 + j] = pk_bf16(y[2], y[3]);
        }
    }
}

__device__ __forceinline__ float norm_bound(const float* v, float sc) {
    uint32_t m = 0;
#pragma unroll
    for (int h = 0; h < 4; h++) {
        const float* u = v + 8 * h;
        m = max(m, __float_as_uint(fmaf(u[0], u[0], fmaf(u[1], u[1], fmaf(u[4], u[4], u[5] * u[5])))));
        m = max(m, __float_as_uint(fmaf(u[2], u[2], fmaf(u[3], u[3], fmaf(u[6], u[6], u[7] * u[7])))));
    }
#pragma unroll
    for (int o = 4; o < 32; o <<= 1) m = max(m, __shfl_xor_sync(0xffffffffu, m, o));
    float f = __uint_as_float(m);
    f += __shfl_xor_sync(0xffffffffu, f, 1);
    f += __shfl_xor_sync(0xffffffffu, f, 2);
    return f * sc;
}

__device__ __forceinline__ uint32_t exp2_pair(float a, float b, uint32_t m1) {
    const uint32_t w = __byte_perm(__float_as_uint(a), __float_as_uint(b), 0x6521);
    uint32_t m, r;
    asm("lop3.b32 %0, %1, 0x007f007f, 0x9f809f80, 0xEA;" : "=r"(m) : "r"(w));
    const uint32_t e = m * m1 + w;
    asm("fma.rn.bf16x2 %0, %1, %2, %3;" : "=r"(r) : "r"(w), "r"(m), "r"(e));
    return r;
}

__device__ __forceinline__ uint32_t exp2_pair_b(float a, float b) {
    const uint32_t w = __byte_perm(__float_as_uint(a), __float_as_uint(b), 0x6521);
    uint32_t m, r;
    asm("lop3.b32 %0, %1, 0x007f007f, 0xbf00bf00, 0xEA;" : "=r"(m) : "r"(w));
    asm("fma.rn.bf16x2 %0, %1, %2, %3;" : "=r"(r) : "r"(w), "r"(m), "r"(w & 0x7f807f80u));
    return r;
}
__device__ __forceinline__ void store_o(const float* o, uint4* dst, uint32_t par) {
    const float s0 = __fdividef(1.f, o[8]), s1 = __fdividef(1.f, o[10]);
    const uint32_t d0 = (pk_bf16(o[0] * s0, o[1] * s0) & ~1u) | par;
    asm volatile("{\n.reg .b128 t;\nmov.b128 t, {%0, %1, %2, %3};\nst.relaxed.gpu.global.b128 [%4], t;\n}" ::"r"(d0),
                 "r"(pk_bf16(o[2] * s1, o[3] * s1)), "r"(pk_bf16(o[4] * s0, o[5] * s0)), "r"(pk_bf16(o[6] * s1, o[7] * s1)), "l"(dst) : "memory");
}
__device__ __forceinline__ uint4 load_o(const uint4* src) {
    uint4 v;
    asm volatile("{\n.reg .b128 t;\nld.relaxed.gpu.global.b128 t, [%4];\nmov.b128 {%0, %1, %2, %3}, t;\n}"
                 : "=r"(v.x), "=r"(v.y), "=r"(v.z), "=r"(v.w) : "l"(src) : "memory");
    return v;
}
template <int N> __device__ __forceinline__ void fetch_o(uint4* v, const uint4* src, uint32_t ep) {
    int spins = 0;
    while (true) {
        uint32_t bad = 0;
#pragma unroll
        for (int k = 0; k < N; k++) bad |= v[k].x ^ ep;
        if (!__any_sync(0xffffffffu, (bad & 1) != 0)) break;
        if (++spins > (1 << 22)) __trap();
#pragma unroll
        for (int k = 0; k < N; k++)
            if (((v[k].x ^ ep) & 1) != 0) v[k] = load_o(src + k * 128);
    }
}
__device__ __forceinline__ uint32_t bmul2(uint32_t a, uint32_t b) { uint32_t r; asm("mul.rn.bf16x2 %0, %1, %2;" : "=r"(r) : "r"(a), "r"(b)); return r; }
__device__ __forceinline__ void sts32(uint32_t a, uint32_t v) { asm volatile("st.shared.u32 [%0], %1;" ::"r"(a), "r"(v) : "memory"); }
__device__ __forceinline__ void stage_o(const uint4* v, uint32_t a0, uint32_t g0, uint32_t g1, int lane) {
#pragma unroll
    for (int i = 0; i < 4; i++)
        asm volatile("stmatrix.sync.aligned.m8n8.x4.shared.b16 [%0], {%1, %2, %3, %4};" ::"r"(a0 + (((i * 2 + (lane >> 4)) ^ (lane & 7)) << 4)),
                     "r"(bmul2(v[i].x, g0)), "r"(bmul2(v[i].y, g1)), "r"(bmul2(v[i].z, g0)), "r"(bmul2(v[i].w, g1)) : "memory");
    asm volatile("fence.proxy.async.shared::cta;" ::: "memory");
}
__device__ __forceinline__ void load_q(uint32_t* q, int h, int row, int t) {
    const uint8_t* p = gQ + (size_t)h * (SEQ * 32) + (size_t)row * 32 + t * 4;
    q[0] = __ldcg((const uint32_t*)p); q[1] = __ldcg((const uint32_t*)(p + 256));
    q[2] = __ldcg((const uint32_t*)(p + 16)); q[3] = __ldcg((const uint32_t*)(p + 272));
}

template <int NT>
__device__ __forceinline__ void proj16(float (*c)[8], const __nv_bfloat16* x, const __nv_bfloat16* w, int row0, int rstep, int col, int g, int t) {
#pragma unroll
    for (int i = 0; i < NT; i++)
#pragma unroll
        for (int j = 0; j < 8; j++) c[i][j] = 0.f;
    const unsigned short* wu = (const unsigned short*)w;
#pragma unroll 1
    for (int k = 0; k < DM; k += 16) {
        uint32_t b[4];
#pragma unroll
        for (int j = 0; j < 4; j++) {
            const int kr = k + 2 * t + (j & 1) * 8, cc = col + g + (j >> 1) * 8;
            b[j] = (uint32_t)wu[(size_t)kr * (3 * DM) + cc] | ((uint32_t)wu[(size_t)(kr + 1) * (3 * DM) + cc] << 16);
        }
#pragma unroll
        for (int i = 0; i < NT; i++) {
            const __nv_bfloat16* xp = x + (size_t)(row0 + i * rstep + g) * DM + k + 2 * t;
            const uint32_t a0 = *(const uint32_t*)xp, a1 = *(const uint32_t*)(xp + 8 * DM);
            const uint32_t a2 = *(const uint32_t*)(xp + 8), a3 = *(const uint32_t*)(xp + 8 * DM + 8);
#pragma unroll
            for (int j = 0; j < 2; j++)
                asm volatile("mma.sync.aligned.m16n8k16.row.col.f32.bf16.bf16.f32 {%0,%1,%2,%3}, {%4,%5,%6,%7}, {%8,%9}, {%0,%1,%2,%3};"
                             : "+f"(c[i][4 * j]), "+f"(c[i][4 * j + 1]), "+f"(c[i][4 * j + 2]), "+f"(c[i][4 * j + 3])
                             : "r"(a0), "r"(a1), "r"(a2), "r"(a3), "r"(b[2 * j]), "r"(b[2 * j + 1]));
        }
    }
}

struct Maps { CUtensorMap x, kv, q, f1, f3, h, w2, wo, hs, kvs; };

template <int I0, int I1>
__device__ __forceinline__ void issue_stream(const Maps& tm, uint32_t sb, uint32_t rank, int nb, int mb) {
    const uint32_t bar = sb + OFF_BAR;
    const uint32_t dst = sb + OFF_R;
    const int kr = rank * 32;
#pragma unroll
    for (int it = I0; it < I1; it++) {
        const int s = it % NR;
        const uint32_t fb = bar + B_F1 + 8 * it;
        if (it >= 24 + NR) mbar_wait(bar + B_XD + 8 * (it - 24 - NR), 0);
        else if (it >= NR) mbar_wait(bar + B_E1 + 8 * s, ((it / NR) - 1) & 1);
        const int nkv = __builtin_popcount(KVMASK & ((1u << it) - 1));
        if (it < 16 && ((KVMASK >> it) & 1)) {
            tma3d_mc(dst + s * 16384 + rank * 8192, &tm.kv, nb * 64, nkv * 64 + kr, 1, fb);
        } else if (it < 16) {
            tma3d_mc(dst + s * 16384 + rank * 6144, &tm.q, 0, (it - nkv) * 64 + kr, nb * 2, fb);
            tma3d_mc(dst + s * 16384 + rank * 6144 + 4096, &tm.f1, 0, (it - nkv) * 64 + kr, nb * 7, fb);
        } else {
            tma3d_mc(dst + s * 16384 + rank * 6144, &tm.f3, 0, (it & 7) * 64 + kr, nb * 7 + (it < 24 ? 1 : 4), fb);
        }
        if ((XMASK >> it) & 1) {
            const int xc = 1 + __builtin_popcount(XMASK & ((1u << it) - 1));
            tma2d(sb + xc * 16384, &tm.x, xc * 64, mb * 128, bar + B_X + 8 * xc);
        }
    }
}

__global__ void __cluster_dims__(2, 1, 1) __launch_bounds__(640, 1)
fused_kernel(const __grid_constant__ Maps tm, const __nv_bfloat16* __restrict__ x, const __nv_bfloat16* __restrict__ wqkv,
             const __nv_bfloat16* __restrict__ wo, const __nv_bfloat16* __restrict__ w1, const __nv_bfloat16* __restrict__ b1,
             const __nv_bfloat16* __restrict__ w2, const __nv_bfloat16* __restrict__ b2, const __nv_bfloat16* __restrict__ gate,
             __nv_bfloat16* __restrict__ out, const uint32_t m1) {
    const uint32_t sb = smem_u32(smem_raw);
    const uint32_t bar = sb + OFF_BAR;
    const int tid = threadIdx.x, lane = tid & 31;
    const int warp = __shfl_sync(0xffffffffu, tid >> 5, 0);
    const uint32_t rank = cluster_rank();
    const int cl = blockIdx.x >> 1;
    const int nb = cl & 7, mb = (cl >> 3) * 2 + rank;
    const int g = lane >> 2, t = lane & 3;

    const int cb = nb & 3, rb = mb * 2 + (nb >> 2);
    const int rn = (mb >> 1) & 1;
    if (tid == 0) TLM(0, 0);
    TL_INIT();
    if (tid == 512) {
        for (int i = 0; i < 8; i++) { mbar_init(bar + B_X + 8 * i, 1); mbar_init(bar + B_KV + 8 * i, 1); mbar_init(bar + B_T + 8 * i, i < 4 ? 1 : 5); mbar_init(bar + B_XD + 8 * i, 16); }
        for (int i = 0; i < NR; i++) mbar_init(bar + B_E1 + 8 * i, 16);
        for (int i = 0; i < 4; i++) { mbar_init(bar + B_F2 + 8 * i, 1); mbar_init(bar + B_E2 + 8 * i, 8); }
        asm volatile("fence.mbarrier_init.release.cluster;" ::: "memory");
    } else if (tid == 608) {
        for (int i = 0; i < 32; i++) mbar_init(bar + B_F1 + 8 * i, 1);
        mbar_init(bar + B_G, 1);
        mbar_init(bar + B_DONE, 16);
        mbar_init(bar + B_DONE2, TRIG);
        for (int i = 0; i < 3; i++) mbar_init(bar + B_SF + 8 * i, i == 1 ? 2 : 1);
        mbar_init(bar + B_SF2, 2);
        mbar_init(bar + B_G3, 1);
        mbar_init(bar + B_G2, 4);
        asm volatile("fence.mbarrier_init.release.cluster;" ::: "memory");
    }
    __syncwarp();
    asm volatile("barrier.cluster.arrive.relaxed.aligned;" ::: "memory");
    if (warp == 19) mbar_expect(bar + B_F1 + 8 * lane, ((KVMASK >> lane) & 1) ? 16384 : 12288);
    if (warp == 16 && lane < 24) mbar_expect(bar + (lane < 8 ? B_X : lane < 16 ? B_KV - 64 : B_T - 128) + 8 * lane, 16384);
    if (tid == 512) {
        tma2d(sb, &tm.x, 0, mb * 128, bar + B_X);
    } else if (tid == 544) {
        map_prefetch(&tm.kv);
        l2_prefetch((const uint8_t*)wqkv + (size_t)blockIdx.x * 3072, 3072);
        l2_prefetch((const uint8_t*)w1 + (size_t)blockIdx.x * 1792, 1792);
        map_prefetch(&tm.q); map_prefetch(&tm.f1); map_prefetch(&tm.f3);
    }
    if (warp == 18) {
#pragma unroll
        for (int i = 0; i < XPF / 2; i++)
            asm volatile("prefetch.global.L2 [%0];" ::"l"(x + (size_t)(mb * 128 + nb * 16 + (lane & 15)) * DM + ((lane >> 4) + 2 * i) * 64));
    }
    if ((sb & 0xFFFFFF) != SBD) __trap();
    __syncwarp();
    asm volatile("barrier.cluster.wait.aligned;" ::: "memory");
    if (tid == 512) issue_stream<0, NR>(tm, sb, rank, nb, mb);
    if (tid == 0) { TLM(0, 1); TLC(0, 30); }

    if (warp < 16) {
        const int wg = warp >> 2;
        const int h = cl >> 1, qd = (cl & 1) * 2 + rank;
        const int flip = (h >> 2) & 1;
        uint32_t q[4];
        {
            const int w8 = warp & 7;
            const int T = mb * 8 + w8, row0 = T * 16 + g;
            const uint64_t dA0 = mkdesc(SBD + (wg & 1) * 8192, 16, 1024, 1);
            if (wg < 2) {
                float acc[64];
#pragma unroll
                for (int i = 0; i < 64; i++) acc[i] = 0.f;
                gemm_pass<128, 8192, 2048, 4096, 1024, 1>(acc, bar, dA0, lane, strm_pos(3, 0), strm_code(3), HOLD < 8 ? 4 : 0, true, false);
                if (tid == 0) TLM(0, 2);
                {
                    uint32_t pv[16];
#pragma unroll
                    for (int i = 0; i < 16; i++) pv[i] = pk_bf16(acc[32 + 2 * i], acc[33 + 2 * i]);
                    uint8_t* vp = gKV + (size_t)(nb * 4) * (SEQ * 64) + 65536 + (((T >> 6) * 16 + 2 * g) * 64 + (T & 63)) * 32 + ((t * 8) ^ ((w8 >> 2) << 4));
#pragma unroll
                    for (int hh = 2; hh < 4; hh++) {
                        *(uint2*)(vp + (size_t)hh * (SEQ * 64)) = make_uint2(pv[4 * hh], pv[4 * hh + 2]);
                        *(uint2*)(vp + (size_t)hh * (SEQ * 64) + 2048) = make_uint2(pv[4 * hh + 1], pv[4 * hh + 3]);
                    }
                    const uint32_t kp = sb + OFF_R + 12288 + (w8 >> 2) * 1024 + g * 128 + ((((w8 & 3) * 2 + ((t >> 1) ^ (w8 >> 2))) ^ g) << 4) + (t & 1) * 8;
                    bar_sync(9, 256);
#pragma unroll
                    for (int hh = 0; hh < 2; hh++) {
                        sts64(kp + (4 + hh) * 16384, pv[4 * hh], pv[4 * hh + 2]);
                        sts64(kp + (4 + hh) * 16384 + 2048, pv[4 * hh + 1], pv[4 * hh + 3]);
                    }
                    const float gm = g == 0 ? 0.f : -1.f;
#pragma unroll
                    for (int hh = 0; hh < 4; hh++) {
                        const float* v = acc + 8 * hh;
                        const float p0 = __shfl_up_sync(0xffffffffu, v[2], 4), p1 = __shfl_up_sync(0xffffffffu, v[3], 4);
                        const float p2 = __shfl_up_sync(0xffffffffu, v[6], 4), p3 = __shfl_up_sync(0xffffffffu, v[7], 4);
                        sts64(kp + hh * 16384, pk_f16(fmaf(p0, gm, v[0]), fmaf(p1, gm, v[1])), pk_f16(fmaf(p2, gm, v[4]), fmaf(p3, gm, v[5])));
                        sts64(kp + hh * 16384 + 2048, pk_f16(v[2] - v[0], v[3] - v[1]), pk_f16(v[6] - v[4], v[7] - v[5]));
                    }
                    uint32_t big = 0;
#pragma unroll
                    for (int i = 0; i < 16; i++) big |= pv[i] & (pv[i] << 1);
                    const bool vbig = __any_sync(0xffffffffu, (big & 0x40004000u) != 0);
                    const float km = norm_bound(acc, 1.f);
                    if (lane == 0) gN[1024 + nb * 128 + T] = vbig ? 3.0e38f : km;
                }
                asm volatile("fence.proxy.async.shared::cta;" ::: "memory");
                bar_arrive(10, 288);
                if (tid == 0) TLM(0, 3);
            }
#pragma unroll 1
            for (int p = wg < 2 ? 1 : 0; p < 3; p += 2) {
                float acc[48];
#pragma unroll
                for (int i = 0; i < 48; i++) acc[i] = 0.f;
                pin<48>(acc);
                if (p) bar_sync(5 + p, 512);
                gemm_pass<96, 6144, 1024, 2048, 512, 2>(acc, bar, dA0, lane, p == 0 ? strm_pos(0, 0) : 8 + 8 * p, p == 0 ? strm_code(0) : strm_code(1), p < 2 ? 6 + p : 0, p == 0, p == 2);
                if ((tid & 255) == 0) TLM(0, 4 + 2 * p);
                const uint32_t hp = sb + OFF_R + (p == 2 ? 0 : 12288) + (wg & 1) * 16384 + ((warp & 3) * 16 + g) * 64 + t * 16;
                const uint32_t bp = sb + OFF_BIAS + p * 384 - 256 + t * 8;
                uint32_t ho[24];
                mbar_wait(bar + B_BI, 0);
                if (p == 0) {
                    const float qm = norm_bound(acc, QSCALE * QSCALE);
                    if (lane == 0) gN[nb * 128 + T] = qm;
                    uint8_t* qp = gQ + (size_t)(nb * 4) * (SEQ * 32) + (size_t)row0 * 32 + t * 8;
#pragma unroll
                    for (int hh = 0; hh < 4; hh++) {
                        const float* v = acc + 8 * hh;
                        *(uint2*)(qp + hh * (SEQ * 32)) = make_uint2(pk_f16(v[0] * QSCALE, v[1] * QSCALE), pk_f16(v[4] * QSCALE, v[5] * QSCALE));
                        *(uint2*)(qp + hh * (SEQ * 32) + 256) = make_uint2(pk_f16(v[2] * QSCALE, v[3] * QSCALE), pk_f16(v[6] * QSCALE, v[7] * QSCALE));
                    }
                    bar_arrive(12, 288);
                } else {
                    gelu_pack<0, 2>(acc, bp, ho);
                    pin<16>(ho);
                    mbar_wait(bar + B_G, 0);
                    load_q(q, h, qd * 512 + flip * 256 + warp * 16 + g, t);
                }
                gelu_pack<2, 3>(acc, bp, ho);
                pin<8>(ho + 16);
                if (p == 2) bar_sync(9, 256);
                else mbar_wait(bar + B_SF + 8 * p, 0);
                if (p) {
#pragma unroll
                    for (int i = 0; i < 4; i++) sts128(hp + (i >> 1) * 32768 + (i & 1) * 512, ho + 4 * i);
                }
                sts128(hp + 65536, ho + 16);
                sts128(hp + 65536 + 512, ho + 20);
                asm volatile("fence.proxy.async.shared::cta;" ::: "memory");
                bar_arrive(p == 1 ? 14 : 11, 288);
                if ((tid & 255) == 0) TLM(0, 5 + 2 * p);
            }
        }
        uint32_t ep = 2;
        uint4* const op = gO + ((qd * 8 + wg) * NH + h) * 128 + (tid & 127);
        const uint64_t kd0 = mkdesc(SBD, 16, 256, 3);
        const uint64_t vd0 = mkdesc(SBD + 8192, OFF_ONE - 8192, 256, 3);
        {
            float o[12];
            uint32_t qn[4];
#pragma unroll 1
            for (int rh = 0; rh < 4; rh++) {
                if (rh == 1) {
                    mbar_wait(bar + B_G3, 0);
                    ep = lds32(sb + OFF_G + 256);
                    if (!(ep & 2)) break;
                    load_q(qn, h, qd * 512 + (flip ^ 1) * 256 + warp * 16 + g, t);
                }
                if (rh == 3 && lane == 0) mbar_arrive(bar + B_DONE);
                if (!(rh & 1)) {
#pragma unroll
                    for (int i = 0; i < 12; i++) o[i] = 0.f;
                }
                uint64_t kd = kd0 + (rh & 1) * 4096, vd = vd0 + (rh & 1) * (128 * VSTEP);
                uint32_t kvb = bar + B_KV + (rh & 1) * 32;
                float s[32];
#pragma unroll
                for (int i = 0; i < 32; i++) s[i] = i < 2 * NMUFU ? 0.f : ((ANDM >> (i >> 1)) & 1) ? MAGIC - 63.f : MAGIC;
                if ((tid & 255) == 0) TLM(1, (tid >> 8) * 4 + rh);
#pragma unroll 1
                for (int c = 0; c < 4; c++) {
                    mbar_wait(kvb, 0);
                    kvb += 8;
#pragma unroll
                    for (int j = 0; j < 4; j++) {
                        uint32_t p[16];
                        if (!MERGE || j == 0) {
                            wg_fence();
                            wgmma_qk_f16_acc(s, q, kd + j * 128);
                            wg_commit();
                        }
                        wg_wait<0>();
                        pin<32>(s);
#pragma unroll
                        for (int i = 0; i < 16; i++)
                            p[i] = i < NMUFU ? pk_bf16(ex2f(s[2 * i]), ex2f(s[2 * i + 1])) : ((ANDM >> i) & 1) ? exp2_pair_b(s[2 * i], s[2 * i + 1]) : exp2_pair(s[2 * i], s[2 * i + 1], m1);
                        pin<16>(p);
                        wg_fence();
#pragma unroll
                        for (int u = 0; u < 4; u++) {
                            if (MERGE && j < 3 && u == 5 - MERGE) wgmma_qk_f16_acc(s, q, kd + (j + 1) * 128);
                            wgmma_pv(o, p + 4 * u, vd + (j * 4 + u) * VSTEP);
                        }
                        if (MERGE == 1 && j < 3) wgmma_qk_f16_acc(s, q, kd + (j + 1) * 128);
                        wg_commit();
                    }
                    kd += 1024;
                    vd += 32 * VSTEP;
                }
                wg_wait<0>();
                pin<12>(o);
                if (rh & 1) {
                    if ((tid & 127) == 0 && rh == 3) TLM(1, 8 + wg);
                    store_o(o, op + ((rh >> 1) ^ flip) * (4 * NH * 128), ep & 1);
#pragma unroll
                    for (int i = 0; i < 4; i++) q[i] = qn[i];
                }
            }
            if (tid == 0) { TLM(1, 12); TLC(0, 31); }
        }
        if (!(ep & 2)) {
            bar_sync(8, 512);
            for (int c = 0; c < 8; c++) mbar_wait(bar + B_KV + 8 * c, 0);
            {
                float kc[8][8];
                proj16<8>(kc, x, wqkv, warp * 16, 256, DM + h * 16, g, t);
#pragma unroll
                for (int i = 0; i < 8; i++) {
                    const int T = warp + i * 16;
                    const int pos = ((T >> 6) * 16 + 2 * g) * 64 + (T & 63);
                    const uint32_t a = sb + (pos >> 8) * 16384 + (pos & 255) * 32 + t * 4, sw = ((T >> 2) & 1) << 4;
                    asm volatile("st.shared.u32 [%0], %1;" ::"r"(a + sw), "r"(pk_bf16(kc[i][0], kc[i][1])) : "memory");
                    asm volatile("st.shared.u32 [%0], %1;" ::"r"(a + (sw ^ 16)), "r"(pk_bf16(kc[i][4], kc[i][5])) : "memory");
                    asm volatile("st.shared.u32 [%0], %1;" ::"r"(a + 2048 + sw), "r"(pk_bf16(kc[i][2], kc[i][3])) : "memory");
                    asm volatile("st.shared.u32 [%0], %1;" ::"r"(a + 2048 + (sw ^ 16)), "r"(pk_bf16(kc[i][6], kc[i][7])) : "memory");
                }
                asm volatile("fence.proxy.async.shared::cta;" ::: "memory");
                bar_sync(8, 512);
            }
#pragma unroll 1
            for (int r = 0; r < 2; r++) {
                const int row = qd * 512 + (r ^ flip) * 256 + warp * 16 + g;
                {
                    float qc[1][8];
                    proj16<1>(qc, x, wqkv, row - g, 0, h * 16, g, t);
#pragma unroll
                    for (int i = 0; i < 4; i++) q[i] = pk_bf16(qc[0][2 * i] * QSCALE, qc[0][2 * i + 1] * QSCALE);
                }
                float o[12];
#pragma unroll
                for (int i = 0; i < 12; i++) o[i] = 0.f;
                float m0 = -INFINITY, m1 = -INFINITY;
#pragma unroll 1
                for (int j = 0; j < 32; j++) {
                    const uint64_t kd = kd0 + (j >> 2) * 1024 + (j & 3) * 128, vd = vd0 + ((j >> 2) * 32 + (j & 3) * 4) * VSTEP;
                    float s[32];
                    uint32_t p[16];
                    wg_fence();
                    wgmma_qk_bf16_zero(s, q, kd);
                    wg_commit();
                    wg_wait<0>();
                    pin<32>(s);
                    pin<12>(o);
                    float n0 = m0, n1 = m1;
#pragma unroll
                    for (int i = 0; i < 8; i++) {
                        n0 = fmaxf(n0, fmaxf(s[4 * i], s[4 * i + 1]));
                        n1 = fmaxf(n1, fmaxf(s[4 * i + 2], s[4 * i + 3]));
                    }
                    n0 = fmaxf(n0, __shfl_xor_sync(0xffffffffu, n0, 1));
                    n1 = fmaxf(n1, __shfl_xor_sync(0xffffffffu, n1, 1));
                    n0 = fmaxf(n0, __shfl_xor_sync(0xffffffffu, n0, 2));
                    n1 = fmaxf(n1, __shfl_xor_sync(0xffffffffu, n1, 2));
                    const float c0 = ex2f(m0 - n0), c1 = ex2f(m1 - n1);
                    m0 = n0;
                    m1 = n1;
#pragma unroll
                    for (int i = 0; i < 3; i++) { o[4 * i] *= c0; o[4 * i + 1] *= c0; o[4 * i + 2] *= c1; o[4 * i + 3] *= c1; }
#pragma unroll
                    for (int i = 0; i < 8; i++) {
                        p[2 * i] = pk_bf16(ex2f(s[4 * i] - m0), ex2f(s[4 * i + 1] - m0));
                        p[2 * i + 1] = pk_bf16(ex2f(s[4 * i + 2] - m1), ex2f(s[4 * i + 3] - m1));
                    }
                    pin<16>(p);
                    pin<12>(o);
                    wg_fence();
#pragma unroll
                    for (int u = 0; u < 4; u++) wgmma_pv(o, p + 4 * u, vd + u * VSTEP);
                    wg_commit();
                }
                wg_wait<0>();
                pin<12>(o);
                store_o(o, op + (r ^ flip) * (4 * NH * 128), ep & 1);
                if (r == 1 && lane == 0) mbar_arrive(bar + B_DONE);
            }
        }
        if (lane == 0 && warp >= 16 - TRIG) mbar_arrive(bar + B_DONE2);
        {
            const uint4* src = gO + (rb * NH + (wg * 2 + (rn ^ 1)) * 4) * 128 + (tid & 127);
            uint4 v[4];
#pragma unroll
            for (int i = 0; i < 4; i++) v[i] = load_o(src + i * 128);
            mbar_wait(bar + B_G2, 0);
            const int lr = (warp & 3) * 16;
            const uint32_t g0 = lds32(sb + OFF_G + (lr + g) * 4), g1 = lds32(sb + OFF_G + (lr + g) * 4 + 32);
            fetch_o<4>(v, src, ep);
            stage_o(v, sb + OFF_R + 65536 + wg * 8192 + (lr + (lane & 15)) * 128, g0, g1, lane);
            __syncwarp();
            if (lane == 0) mbar_arrive(bar + B_T + 32 + 8 * wg);
            if ((tid & 127) == 0) TLM(1, 20 + wg);
        }
    } else {
        if (warp == 16) {
            if (lane == 0) {
                issue_stream<NR, 32>(tm, sb, rank, nb, mb);
                mbar_wait(bar + B_SF2, 0);
#pragma unroll
                for (int s = 0; s < 4; s++) {
                    mbar_expect(bar + B_F2 + 8 * s, 24576);
                    tma5d_mc(sb + OFF_R + s * 24576 + 8192 + rank * 8192, &tm.w2, cb * 128 + rank * 64, s * 2, bar + B_F2 + 8 * s);
                }
                cnt_wait(gCntH + mb * 32, epoch() * 8);
                asm volatile("fence.proxy.async.global;" ::: "memory");
                TLM(1, 13);
#pragma unroll
                for (int s = 0; s < 4; s++) tma2d(sb + OFF_R + s * 24576, &tm.h, s * 64, rb * 64, bar + B_F2 + 8 * s);
            }
        } else if (warp == 17) {
            {
                uint32_t bv[4], b2v[2];
#pragma unroll
                for (int i = 0; i < 4; i++) bv[i] = lane + 32 * i < 112 ? *(const uint32_t*)(b1 + nb * 224 + (lane + 32 * i) * 2) : 0;
#pragma unroll
                for (int i = 0; i < 2; i++) b2v[i] = *(const uint32_t*)(b2 + cb * 128 + (lane + 32 * i) * 2);
#pragma unroll
                for (int i = 0; i < 4; i++) {
                    sts32(sb + OFF_ONE + (lane + 32 * i) * 4, 0x3f803f80u);
                    if (lane + 32 * i < 112) sts64(sb + OFF_BIAS + (lane + 32 * i) * 8, bv[i] << 16, bv[i] & 0xffff0000u);
                }
#pragma unroll
                for (int i = 0; i < 2; i++) sts32(sb + OFF_BIAS + 896 + (lane + 32 * i) * 4, b2v[i]);
                asm volatile("fence.proxy.async.shared::cta;" ::: "memory");
                __syncwarp();
                if (lane == 0) mbar_arrive(bar + B_BI);
            }
            mbar_wait(bar + B_X + 8 * PFX, 0);
            if (lane == 0) {
                l2_prefetch((const uint8_t*)wqkv + 128 * 3072 + (size_t)blockIdx.x * 9216, 9216);
                l2_prefetch((const uint8_t*)w1 + (size_t)blockIdx.x * 14336, 14336);
            }
            mbar_wait(bar + B_X + 8 * 7, 0);
            if (lane == 0) {
                l2_prefetch((const uint8_t*)w2 + (size_t)blockIdx.x * 14336, 14336);
                l2_prefetch((const uint8_t*)wo + (size_t)blockIdx.x * 4096, 4096);
                map_prefetch(&tm.h); map_prefetch(&tm.w2); map_prefetch(&tm.wo); map_prefetch(&tm.hs); map_prefetch(&tm.kvs);
                TLM(0, 11);
            }
            bar_sync(10, 288);
            if (lane == 0) {
#pragma unroll 1
                for (int b = 5; b >= 0; b--) {
                    tma5d_st(&tm.kvs, sb + OFF_R + 12288 + b * 16384, (mb >> 3) * 8, (mb & 7) * 2, nb * 8 + (b < 4 ? 2 * b : 2 * b - 7));
                    asm volatile("cp.async.bulk.commit_group;\ncp.async.bulk.wait_group.read %0;" ::"n"(PACE) : "memory");
                    if (b == 4 - PACE) mbar_arrive(bar + B_SF);
                }
                asm volatile("cp.async.bulk.wait_group.read 0;" ::: "memory");
                mbar_arrive(bar + B_SF + 8);
            }
            __syncwarp();
            bar_sync(12, 288);
            if (lane == 0) {
                asm volatile("cp.async.bulk.wait_group 0;\nfence.proxy.async.global;" ::: "memory");
                cnt_add(gCntQ + nb * 32);
                TLM(0, 13);
            }
        } else {
            {
                mbar_wait(bar + B_X + 8 * GDEL, 0);
                const int r0 = mb * 128 + nb * 16 + (warp - 18) * 8;
                uint4 xv[16];
#pragma unroll
                for (int i = 0; i < 16; i++) xv[i] = *(const uint4*)(x + (size_t)(r0 + (i >> 1)) * DM + (i & 1) * 256 + lane * 8);
                const uint4 ga = *(const uint4*)(gate + lane * 8), gb = *(const uint4*)(gate + 256 + lane * 8);
                float z[8];
#pragma unroll
                for (int r = 0; r < 8; r++) z[r] = dot8(xv[2 * r], ga) + dot8(xv[2 * r + 1], gb);
#pragma unroll
                for (int w = 4; w >= 1; w >>= 1)
#pragma unroll
                    for (int r = 0; r < w; r++) {
                        const bool up = lane & w;
                        z[r] = (up ? z[r + w] : z[r]) + __shfl_xor_sync(0xffffffffu, up ? z[r] : z[r + w], w);
                    }
                z[0] += __shfl_xor_sync(0xffffffffu, z[0], 8);
                z[0] += __shfl_xor_sync(0xffffffffu, z[0], 16);
                if (lane < 8) gG[r0 + lane] = 1.f / (1.f + __expf(-z[0]));
                if (tid == 576) TLM(0, 12);
            }
            if (warp == 19) {
#pragma unroll 1
                for (int e = 0; e < 3; e++) {
                    bar_sync(e == 1 ? 14 : 11, 288);
                    if (lane == 0) {
#pragma unroll 1
                        for (int b = e == 0 ? 4 : 0; b < 6; b++) {
                            tma3d_st(&tm.hs, sb + OFF_R + (e == 2 ? 0 : 12288) + b * 16384, 0, mb * 128 + (b & 1) * 64, nb * 7 + e * 3 - 2 + (b >> 1));
                            asm volatile("cp.async.bulk.commit_group;\ncp.async.bulk.wait_group.read %0;" ::"n"(PACE) : "memory");
                        }
                        asm volatile("cp.async.bulk.wait_group.read 0;" ::: "memory");
                        if (e == 0) mbar_arrive(bar + B_SF + 8);
                        if (e == 2) { mbar_arrive_cluster(bar + B_SF2, 0); mbar_arrive_cluster(bar + B_SF2, 1); }
                    }
                    __syncwarp();
                }
                bar_sync(13, 64);
                if (lane == 0) {
                    asm volatile("cp.async.bulk.wait_group 0;\nfence.proxy.async.global;" ::: "memory");
                    cnt_add(gCntH + mb * 32);
                    TLM(0, 15);
                }
            } else {
                bar_arrive(13, 64);
                const int h = cl >> 1, qd = (cl & 1) * 2 + rank;
                const uint32_t ep = epoch();
                if (lane == 0) {
                    cnt_wait(gCntQ + (h >> 2) * 32, ep * 16);
                    mbar_arrive(bar + B_G);
                    TLM(0, 14);
                    asm volatile("fence.proxy.async.global;" ::: "memory");
#pragma unroll
                    for (int c = 0; c < 2; c++) {
                        mbar_wait(bar + B_XD + 8 * c, 0);
                        bulk_mc(sb + c * 16384 + rank * 8192, gKV + (size_t)h * (SEQ * 64) + rank * 65536 + c * 8192, 8192, bar + B_KV + 8 * c);
                    }
                }
                __syncwarp();
            const int hb = h >> 2;
            const uint4 kq = __ldcg((const uint4*)(gN + 1024 + hb * 128 + lane * 4));
            const float qq = ldcg_f(gN + hb * 128 + qd * 32 + lane);
            const float kf = __uint_as_float(__reduce_max_sync(0xffffffffu, max(max(kq.x, kq.y), max(kq.z, kq.w))));
            const float qf = __uint_as_float(__reduce_max_sync(0xffffffffu, __float_as_uint(qq)));
            if (lane == 0) {
                sts32(sb + OFF_G + 256, (ep & 1) | ((kf <= 1.0e6f) && (qf <= 1.0e6f) && (kf * qf <= 2300.f) ? 2 : 0));
                mbar_arrive(bar + B_G3);
                TLM(0, 16);
#pragma unroll
                for (int c = 2; c < 8; c++) {
                    mbar_wait(bar + B_XD + 8 * c, 0);
                    bulk_mc(sb + c * 16384 + rank * 8192, gKV + (size_t)h * (SEQ * 64) + rank * 65536 + c * 8192, 8192, bar + B_KV + 8 * c);
                }
                TLM(0, 10);
            }
            }
        }
        __syncwarp();
        float acc[64];
#pragma unroll
        for (int i = 0; i < 64; i++) acc[i] = 0.f;
#pragma unroll 1
        for (int io = 0; io < 7; io++) {
#pragma unroll
            for (int s = 0; s < 4; s++) {
                const int it = io * 4 + s;
                mbar_wait(bar + B_F2 + 8 * s, io & 1);
                if (tid == 512 && s == 0 && (io == 0 || io == 4)) TLM(1, 14 + io / 4);
                const uint64_t dA = mkdesc(SBD + OFF_R + s * 24576, 16, 1024, 1);
                const uint64_t dB = mkdesc(SBD + OFF_R + s * 24576 + 8192, 8192, 1024, 1);
                wg_fence();
#pragma unroll
                for (int kk = 0; kk < EXP_FKK; kk++) {
                    wgmma_ss_n128(acc, dA + kk * 2, dB + kk * 128);
                    if (kk < 3 && (FSER != 3 || kk == 1)) {
                        wg_commit();
                        wg_wait<0>();
                    }
                }
                wg_commit();
                if (warp < 18 && it >= 2 && it < 26) {
                    const int s2 = (s + 2) & 3;
                    mbar_wait(bar + B_E2 + 8 * s2, (io - (s < 2)) & 1);
                    if (elect()) {
                        if (warp == 16) {
                            mbar_expect(bar + B_F2 + 8 * s2, 24576);
                            tma5d_mc(sb + OFF_R + s2 * 24576 + 8192 + rank * 8192, &tm.w2, cb * 128 + rank * 64, it * 2 + 4, bar + B_F2 + 8 * s2);
                        } else {
                            asm volatile("fence.proxy.async.global;" ::: "memory");
                            tma2d(sb + OFF_R + s2 * 24576, &tm.h, it * 64 + 128, rb * 64, bar + B_F2 + 8 * s2);
                        }
                    }
                    __syncwarp();
                }
                wg_wait<1>();
                if (it >= 1 && lane < 2) mbar_arrive_cluster(bar + B_E2 + 8 * ((s + 3) & 3), lane);
            }
        }
        wg_wait<0>();
        if (lane < 2) mbar_arrive_cluster(bar + B_E2 + 8 * 3, lane);
        pin<64>(acc);
        if (tid == 576) gEpoch[blockIdx.x] = epoch();
        if (warp == 16) {
            if (lane == 0) TLM(1, 16);
            for (int s = 0; s < 4; s++) mbar_wait(bar + B_E2 + 8 * s, 0);
            if (elect()) {
#pragma unroll
                for (int i = 0; i < 4; i++)
                    tma5d_mc(sb + OFF_R + i * 16384 + rank * 8192, &tm.wo, cb * 128 + rank * 64, (i * 2 + rn) * 4, bar + B_T + 8 * i);
            }
            __syncwarp();
        }
        uint32_t pa;
        {
            const int lr = (warp - 16) * 16 + g;
            pa = pk_bf16(ldcg_f(gG + rb * 64 + lr), ldcg_f(gG + rb * 64 + lr + 8));
            if (t == 0) {
                sts32(sb + OFF_G + lr * 4, __byte_perm(pa, pa, 0x1010));
                sts32(sb + OFF_G + lr * 4 + 32, __byte_perm(pa, pa, 0x3232));
            }
            const float ga = bf_lo(pa), gb = bf_hi(pa);
            const float g0 = 1.f - ga, g1 = 1.f - gb;
#pragma unroll
            for (int j = 0; j < 16; j++) {
                const uint32_t bv = lds32(sb + OFF_BIAS + 896 + j * 16 + t * 4);
                acc[4 * j] = fmaf(acc[4 * j], 0.5f, bf_lo(bv)) * g0;
                acc[4 * j + 1] = fmaf(acc[4 * j + 1], 0.5f, bf_hi(bv)) * g0;
                acc[4 * j + 2] = fmaf(acc[4 * j + 2], 0.5f, bf_lo(bv)) * g1;
                acc[4 * j + 3] = fmaf(acc[4 * j + 3], 0.5f, bf_hi(bv)) * g1;
            }
            pin<64>(acc);
        }
        {
            mbar_wait(bar + B_G3, 0);
            const uint32_t ep = lds32(sb + OFF_G + 256);
            const uint4* src = gO + (rb * NH + rn * 4) * 128 + (tid & 127);
            bar_sync(15, 128);
#pragma unroll 1
            for (int e = 0; e < 4; e++) {
                uint4 v[4];
#pragma unroll
                for (int i = 0; i < 4; i++) v[i] = load_o(src + i * 128);
                fetch_o<4>(v, src, ep);
                stage_o(v, sb + OFF_R + 65536 + e * 8192 + ((warp - 16) * 16 + (lane & 15)) * 128, __byte_perm(pa, pa, 0x1010), __byte_perm(pa, pa, 0x3232), lane);
                src += 8 * 128;
            }
            if (warp == 16) {
                mbar_wait(bar + B_DONE, 0);
                if (elect()) {
#pragma unroll
                    for (int i = 0; i < 8; i++)
                        tma5d(sb + i * 8192, &tm.wo, cb * 128 + (i & 1) * 64, ((i >> 1) * 2 + (rn ^ 1)) * 4, bar + B_T + 32 + 8 * (i >> 1));
                }
                __syncwarp();
            }
            bar_sync(15, 128);
            if (tid == 512) TLM(1, 17);
            mbar_wait(bar + B_DONE2, 0);
        }
#pragma unroll 1
        for (int late = 0; late < 2; late++) {
            const uint64_t dB0 = mkdesc(SBD + OFF_R, 8192, 1024, 1) - late * (OFF_R / 16);
#pragma unroll
            for (int i = 0; i < 4; i++) {
                mbar_wait(bar + B_T + late * 32 + 8 * i, 0);
                const uint64_t dA = mkdesc(SBD + OFF_R + 65536 + i * 8192, 16, 1024, 1);
                wg_fence();
#pragma unroll
                for (int kk = 0; kk < 4; kk++) wgmma_ss_n128(acc, dA + kk * 2, dB0 + i * 1024 + kk * 128);
                wg_commit();
            }
            if (!late) {
                wg_wait<0>();
                if (lane == 0) mbar_arrive(bar + B_G2);
            }
        }
        wg_wait<0>();
        pin<64>(acc);
        if (tid == 512) TLM(1, 18);
        {
            const uint32_t st = sb + 98304 + (warp - 16) * 4352;
            const uint32_t wa = st + (lane & 15) * 272 + (lane >> 4) * 16;
#pragma unroll
            for (int j = 0; j < 8; j++)
                asm volatile("stmatrix.sync.aligned.m8n8.x4.shared.b16 [%0], {%1, %2, %3, %4};" ::"r"(wa + j * 32),
                             "r"(pk_bf16(acc[8 * j], acc[8 * j + 1])), "r"(pk_bf16(acc[8 * j + 2], acc[8 * j + 3])),
                             "r"(pk_bf16(acc[8 * j + 4], acc[8 * j + 5])), "r"(pk_bf16(acc[8 * j + 6], acc[8 * j + 7])) : "memory");
            __syncwarp();
            __nv_bfloat16* op = out + (size_t)(rb * 64 + (warp - 16) * 16 + (lane >> 4)) * DM + cb * 128 + (lane & 15) * 8;
#pragma unroll
            for (int j = 0; j < 8; j++) {
                uint4 v;
                asm volatile("ld.shared.v4.u32 {%0, %1, %2, %3}, [%4];" : "=r"(v.x), "=r"(v.y), "=r"(v.z), "=r"(v.w)
                             : "r"(st + (2 * j + (lane >> 4)) * 272 + (lane & 15) * 16));
                *(uint4*)(op + (size_t)j * 2 * DM) = v;
            }
        }
        if (tid == 512) TLM(1, 19);
        TL_DUMP();
    }
}

typedef CUresult (*EncodeFn)(CUtensorMap*, CUtensorMapDataType, cuuint32_t, void*, const cuuint64_t*, const cuuint64_t*, const cuuint32_t*,
                             const cuuint32_t*, CUtensorMapInterleave, CUtensorMapSwizzle, CUtensorMapL2promotion, CUtensorMapFloatOOBfill);

static void make_map(EncodeFn enc, CUtensorMap* m, const void* p, int rank, const cuuint64_t* dims, const cuuint64_t* strides,
                     const cuuint32_t* box, CUtensorMapSwizzle swz) {
    const cuuint32_t es[5] = {1, 1, 1, 1, 1};
    enc(m, CU_TENSOR_MAP_DATA_TYPE_BFLOAT16, rank, (void*)p, dims, strides, box, es, CU_TENSOR_MAP_INTERLEAVE_NONE, swz,
        CU_TENSOR_MAP_L2_PROMOTION_L2_128B, CU_TENSOR_MAP_FLOAT_OOB_FILL_NONE);
}

extern "C" void kernel_launch(void* const* d_in, const int* in_sizes, int n_in, void* d_out, int out_size) {
    const __nv_bfloat16* x = (const __nv_bfloat16*)d_in[0];
    const __nv_bfloat16* wqkv = (const __nv_bfloat16*)d_in[1];
    const __nv_bfloat16* wo = (const __nv_bfloat16*)d_in[2];
    const __nv_bfloat16* w1 = (const __nv_bfloat16*)d_in[4];
    const __nv_bfloat16* b1 = (const __nv_bfloat16*)d_in[5];
    const __nv_bfloat16* w2 = (const __nv_bfloat16*)d_in[6];
    const __nv_bfloat16* b2 = (const __nv_bfloat16*)d_in[7];
    const __nv_bfloat16* gate = (const __nv_bfloat16*)d_in[8];

    void* fp = nullptr;
    cudaDriverEntryPointQueryResult qr;
    cudaGetDriverEntryPoint("cuTensorMapEncodeTiled", &fp, cudaEnableDefault, &qr);
    EncodeFn enc = (EncodeFn)fp;
    void *pH, *pKV;
    cudaGetSymbolAddress(&pH, gH);
    cudaGetSymbolAddress(&pKV, gKV);

    Maps tm;
    const CUtensorMapSwizzle S128 = CU_TENSOR_MAP_SWIZZLE_128B, S64 = CU_TENSOR_MAP_SWIZZLE_64B;
    { cuuint64_t d[2] = {DM, SEQ}, s[1] = {DM * 2}; cuuint32_t b[2] = {64, 128}; make_map(enc, &tm.x, x, 2, d, s, b, S128); }
    { cuuint64_t d[3] = {DM, DM, 3}, s[2] = {3 * DM * 2, DM * 2}; cuuint32_t b[3] = {64, 32, 2}; make_map(enc, &tm.kv, wqkv, 3, d, s, b, S128); }
    { cuuint64_t d[3] = {32, DM, 3 * DM / 32}, s[2] = {3 * DM * 2, 64}; cuuint32_t b[3] = {32, 32, 2}; make_map(enc, &tm.q, wqkv, 3, d, s, b, S64); }
    { cuuint64_t d[3] = {32, DM, FF / 32}, s[2] = {FF * 2, 64}; cuuint32_t b[3] = {32, 32, 1}; make_map(enc, &tm.f1, w1, 3, d, s, b, S64); }
    { cuuint64_t d[3] = {32, DM, FF / 32}, s[2] = {FF * 2, 64}; cuuint32_t b[3] = {32, 32, 3}; make_map(enc, &tm.f3, w1, 3, d, s, b, S64); }
    { cuuint64_t d[2] = {FF, SEQ}, s[1] = {FF * 2}; cuuint32_t b[2] = {64, 64}; make_map(enc, &tm.h, pH, 2, d, s, b, S128); }
    { cuuint64_t d[5] = {DM, 2, 4, 4, FF / 32}, s[4] = {1024, 8 * 1024, 2 * 1024, 32 * 1024}; cuuint32_t b[5] = {64, 2, 4, 4, 2};
      make_map(enc, &tm.w2, w2, 5, d, s, b, S128); }
    { cuuint64_t d[5] = {DM, 2, 2, 4, NH}, s[4] = {1024, 8 * 1024, 2 * 1024, 16 * 1024}; cuuint32_t b[5] = {64, 2, 2, 4, 4};
      make_map(enc, &tm.wo, wo, 5, d, s, b, S128); }

    { cuuint64_t d[3] = {32, SEQ, FF / 32}, s[2] = {FF * 2, 64}; cuuint32_t b[3] = {32, 64, 1}; make_map(enc, &tm.hs, pH, 3, d, s, b, CU_TENSOR_MAP_SWIZZLE_NONE); }
    { cuuint64_t d[5] = {64, 16, 16, 2, 2 * NH}, s[4] = {4096, 128, 2048, 65536}; cuuint32_t b[5] = {64, 8, 2, 2, 1};
      make_map(enc, &tm.kvs, pKV, 5, d, s, b, S128); }
    cudaFuncSetAttribute(fused_kernel, cudaFuncAttributeMaxDynamicSharedMemorySize, TL_SMEM);
    fused_kernel<<<128, 640, TL_SMEM, cudaStreamPerThread>>>(tm, x, wqkv, wo, w1, b1, w2, b2, gate, (__nv_bfloat16*)d_out, 0xffffffffu);
}
```

```cpp
#include <cuda_runtime.h>
#include <cuda_bf16.h>
#include <cuda_fp16.h>
#include <cuda.h>
#include <stdint.h>

#define SEQ 2048
#define DM 512
#define FF 1792
#define NH 32

__device__ __align__(1024) uint8_t gQ[NH * SEQ * 32];
__device__ __align__(1024) uint8_t gKV[NH * SEQ * 64];
__device__ __align__(1024) __nv_bfloat16 gH[SEQ * FF];
__device__ __align__(1024) uint4 gO[32 * NH * 128];
__device__ float gG[SEQ];
__device__ float gN[3 * 8 * 128];
__device__ unsigned int gCntQ[8 * 32];
__device__ unsigned int gCntH[32 * 32];
__device__ unsigned int gEpoch[128];

__device__ __forceinline__ uint32_t smem_u32(const void* p) { return (uint32_t)__cvta_generic_to_shared(p); }
__device__ __forceinline__ void mbar_init(uint32_t a, uint32_t c) { asm volatile("mbarrier.init.shared::cta.b64 [%0], %1;" ::"r"(a), "r"(c)); }
__device__ __forceinline__ void mbar_expect(uint32_t a, uint32_t b) { asm volatile("mbarrier.arrive.expect_tx.shared::cta.b64 _, [%0], %1;" ::"r"(a), "r"(b) : "memory"); }
__device__ __forceinline__ void mbar_arrive(uint32_t a) { asm volatile("mbarrier.arrive.shared::cta.b64 _, [%0];" ::"r"(a) : "memory"); }
__device__ __forceinline__ void mbar_wait(uint32_t a, uint32_t ph) {
    asm volatile("{\n.reg .pred p;\n.reg .u32 n;\nmov.u32 n, 0;\nW_%=:\nmbarrier.try_wait.parity.shared::cta.b64 p, [%0], %1;\n@p bra D_%=;\n"
                 "add.u32 n, n, 1;\nsetp.lt.u32 p, n, 0x400000;\n@p bra W_%=;\ntrap;\nD_%=:\n}" ::"r"(a), "r"(ph) : "memory");
}
__device__ __forceinline__ void mbar_arrive_cluster(uint32_t a, uint32_t cta) {
    asm volatile("{\n.reg .b32 r;\nmapa.shared::cluster.u32 r, %0, %1;\nmbarrier.arrive.shared::cluster.b64 _, [r];\n}" ::"r"(a), "r"(cta) : "memory");
}
__device__ __forceinline__ void bar_sync(int id, int n) { asm volatile("bar.sync %0, %1;" ::"r"(id), "r"(n) : "memory"); }
__device__ __forceinline__ void bar_arrive(int id, int n) { asm volatile("bar.arrive %0, %1;" ::"r"(id), "r"(n) : "memory"); }
__device__ __forceinline__ uint32_t cluster_rank() { uint32_t r; asm("mov.u32 %0, %%cluster_ctarank;" : "=r"(r)); return r; }
__device__ __forceinline__ void cnt_add(unsigned int* c) { asm volatile("red.release.gpu.global.add.u32 [%0], 1;" ::"l"(c) : "memory"); }
__device__ __forceinline__ void cnt_wait(const unsigned int* c, uint32_t target) {
    uint32_t v;
    int spins = 0;
    while (true) {
        asm volatile("ld.acquire.gpu.global.u32 %0, [%1];" : "=r"(v) : "l"(c) : "memory");
        if ((int)(v - target) >= 0) break;
        if (++spins > (1 << 22)) __trap();
        __nanosleep(40);
    }
}
__device__ __forceinline__ void tma2d(uint32_t dst, const CUtensorMap* m, int c0, int c1, uint32_t bar) {
    asm volatile("cp.async.bulk.tensor.2d.shared::cluster.global.mbarrier::complete_tx::bytes [%0], [%1, {%3, %4}], [%2];"
                 ::"r"(dst), "l"(m), "r"(bar), "r"(c0), "r"(c1) : "memory");
}
__device__ __forceinline__ void tma2d_mc(uint32_t dst, const CUtensorMap* m, int c0, int c1, uint32_t bar) {
    asm volatile("cp.async.bulk.tensor.2d.shared::cluster.global.mbarrier::complete_tx::bytes.multicast::cluster [%0], [%1, {%3, %4}], [%2], %5;"
                 ::"r"(dst), "l"(m), "r"(bar), "r"(c0), "r"(c1), "h"((uint16_t)3) : "memory");
}
__device__ __forceinline__ void tma3d_mc(uint32_t dst, const CUtensorMap* m, int c0, int c1, int c2, uint32_t bar) {
    asm volatile("cp.async.bulk.tensor.3d.shared::cluster.global.mbarrier::complete_tx::bytes.multicast::cluster [%0], [%1, {%3, %4, %5}], [%2], %6;"
                 ::"r"(dst), "l"(m), "r"(bar), "r"(c0), "r"(c1), "r"(c2), "h"((uint16_t)3) : "memory");
}
__device__ __forceinline__ void tma5d_mc(uint32_t dst, const CUtensorMap* m, int c0, int c4, uint32_t bar) {
    asm volatile("cp.async.bulk.tensor.5d.shared::cluster.global.mbarrier::complete_tx::bytes.multicast::cluster [%0], [%1, {%3, %5, %5, %5, %4}], [%2], %6;"
                 ::"r"(dst), "l"(m), "r"(bar), "r"(c0), "r"(c4), "r"(0), "h"((uint16_t)3) : "memory");
}
__device__ __forceinline__ void tma5d(uint32_t dst, const CUtensorMap* m, int c0, int c4, uint32_t bar) {
    asm volatile("cp.async.bulk.tensor.5d.shared::cluster.global.mbarrier::complete_tx::bytes [%0], [%1, {%3, %5, %5, %5, %4}], [%2];"
                 ::"r"(dst), "l"(m), "r"(bar), "r"(c0), "r"(c4), "r"(0) : "memory");
}
__device__ __forceinline__ void bulk_mc(uint32_t dst, const void* src, uint32_t bytes, uint32_t bar) {
    asm volatile("cp.async.bulk.shared::cluster.global.mbarrier::complete_tx::bytes.multicast::cluster [%0], [%1], %2, [%3], %4;"
                 ::"r"(dst), "l"(src), "r"(bytes), "r"(bar), "h"((uint16_t)3) : "memory");
}
__device__ __forceinline__ void tma3d_st(const CUtensorMap* m, uint32_t src, int c0, int c1, int c2) {
    asm volatile("cp.async.bulk.tensor.3d.global.shared::cta.bulk_group [%0, {%2, %3, %4}], [%1];" ::"l"(m), "r"(src), "r"(c0), "r"(c1), "r"(c2) : "memory");
}
__device__ __forceinline__ void tma5d_st(const CUtensorMap* m, uint32_t src, int c1, int c2, int c4) {
    asm volatile("cp.async.bulk.tensor.5d.global.shared::cta.bulk_group [%0, {%5, %2, %3, %5, %4}], [%1];"
                 ::"l"(m), "r"(src), "r"(c1), "r"(c2), "r"(c4), "r"(0) : "memory");
}
__device__ __forceinline__ void bulk_st(void* dst, uint32_t src, uint32_t bytes) {
    asm volatile("cp.async.bulk.global.shared::cta.bulk_group [%0], [%1], %2;" ::"l"(dst), "r"(src), "r"(bytes) : "memory");
}
__device__ __forceinline__ void sts64(uint32_t a, uint32_t x, uint32_t y) { asm volatile("st.shared.v2.u32 [%0], {%1, %2};" ::"r"(a), "r"(x), "r"(y) : "memory"); }
__device__ __forceinline__ void sts128(uint32_t a, const uint32_t* v) {
    asm volatile("st.shared.v4.u32 [%0], {%1, %2, %3, %4};" ::"r"(a), "r"(v[0]), "r"(v[1]), "r"(v[2]), "r"(v[3]) : "memory");
}
__device__ __forceinline__ void l2_prefetch(const void* src, uint32_t bytes) {
    asm volatile("cp.async.bulk.prefetch.L2.global [%0], %1;" ::"l"(src), "r"(bytes) : "memory");
}
__device__ __forceinline__ void map_prefetch(const CUtensorMap* m) { asm volatile("prefetch.tensormap [%0];" ::"l"(m) : "memory"); }
__device__ __forceinline__ void wg_fence() { asm volatile("wgmma.fence.sync.aligned;" ::: "memory"); }
__device__ __forceinline__ void wg_commit() { asm volatile("wgmma.commit_group.sync.aligned;" ::: "memory"); }
template <int N> __device__ __forceinline__ void wg_wait() { asm volatile("wgmma.wait_group.sync.aligned %0;" ::"n"(N) : "memory"); }
template <int N> __device__ __forceinline__ void pin(float* s) {
#pragma unroll
    for (int i = 0; i < N; i++) asm volatile("" : "+f"(s[i])::"memory");
}
template <int N> __device__ __forceinline__ void pin(uint32_t* s) {
#pragma unroll
    for (int i = 0; i < N; i++) asm volatile("" : "+r"(s[i])::"memory");
}
__device__ __forceinline__ uint64_t mkdesc(uint32_t addr, uint32_t lbo, uint32_t sbo, uint32_t swz) {
    return (uint64_t)((addr & 0x3FFFF) >> 4) | ((uint64_t)(lbo >> 4) << 16) | ((uint64_t)(sbo >> 4) << 32) | ((uint64_t)swz << 62);
}
__device__ __forceinline__ float ex2f(float x) { float y; asm("ex2.approx.ftz.f32 %0, %1;" : "=f"(y) : "f"(x)); return y; }
__device__ __forceinline__ float tanhf_(float x) { float y; asm("tanh.approx.f32 %0, %1;" : "=f"(y) : "f"(x)); return y; }
__device__ __forceinline__ uint32_t pk_bf16(float lo, float hi) { uint32_t r; asm("cvt.rn.bf16x2.f32 %0, %1, %2;" : "=r"(r) : "f"(hi), "f"(lo)); return r; }
__device__ __forceinline__ uint32_t pk_f16(float lo, float hi) { uint32_t r; asm("cvt.rn.f16x2.f32 %0, %1, %2;" : "=r"(r) : "f"(hi), "f"(lo)); return r; }
__device__ __forceinline__ float bf_lo(uint32_t v) { return __uint_as_float(v << 16); }
__device__ __forceinline__ float bf_hi(uint32_t v) { return __uint_as_float(v & 0xffff0000u); }
__device__ __forceinline__ float dot8(const uint4& a, const uint4& b) {
    return fmaf(bf_lo(a.x), bf_lo(b.x), fmaf(bf_hi(a.x), bf_hi(b.x), fmaf(bf_lo(a.y), bf_lo(b.y), bf_hi(a.y) * bf_hi(b.y)))) +
           fmaf(bf_lo(a.z), bf_lo(b.z), fmaf(bf_hi(a.z), bf_hi(b.z), fmaf(bf_lo(a.w), bf_lo(b.w), bf_hi(a.w) * bf_hi(b.w))));
}
__device__ __forceinline__ uint32_t epoch() {
    uint32_t v;
    asm volatile("ld.global.u32 %0, [%1];" : "=r"(v) : "l"(gEpoch + blockIdx.x));
    return v + 1;
}
__device__ __forceinline__ float ldcg_f(const float* p) { return __ldcg(p); }

extern __shared__ __align__(1024) uint8_t smem_raw[];
#define TLM(k, slot) do {} while (0)
#define TLC(k, slot) do {} while (0)
#define TL_INIT() do {} while (0)
#define TL_DUMP() do {} while (0)
#define TL_SMEM SMEM_BYTES

__device__ __forceinline__ void wgmma_ss_n128(float* d, uint64_t da, uint64_t db) {
    asm volatile("wgmma.mma_async.sync.aligned.m64n128k16.f32.bf16.bf16 {"
        "%0, %1, %2, %3, %4, %5, %6, %7, %8, %9, %10, %11, %12, %13, %14, %15,"
        "%16, %17, %18, %19, %20, %21, %22, %23, %24, %25, %26, %27, %28, %29, %30, %31,"
        "%32, %33, %34, %35, %36, %37, %38, %39, %40, %41, %42, %43, %44, %45, %46, %47,"
        "%48, %49, %50, %51, %52, %53, %54, %55, %56, %57, %58, %59, %60, %61, %62, %63}, %64, %65, 1, 1, 1, 0, 1;\n"
        :
        "+f"(d[0]), "+f"(d[1]), "+f"(d[2]), "+f"(d[3]), "+f"(d[4]), "+f"(d[5]), "+f"(d[6]), "+f"(d[7]),
        "+f"(d[8]), "+f"(d[9]), "+f"(d[10]), "+f"(d[11]), "+f"(d[12]), "+f"(d[13]), "+f"(d[14]), "+f"(d[15]),
        "+f"(d[16]), "+f"(d[17]), "+f"(d[18]), "+f"(d[19]), "+f"(d[20]), "+f"(d[21]), "+f"(d[22]), "+f"(d[23]),
        "+f"(d[24]), "+f"(d[25]), "+f"(d[26]), "+f"(d[27]), "+f"(d[28]), "+f"(d[29]), "+f"(d[30]), "+f"(d[31]),
        "+f"(d[32]), "+f"(d[33]), "+f"(d[34]), "+f"(d[35]), "+f"(d[36]), "+f"(d[37]), "+f"(d[38]), "+f"(d[39]),
        "+f"(d[40]), "+f"(d[41]), "+f"(d[42]), "+f"(d[43]), "+f"(d[44]), "+f"(d[45]), "+f"(d[46]), "+f"(d[47]),
        "+f"(d[48]), "+f"(d[49]), "+f"(d[50]), "+f"(d[51]), "+f"(d[52]), "+f"(d[53]), "+f"(d[54]), "+f"(d[55]),
        "+f"(d[56]), "+f"(d[57]), "+f"(d[58]), "+f"(d[59]), "+f"(d[60]), "+f"(d[61]), "+f"(d[62]), "+f"(d[63])
        : "l"(da), "l"(db));
}
__device__ __forceinline__ void wgmma_ss_n96(float* d, uint64_t da, uint64_t db) {
    asm volatile("wgmma.mma_async.sync.aligned.m64n96k16.f32.bf16.bf16 {"
        "%0, %1, %2, %3, %4, %5, %6, %7, %8, %9, %10, %11, %12, %13, %14, %15,"
        "%16, %17, %18, %19, %20, %21, %22, %23, %24, %25, %26, %27, %28, %29, %30, %31,"
        "%32, %33, %34, %35, %36, %37, %38, %39, %40, %41, %42, %43, %44, %45, %46, %47}, %48, %49, 1, 1, 1, 0, 1;\n"
        :
        "+f"(d[0]), "+f"(d[1]), "+f"(d[2]), "+f"(d[3]), "+f"(d[4]), "+f"(d[5]), "+f"(d[6]), "+f"(d[7]),
        "+f"(d[8]), "+f"(d[9]), "+f"(d[10]), "+f"(d[11]), "+f"(d[12]), "+f"(d[13]), "+f"(d[14]), "+f"(d[15]),
        "+f"(d[16]), "+f"(d[17]), "+f"(d[18]), "+f"(d[19]), "+f"(d[20]), "+f"(d[21]), "+f"(d[22]), "+f"(d[23]),
        "+f"(d[24]), "+f"(d[25]), "+f"(d[26]), "+f"(d[27]), "+f"(d[28]), "+f"(d[29]), "+f"(d[30]), "+f"(d[31]),
        "+f"(d[32]), "+f"(d[33]), "+f"(d[34]), "+f"(d[35]), "+f"(d[36]), "+f"(d[37]), "+f"(d[38]), "+f"(d[39]),
        "+f"(d[40]), "+f"(d[41]), "+f"(d[42]), "+f"(d[43]), "+f"(d[44]), "+f"(d[45]), "+f"(d[46]), "+f"(d[47])
        : "l"(da), "l"(db));
}
__device__ __forceinline__ void wgmma_ss_n64(float* d, uint64_t da, uint64_t db) {
    asm volatile("wgmma.mma_async.sync.aligned.m64n64k16.f32.bf16.bf16 {"
        "%0, %1, %2, %3, %4, %5, %6, %7, %8, %9, %10, %11, %12, %13, %14, %15,"
        "%16, %17, %18, %19, %20, %21, %22, %23, %24, %25, %26, %27, %28, %29, %30, %31}, %32, %33, 1, 1, 1, 0, 1;\n"
        :
        "+f"(d[0]), "+f"(d[1]), "+f"(d[2]), "+f"(d[3]), "+f"(d[4]), "+f"(d[5]), "+f"(d[6]), "+f"(d[7]),
        "+f"(d[8]), "+f"(d[9]), "+f"(d[10]), "+f"(d[11]), "+f"(d[12]), "+f"(d[13]), "+f"(d[14]), "+f"(d[15]),
        "+f"(d[16]), "+f"(d[17]), "+f"(d[18]), "+f"(d[19]), "+f"(d[20]), "+f"(d[21]), "+f"(d[22]), "+f"(d[23]),
        "+f"(d[24]), "+f"(d[25]), "+f"(d[26]), "+f"(d[27]), "+f"(d[28]), "+f"(d[29]), "+f"(d[30]), "+f"(d[31])
        : "l"(da), "l"(db));
}
__device__ __forceinline__ void wgmma_rs_n128(float* d, const uint32_t* a, uint64_t db) {
    asm volatile("wgmma.mma_async.sync.aligned.m64n128k16.f32.bf16.bf16 {"
        "%0, %1, %2, %3, %4, %5, %6, %7, %8, %9, %10, %11, %12, %13, %14, %15,"
        "%16, %17, %18, %19, %20, %21, %22, %23, %24, %25, %26, %27, %28, %29, %30, %31,"
        "%32, %33, %34, %35, %36, %37, %38, %39, %40, %41, %42, %43, %44, %45, %46, %47,"
        "%48, %49, %50, %51, %52, %53, %54, %55, %56, %57, %58, %59, %60, %61, %62, %63}, {%64, %65, %66, %67}, %68, 1, 1, 1, 1;\n"
        :
        "+f"(d[0]), "+f"(d[1]), "+f"(d[2]), "+f"(d[3]), "+f"(d[4]), "+f"(d[5]), "+f"(d[6]), "+f"(d[7]),
        "+f"(d[8]), "+f"(d[9]), "+f"(d[10]), "+f"(d[11]), "+f"(d[12]), "+f"(d[13]), "+f"(d[14]), "+f"(d[15]),
        "+f"(d[16]), "+f"(d[17]), "+f"(d[18]), "+f"(d[19]), "+f"(d[20]), "+f"(d[21]), "+f"(d[22]), "+f"(d[23]),
        "+f"(d[24]), "+f"(d[25]), "+f"(d[26]), "+f"(d[27]), "+f"(d[28]), "+f"(d[29]), "+f"(d[30]), "+f"(d[31]),
        "+f"(d[32]), "+f"(d[33]), "+f"(d[34]), "+f"(d[35]), "+f"(d[36]), "+f"(d[37]), "+f"(d[38]), "+f"(d[39]),
        "+f"(d[40]), "+f"(d[41]), "+f"(d[42]), "+f"(d[43]), "+f"(d[44]), "+f"(d[45]), "+f"(d[46]), "+f"(d[47]),
        "+f"(d[48]), "+f"(d[49]), "+f"(d[50]), "+f"(d[51]), "+f"(d[52]), "+f"(d[53]), "+f"(d[54]), "+f"(d[55]),
        "+f"(d[56]), "+f"(d[57]), "+f"(d[58]), "+f"(d[59]), "+f"(d[60]), "+f"(d[61]), "+f"(d[62]), "+f"(d[63])
        : "r"(a[0]), "r"(a[1]), "r"(a[2]), "r"(a[3]), "l"(db));
}
__device__ __forceinline__ void wgmma_qk_f16_acc(float* d, const uint32_t* a, uint64_t db) {
    asm volatile("wgmma.mma_async.sync.aligned.m64n64k16.f32.f16.f16 {"
        "%0, %1, %2, %3, %4, %5, %6, %7, %8, %9, %10, %11, %12, %13, %14, %15,"
        "%16, %17, %18, %19, %20, %21, %22, %23, %24, %25, %26, %27, %28, %29, %30, %31}, {%32, %33, %34, %35}, %36, 1, 1, 1, 0;\n"
        :
        "+f"(d[0]), "+f"(d[1]), "+f"(d[2]), "+f"(d[3]), "+f"(d[4]), "+f"(d[5]), "+f"(d[6]), "+f"(d[7]),
        "+f"(d[8]), "+f"(d[9]), "+f"(d[10]), "+f"(d[11]), "+f"(d[12]), "+f"(d[13]), "+f"(d[14]), "+f"(d[15]),
        "+f"(d[16]), "+f"(d[17]), "+f"(d[18]), "+f"(d[19]), "+f"(d[20]), "+f"(d[21]), "+f"(d[22]), "+f"(d[23]),
        "+f"(d[24]), "+f"(d[25]), "+f"(d[26]), "+f"(d[27]), "+f"(d[28]), "+f"(d[29]), "+f"(d[30]), "+f"(d[31])
        : "r"(a[0]), "r"(a[1]), "r"(a[2]), "r"(a[3]), "l"(db));
}
__device__ __forceinline__ void wgmma_qk_bf16_zero(float* d, const uint32_t* a, uint64_t db) {
    asm volatile("wgmma.mma_async.sync.aligned.m64n64k16.f32.bf16.bf16 {"
        "%0, %1, %2, %3, %4, %5, %6, %7, %8, %9, %10, %11, %12, %13, %14, %15,"
        "%16, %17, %18, %19, %20, %21, %22, %23, %24, %25, %26, %27, %28, %29, %30, %31}, {%32, %33, %34, %35}, %36, 0, 1, 1, 0;\n"
        :
        "=f"(d[0]), "=f"(d[1]), "=f"(d[2]), "=f"(d[3]), "=f"(d[4]), "=f"(d[5]), "=f"(d[6]), "=f"(d[7]),
        "=f"(d[8]), "=f"(d[9]), "=f"(d[10]), "=f"(d[11]), "=f"(d[12]), "=f"(d[13]), "=f"(d[14]), "=f"(d[15]),
        "=f"(d[16]), "=f"(d[17]), "=f"(d[18]), "=f"(d[19]), "=f"(d[20]), "=f"(d[21]), "=f"(d[22]), "=f"(d[23]),
        "=f"(d[24]), "=f"(d[25]), "=f"(d[26]), "=f"(d[27]), "=f"(d[28]), "=f"(d[29]), "=f"(d[30]), "=f"(d[31])
        : "r"(a[0]), "r"(a[1]), "r"(a[2]), "r"(a[3]), "l"(db));
}
__device__ __forceinline__ void wgmma_pv(float* d, const uint32_t* a, uint64_t db) {
    asm volatile("wgmma.mma_async.sync.aligned.m64n24k16.f32.bf16.bf16 {"
        "%0, %1, %2, %3, %4, %5, %6, %7, %8, %9, %10, %11}, {%12, %13, %14, %15}, %16, 1, 1, 1, 1;\n"
        :
        "+f"(d[0]), "+f"(d[1]), "+f"(d[2]), "+f"(d[3]), "+f"(d[4]), "+f"(d[5]), "+f"(d[6]), "+f"(d[7]),
        "+f"(d[8]), "+f"(d[9]), "+f"(d[10]), "+f"(d[11])
        : "r"(a[0]), "r"(a[1]), "r"(a[2]), "r"(a[3]), "l"(db));
}

template <int N> __device__ __forceinline__ void wgmma_ss(float* d, uint64_t a, uint64_t b) {
    if (N == 128) wgmma_ss_n128(d, a, b);
    if (N == 96) wgmma_ss_n96(d, a, b);
    if (N == 64) wgmma_ss_n64(d, a, b);
}

#define OFF_R 131072
#define OFF_ONE 229376
#define OFF_BAR 229888
#define OFF_BIAS (OFF_BAR + 736)
#define OFF_G (OFF_BIAS + 1152)
#define SMEM_BYTES (OFF_G + 272)
#define SBD 1024u
#define B_X 0
#define B_F1 416
#define B_E1 64
#define B_XD 672
#define B_KV 160
#define B_F2 224
#define B_E2 256
#define B_T 288
#define B_G 360
#define B_G2 368
#define B_G3 376
#define B_SF 384
#define B_BI 400
#define B_DONE 112
#define B_DONE2 120

#define B_SF2 408
#define NR 6

#define PF 1
#define PFX 0
#define PACE 1
#define FSER 1
#define MERGE 1
#define EB 2
#define ANDM 0x4440
#define HOLD 8
#define TRIG 16
#define XPF 4
#define GDEL 7
#define WPF 0
#define EXP_FKK 4
#define QSCALE 0.36067376022224085f
#define MAGIC 445.41763f
#define FORCE_IMAD
#define NMUFU 5
#define VSTEP ((uint64_t)((long long)32 - ((long long)32 << 16)))

#define XMASK 0x0D55u
#define KVMASK 0x1D55u
__host__ __device__ constexpr int strm_pos(int pass, int i) {
    if (pass == 1 || pass == 2) return 8 + 8 * pass + i;
    int n = 0;
    for (int p = 0; p < 16; p++)
        if ((int)((KVMASK >> p) & 1) == (pass == 3)) { if (n == i) return p; n++; }
    return 0;
}
__host__ __device__ constexpr uint32_t strm_code(int pass) {
    uint32_t c = 0;
    for (int i = 0; i < 7; i++) c |= (uint32_t)(strm_pos(pass, i + 1) - strm_pos(pass, i)) << (4 * i);
    return c;
}

template <int N, int SUB, int KST, int LBO, int SBO, int SWZ>
__device__ __forceinline__ void gemm_pass(float* acc, uint32_t bar, uint64_t dA, int lane, uint32_t pos, uint32_t code, int barNext, bool waitx, bool last) {
    uint32_t prev = 0, slot = pos % NR;
#pragma unroll 1
    for (int i = 0; i < 8; i++) {
        if (waitx) {
            mbar_wait(bar + B_X + 8 * i, 0);
            if (N == 96 && i == HOLD) bar_sync(4, 512);
        }
        mbar_wait(bar + B_F1 + 8 * pos, 0);
        const uint64_t dB = mkdesc(SBD + OFF_R, LBO, SBO, SWZ) + slot * 1024;
        wg_fence();
        wgmma_ss<N>(acc, dA, dB);
        wgmma_ss<N>(acc, dA + 2, dB + KST / 16);
        wg_commit();
        wg_wait<1>();
        if (i > 0 && lane < 2) mbar_arrive_cluster(prev, lane);
        wgmma_ss<N>(acc, dA + 4, dB + SUB / 16);
        wgmma_ss<N>(acc, dA + 6, dB + (SUB + KST) / 16);
        wg_commit();
        prev = last ? bar + B_XD + 8 * i : bar + B_E1 + 8 * slot;
        pos += code & 15;
        slot += code & 15;
        if (slot >= NR) slot -= NR;
        code >>= 4;
        dA += 1024;
    }
    if (barNext) bar_arrive(barNext, 512);
    wg_wait<0>();
    if (lane < 2) mbar_arrive_cluster(prev, lane);
    pin<N / 2>(acc);
}

__device__ __forceinline__ uint32_t lds32(uint32_t a) { uint32_t v; asm volatile("ld.shared.u32 %0, [%1];" : "=r"(v) : "r"(a)); return v; }
__device__ __forceinline__ bool elect() {
    uint32_t p;
    asm volatile("{\n.reg .pred p;\nelect.sync _|p, 0xffffffff;\nselp.u32 %0, 1, 0, p;\n}" : "=r"(p));
    return p;
}

template <int G0, int G1> __device__ __forceinline__ void gelu_pack(const float* acc, uint32_t bias, uint32_t* out) {
#pragma unroll
    for (int G = G0; G < G1; G++) {
        uint32_t* o = out + 8 * G;
#pragma unroll
        for (int j = 0; j < 4; j++) {
            float bv[2];
            asm volatile("ld.shared.v2.f32 {%0, %1}, [%2];" : "=f"(bv[0]), "=f"(bv[1]) : "r"(bias + G * 128 + j * 32));
            float y[4];
#pragma unroll
            for (int i = 0; i < 4; i++) {
                const float h = acc[16 * G + 4 * j + i] + bv[i & 1];
                const float z = h * fmaf(h * h, 0.035677408136300125f, 0.7978845608028654f);
                y[i] = fmaf(h, tanhf_(z), h);
            }
            o[j] = pk_bf16(y[0], y[1]);
            o[4 + j] = pk_bf16(y[2], y[3]);
        }
    }
}

__device__ __forceinline__ uint32_t badd2(uint32_t a, uint32_t b) { uint32_t r; asm("add.rn.bf16x2 %0, %1, %2;" : "=r"(r) : "r"(a), "r"(b)); return r; }
__device__ __forceinline__ void norm_part(const float* v, uint32_t* n) {
#pragma unroll
    for (int h = 0; h < 4; h++) {
        const float* u = v + 8 * h;
        n[h] = pk_bf16(fmaf(u[0], u[0], fmaf(u[1], u[1], fmaf(u[4], u[4], u[5] * u[5]))), fmaf(u[2], u[2], fmaf(u[3], u[3], fmaf(u[6], u[6], u[7] * u[7]))));
    }
#pragma unroll
    for (int h = 0; h < 4; h++) n[h] = badd2(n[h], __shfl_xor_sync(0xffffffffu, n[h], 1));
}
__device__ __forceinline__ float norm_finish(uint32_t* n, float sc) {
#pragma unroll
    for (int h = 0; h < 4; h++) n[h] = badd2(n[h], __shfl_xor_sync(0xffffffffu, n[h], 2));
    const uint32_t m = __vimax3_u16x2(__vmaxu2(n[0], n[1]), n[2], n[3]);
    return __uint_as_float(__reduce_max_sync(0xffffffffu, max(m << 16, m & 0xffff0000u))) * (1.03f * sc);
}

__device__ __forceinline__ uint32_t exp2_pair(float a, float b, uint32_t m1) {
    const uint32_t w = __byte_perm(__float_as_uint(a), __float_as_uint(b), 0x6521);
    uint32_t m, r;
    asm("lop3.b32 %0, %1, 0x007f007f, 0x9f809f80, 0xEA;" : "=r"(m) : "r"(w));
    const uint32_t e = m * m1 + w;
    asm("fma.rn.bf16x2 %0, %1, %2, %3;" : "=r"(r) : "r"(w), "r"(m), "r"(e));
    return r;
}

__device__ __forceinline__ uint32_t exp2_pair_b(float a, float b) {
    const uint32_t w = __byte_perm(__float_as_uint(a), __float_as_uint(b), 0x6521);
    uint32_t m, r;
    asm("lop3.b32 %0, %1, 0x007f007f, 0xbf00bf00, 0xEA;" : "=r"(m) : "r"(w));
    asm("fma.rn.bf16x2 %0, %1, %2, %3;" : "=r"(r) : "r"(w), "r"(m), "r"(w & 0x7f807f80u));
    return r;
}
__device__ __forceinline__ void store_o(const float* o, uint4* dst, uint32_t par) {
    const float s0 = __fdividef(1.f, o[8]), s1 = __fdividef(1.f, o[10]);
    const uint32_t d0 = (pk_bf16(o[0] * s0, o[1] * s0) & ~1u) | par;
    asm volatile("{\n.reg .b128 t;\nmov.b128 t, {%0, %1, %2, %3};\nst.relaxed.gpu.global.b128 [%4], t;\n}" ::"r"(d0),
                 "r"(pk_bf16(o[2] * s1, o[3] * s1)), "r"(pk_bf16(o[4] * s0, o[5] * s0)), "r"(pk_bf16(o[6] * s1, o[7] * s1)), "l"(dst) : "memory");
}
__device__ __forceinline__ uint4 load_o(const uint4* src) {
    uint4 v;
    asm volatile("{\n.reg .b128 t;\nld.relaxed.gpu.global.b128 t, [%4];\nmov.b128 {%0, %1, %2, %3}, t;\n}"
                 : "=r"(v.x), "=r"(v.y), "=r"(v.z), "=r"(v.w) : "l"(src) : "memory");
    return v;
}
template <int N> __device__ __forceinline__ void fetch_o(uint4* v, const uint4* src, uint32_t ep) {
    int spins = 0;
    while (true) {
        uint32_t bad = 0;
#pragma unroll
        for (int k = 0; k < N; k++) bad |= v[k].x ^ ep;
        if (!__any_sync(0xffffffffu, (bad & 1) != 0)) break;
        if (++spins > (1 << 22)) __trap();
#pragma unroll
        for (int k = 0; k < N; k++)
            if (((v[k].x ^ ep) & 1) != 0) v[k] = load_o(src + k * 128);
    }
}
__device__ __forceinline__ uint32_t bmul2(uint32_t a, uint32_t b) { uint32_t r; asm("mul.rn.bf16x2 %0, %1, %2;" : "=r"(r) : "r"(a), "r"(b)); return r; }
__device__ __forceinline__ void sts32(uint32_t a, uint32_t v) { asm volatile("st.shared.u32 [%0], %1;" ::"r"(a), "r"(v) : "memory"); }
__device__ __forceinline__ void stage_o(const uint4* v, uint32_t a0, uint32_t g0, uint32_t g1, int lane) {
#pragma unroll
    for (int i = 0; i < 4; i++)
        asm volatile("stmatrix.sync.aligned.m8n8.x4.shared.b16 [%0], {%1, %2, %3, %4};" ::"r"(a0 + (((i * 2 + (lane >> 4)) ^ (lane & 7)) << 4)),
                     "r"(bmul2(v[i].x, g0)), "r"(bmul2(v[i].y, g1)), "r"(bmul2(v[i].z, g0)), "r"(bmul2(v[i].w, g1)) : "memory");
    asm volatile("fence.proxy.async.shared::cta;" ::: "memory");
}
__device__ __forceinline__ void load_q(uint32_t* q, int h, int row, int t) {
    const uint8_t* p = gQ + (size_t)h * (SEQ * 32) + (size_t)row * 32 + t * 4;
    q[0] = __ldcg((const uint32_t*)p); q[1] = __ldcg((const uint32_t*)(p + 256));
    q[2] = __ldcg((const uint32_t*)(p + 16)); q[3] = __ldcg((const uint32_t*)(p + 272));
}

template <int NT>
__device__ __forceinline__ void proj16(float (*c)[8], const __nv_bfloat16* x, const __nv_bfloat16* w, int row0, int rstep, int col, int g, int t) {
#pragma unroll
    for (int i = 0; i < NT; i++)
#pragma unroll
        for (int j = 0; j < 8; j++) c[i][j] = 0.f;
    const unsigned short* wu = (const unsigned short*)w;
#pragma unroll 1
    for (int k = 0; k < DM; k += 16) {
        uint32_t b[4];
#pragma unroll
        for (int j = 0; j < 4; j++) {
            const int kr = k + 2 * t + (j & 1) * 8, cc = col + g + (j >> 1) * 8;
            b[j] = (uint32_t)wu[(size_t)kr * (3 * DM) + cc] | ((uint32_t)wu[(size_t)(kr + 1) * (3 * DM) + cc] << 16);
        }
#pragma unroll
        for (int i = 0; i < NT; i++) {
            const __nv_bfloat16* xp = x + (size_t)(row0 + i * rstep + g) * DM + k + 2 * t;
            const uint32_t a0 = *(const uint32_t*)xp, a1 = *(const uint32_t*)(xp + 8 * DM);
            const uint32_t a2 = *(const uint32_t*)(xp + 8), a3 = *(const uint32_t*)(xp + 8 * DM + 8);
#pragma unroll
            for (int j = 0; j < 2; j++)
                asm volatile("mma.sync.aligned.m16n8k16.row.col.f32.bf16.bf16.f32 {%0,%1,%2,%3}, {%4,%5,%6,%7}, {%8,%9}, {%0,%1,%2,%3};"
                             : "+f"(c[i][4 * j]), "+f"(c[i][4 * j + 1]), "+f"(c[i][4 * j + 2]), "+f"(c[i][4 * j + 3])
                             : "r"(a0), "r"(a1), "r"(a2), "r"(a3), "r"(b[2 * j]), "r"(b[2 * j + 1]));
        }
    }
}

struct Maps { CUtensorMap x, kv, q, f1, f3, h, w2, wo, hs, kvs; };

template <int I0, int I1>
__device__ __forceinline__ void issue_stream(const Maps& tm, uint32_t sb, uint32_t rank, int nb, int mb) {
    const uint32_t bar = sb + OFF_BAR;
    const uint32_t dst = sb + OFF_R;
    const int kr = rank * 32;
#pragma unroll
    for (int it = I0; it < I1; it++) {
        const int s = it % NR;
        const uint32_t fb = bar + B_F1 + 8 * it;
        if (it >= 24 + NR) mbar_wait(bar + B_XD + 8 * (it - 24 - NR), 0);
        else if (it >= NR) mbar_wait(bar + B_E1 + 8 * s, ((it / NR) - 1) & 1);
        const int nkv = __builtin_popcount(KVMASK & ((1u << it) - 1));
        if (it < 16 && ((KVMASK >> it) & 1)) {
            tma3d_mc(dst + s * 16384 + rank * 8192, &tm.kv, nb * 64, nkv * 64 + kr, 1, fb);
        } else if (it < 16) {
            tma3d_mc(dst + s * 16384 + rank * 6144, &tm.q, 0, (it - nkv) * 64 + kr, nb * 2, fb);
            tma3d_mc(dst + s * 16384 + rank * 6144 + 4096, &tm.f1, 0, (it - nkv) * 64 + kr, nb * 7, fb);
        } else {
            tma3d_mc(dst + s * 16384 + rank * 6144, &tm.f3, 0, (it & 7) * 64 + kr, nb * 7 + (it < 24 ? 1 : 4), fb);
        }
        if ((XMASK >> it) & 1) {
            const int xc = 1 + __builtin_popcount(XMASK & ((1u << it) - 1));
            tma2d(sb + xc * 16384, &tm.x, xc * 64, mb * 128, bar + B_X + 8 * xc);
        }
    }
}

__global__ void __cluster_dims__(2, 1, 1) __launch_bounds__(640, 1)
fused_kernel(const __grid_constant__ Maps tm, const __nv_bfloat16* __restrict__ x, const __nv_bfloat16* __restrict__ wqkv,
             const __nv_bfloat16* __restrict__ wo, const __nv_bfloat16* __restrict__ w1, const __nv_bfloat16* __restrict__ b1,
             const __nv_bfloat16* __restrict__ w2, const __nv_bfloat16* __restrict__ b2, const __nv_bfloat16* __restrict__ gate,
             __nv_bfloat16* __restrict__ out, const uint32_t m1) {
    const uint32_t sb = smem_u32(smem_raw);
    const uint32_t bar = sb + OFF_BAR;
    const int tid = threadIdx.x, lane = tid & 31;
    const int warp = __shfl_sync(0xffffffffu, tid >> 5, 0);
    const uint32_t rank = cluster_rank();
    const int cl = blockIdx.x >> 1;
    const int nb = cl & 7, mb = (cl >> 3) * 2 + rank;
    const int g = lane >> 2, t = lane & 3;

    const int cb = nb & 3, rb = mb * 2 + (nb >> 2);
    const int rn = (mb >> 1) & 1;
    if (tid == 0) TLM(0, 0);
    TL_INIT();
    if (tid == 512) {
        for (int i = 0; i < 8; i++) { mbar_init(bar + B_X + 8 * i, 1); mbar_init(bar + B_KV + 8 * i, 1); mbar_init(bar + B_T + 8 * i, i < 4 ? 1 : 5); mbar_init(bar + B_XD + 8 * i, 16); }
        for (int i = 0; i < NR; i++) mbar_init(bar + B_E1 + 8 * i, 16);
        for (int i = 0; i < 4; i++) { mbar_init(bar + B_F2 + 8 * i, 1); mbar_init(bar + B_E2 + 8 * i, 8); }
        asm volatile("fence.mbarrier_init.release.cluster;" ::: "memory");
    } else if (tid == 608) {
        for (int i = 0; i < 32; i++) mbar_init(bar + B_F1 + 8 * i, 1);
        mbar_init(bar + B_G, 1);
        mbar_init(bar + B_DONE, 16);
        mbar_init(bar + B_DONE2, TRIG);
        for (int i = 0; i < 3; i++) mbar_init(bar + B_SF + 8 * i, i == 1 ? 2 : 1);
        mbar_init(bar + B_SF2, 2);
        mbar_init(bar + B_G3, 1);
        mbar_init(bar + B_G2, 4);
        asm volatile("fence.mbarrier_init.release.cluster;" ::: "memory");
    }
    __syncwarp();
    asm volatile("barrier.cluster.arrive.relaxed.aligned;" ::: "memory");
    if (warp == 19) mbar_expect(bar + B_F1 + 8 * lane, ((KVMASK >> lane) & 1) ? 16384 : 12288);
    if (warp == 16 && lane < 24) mbar_expect(bar + (lane < 8 ? B_X : lane < 16 ? B_KV - 64 : B_T - 128) + 8 * lane, 16384);
    if (tid == 512) {
        tma2d(sb, &tm.x, 0, mb * 128, bar + B_X);
    } else if (tid == 544) {
        map_prefetch(&tm.kv);
        l2_prefetch((const uint8_t*)wqkv + (size_t)blockIdx.x * 3072, 3072);
        l2_prefetch((const uint8_t*)w1 + (size_t)blockIdx.x * 1792, 1792);
        map_prefetch(&tm.q); map_prefetch(&tm.f1); map_prefetch(&tm.f3);
    }
    if (warp == 18) {
#pragma unroll
        for (int i = 0; i < XPF / 2; i++)
            asm volatile("prefetch.global.L2 [%0];" ::"l"(x + (size_t)(mb * 128 + nb * 16 + (lane & 15)) * DM + ((lane >> 4) + 2 * i) * 64));
    }
    if ((sb & 0xFFFFFF) != SBD) __trap();
    __syncwarp();
    asm volatile("barrier.cluster.wait.aligned;" ::: "memory");
    if (tid == 512) issue_stream<0, NR>(tm, sb, rank, nb, mb);
    if (tid == 0) { TLM(0, 1); TLC(0, 30); }

    if (warp < 16) {
        const int wg = warp >> 2;
        const int h = cl >> 1, qd = (cl & 1) * 2 + rank;
        const int flip = (h >> 2) & 1;
        uint32_t q[4];
        {
            const int w8 = warp & 7;
            const int T = mb * 8 + w8, row0 = T * 16 + g;
            const uint64_t dA0 = mkdesc(SBD + (wg & 1) * 8192, 16, 1024, 1);
            if (wg < 2) {
                float acc[64];
#pragma unroll
                for (int i = 0; i < 64; i++) acc[i] = 0.f;
                gemm_pass<128, 8192, 2048, 4096, 1024, 1>(acc, bar, dA0, lane, strm_pos(3, 0), strm_code(3), HOLD < 8 ? 4 : 0, true, false);
                if (tid == 0) TLM(0, 2);
                {
                    float pr[16];
#pragma unroll
                    for (int i = 0; i < 16; i++) pr[i] = __shfl_up_sync(0xffffffffu, acc[(i >> 1) * 4 + 2 + (i & 1)], 4);
                    uint32_t nn[4], pv[16];
                    norm_part(acc, nn);
#pragma unroll
                    for (int i = 0; i < 16; i++) pv[i] = pk_bf16(acc[32 + 2 * i], acc[33 + 2 * i]);
                    const uint32_t kp = sb + OFF_R + 12288 + (w8 >> 2) * 1024 + g * 128 + ((((w8 & 3) * 2 + ((t >> 1) ^ (w8 >> 2))) ^ g) << 4) + (t & 1) * 8;
                    bar_sync(9, 256);
#pragma unroll
                    for (int hh = 0; hh < 2; hh++) {
                        sts64(kp + (4 + hh) * 16384, pv[4 * hh], pv[4 * hh + 2]);
                        sts64(kp + (4 + hh) * 16384 + 2048, pv[4 * hh + 1], pv[4 * hh + 3]);
                    }
                    const float gm = g == 0 ? 0.f : -1.f;
#pragma unroll
                    for (int hh = 0; hh < 4; hh++) {
                        const float* v = acc + 8 * hh;
                        const float* p = pr + 4 * hh;
                        sts64(kp + hh * 16384 + 2048, pk_f16(v[2] - v[0], v[3] - v[1]), pk_f16(v[6] - v[4], v[7] - v[5]));
                        sts64(kp + hh * 16384, pk_f16(fmaf(p[0], gm, v[0]), fmaf(p[1], gm, v[1])), pk_f16(fmaf(p[2], gm, v[4]), fmaf(p[3], gm, v[5])));
                    }
                    uint32_t big = 0;
#pragma unroll
                    for (int i = 0; i < 16; i++) big |= pv[i] & (pv[i] << 1);
                    if (big & 0x40004000u) nn[0] = 0x7f007f00u;
                    const float km = norm_finish(nn, 1.f);
                    asm volatile("fence.proxy.async.shared::cta;" ::: "memory");
                    bar_arrive(10, 288);
                    uint8_t* vp = gKV + (size_t)(nb * 4) * (SEQ * 64) + 65536 + (((T >> 6) * 16 + 2 * g) * 64 + (T & 63)) * 32 + ((t * 8) ^ ((w8 >> 2) << 4));
#pragma unroll
                    for (int hh = 2; hh < 4; hh++) {
                        *(uint2*)(vp + (size_t)hh * (SEQ * 64)) = make_uint2(pv[4 * hh], pv[4 * hh + 2]);
                        *(uint2*)(vp + (size_t)hh * (SEQ * 64) + 2048) = make_uint2(pv[4 * hh + 1], pv[4 * hh + 3]);
                    }
                    if (lane == 0) gN[1024 + nb * 128 + T] = km;
                }
                bar_arrive(12, 544);
                if (tid == 0) TLM(0, 3);
            }
#pragma unroll 1
            for (int p = wg < 2 ? 1 : 0; p < 3; p += 2) {
                float acc[48];
#pragma unroll
                for (int i = 0; i < 48; i++) acc[i] = 0.f;
                pin<48>(acc);
                if (p) bar_sync(5 + p, 512);
                gemm_pass<96, 6144, 1024, 2048, 512, 2>(acc, bar, dA0, lane, p == 0 ? strm_pos(0, 0) : 8 + 8 * p, p == 0 ? strm_code(0) : strm_code(1), p < 2 ? 6 + p : 0, p == 0, p == 2);
                if ((tid & 255) == 0) TLM(0, 4 + 2 * p);
                const uint32_t hp = sb + OFF_R + (p == 2 ? 0 : 12288) + (wg & 1) * 16384 + ((warp & 3) * 16 + g) * 64 + t * 16;
                const uint32_t bp = sb + OFF_BIAS + p * 384 - 256 + t * 8;
                uint32_t ho[24];
                mbar_wait(bar + B_BI, 0);
                if (p == 0) {
                    uint32_t nn[4];
                    norm_part(acc, nn);
                    const float qm = norm_finish(nn, QSCALE * QSCALE);
                    if (lane == 0) gN[nb * 128 + T] = qm;
                    uint8_t* qp = gQ + (size_t)(nb * 4) * (SEQ * 32) + (size_t)row0 * 32 + t * 8;
#pragma unroll
                    for (int hh = 0; hh < 4; hh++) {
                        const float* v = acc + 8 * hh;
                        *(uint2*)(qp + hh * (SEQ * 32)) = make_uint2(pk_f16(v[0] * QSCALE, v[1] * QSCALE), pk_f16(v[4] * QSCALE, v[5] * QSCALE));
                        *(uint2*)(qp + hh * (SEQ * 32) + 256) = make_uint2(pk_f16(v[2] * QSCALE, v[3] * QSCALE), pk_f16(v[6] * QSCALE, v[7] * QSCALE));
                    }
                    bar_arrive(12, 544);
                } else {
                    gelu_pack<0, 2>(acc, bp, ho);
                    pin<16>(ho);
                    mbar_wait(bar + B_G, 0);
                    load_q(q, h, qd * 512 + flip * 256 + warp * 16 + g, t);
                }
                gelu_pack<2, 3>(acc, bp, ho);
                pin<8>(ho + 16);
                if (p == 2) bar_sync(9, 256);
                else mbar_wait(bar + B_SF + 8 * p, 0);
                if (p) {
#pragma unroll
                    for (int i = 0; i < 4; i++) sts128(hp + (i >> 1) * 32768 + (i & 1) * 512, ho + 4 * i);
                }
                sts128(hp + 65536, ho + 16);
                sts128(hp + 65536 + 512, ho + 20);
                asm volatile("fence.proxy.async.shared::cta;" ::: "memory");
                bar_arrive(p == 1 ? 14 : 11, 288);
                if ((tid & 255) == 0) TLM(0, 5 + 2 * p);
            }
        }
        uint32_t ep = 2;
        uint4* const op = gO + ((qd * 8 + wg) * NH + h) * 128 + (tid & 127);
        const uint64_t kd0 = mkdesc(SBD, 16, 256, 3);
        const uint64_t vd0 = mkdesc(SBD + 8192, OFF_ONE - 8192, 256, 3);
        {
            float o[12];
            uint32_t qn[4];
#pragma unroll 1
            for (int rh = 0; rh < 4; rh++) {
                if (rh == 1) {
                    mbar_wait(bar + B_G3, 0);
                    ep = lds32(sb + OFF_G + 256);
                    if (!(ep & 2)) break;
                    load_q(qn, h, qd * 512 + (flip ^ 1) * 256 + warp * 16 + g, t);
                }
                if (rh == 3 && lane == 0) mbar_arrive(bar + B_DONE);
                if (!(rh & 1)) {
#pragma unroll
                    for (int i = 0; i < 12; i++) o[i] = 0.f;
                }
                uint64_t kd = kd0 + (rh & 1) * 4096, vd = vd0 + (rh & 1) * (128 * VSTEP);
                uint32_t kvb = bar + B_KV + (rh & 1) * 32;
                float s[32];
#pragma unroll
                for (int i = 0; i < 32; i++) s[i] = i < 2 * NMUFU ? 0.f : ((ANDM >> (i >> 1)) & 1) ? MAGIC - 63.f : MAGIC;
                if ((tid & 255) == 0) TLM(1, (tid >> 8) * 4 + rh);
#pragma unroll 1
                for (int c = 0; c < 4; c++) {
                    mbar_wait(kvb, 0);
                    kvb += 8;
#pragma unroll
                    for (int j = 0; j < 4; j++) {
                        uint32_t p[16];
                        if (!MERGE || j == 0) {
                            wg_fence();
                            wgmma_qk_f16_acc(s, q, kd + j * 128);
                            wg_commit();
                        }
                        wg_wait<0>();
                        pin<32>(s);
#pragma unroll
                        for (int i = 0; i < 16; i++)
                            p[i] = i < NMUFU ? pk_bf16(ex2f(s[2 * i]), ex2f(s[2 * i + 1])) : ((ANDM >> i) & 1) ? exp2_pair_b(s[2 * i], s[2 * i + 1]) : exp2_pair(s[2 * i], s[2 * i + 1], m1);
                        pin<16>(p);
                        wg_fence();
#pragma unroll
                        for (int u = 0; u < 4; u++) {
                            if (MERGE && j < 3 && u == 5 - MERGE) wgmma_qk_f16_acc(s, q, kd + (j + 1) * 128);
                            wgmma_pv(o, p + 4 * u, vd + (j * 4 + u) * VSTEP);
                        }
                        if (MERGE == 1 && j < 3) wgmma_qk_f16_acc(s, q, kd + (j + 1) * 128);
                        wg_commit();
                    }
                    kd += 1024;
                    vd += 32 * VSTEP;
                }
                wg_wait<0>();
                pin<12>(o);
                if (rh & 1) {
                    if ((tid & 127) == 0 && rh == 3) TLM(1, 8 + wg);
                    store_o(o, op + ((rh >> 1) ^ flip) * (4 * NH * 128), ep & 1);
#pragma unroll
                    for (int i = 0; i < 4; i++) q[i] = qn[i];
                }
            }
            if (tid == 0) { TLM(1, 12); TLC(0, 31); }
        }
        if (!(ep & 2)) {
            bar_sync(8, 512);
            for (int c = 0; c < 8; c++) mbar_wait(bar + B_KV + 8 * c, 0);
            {
                float kc[8][8];
                proj16<8>(kc, x, wqkv, warp * 16, 256, DM + h * 16, g, t);
#pragma unroll
                for (int i = 0; i < 8; i++) {
                    const int T = warp + i * 16;
                    const int pos = ((T >> 6) * 16 + 2 * g) * 64 + (T & 63);
                    const uint32_t a = sb + (pos >> 8) * 16384 + (pos & 255) * 32 + t * 4, sw = ((T >> 2) & 1) << 4;
                    asm volatile("st.shared.u32 [%0], %1;" ::"r"(a + sw), "r"(pk_bf16(kc[i][0], kc[i][1])) : "memory");
                    asm volatile("st.shared.u32 [%0], %1;" ::"r"(a + (sw ^ 16)), "r"(pk_bf16(kc[i][4], kc[i][5])) : "memory");
                    asm volatile("st.shared.u32 [%0], %1;" ::"r"(a + 2048 + sw), "r"(pk_bf16(kc[i][2], kc[i][3])) : "memory");
                    asm volatile("st.shared.u32 [%0], %1;" ::"r"(a + 2048 + (sw ^ 16)), "r"(pk_bf16(kc[i][6], kc[i][7])) : "memory");
                }
                asm volatile("fence.proxy.async.shared::cta;" ::: "memory");
                bar_sync(8, 512);
            }
#pragma unroll 1
            for (int r = 0; r < 2; r++) {
                const int row = qd * 512 + (r ^ flip) * 256 + warp * 16 + g;
                {
                    float qc[1][8];
                    proj16<1>(qc, x, wqkv, row - g, 0, h * 16, g, t);
#pragma unroll
                    for (int i = 0; i < 4; i++) q[i] = pk_bf16(qc[0][2 * i] * QSCALE, qc[0][2 * i + 1] * QSCALE);
                }
                float o[12];
#pragma unroll
                for (int i = 0; i < 12; i++) o[i] = 0.f;
                float m0 = -INFINITY, m1 = -INFINITY;
#pragma unroll 1
                for (int j = 0; j < 32; j++) {
                    const uint64_t kd = kd0 + (j >> 2) * 1024 + (j & 3) * 128, vd = vd0 + ((j >> 2) * 32 + (j & 3) * 4) * VSTEP;
                    float s[32];
                    uint32_t p[16];
                    wg_fence();
                    wgmma_qk_bf16_zero(s, q, kd);
                    wg_commit();
                    wg_wait<0>();
                    pin<32>(s);
                    pin<12>(o);
                    float n0 = m0, n1 = m1;
#pragma unroll
                    for (int i = 0; i < 8; i++) {
                        n0 = fmaxf(n0, fmaxf(s[4 * i], s[4 * i + 1]));
                        n1 = fmaxf(n1, fmaxf(s[4 * i + 2], s[4 * i + 3]));
                    }
                    n0 = fmaxf(n0, __shfl_xor_sync(0xffffffffu, n0, 1));
                    n1 = fmaxf(n1, __shfl_xor_sync(0xffffffffu, n1, 1));
                    n0 = fmaxf(n0, __shfl_xor_sync(0xffffffffu, n0, 2));
                    n1 = fmaxf(n1, __shfl_xor_sync(0xffffffffu, n1, 2));
                    const float c0 = ex2f(m0 - n0), c1 = ex2f(m1 - n1);
                    m0 = n0;
                    m1 = n1;
#pragma unroll
                    for (int i = 0; i < 3; i++) { o[4 * i] *= c0; o[4 * i + 1] *= c0; o[4 * i + 2] *= c1; o[4 * i + 3] *= c1; }
#pragma unroll
                    for (int i = 0; i < 8; i++) {
                        p[2 * i] = pk_bf16(ex2f(s[4 * i] - m0), ex2f(s[4 * i + 1] - m0));
                        p[2 * i + 1] = pk_bf16(ex2f(s[4 * i + 2] - m1), ex2f(s[4 * i + 3] - m1));
                    }
                    pin<16>(p);
                    pin<12>(o);
                    wg_fence();
#pragma unroll
                    for (int u = 0; u < 4; u++) wgmma_pv(o, p + 4 * u, vd + u * VSTEP);
                    wg_commit();
                }
                wg_wait<0>();
                pin<12>(o);
                store_o(o, op + (r ^ flip) * (4 * NH * 128), ep & 1);
                if (r == 1 && lane == 0) mbar_arrive(bar + B_DONE);
            }
        }
        if (lane == 0 && warp >= 16 - TRIG) mbar_arrive(bar + B_DONE2);
        {
            const uint4* src = gO + (rb * NH + (wg * 2 + (rn ^ 1)) * 4) * 128 + (tid & 127);
            uint4 v[4];
#pragma unroll
            for (int i = 0; i < 4; i++) v[i] = load_o(src + i * 128);
            mbar_wait(bar + B_G2, 0);
            const int lr = (warp & 3) * 16;
            const uint32_t g0 = lds32(sb + OFF_G + (lr + g) * 4), g1 = lds32(sb + OFF_G + (lr + g) * 4 + 32);
            fetch_o<4>(v, src, ep);
            stage_o(v, sb + OFF_R + 65536 + wg * 8192 + (lr + (lane & 15)) * 128, g0, g1, lane);
            __syncwarp();
            if (lane == 0) mbar_arrive(bar + B_T + 32 + 8 * wg);
            if ((tid & 127) == 0) TLM(1, 20 + wg);
        }
    } else {
        if (warp == 16) {
            if (lane == 0) {
                issue_stream<NR, 32>(tm, sb, rank, nb, mb);
                mbar_wait(bar + B_SF2, 0);
#pragma unroll
                for (int s = 0; s < 4; s++) {
                    mbar_expect(bar + B_F2 + 8 * s, 24576);
                    tma5d_mc(sb + OFF_R + s * 24576 + 8192 + rank * 8192, &tm.w2, cb * 128 + rank * 64, s * 2, bar + B_F2 + 8 * s);
                }
                cnt_wait(gCntH + mb * 32, epoch() * 8);
                asm volatile("fence.proxy.async.global;" ::: "memory");
                TLM(1, 13);
#pragma unroll
                for (int s = 0; s < 4; s++) tma2d(sb + OFF_R + s * 24576, &tm.h, s * 64, rb * 64, bar + B_F2 + 8 * s);
            }
        } else if (warp == 17) {
            {
                uint32_t bv[4], b2v[2];
#pragma unroll
                for (int i = 0; i < 4; i++) bv[i] = lane + 32 * i < 112 ? *(const uint32_t*)(b1 + nb * 224 + (lane + 32 * i) * 2) : 0;
#pragma unroll
                for (int i = 0; i < 2; i++) b2v[i] = *(const uint32_t*)(b2 + cb * 128 + (lane + 32 * i) * 2);
#pragma unroll
                for (int i = 0; i < 4; i++) {
                    sts32(sb + OFF_ONE + (lane + 32 * i) * 4, 0x3f803f80u);
                    if (lane + 32 * i < 112) sts64(sb + OFF_BIAS + (lane + 32 * i) * 8, bv[i] << 16, bv[i] & 0xffff0000u);
                }
#pragma unroll
                for (int i = 0; i < 2; i++) sts32(sb + OFF_BIAS + 896 + (lane + 32 * i) * 4, b2v[i]);
                asm volatile("fence.proxy.async.shared::cta;" ::: "memory");
                __syncwarp();
                if (lane == 0) mbar_arrive(bar + B_BI);
            }
            mbar_wait(bar + B_X + 8 * PFX, 0);
            if (lane == 0) {
                l2_prefetch((const uint8_t*)wqkv + 128 * 3072 + (size_t)blockIdx.x * 9216, 9216);
                l2_prefetch((const uint8_t*)w1 + (size_t)blockIdx.x * 14336, 14336);
            }
            mbar_wait(bar + B_X + 8 * 7, 0);
            if (lane == 0) {
                l2_prefetch((const uint8_t*)w2 + (size_t)blockIdx.x * 14336, 14336);
                l2_prefetch((const uint8_t*)wo + (size_t)blockIdx.x * 4096, 4096);
                map_prefetch(&tm.h); map_prefetch(&tm.w2); map_prefetch(&tm.wo); map_prefetch(&tm.hs); map_prefetch(&tm.kvs);
                TLM(0, 11);
            }
            bar_sync(10, 288);
            if (lane == 0) {
#pragma unroll 1
                for (int b = 5; b >= 0; b--) {
                    tma5d_st(&tm.kvs, sb + OFF_R + 12288 + b * 16384, (mb >> 3) * 8, (mb & 7) * 2, nb * 8 + (b < 4 ? 2 * b : 2 * b - 7));
                    asm volatile("cp.async.bulk.commit_group;\ncp.async.bulk.wait_group.read %0;" ::"n"(PACE) : "memory");
                    if (b == 4 - PACE) mbar_arrive(bar + B_SF);
                }
                asm volatile("cp.async.bulk.wait_group.read 0;" ::: "memory");
                mbar_arrive(bar + B_SF + 8);
            }
            __syncwarp();
            bar_sync(12, 544);
            if (lane == 0) {
                asm volatile("cp.async.bulk.wait_group 0;\nfence.proxy.async.global;" ::: "memory");
                cnt_add(gCntQ + nb * 32);
                TLM(0, 13);
            }
        } else {
            {
                mbar_wait(bar + B_X + 8 * GDEL, 0);
                const int r0 = mb * 128 + nb * 16 + (warp - 18) * 8;
                uint4 xv[16];
#pragma unroll
                for (int i = 0; i < 16; i++) xv[i] = *(const uint4*)(x + (size_t)(r0 + (i >> 1)) * DM + (i & 1) * 256 + lane * 8);
                const uint4 ga = *(const uint4*)(gate + lane * 8), gb = *(const uint4*)(gate + 256 + lane * 8);
                float z[8];
#pragma unroll
                for (int r = 0; r < 8; r++) z[r] = dot8(xv[2 * r], ga) + dot8(xv[2 * r + 1], gb);
#pragma unroll
                for (int w = 4; w >= 1; w >>= 1)
#pragma unroll
                    for (int r = 0; r < w; r++) {
                        const bool up = lane & w;
                        z[r] = (up ? z[r + w] : z[r]) + __shfl_xor_sync(0xffffffffu, up ? z[r] : z[r + w], w);
                    }
                z[0] += __shfl_xor_sync(0xffffffffu, z[0], 8);
                z[0] += __shfl_xor_sync(0xffffffffu, z[0], 16);
                if (lane < 8) gG[r0 + lane] = 1.f / (1.f + __expf(-z[0]));
                if (tid == 576) TLM(0, 12);
            }
            if (warp == 19) {
#pragma unroll 1
                for (int e = 0; e < 3; e++) {
                    bar_sync(e == 1 ? 14 : 11, 288);
                    if (lane == 0) {
#pragma unroll 1
                        for (int b = e == 0 ? 4 : 0; b < 6; b++) {
                            tma3d_st(&tm.hs, sb + OFF_R + (e == 2 ? 0 : 12288) + b * 16384, 0, mb * 128 + (b & 1) * 64, nb * 7 + e * 3 - 2 + (b >> 1));
                            asm volatile("cp.async.bulk.commit_group;\ncp.async.bulk.wait_group.read %0;" ::"n"(PACE) : "memory");
                        }
                        asm volatile("cp.async.bulk.wait_group.read 0;" ::: "memory");
                        if (e == 0) mbar_arrive(bar + B_SF + 8);
                        if (e == 2) { mbar_arrive_cluster(bar + B_SF2, 0); mbar_arrive_cluster(bar + B_SF2, 1); }
                    }
                    __syncwarp();
                }
                bar_sync(13, 64);
                if (lane == 0) {
                    asm volatile("cp.async.bulk.wait_group 0;\nfence.proxy.async.global;" ::: "memory");
                    cnt_add(gCntH + mb * 32);
                    TLM(0, 15);
                }
            } else {
                bar_arrive(13, 64);
                const int h = cl >> 1, qd = (cl & 1) * 2 + rank;
                const uint32_t ep = epoch();
                if (lane == 0) {
                    cnt_wait(gCntQ + (h >> 2) * 32, ep * 16);
                    mbar_arrive(bar + B_G);
                    TLM(0, 14);
                    asm volatile("fence.proxy.async.global;" ::: "memory");
#pragma unroll
                    for (int c = 0; c < 2; c++) {
                        mbar_wait(bar + B_XD + 8 * c, 0);
                        bulk_mc(sb + c * 16384 + rank * 8192, gKV + (size_t)h * (SEQ * 64) + rank * 65536 + c * 8192, 8192, bar + B_KV + 8 * c);
                    }
                }
                __syncwarp();
            const int hb = h >> 2;
            const uint4 kq = __ldcg((const uint4*)(gN + 1024 + hb * 128 + lane * 4));
            const float qq = ldcg_f(gN + hb * 128 + qd * 32 + lane);
            const float kf = __uint_as_float(__reduce_max_sync(0xffffffffu, max(max(kq.x, kq.y), max(kq.z, kq.w))));
            const float qf = __uint_as_float(__reduce_max_sync(0xffffffffu, __float_as_uint(qq)));
            if (lane == 0) {
                sts32(sb + OFF_G + 256, (ep & 1) | ((kf <= 1.0e6f) && (qf <= 1.0e6f) && (kf * qf <= 2300.f) ? 2 : 0));
                mbar_arrive(bar + B_G3);
                TLM(0, 16);
#pragma unroll
                for (int c = 2; c < 8; c++) {
                    mbar_wait(bar + B_XD + 8 * c, 0);
                    bulk_mc(sb + c * 16384 + rank * 8192, gKV + (size_t)h * (SEQ * 64) + rank * 65536 + c * 8192, 8192, bar + B_KV + 8 * c);
                }
                TLM(0, 10);
            }
            }
        }
        __syncwarp();
        float acc[64];
#pragma unroll
        for (int i = 0; i < 64; i++) acc[i] = 0.f;
#pragma unroll 1
        for (int io = 0; io < 7; io++) {
#pragma unroll
            for (int s = 0; s < 4; s++) {
                const int it = io * 4 + s;
                mbar_wait(bar + B_F2 + 8 * s, io & 1);
                if (tid == 512 && s == 0 && (io == 0 || io == 4)) TLM(1, 14 + io / 4);
                const uint64_t dA = mkdesc(SBD + OFF_R + s * 24576, 16, 1024, 1);
                const uint64_t dB = mkdesc(SBD + OFF_R + s * 24576 + 8192, 8192, 1024, 1);
                wg_fence();
#pragma unroll
                for (int kk = 0; kk < EXP_FKK; kk++) {
                    wgmma_ss_n128(acc, dA + kk * 2, dB + kk * 128);
                    if (kk < 3 && (FSER != 3 || kk == 1)) {
                        wg_commit();
                        wg_wait<0>();
                    }
                }
                wg_commit();
                if (warp < 18 && it >= 2 && it < 26) {
                    const int s2 = (s + 2) & 3;
                    mbar_wait(bar + B_E2 + 8 * s2, (io - (s < 2)) & 1);
                    if (elect()) {
                        if (warp == 16) {
                            mbar_expect(bar + B_F2 + 8 * s2, 24576);
                            tma5d_mc(sb + OFF_R + s2 * 24576 + 8192 + rank * 8192, &tm.w2, cb * 128 + rank * 64, it * 2 + 4, bar + B_F2 + 8 * s2);
                        } else {
                            asm volatile("fence.proxy.async.global;" ::: "memory");
                            tma2d(sb + OFF_R + s2 * 24576, &tm.h, it * 64 + 128, rb * 64, bar + B_F2 + 8 * s2);
                        }
                    }
                    __syncwarp();
                }
                wg_wait<1>();
                if (it >= 1 && lane < 2) mbar_arrive_cluster(bar + B_E2 + 8 * ((s + 3) & 3), lane);
            }
        }
        wg_wait<0>();
        if (lane < 2) mbar_arrive_cluster(bar + B_E2 + 8 * 3, lane);
        pin<64>(acc);
        if (tid == 576) gEpoch[blockIdx.x] = epoch();
        if (warp == 16) {
            if (lane == 0) TLM(1, 16);
            for (int s = 0; s < 4; s++) mbar_wait(bar + B_E2 + 8 * s, 0);
            if (elect()) {
#pragma unroll
                for (int i = 0; i < 4; i++)
                    tma5d_mc(sb + OFF_R + i * 16384 + rank * 8192, &tm.wo, cb * 128 + rank * 64, (i * 2 + rn) * 4, bar + B_T + 8 * i);
            }
            __syncwarp();
        }
        uint32_t pa;
        {
            const int lr = (warp - 16) * 16 + g;
            pa = pk_bf16(ldcg_f(gG + rb * 64 + lr), ldcg_f(gG + rb * 64 + lr + 8));
            if (t == 0) {
                sts32(sb + OFF_G + lr * 4, __byte_perm(pa, pa, 0x1010));
                sts32(sb + OFF_G + lr * 4 + 32, __byte_perm(pa, pa, 0x3232));
            }
            const float ga = bf_lo(pa), gb = bf_hi(pa);
            const float g0 = 1.f - ga, g1 = 1.f - gb;
#pragma unroll
            for (int j = 0; j < 16; j++) {
                const uint32_t bv = lds32(sb + OFF_BIAS + 896 + j * 16 + t * 4);
                acc[4 * j] = fmaf(acc[4 * j], 0.5f, bf_lo(bv)) * g0;
                acc[4 * j + 1] = fmaf(acc[4 * j + 1], 0.5f, bf_hi(bv)) * g0;
                acc[4 * j + 2] = fmaf(acc[4 * j + 2], 0.5f, bf_lo(bv)) * g1;
                acc[4 * j + 3] = fmaf(acc[4 * j + 3], 0.5f, bf_hi(bv)) * g1;
            }
            pin<64>(acc);
        }
        {
            mbar_wait(bar + B_G3, 0);
            const uint32_t ep = lds32(sb + OFF_G + 256);
            const uint4* src = gO + (rb * NH + rn * 4) * 128 + (tid & 127);
            bar_sync(15, 128);
#pragma unroll 1
            for (int e = 0; e < 4; e++) {
                uint4 v[4];
#pragma unroll
                for (int i = 0; i < 4; i++) v[i] = load_o(src + i * 128);
                fetch_o<4>(v, src, ep);
                stage_o(v, sb + OFF_R + 65536 + e * 8192 + ((warp - 16) * 16 + (lane & 15)) * 128, __byte_perm(pa, pa, 0x1010), __byte_perm(pa, pa, 0x3232), lane);
                src += 8 * 128;
            }
            if (warp == 16) {
                mbar_wait(bar + B_DONE, 0);
                if (elect()) {
#pragma unroll
                    for (int i = 0; i < 8; i++)
                        tma5d(sb + i * 8192, &tm.wo, cb * 128 + (i & 1) * 64, ((i >> 1) * 2 + (rn ^ 1)) * 4, bar + B_T + 32 + 8 * (i >> 1));
                }
                __syncwarp();
            }
            bar_sync(15, 128);
            if (tid == 512) TLM(1, 17);
            mbar_wait(bar + B_DONE2, 0);
        }
#pragma unroll 1
        for (int late = 0; late < 2; late++) {
            const uint64_t dB0 = mkdesc(SBD + OFF_R, 8192, 1024, 1) - late * (OFF_R / 16);
#pragma unroll
            for (int i = 0; i < 4; i++) {
                mbar_wait(bar + B_T + late * 32 + 8 * i, 0);
                const uint64_t dA = mkdesc(SBD + OFF_R + 65536 + i * 8192, 16, 1024, 1);
                wg_fence();
#pragma unroll
                for (int kk = 0; kk < 4; kk++) wgmma_ss_n128(acc, dA + kk * 2, dB0 + i * 1024 + kk * 128);
                wg_commit();
            }
            if (!late) {
                wg_wait<0>();
                if (lane == 0) mbar_arrive(bar + B_G2);
            }
        }
        wg_wait<0>();
        pin<64>(acc);
        if (tid == 512) TLM(1, 18);
        {
            const uint32_t st = sb + 98304 + (warp - 16) * 4352;
            const uint32_t wa = st + (lane & 15) * 272 + (lane >> 4) * 16;
#pragma unroll
            for (int j = 0; j < 8; j++)
                asm volatile("stmatrix.sync.aligned.m8n8.x4.shared.b16 [%0], {%1, %2, %3, %4};" ::"r"(wa + j * 32),
                             "r"(pk_bf16(acc[8 * j], acc[8 * j + 1])), "r"(pk_bf16(acc[8 * j + 2], acc[8 * j + 3])),
                             "r"(pk_bf16(acc[8 * j + 4], acc[8 * j + 5])), "r"(pk_bf16(acc[8 * j + 6], acc[8 * j + 7])) : "memory");
            __syncwarp();
            __nv_bfloat16* op = out + (size_t)(rb * 64 + (warp - 16) * 16 + (lane >> 4)) * DM + cb * 128 + (lane & 15) * 8;
#pragma unroll
            for (int j = 0; j < 8; j++) {
                uint4 v;
                asm volatile("ld.shared.v4.u32 {%0, %1, %2, %3}, [%4];" : "=r"(v.x), "=r"(v.y), "=r"(v.z), "=r"(v.w)
                             : "r"(st + (2 * j + (lane >> 4)) * 272 + (lane & 15) * 16));
                *(uint4*)(op + (size_t)j * 2 * DM) = v;
            }
        }
        if (tid == 512) TLM(1, 19);
        TL_DUMP();
    }
}

typedef CUresult (*EncodeFn)(CUtensorMap*, CUtensorMapDataType, cuuint32_t, void*, const cuuint64_t*, const cuuint64_t*, const cuuint32_t*,
                             const cuuint32_t*, CUtensorMapInterleave, CUtensorMapSwizzle, CUtensorMapL2promotion, CUtensorMapFloatOOBfill);

static void make_map(EncodeFn enc, CUtensorMap* m, const void* p, int rank, const cuuint64_t* dims, const cuuint64_t* strides,
                     const cuuint32_t* box, CUtensorMapSwizzle swz) {
    const cuuint32_t es[5] = {1, 1, 1, 1, 1};
    enc(m, CU_TENSOR_MAP_DATA_TYPE_BFLOAT16, rank, (void*)p, dims, strides, box, es, CU_TENSOR_MAP_INTERLEAVE_NONE, swz,
        CU_TENSOR_MAP_L2_PROMOTION_L2_128B, CU_TENSOR_MAP_FLOAT_OOB_FILL_NONE);
}

extern "C" void kernel_launch(void* const* d_in, const int* in_sizes, int n_in, void* d_out, int out_size) {
    const __nv_bfloat16* x = (const __nv_bfloat16*)d_in[0];
    const __nv_bfloat16* wqkv = (const __nv_bfloat16*)d_in[1];
    const __nv_bfloat16* wo = (const __nv_bfloat16*)d_in[2];
    const __nv_bfloat16* w1 = (const __nv_bfloat16*)d_in[4];
    const __nv_bfloat16* b1 = (const __nv_bfloat16*)d_in[5];
    const __nv_bfloat16* w2 = (const __nv_bfloat16*)d_in[6];
    const __nv_bfloat16* b2 = (const __nv_bfloat16*)d_in[7];
    const __nv_bfloat16* gate = (const __nv_bfloat16*)d_in[8];

    void* fp = nullptr;
    cudaDriverEntryPointQueryResult qr;
    cudaGetDriverEntryPoint("cuTensorMapEncodeTiled", &fp, cudaEnableDefault, &qr);
    EncodeFn enc = (EncodeFn)fp;
    void *pH, *pKV;
    cudaGetSymbolAddress(&pH, gH);
    cudaGetSymbolAddress(&pKV, gKV);

    Maps tm;
    const CUtensorMapSwizzle S128 = CU_TENSOR_MAP_SWIZZLE_128B, S64 = CU_TENSOR_MAP_SWIZZLE_64B;
    { cuuint64_t d[2] = {DM, SEQ}, s[1] = {DM * 2}; cuuint32_t b[2] = {64, 128}; make_map(enc, &tm.x, x, 2, d, s, b, S128); }
    { cuuint64_t d[3] = {DM, DM, 3}, s[2] = {3 * DM * 2, DM * 2}; cuuint32_t b[3] = {64, 32, 2}; make_map(enc, &tm.kv, wqkv, 3, d, s, b, S128); }
    { cuuint64_t d[3] = {32, DM, 3 * DM / 32}, s[2] = {3 * DM * 2, 64}; cuuint32_t b[3] = {32, 32, 2}; make_map(enc, &tm.q, wqkv, 3, d, s, b, S64); }
    { cuuint64_t d[3] = {32, DM, FF / 32}, s[2] = {FF * 2, 64}; cuuint32_t b[3] = {32, 32, 1}; make_map(enc, &tm.f1, w1, 3, d, s, b, S64); }
    { cuuint64_t d[3] = {32, DM, FF / 32}, s[2] = {FF * 2, 64}; cuuint32_t b[3] = {32, 32, 3}; make_map(enc, &tm.f3, w1, 3, d, s, b, S64); }
    { cuuint64_t d[2] = {FF, SEQ}, s[1] = {FF * 2}; cuuint32_t b[2] = {64, 64}; make_map(enc, &tm.h, pH, 2, d, s, b, S128); }
    { cuuint64_t d[5] = {DM, 2, 4, 4, FF / 32}, s[4] = {1024, 8 * 1024, 2 * 1024, 32 * 1024}; cuuint32_t b[5] = {64, 2, 4, 4, 2};
      make_map(enc, &tm.w2, w2, 5, d, s, b, S128); }
    { cuuint64_t d[5] = {DM, 2, 2, 4, NH}, s[4] = {1024, 8 * 1024, 2 * 1024, 16 * 1024}; cuuint32_t b[5] = {64, 2, 2, 4, 4};
      make_map(enc, &tm.wo, wo, 5, d, s, b, S128); }

    { cuuint64_t d[3] = {32, SEQ, FF / 32}, s[2] = {FF * 2, 64}; cuuint32_t b[3] = {32, 64, 1}; make_map(enc, &tm.hs, pH, 3, d, s, b, CU_TENSOR_MAP_SWIZZLE_NONE); }
    { cuuint64_t d[5] = {64, 16, 16, 2, 2 * NH}, s[4] = {4096, 128, 2048, 65536}; cuuint32_t b[5] = {64, 8, 2, 2, 1};
      make_map(enc, &tm.kvs, pKV, 5, d, s, b, S128); }
    cudaFuncSetAttribute(fused_kernel, cudaFuncAttributeMaxDynamicSharedMemorySize, TL_SMEM);
    fused_kernel<<<128, 640, TL_SMEM, cudaStreamPerThread>>>(tm, x, wqkv, wo, w1, b1, w2, b2, gate, (__nv_bfloat16*)d_out, 0xffffffffu);
}
```

```cpp
#include <cuda_runtime.h>
#include <cuda_bf16.h>
#include <cuda_fp16.h>
#include <cuda.h>
#include <stdint.h>

#define SEQ 2048
#define DM 512
#define FF 1792
#define NH 32

__device__ __align__(1024) uint8_t gQ[NH * SEQ * 32];
__device__ __align__(1024) uint8_t gKV[NH * SEQ * 64];
__device__ __align__(1024) __nv_bfloat16 gH[SEQ * FF];
__device__ __align__(1024) uint4 gO[32 * NH * 128];
__device__ float gG[SEQ];
__device__ float gN[3 * 8 * 128];
__device__ unsigned int gCntQ[8 * 32];
__device__ unsigned int gCntH[32 * 32];
__device__ unsigned int gEpoch[128];

__device__ __forceinline__ uint32_t smem_u32(const void* p) { return (uint32_t)__cvta_generic_to_shared(p); }
__device__ __forceinline__ void mbar_init(uint32_t a, uint32_t c) { asm volatile("mbarrier.init.shared::cta.b64 [%0], %1;" ::"r"(a), "r"(c)); }
__device__ __forceinline__ void mbar_expect(uint32_t a, uint32_t b) { asm volatile("mbarrier.arrive.expect_tx.shared::cta.b64 _, [%0], %1;" ::"r"(a), "r"(b) : "memory"); }
__device__ __forceinline__ void mbar_arrive(uint32_t a) { asm volatile("mbarrier.arrive.shared::cta.b64 _, [%0];" ::"r"(a) : "memory"); }
__device__ __forceinline__ void mbar_wait(uint32_t a, uint32_t ph) {
    asm volatile("{\n.reg .pred p;\n.reg .u32 n;\nmov.u32 n, 0;\nW_%=:\nmbarrier.try_wait.parity.shared::cta.b64 p, [%0], %1;\n@p bra D_%=;\n"
                 "add.u32 n, n, 1;\nsetp.lt.u32 p, n, 0x400000;\n@p bra W_%=;\ntrap;\nD_%=:\n}" ::"r"(a), "r"(ph) : "memory");
}
__device__ __forceinline__ void mbar_arrive_cluster(uint32_t a, uint32_t cta) {
    asm volatile("{\n.reg .b32 r;\nmapa.shared::cluster.u32 r, %0, %1;\nmbarrier.arrive.shared::cluster.b64 _, [r];\n}" ::"r"(a), "r"(cta) : "memory");
}
__device__ __forceinline__ void bar_sync(int id, int n) { asm volatile("bar.sync %0, %1;" ::"r"(id), "r"(n) : "memory"); }
__device__ __forceinline__ void bar_arrive(int id, int n) { asm volatile("bar.arrive %0, %1;" ::"r"(id), "r"(n) : "memory"); }
__device__ __forceinline__ uint32_t cluster_rank() { uint32_t r; asm("mov.u32 %0, %%cluster_ctarank;" : "=r"(r)); return r; }
__device__ __forceinline__ void cnt_add(unsigned int* c) { asm volatile("red.release.gpu.global.add.u32 [%0], 1;" ::"l"(c) : "memory"); }
__device__ __forceinline__ void cnt_wait(const unsigned int* c, uint32_t target) {
    uint32_t v;
    int spins = 0;
    while (true) {
        asm volatile("ld.acquire.gpu.global.u32 %0, [%1];" : "=r"(v) : "l"(c) : "memory");
        if ((int)(v - target) >= 0) break;
        if (++spins > (1 << 22)) __trap();
        __nanosleep(40);
    }
}
__device__ __forceinline__ void tma2d(uint32_t dst, const CUtensorMap* m, int c0, int c1, uint32_t bar) {
    asm volatile("cp.async.bulk.tensor.2d.shared::cluster.global.mbarrier::complete_tx::bytes [%0], [%1, {%3, %4}], [%2];"
                 ::"r"(dst), "l"(m), "r"(bar), "r"(c0), "r"(c1) : "memory");
}
__device__ __forceinline__ void tma2d_mc(uint32_t dst, const CUtensorMap* m, int c0, int c1, uint32_t bar) {
    asm volatile("cp.async.bulk.tensor.2d.shared::cluster.global.mbarrier::complete_tx::bytes.multicast::cluster [%0], [%1, {%3, %4}], [%2], %5;"
                 ::"r"(dst), "l"(m), "r"(bar), "r"(c0), "r"(c1), "h"((uint16_t)3) : "memory");
}
__device__ __forceinline__ void tma3d_mc(uint32_t dst, const CUtensorMap* m, int c0, int c1, int c2, uint32_t bar) {
    asm volatile("cp.async.bulk.tensor.3d.shared::cluster.global.mbarrier::complete_tx::bytes.multicast::cluster [%0], [%1, {%3, %4, %5}], [%2], %6;"
                 ::"r"(dst), "l"(m), "r"(bar), "r"(c0), "r"(c1), "r"(c2), "h"((uint16_t)3) : "memory");
}
__device__ __forceinline__ void tma3d_m(uint32_t dst, const CUtensorMap* m, int c0, int c1, int c2, uint32_t bar, uint16_t mask) {
    asm volatile("cp.async.bulk.tensor.3d.shared::cluster.global.mbarrier::complete_tx::bytes.multicast::cluster [%0], [%1, {%3, %4, %5}], [%2], %6;"
                 ::"r"(dst), "l"(m), "r"(bar), "r"(c0), "r"(c1), "r"(c2), "h"(mask) : "memory");
}
__device__ __forceinline__ void tma5d_mc(uint32_t dst, const CUtensorMap* m, int c0, int c4, uint32_t bar) {
    asm volatile("cp.async.bulk.tensor.5d.shared::cluster.global.mbarrier::complete_tx::bytes.multicast::cluster [%0], [%1, {%3, %5, %5, %5, %4}], [%2], %6;"
                 ::"r"(dst), "l"(m), "r"(bar), "r"(c0), "r"(c4), "r"(0), "h"((uint16_t)3) : "memory");
}
__device__ __forceinline__ void tma5d(uint32_t dst, const CUtensorMap* m, int c0, int c4, uint32_t bar) {
    asm volatile("cp.async.bulk.tensor.5d.shared::cluster.global.mbarrier::complete_tx::bytes [%0], [%1, {%3, %5, %5, %5, %4}], [%2];"
                 ::"r"(dst), "l"(m), "r"(bar), "r"(c0), "r"(c4), "r"(0) : "memory");
}
__device__ __forceinline__ void bulk_mc(uint32_t dst, const void* src, uint32_t bytes, uint32_t bar) {
    asm volatile("cp.async.bulk.shared::cluster.global.mbarrier::complete_tx::bytes.multicast::cluster [%0], [%1], %2, [%3], %4;"
                 ::"r"(dst), "l"(src), "r"(bytes), "r"(bar), "h"((uint16_t)3) : "memory");
}
__device__ __forceinline__ void tma3d_st(const CUtensorMap* m, uint32_t src, int c0, int c1, int c2) {
    asm volatile("cp.async.bulk.tensor.3d.global.shared::cta.bulk_group [%0, {%2, %3, %4}], [%1];" ::"l"(m), "r"(src), "r"(c0), "r"(c1), "r"(c2) : "memory");
}
__device__ __forceinline__ void tma5d_st(const CUtensorMap* m, uint32_t src, int c1, int c2, int c4) {
    asm volatile("cp.async.bulk.tensor.5d.global.shared::cta.bulk_group [%0, {%5, %2, %3, %5, %4}], [%1];"
                 ::"l"(m), "r"(src), "r"(c1), "r"(c2), "r"(c4), "r"(0) : "memory");
}
__device__ __forceinline__ void bulk_st(void* dst, uint32_t src, uint32_t bytes) {
    asm volatile("cp.async.bulk.global.shared::cta.bulk_group [%0], [%1], %2;" ::"l"(dst), "r"(src), "r"(bytes) : "memory");
}
__device__ __forceinline__ void sts64(uint32_t a, uint32_t x, uint32_t y) { asm volatile("st.shared.v2.u32 [%0], {%1, %2};" ::"r"(a), "r"(x), "r"(y) : "memory"); }
__device__ __forceinline__ void sts128(uint32_t a, const uint32_t* v) {
    asm volatile("st.shared.v4.u32 [%0], {%1, %2, %3, %4};" ::"r"(a), "r"(v[0]), "r"(v[1]), "r"(v[2]), "r"(v[3]) : "memory");
}
__device__ __forceinline__ void l2_prefetch(const void* src, uint32_t bytes) {
    asm volatile("cp.async.bulk.prefetch.L2.global [%0], %1;" ::"l"(src), "r"(bytes) : "memory");
}
__device__ __forceinline__ void map_prefetch(const CUtensorMap* m) { asm volatile("prefetch.tensormap [%0];" ::"l"(m) : "memory"); }
__device__ __forceinline__ void wg_fence() { asm volatile("wgmma.fence.sync.aligned;" ::: "memory"); }
__device__ __forceinline__ void wg_commit() { asm volatile("wgmma.commit_group.sync.aligned;" ::: "memory"); }
template <int N> __device__ __forceinline__ void wg_wait() { asm volatile("wgmma.wait_group.sync.aligned %0;" ::"n"(N) : "memory"); }
template <int N> __device__ __forceinline__ void pin(float* s) {
#pragma unroll
    for (int i = 0; i < N; i++) asm volatile("" : "+f"(s[i])::"memory");
}
template <int N> __device__ __forceinline__ void pin(uint32_t* s) {
#pragma unroll
    for (int i = 0; i < N; i++) asm volatile("" : "+r"(s[i])::"memory");
}
__device__ __forceinline__ uint64_t mkdesc(uint32_t addr, uint32_t lbo, uint32_t sbo, uint32_t swz) {
    return (uint64_t)((addr & 0x3FFFF) >> 4) | ((uint64_t)(lbo >> 4) << 16) | ((uint64_t)(sbo >> 4) << 32) | ((uint64_t)swz << 62);
}
__device__ __forceinline__ float ex2f(float x) { float y; asm("ex2.approx.ftz.f32 %0, %1;" : "=f"(y) : "f"(x)); return y; }
__device__ __forceinline__ float tanhf_(float x) { float y; asm("tanh.approx.f32 %0, %1;" : "=f"(y) : "f"(x)); return y; }
__device__ __forceinline__ uint32_t pk_bf16(float lo, float hi) { uint32_t r; asm("cvt.rn.bf16x2.f32 %0, %1, %2;" : "=r"(r) : "f"(hi), "f"(lo)); return r; }
__device__ __forceinline__ uint32_t pk_f16(float lo, float hi) { uint32_t r; asm("cvt.rn.f16x2.f32 %0, %1, %2;" : "=r"(r) : "f"(hi), "f"(lo)); return r; }
__device__ __forceinline__ float bf_lo(uint32_t v) { return __uint_as_float(v << 16); }
__device__ __forceinline__ float bf_hi(uint32_t v) { return __uint_as_float(v & 0xffff0000u); }
__device__ __forceinline__ float dot8(const uint4& a, const uint4& b) {
    return fmaf(bf_lo(a.x), bf_lo(b.x), fmaf(bf_hi(a.x), bf_hi(b.x), fmaf(bf_lo(a.y), bf_lo(b.y), bf_hi(a.y) * bf_hi(b.y)))) +
           fmaf(bf_lo(a.z), bf_lo(b.z), fmaf(bf_hi(a.z), bf_hi(b.z), fmaf(bf_lo(a.w), bf_lo(b.w), bf_hi(a.w) * bf_hi(b.w))));
}
__device__ __forceinline__ uint32_t epoch() {
    uint32_t v;
    asm volatile("ld.global.u32 %0, [%1];" : "=r"(v) : "l"(gEpoch + blockIdx.x));
    return v + 1;
}
__device__ __forceinline__ float ldcg_f(const float* p) { return __ldcg(p); }

extern __shared__ __align__(1024) uint8_t smem_raw[];
#define TLM(k, slot) do {} while (0)
#define TLC(k, slot) do {} while (0)
#define TL_INIT() do {} while (0)
#define TL_DUMP() do {} while (0)
#define TL_SMEM SMEM_BYTES

__device__ __forceinline__ void wgmma_ss_n128(float* d, uint64_t da, uint64_t db) {
    asm volatile("wgmma.mma_async.sync.aligned.m64n128k16.f32.bf16.bf16 {"
        "%0, %1, %2, %3, %4, %5, %6, %7, %8, %9, %10, %11, %12, %13, %14, %15,"
        "%16, %17, %18, %19, %20, %21, %22, %23, %24, %25, %26, %27, %28, %29, %30, %31,"
        "%32, %33, %34, %35, %36, %37, %38, %39, %40, %41, %42, %43, %44, %45, %46, %47,"
        "%48, %49, %50, %51, %52, %53, %54, %55, %56, %57, %58, %59, %60, %61, %62, %63}, %64, %65, 1, 1, 1, 0, 1;\n"
        :
        "+f"(d[0]), "+f"(d[1]), "+f"(d[2]), "+f"(d[3]), "+f"(d[4]), "+f"(d[5]), "+f"(d[6]), "+f"(d[7]),
        "+f"(d[8]), "+f"(d[9]), "+f"(d[10]), "+f"(d[11]), "+f"(d[12]), "+f"(d[13]), "+f"(d[14]), "+f"(d[15]),
        "+f"(d[16]), "+f"(d[17]), "+f"(d[18]), "+f"(d[19]), "+f"(d[20]), "+f"(d[21]), "+f"(d[22]), "+f"(d[23]),
        "+f"(d[24]), "+f"(d[25]), "+f"(d[26]), "+f"(d[27]), "+f"(d[28]), "+f"(d[29]), "+f"(d[30]), "+f"(d[31]),
        "+f"(d[32]), "+f"(d[33]), "+f"(d[34]), "+f"(d[35]), "+f"(d[36]), "+f"(d[37]), "+f"(d[38]), "+f"(d[39]),
        "+f"(d[40]), "+f"(d[41]), "+f"(d[42]), "+f"(d[43]), "+f"(d[44]), "+f"(d[45]), "+f"(d[46]), "+f"(d[47]),
        "+f"(d[48]), "+f"(d[49]), "+f"(d[50]), "+f"(d[51]), "+f"(d[52]), "+f"(d[53]), "+f"(d[54]), "+f"(d[55]),
        "+f"(d[56]), "+f"(d[57]), "+f"(d[58]), "+f"(d[59]), "+f"(d[60]), "+f"(d[61]), "+f"(d[62]), "+f"(d[63])
        : "l"(da), "l"(db));
}
__device__ __forceinline__ void wgmma_ss_n96(float* d, uint64_t da, uint64_t db) {
    asm volatile("wgmma.mma_async.sync.aligned.m64n96k16.f32.bf16.bf16 {"
        "%0, %1, %2, %3, %4, %5, %6, %7, %8, %9, %10, %11, %12, %13, %14, %15,"
        "%16, %17, %18, %19, %20, %21, %22, %23, %24, %25, %26, %27, %28, %29, %30, %31,"
        "%32, %33, %34, %35, %36, %37, %38, %39, %40, %41, %42, %43, %44, %45, %46, %47}, %48, %49, 1, 1, 1, 0, 1;\n"
        :
        "+f"(d[0]), "+f"(d[1]), "+f"(d[2]), "+f"(d[3]), "+f"(d[4]), "+f"(d[5]), "+f"(d[6]), "+f"(d[7]),
        "+f"(d[8]), "+f"(d[9]), "+f"(d[10]), "+f"(d[11]), "+f"(d[12]), "+f"(d[13]), "+f"(d[14]), "+f"(d[15]),
        "+f"(d[16]), "+f"(d[17]), "+f"(d[18]), "+f"(d[19]), "+f"(d[20]), "+f"(d[21]), "+f"(d[22]), "+f"(d[23]),
        "+f"(d[24]), "+f"(d[25]), "+f"(d[26]), "+f"(d[27]), "+f"(d[28]), "+f"(d[29]), "+f"(d[30]), "+f"(d[31]),
        "+f"(d[32]), "+f"(d[33]), "+f"(d[34]), "+f"(d[35]), "+f"(d[36]), "+f"(d[37]), "+f"(d[38]), "+f"(d[39]),
        "+f"(d[40]), "+f"(d[41]), "+f"(d[42]), "+f"(d[43]), "+f"(d[44]), "+f"(d[45]), "+f"(d[46]), "+f"(d[47])
        : "l"(da), "l"(db));
}
__device__ __forceinline__ void wgmma_ss_n64(float* d, uint64_t da, uint64_t db) {
    asm volatile("wgmma.mma_async.sync.aligned.m64n64k16.f32.bf16.bf16 {"
        "%0, %1, %2, %3, %4, %5, %6, %7, %8, %9, %10, %11, %12, %13, %14, %15,"
        "%16, %17, %18, %19, %20, %21, %22, %23, %24, %25, %26, %27, %28, %29, %30, %31}, %32, %33, 1, 1, 1, 0, 1;\n"
        :
        "+f"(d[0]), "+f"(d[1]), "+f"(d[2]), "+f"(d[3]), "+f"(d[4]), "+f"(d[5]), "+f"(d[6]), "+f"(d[7]),
        "+f"(d[8]), "+f"(d[9]), "+f"(d[10]), "+f"(d[11]), "+f"(d[12]), "+f"(d[13]), "+f"(d[14]), "+f"(d[15]),
        "+f"(d[16]), "+f"(d[17]), "+f"(d[18]), "+f"(d[19]), "+f"(d[20]), "+f"(d[21]), "+f"(d[22]), "+f"(d[23]),
        "+f"(d[24]), "+f"(d[25]), "+f"(d[26]), "+f"(d[27]), "+f"(d[28]), "+f"(d[29]), "+f"(d[30]), "+f"(d[31])
        : "l"(da), "l"(db));
}
__device__ __forceinline__ void wgmma_rs_n128(float* d, const uint32_t* a, uint64_t db) {
    asm volatile("wgmma.mma_async.sync.aligned.m64n128k16.f32.bf16.bf16 {"
        "%0, %1, %2, %3, %4, %5, %6, %7, %8, %9, %10, %11, %12, %13, %14, %15,"
        "%16, %17, %18, %19, %20, %21, %22, %23, %24, %25, %26, %27, %28, %29, %30, %31,"
        "%32, %33, %34, %35, %36, %37, %38, %39, %40, %41, %42, %43, %44, %45, %46, %47,"
        "%48, %49, %50, %51, %52, %53, %54, %55, %56, %57, %58, %59, %60, %61, %62, %63}, {%64, %65, %66, %67}, %68, 1, 1, 1, 1;\n"
        :
        "+f"(d[0]), "+f"(d[1]), "+f"(d[2]), "+f"(d[3]), "+f"(d[4]), "+f"(d[5]), "+f"(d[6]), "+f"(d[7]),
        "+f"(d[8]), "+f"(d[9]), "+f"(d[10]), "+f"(d[11]), "+f"(d[12]), "+f"(d[13]), "+f"(d[14]), "+f"(d[15]),
        "+f"(d[16]), "+f"(d[17]), "+f"(d[18]), "+f"(d[19]), "+f"(d[20]), "+f"(d[21]), "+f"(d[22]), "+f"(d[23]),
        "+f"(d[24]), "+f"(d[25]), "+f"(d[26]), "+f"(d[27]), "+f"(d[28]), "+f"(d[29]), "+f"(d[30]), "+f"(d[31]),
        "+f"(d[32]), "+f"(d[33]), "+f"(d[34]), "+f"(d[35]), "+f"(d[36]), "+f"(d[37]), "+f"(d[38]), "+f"(d[39]),
        "+f"(d[40]), "+f"(d[41]), "+f"(d[42]), "+f"(d[43]), "+f"(d[44]), "+f"(d[45]), "+f"(d[46]), "+f"(d[47]),
        "+f"(d[48]), "+f"(d[49]), "+f"(d[50]), "+f"(d[51]), "+f"(d[52]), "+f"(d[53]), "+f"(d[54]), "+f"(d[55]),
        "+f"(d[56]), "+f"(d[57]), "+f"(d[58]), "+f"(d[59]), "+f"(d[60]), "+f"(d[61]), "+f"(d[62]), "+f"(d[63])
        : "r"(a[0]), "r"(a[1]), "r"(a[2]), "r"(a[3]), "l"(db));
}
__device__ __forceinline__ void wgmma_qk_f16_acc(float* d, const uint32_t* a, uint64_t db) {
    asm volatile("wgmma.mma_async.sync.aligned.m64n64k16.f32.f16.f16 {"
        "%0, %1, %2, %3, %4, %5, %6, %7, %8, %9, %10, %11, %12, %13, %14, %15,"
        "%16, %17, %18, %19, %20, %21, %22, %23, %24, %25, %26, %27, %28, %29, %30, %31}, {%32, %33, %34, %35}, %36, 1, 1, 1, 0;\n"
        :
        "+f"(d[0]), "+f"(d[1]), "+f"(d[2]), "+f"(d[3]), "+f"(d[4]), "+f"(d[5]), "+f"(d[6]), "+f"(d[7]),
        "+f"(d[8]), "+f"(d[9]), "+f"(d[10]), "+f"(d[11]), "+f"(d[12]), "+f"(d[13]), "+f"(d[14]), "+f"(d[15]),
        "+f"(d[16]), "+f"(d[17]), "+f"(d[18]), "+f"(d[19]), "+f"(d[20]), "+f"(d[21]), "+f"(d[22]), "+f"(d[23]),
        "+f"(d[24]), "+f"(d[25]), "+f"(d[26]), "+f"(d[27]), "+f"(d[28]), "+f"(d[29]), "+f"(d[30]), "+f"(d[31])
        : "r"(a[0]), "r"(a[1]), "r"(a[2]), "r"(a[3]), "l"(db));
}
__device__ __forceinline__ void wgmma_qk_bf16_zero(float* d, const uint32_t* a, uint64_t db) {
    asm volatile("wgmma.mma_async.sync.aligned.m64n64k16.f32.bf16.bf16 {"
        "%0, %1, %2, %3, %4, %5, %6, %7, %8, %9, %10, %11, %12, %13, %14, %15,"
        "%16, %17, %18, %19, %20, %21, %22, %23, %24, %25, %26, %27, %28, %29, %30, %31}, {%32, %33, %34, %35}, %36, 0, 1, 1, 0;\n"
        :
        "=f"(d[0]), "=f"(d[1]), "=f"(d[2]), "=f"(d[3]), "=f"(d[4]), "=f"(d[5]), "=f"(d[6]), "=f"(d[7]),
        "=f"(d[8]), "=f"(d[9]), "=f"(d[10]), "=f"(d[11]), "=f"(d[12]), "=f"(d[13]), "=f"(d[14]), "=f"(d[15]),
        "=f"(d[16]), "=f"(d[17]), "=f"(d[18]), "=f"(d[19]), "=f"(d[20]), "=f"(d[21]), "=f"(d[22]), "=f"(d[23]),
        "=f"(d[24]), "=f"(d[25]), "=f"(d[26]), "=f"(d[27]), "=f"(d[28]), "=f"(d[29]), "=f"(d[30]), "=f"(d[31])
        : "r"(a[0]), "r"(a[1]), "r"(a[2]), "r"(a[3]), "l"(db));
}
__device__ __forceinline__ void wgmma_pv(float* d, const uint32_t* a, uint64_t db) {
    asm volatile("wgmma.mma_async.sync.aligned.m64n24k16.f32.bf16.bf16 {"
        "%0, %1, %2, %3, %4, %5, %6, %7, %8, %9, %10, %11}, {%12, %13, %14, %15}, %16, 1, 1, 1, 1;\n"
        :
        "+f"(d[0]), "+f"(d[1]), "+f"(d[2]), "+f"(d[3]), "+f"(d[4]), "+f"(d[5]), "+f"(d[6]), "+f"(d[7]),
        "+f"(d[8]), "+f"(d[9]), "+f"(d[10]), "+f"(d[11])
        : "r"(a[0]), "r"(a[1]), "r"(a[2]), "r"(a[3]), "l"(db));
}

template <int N> __device__ __forceinline__ void wgmma_ss(float* d, uint64_t a, uint64_t b) {
    if (N == 128) wgmma_ss_n128(d, a, b);
    if (N == 96) wgmma_ss_n96(d, a, b);
    if (N == 64) wgmma_ss_n64(d, a, b);
}

#define OFF_R 131072
#define OFF_ONE 229376
#define OFF_BAR 229888
#define OFF_BIAS (OFF_BAR + 736)
#define OFF_G (OFF_BIAS + 1152)
#define SMEM_BYTES (OFF_G + 272)
#define SBD 1024u
#define B_X 0
#define B_F1 416
#define B_E1 64
#define B_XD 672
#define B_KV 160
#define B_F2 224
#define B_E2 256
#define B_T 288
#define B_G 360
#define B_G2 368
#define B_G3 376
#define B_SF 384
#define B_BI 400
#define B_DONE 112
#define B_DONE2 120

#define B_SF2 408
#define NR 6

#define PF 1
#define PFX 0
#define PACE 1
#define FSER 1
#define MERGE 1
#define EB 2
#define ANDM 0x4440
#define HOLD 8
#define TRIG 16
#define XPF 4
#define GDEL 7
#define WPF 0
#define EXP_FKK 4
#define QSCALE 0.36067376022224085f
#define MAGIC 445.41763f
#define FORCE_IMAD
#define NMUFU 5
#define VSTEP ((uint64_t)((long long)32 - ((long long)32 << 16)))

#define XMASK 0x0D55u
#define KVMASK 0x1D55u
__host__ __device__ constexpr int strm_pos(int pass, int i) {
    if (pass == 1 || pass == 2) return 8 + 8 * pass + i;
    int n = 0;
    for (int p = 0; p < 16; p++)
        if ((int)((KVMASK >> p) & 1) == (pass == 3)) { if (n == i) return p; n++; }
    return 0;
}
__host__ __device__ constexpr uint32_t strm_code(int pass) {
    uint32_t c = 0;
    for (int i = 0; i < 7; i++) c |= (uint32_t)(strm_pos(pass, i + 1) - strm_pos(pass, i)) << (4 * i);
    return c;
}

template <int N, int SUB, int KST, int LBO, int SBO, int SWZ>
__device__ __forceinline__ void gemm_pass(float* acc, uint32_t bar, uint64_t dA, int lane, uint32_t pos, uint32_t code, int barNext, bool waitx, bool last) {
    uint32_t prev = 0, slot = pos % NR;
#pragma unroll 1
    for (int i = 0; i < 8; i++) {
        if (waitx) {
            mbar_wait(bar + B_X + 8 * i, 0);
            if (N == 96 && i == HOLD) bar_sync(4, 512);
        }
        mbar_wait(bar + B_F1 + 8 * pos, 0);
        const uint64_t dB = mkdesc(SBD + OFF_R, LBO, SBO, SWZ) + slot * 1024;
        wg_fence();
        wgmma_ss<N>(acc, dA, dB);
        wgmma_ss<N>(acc, dA + 2, dB + KST / 16);
        wg_commit();
        wg_wait<1>();
        if (i > 0 && lane < 2) mbar_arrive_cluster(prev, lane);
        wgmma_ss<N>(acc, dA + 4, dB + SUB / 16);
        wgmma_ss<N>(acc, dA + 6, dB + (SUB + KST) / 16);
        wg_commit();
        prev = last ? bar + B_XD + 8 * i : bar + B_E1 + 8 * slot;
        pos += code & 15;
        slot += code & 15;
        if (slot >= NR) slot -= NR;
        code >>= 4;
        dA += 1024;
    }
    if (barNext) bar_arrive(barNext, 512);
    wg_wait<0>();
    if (lane < 2) mbar_arrive_cluster(prev, lane);
    pin<N / 2>(acc);
}

__device__ __forceinline__ uint32_t lds32(uint32_t a) { uint32_t v; asm volatile("ld.shared.u32 %0, [%1];" : "=r"(v) : "r"(a)); return v; }
__device__ __forceinline__ bool elect() {
    uint32_t p;
    asm volatile("{\n.reg .pred p;\nelect.sync _|p, 0xffffffff;\nselp.u32 %0, 1, 0, p;\n}" : "=r"(p));
    return p;
}

template <int G0, int G1> __device__ __forceinline__ void gelu_pack(const float* acc, uint32_t bias, uint32_t* out) {
#pragma unroll
    for (int G = G0; G < G1; G++) {
        uint32_t* o = out + 8 * G;
#pragma unroll
        for (int j = 0; j < 4; j++) {
            float bv[2];
            asm volatile("ld.shared.v2.f32 {%0, %1}, [%2];" : "=f"(bv[0]), "=f"(bv[1]) : "r"(bias + G * 128 + j * 32));
            float y[4];
#pragma unroll
            for (int i = 0; i < 4; i++) {
                const float h = acc[16 * G + 4 * j + i] + bv[i & 1];
                const float z = h * fmaf(h * h, 0.035677408136300125f, 0.7978845608028654f);
                y[i] = fmaf(h, tanhf_(z), h);
            }
            o[j] = pk_bf16(y[0], y[1]);
            o[4 + j] = pk_bf16(y[2], y[3]);
        }
    }
}

__device__ __forceinline__ uint32_t badd2(uint32_t a, uint32_t b) { uint32_t r; asm("add.rn.bf16x2 %0, %1, %2;" : "=r"(r) : "r"(a), "r"(b)); return r; }
__device__ __forceinline__ void norm_part(const float* v, uint32_t* n) {
#pragma unroll
    for (int h = 0; h < 4; h++) {
        const float* u = v + 8 * h;
        n[h] = pk_bf16(fmaf(u[0], u[0], fmaf(u[1], u[1], fmaf(u[4], u[4], u[5] * u[5]))), fmaf(u[2], u[2], fmaf(u[3], u[3], fmaf(u[6], u[6], u[7] * u[7]))));
    }
#pragma unroll
    for (int h = 0; h < 4; h++) n[h] = badd2(n[h], __shfl_xor_sync(0xffffffffu, n[h], 1));
}
__device__ __forceinline__ float norm_finish(uint32_t* n, float sc) {
#pragma unroll
    for (int h = 0; h < 4; h++) n[h] = badd2(n[h], __shfl_xor_sync(0xffffffffu, n[h], 2));
    const uint32_t m = __vimax3_u16x2(__vmaxu2(n[0], n[1]), n[2], n[3]);
    return __uint_as_float(__reduce_max_sync(0xffffffffu, max(m << 16, m & 0xffff0000u))) * (1.03f * sc);
}

__device__ __forceinline__ uint32_t exp2_pair(float a, float b, uint32_t m1) {
    const uint32_t w = __byte_perm(__float_as_uint(a), __float_as_uint(b), 0x6521);
    uint32_t m, r;
    asm("lop3.b32 %0, %1, 0x007f007f, 0x9f809f80, 0xEA;" : "=r"(m) : "r"(w));
    const uint32_t e = m * m1 + w;
    asm("fma.rn.bf16x2 %0, %1, %2, %3;" : "=r"(r) : "r"(w), "r"(m), "r"(e));
    return r;
}

__device__ __forceinline__ uint32_t exp2_pair_b(float a, float b) {
    const uint32_t w = __byte_perm(__float_as_uint(a), __float_as_uint(b), 0x6521);
    uint32_t m, r;
    asm("lop3.b32 %0, %1, 0x007f007f, 0xbf00bf00, 0xEA;" : "=r"(m) : "r"(w));
    asm("fma.rn.bf16x2 %0, %1, %2, %3;" : "=r"(r) : "r"(w), "r"(m), "r"(w & 0x7f807f80u));
    return r;
}
__device__ __forceinline__ void store_o(const float* o, uint4* dst, uint32_t par) {
    const float s0 = __fdividef(1.f, o[8]), s1 = __fdividef(1.f, o[10]);
    const uint32_t d0 = (pk_bf16(o[0] * s0, o[1] * s0) & ~1u) | par;
    asm volatile("{\n.reg .b128 t;\nmov.b128 t, {%0, %1, %2, %3};\nst.relaxed.gpu.global.b128 [%4], t;\n}" ::"r"(d0),
                 "r"(pk_bf16(o[2] * s1, o[3] * s1)), "r"(pk_bf16(o[4] * s0, o[5] * s0)), "r"(pk_bf16(o[6] * s1, o[7] * s1)), "l"(dst) : "memory");
}
__device__ __forceinline__ uint4 load_o(const uint4* src) {
    uint4 v;
    asm volatile("{\n.reg .b128 t;\nld.relaxed.gpu.global.b128 t, [%4];\nmov.b128 {%0, %1, %2, %3}, t;\n}"
                 : "=r"(v.x), "=r"(v.y), "=r"(v.z), "=r"(v.w) : "l"(src) : "memory");
    return v;
}
template <int N> __device__ __forceinline__ void fetch_o(uint4* v, const uint4* src, uint32_t ep) {
    int spins = 0;
    while (true) {
        uint32_t bad = 0;
#pragma unroll
        for (int k = 0; k < N; k++) bad |= v[k].x ^ ep;
        if (!__any_sync(0xffffffffu, (bad & 1) != 0)) break;
        if (++spins > (1 << 22)) __trap();
#pragma unroll
        for (int k = 0; k < N; k++)
            if (((v[k].x ^ ep) & 1) != 0) v[k] = load_o(src + k * 128);
    }
}
__device__ __forceinline__ uint32_t bmul2(uint32_t a, uint32_t b) { uint32_t r; asm("mul.rn.bf16x2 %0, %1, %2;" : "=r"(r) : "r"(a), "r"(b)); return r; }
__device__ __forceinline__ void sts32(uint32_t a, uint32_t v) { asm volatile("st.shared.u32 [%0], %1;" ::"r"(a), "r"(v) : "memory"); }
__device__ __forceinline__ void stage_o(const uint4* v, uint32_t a0, uint32_t g0, uint32_t g1, int lane) {
#pragma unroll
    for (int i = 0; i < 4; i++)
        asm volatile("stmatrix.sync.aligned.m8n8.x4.shared.b16 [%0], {%1, %2, %3, %4};" ::"r"(a0 + (((i * 2 + (lane >> 4)) ^ (lane & 7)) << 4)),
                     "r"(bmul2(v[i].x, g0)), "r"(bmul2(v[i].y, g1)), "r"(bmul2(v[i].z, g0)), "r"(bmul2(v[i].w, g1)) : "memory");
    asm volatile("fence.proxy.async.shared::cta;" ::: "memory");
}
__device__ __forceinline__ void load_q(uint32_t* q, int h, int row, int t) {
    const uint8_t* p = gQ + (size_t)h * (SEQ * 32) + (size_t)row * 32 + t * 4;
    q[0] = __ldcg((const uint32_t*)p); q[1] = __ldcg((const uint32_t*)(p + 256));
    q[2] = __ldcg((const uint32_t*)(p + 16)); q[3] = __ldcg((const uint32_t*)(p + 272));
}

template <int NT>
__device__ __forceinline__ void proj16(float (*c)[8], const __nv_bfloat16* x, const __nv_bfloat16* w, int row0, int rstep, int col, int g, int t) {
#pragma unroll
    for (int i = 0; i < NT; i++)
#pragma unroll
        for (int j = 0; j < 8; j++) c[i][j] = 0.f;
    const unsigned short* wu = (const unsigned short*)w;
#pragma unroll 1
    for (int k = 0; k < DM; k += 16) {
        uint32_t b[4];
#pragma unroll
        for (int j = 0; j < 4; j++) {
            const int kr = k + 2 * t + (j & 1) * 8, cc = col + g + (j >> 1) * 8;
            b[j] = (uint32_t)wu[(size_t)kr * (3 * DM) + cc] | ((uint32_t)wu[(size_t)(kr + 1) * (3 * DM) + cc] << 16);
        }
#pragma unroll
        for (int i = 0; i < NT; i++) {
            const __nv_bfloat16* xp = x + (size_t)(row0 + i * rstep + g) * DM + k + 2 * t;
            const uint32_t a0 = *(const uint32_t*)xp, a1 = *(const uint32_t*)(xp + 8 * DM);
            const uint32_t a2 = *(const uint32_t*)(xp + 8), a3 = *(const uint32_t*)(xp + 8 * DM + 8);
#pragma unroll
            for (int j = 0; j < 2; j++)
                asm volatile("mma.sync.aligned.m16n8k16.row.col.f32.bf16.bf16.f32 {%0,%1,%2,%3}, {%4,%5,%6,%7}, {%8,%9}, {%0,%1,%2,%3};"
                             : "+f"(c[i][4 * j]), "+f"(c[i][4 * j + 1]), "+f"(c[i][4 * j + 2]), "+f"(c[i][4 * j + 3])
                             : "r"(a0), "r"(a1), "r"(a2), "r"(a3), "r"(b[2 * j]), "r"(b[2 * j + 1]));
        }
    }
}

struct Maps { CUtensorMap x, kv, q, f1, f3, h, w2, wo, hs, kvs; };

template <int I0, int I1>
__device__ __forceinline__ void issue_stream(const Maps& tm, uint32_t sb, uint32_t rank, int nb, int mb) {
    const uint32_t bar = sb + OFF_BAR;
    const uint32_t dst = sb + OFF_R;
    const int kr = rank * 32;
#pragma unroll
    for (int it = I0; it < I1; it++) {
        const int s = it % NR;
        const uint32_t fb = bar + B_F1 + 8 * it;
        if (it >= 24 + NR) mbar_wait(bar + B_XD + 8 * (it - 24 - NR), 0);
        else if (it >= NR) mbar_wait(bar + B_E1 + 8 * s, ((it / NR) - 1) & 1);
        const int nkv = __builtin_popcount(KVMASK & ((1u << it) - 1));
        if (it < 16 && ((KVMASK >> it) & 1)) {
            tma3d_mc(dst + s * 16384 + rank * 8192, &tm.kv, nb * 64, nkv * 64 + kr, 1, fb);
        } else if (it < 16) {
            tma3d_mc(dst + s * 16384 + rank * 6144, &tm.q, 0, (it - nkv) * 64 + kr, nb * 2, fb);
            tma3d_mc(dst + s * 16384 + rank * 6144 + 4096, &tm.f1, 0, (it - nkv) * 64 + kr, nb * 7, fb);
        } else {
            tma3d_mc(dst + s * 16384 + rank * 6144, &tm.f3, 0, (it & 7) * 64 + kr, nb * 7 + (it < 24 ? 1 : 4), fb);
        }
        if ((XMASK >> it) & 1) {
            const int xc = 1 + __builtin_popcount(XMASK & ((1u << it) - 1));
            tma3d_m(sb + xc * 16384, &tm.x, xc * 64, mb * 128, 0, bar + B_X + 8 * xc, 1 << rank);
        }
    }
}

__global__ void __cluster_dims__(2, 1, 1) __launch_bounds__(640, 1)
fused_kernel(const __grid_constant__ Maps tm, const __nv_bfloat16* __restrict__ x, const __nv_bfloat16* __restrict__ wqkv,
             const __nv_bfloat16* __restrict__ wo, const __nv_bfloat16* __restrict__ w1, const __nv_bfloat16* __restrict__ b1,
             const __nv_bfloat16* __restrict__ w2, const __nv_bfloat16* __restrict__ b2, const __nv_bfloat16* __restrict__ gate,
             __nv_bfloat16* __restrict__ out, const uint32_t m1) {
    const uint32_t sb = smem_u32(smem_raw);
    const uint32_t bar = sb + OFF_BAR;
    const int tid = threadIdx.x, lane = tid & 31;
    const int warp = __shfl_sync(0xffffffffu, tid >> 5, 0);
    const uint32_t rank = cluster_rank();
    const int cl = blockIdx.x >> 1;
    const int nb = cl & 7, mb = (cl >> 3) * 2 + rank;
    const int g = lane >> 2, t = lane & 3;

    const int cb = nb & 3, rb = mb * 2 + (nb >> 2);
    const int rn = (mb >> 1) & 1;
    if (tid == 0) TLM(0, 0);
    TL_INIT();
    if (tid == 512) {
        for (int i = 0; i < 8; i++) { mbar_init(bar + B_X + 8 * i, 1); mbar_init(bar + B_KV + 8 * i, 1); mbar_init(bar + B_T + 8 * i, i < 4 ? 1 : 5); mbar_init(bar + B_XD + 8 * i, 16); }
        for (int i = 0; i < NR; i++) mbar_init(bar + B_E1 + 8 * i, 16);
        for (int i = 0; i < 4; i++) { mbar_init(bar + B_F2 + 8 * i, 1); mbar_init(bar + B_E2 + 8 * i, 8); }
        asm volatile("fence.mbarrier_init.release.cluster;" ::: "memory");
    } else if (tid == 608) {
        for (int i = 0; i < 32; i++) mbar_init(bar + B_F1 + 8 * i, 1);
        mbar_init(bar + B_G, 1);
        mbar_init(bar + B_DONE, 16);
        mbar_init(bar + B_DONE2, TRIG);
        for (int i = 0; i < 3; i++) mbar_init(bar + B_SF + 8 * i, i == 1 ? 2 : 1);
        mbar_init(bar + B_SF2, 2);
        mbar_init(bar + B_G3, 1);
        mbar_init(bar + B_G2, 4);
        asm volatile("fence.mbarrier_init.release.cluster;" ::: "memory");
    }
    __syncwarp();
    asm volatile("barrier.cluster.arrive.relaxed.aligned;" ::: "memory");
    if (warp == 19) mbar_expect(bar + B_F1 + 8 * lane, ((KVMASK >> lane) & 1) ? 16384 : 12288);
    if (warp == 16 && lane < 24) mbar_expect(bar + (lane < 8 ? B_X : lane < 16 ? B_KV - 64 : B_T - 128) + 8 * lane, 16384);
    if (tid == 512) {
        tma3d_m(sb, &tm.x, 0, mb * 128, 0, bar + B_X, 1 << rank);
    } else if (tid == 544) {
        map_prefetch(&tm.kv);
        l2_prefetch((const uint8_t*)wqkv + (size_t)blockIdx.x * 3072, 3072);
        l2_prefetch((const uint8_t*)w1 + (size_t)blockIdx.x * 1792, 1792);
        map_prefetch(&tm.q); map_prefetch(&tm.f1); map_prefetch(&tm.f3);
    }
    if (warp == 18) {
#pragma unroll
        for (int i = 0; i < XPF / 2; i++)
            asm volatile("prefetch.global.L2 [%0];" ::"l"(x + (size_t)(mb * 128 + nb * 16 + (lane & 15)) * DM + ((lane >> 4) + 2 * i) * 64));
    }
    if ((sb & 0xFFFFFF) != SBD) __trap();
    __syncwarp();
    asm volatile("barrier.cluster.wait.aligned;" ::: "memory");
    if (tid == 512) issue_stream<0, NR>(tm, sb, rank, nb, mb);
    if (tid == 0) { TLM(0, 1); TLC(0, 30); }

    if (warp < 16) {
        const int wg = warp >> 2;
        const int h = cl >> 1, qd = (cl & 1) * 2 + rank;
        const int flip = (h >> 2) & 1;
        uint32_t q[4];
        {
            const int w8 = warp & 7;
            const int T = mb * 8 + w8, row0 = T * 16 + g;
            const uint64_t dA0 = mkdesc(SBD + (wg & 1) * 8192, 16, 1024, 1);
            if (wg < 2) {
                float acc[64];
#pragma unroll
                for (int i = 0; i < 64; i++) acc[i] = 0.f;
                gemm_pass<128, 8192, 2048, 4096, 1024, 1>(acc, bar, dA0, lane, strm_pos(3, 0), strm_code(3), HOLD < 8 ? 4 : 0, true, false);
                if (tid == 0) TLM(0, 2);
                {
                    float pr[16];
#pragma unroll
                    for (int i = 0; i < 16; i++) pr[i] = __shfl_up_sync(0xffffffffu, acc[(i >> 1) * 4 + 2 + (i & 1)], 4);
                    uint32_t nn[4], pv[16];
                    norm_part(acc, nn);
#pragma unroll
                    for (int i = 0; i < 16; i++) pv[i] = pk_bf16(acc[32 + 2 * i], acc[33 + 2 * i]);
                    const uint32_t kp = sb + OFF_R + 12288 + (w8 >> 2) * 1024 + g * 128 + ((((w8 & 3) * 2 + ((t >> 1) ^ (w8 >> 2))) ^ g) << 4) + (t & 1) * 8;
                    bar_sync(9, 256);
#pragma unroll
                    for (int hh = 0; hh < 2; hh++) {
                        sts64(kp + (4 + hh) * 16384, pv[4 * hh], pv[4 * hh + 2]);
                        sts64(kp + (4 + hh) * 16384 + 2048, pv[4 * hh + 1], pv[4 * hh + 3]);
                    }
                    const float gm = g == 0 ? 0.f : -1.f;
#pragma unroll
                    for (int hh = 0; hh < 4; hh++) {
                        const float* v = acc + 8 * hh;
                        const float* p = pr + 4 * hh;
                        sts64(kp + hh * 16384 + 2048, pk_f16(v[2] - v[0], v[3] - v[1]), pk_f16(v[6] - v[4], v[7] - v[5]));
                        sts64(kp + hh * 16384, pk_f16(fmaf(p[0], gm, v[0]), fmaf(p[1], gm, v[1])), pk_f16(fmaf(p[2], gm, v[4]), fmaf(p[3], gm, v[5])));
                    }
                    uint32_t big = 0;
#pragma unroll
                    for (int i = 0; i < 16; i++) big |= pv[i] & (pv[i] << 1);
                    if (big & 0x40004000u) nn[0] = 0x7f007f00u;
                    const float km = norm_finish(nn, 1.f);
                    asm volatile("fence.proxy.async.shared::cta;" ::: "memory");
                    bar_arrive(10, 288);
                    uint8_t* vp = gKV + (size_t)(nb * 4) * (SEQ * 64) + 65536 + (((T >> 6) * 16 + 2 * g) * 64 + (T & 63)) * 32 + ((t * 8) ^ ((w8 >> 2) << 4));
#pragma unroll
                    for (int hh = 2; hh < 4; hh++) {
                        *(uint2*)(vp + (size_t)hh * (SEQ * 64)) = make_uint2(pv[4 * hh], pv[4 * hh + 2]);
                        *(uint2*)(vp + (size_t)hh * (SEQ * 64) + 2048) = make_uint2(pv[4 * hh + 1], pv[4 * hh + 3]);
                    }
                    if (lane == 0) gN[1024 + nb * 128 + T] = km;
                }
                bar_arrive(12, 544);
                if (tid == 0) TLM(0, 3);
            }
#pragma unroll 1
            for (int p = wg < 2 ? 1 : 0; p < 3; p += 2) {
                float acc[48];
#pragma unroll
                for (int i = 0; i < 48; i++) acc[i] = 0.f;
                pin<48>(acc);
                if (p) bar_sync(5 + p, 512);
                gemm_pass<96, 6144, 1024, 2048, 512, 2>(acc, bar, dA0, lane, p == 0 ? strm_pos(0, 0) : 8 + 8 * p, p == 0 ? strm_code(0) : strm_code(1), p < 2 ? 6 + p : 0, p == 0, p == 2);
                if ((tid & 255) == 0) TLM(0, 4 + 2 * p);
                const uint32_t hp = sb + OFF_R + (p == 2 ? 0 : 12288) + (wg & 1) * 16384 + ((warp & 3) * 16 + g) * 64 + t * 16;
                const uint32_t bp = sb + OFF_BIAS + p * 384 - 256 + t * 8;
                uint32_t ho[24];
                mbar_wait(bar + B_BI, 0);
                if (p == 0) {
                    uint32_t nn[4];
                    norm_part(acc, nn);
                    const float qm = norm_finish(nn, QSCALE * QSCALE);
                    if (lane == 0) gN[nb * 128 + T] = qm;
                    uint8_t* qp = gQ + (size_t)(nb * 4) * (SEQ * 32) + (size_t)row0 * 32 + t * 8;
#pragma unroll
                    for (int hh = 0; hh < 4; hh++) {
                        const float* v = acc + 8 * hh;
                        *(uint2*)(qp + hh * (SEQ * 32)) = make_uint2(pk_f16(v[0] * QSCALE, v[1] * QSCALE), pk_f16(v[4] * QSCALE, v[5] * QSCALE));
                        *(uint2*)(qp + hh * (SEQ * 32) + 256) = make_uint2(pk_f16(v[2] * QSCALE, v[3] * QSCALE), pk_f16(v[6] * QSCALE, v[7] * QSCALE));
                    }
                    bar_arrive(12, 544);
                } else {
                    gelu_pack<0, 2>(acc, bp, ho);
                    pin<16>(ho);
                    mbar_wait(bar + B_G, 0);
                    load_q(q, h, qd * 512 + flip * 256 + warp * 16 + g, t);
                }
                gelu_pack<2, 3>(acc, bp, ho);
                pin<8>(ho + 16);
                if (p == 2) bar_sync(9, 256);
                else mbar_wait(bar + B_SF + 8 * p, 0);
                if (p) {
#pragma unroll
                    for (int i = 0; i < 4; i++) sts128(hp + (i >> 1) * 32768 + (i & 1) * 512, ho + 4 * i);
                }
                sts128(hp + 65536, ho + 16);
                sts128(hp + 65536 + 512, ho + 20);
                asm volatile("fence.proxy.async.shared::cta;" ::: "memory");
                bar_arrive(p == 1 ? 14 : 11, 288);
                if ((tid & 255) == 0) TLM(0, 5 + 2 * p);
            }
        }
        uint32_t ep = 2;
        uint4* const op = gO + ((qd * 8 + wg) * NH + h) * 128 + (tid & 127);
        const uint64_t kd0 = mkdesc(SBD, 16, 256, 3);
        const uint64_t vd0 = mkdesc(SBD + 8192, OFF_ONE - 8192, 256, 3);
        {
            float o[12];
            uint32_t qn[4];
#pragma unroll 1
            for (int rh = 0; rh < 4; rh++) {
                if (rh == 1) {
                    mbar_wait(bar + B_G3, 0);
                    ep = lds32(sb + OFF_G + 256);
                    if (!(ep & 2)) break;
                    load_q(qn, h, qd * 512 + (flip ^ 1) * 256 + warp * 16 + g, t);
                }
                if (rh == 3 && lane == 0) mbar_arrive(bar + B_DONE);
                if (!(rh & 1)) {
#pragma unroll
                    for (int i = 0; i < 12; i++) o[i] = 0.f;
                }
                uint64_t kd = kd0 + (rh & 1) * 4096, vd = vd0 + (rh & 1) * (128 * VSTEP);
                uint32_t kvb = bar + B_KV + (rh & 1) * 32;
                float s[32];
#pragma unroll
                for (int i = 0; i < 32; i++) s[i] = i < 2 * NMUFU ? 0.f : ((ANDM >> (i >> 1)) & 1) ? MAGIC - 63.f : MAGIC;
                if ((tid & 255) == 0) TLM(1, (tid >> 8) * 4 + rh);
#pragma unroll 1
                for (int c = 0; c < 4; c++) {
                    mbar_wait(kvb, 0);
                    kvb += 8;
#pragma unroll
                    for (int j = 0; j < 4; j++) {
                        uint32_t p[16];
                        if (!MERGE || j == 0) {
                            wg_fence();
                            wgmma_qk_f16_acc(s, q, kd + j * 128);
                            wg_commit();
                        }
                        wg_wait<0>();
                        pin<32>(s);
#pragma unroll
                        for (int i = 0; i < 16; i++)
                            p[i] = i < NMUFU ? pk_bf16(ex2f(s[2 * i]), ex2f(s[2 * i + 1])) : ((ANDM >> i) & 1) ? exp2_pair_b(s[2 * i], s[2 * i + 1]) : exp2_pair(s[2 * i], s[2 * i + 1], m1);
                        pin<16>(p);
                        wg_fence();
#pragma unroll
                        for (int u = 0; u < 4; u++) {
                            if (MERGE && j < 3 && u == 5 - MERGE) wgmma_qk_f16_acc(s, q, kd + (j + 1) * 128);
                            wgmma_pv(o, p + 4 * u, vd + (j * 4 + u) * VSTEP);
                        }
                        if (MERGE == 1 && j < 3) wgmma_qk_f16_acc(s, q, kd + (j + 1) * 128);
                        wg_commit();
                    }
                    kd += 1024;
                    vd += 32 * VSTEP;
                }
                wg_wait<0>();
                pin<12>(o);
                if (rh & 1) {
                    if ((tid & 127) == 0 && rh == 3) TLM(1, 8 + wg);
                    store_o(o, op + ((rh >> 1) ^ flip) * (4 * NH * 128), ep & 1);
#pragma unroll
                    for (int i = 0; i < 4; i++) q[i] = qn[i];
                }
            }
            if (tid == 0) { TLM(1, 12); TLC(0, 31); }
        }
        if (!(ep & 2)) {
            bar_sync(8, 512);
            for (int c = 0; c < 8; c++) mbar_wait(bar + B_KV + 8 * c, 0);
            {
                float kc[8][8];
                proj16<8>(kc, x, wqkv, warp * 16, 256, DM + h * 16, g, t);
#pragma unroll
                for (int i = 0; i < 8; i++) {
                    const int T = warp + i * 16;
                    const int pos = ((T >> 6) * 16 + 2 * g) * 64 + (T & 63);
                    const uint32_t a = sb + (pos >> 8) * 16384 + (pos & 255) * 32 + t * 4, sw = ((T >> 2) & 1) << 4;
                    asm volatile("st.shared.u32 [%0], %1;" ::"r"(a + sw), "r"(pk_bf16(kc[i][0], kc[i][1])) : "memory");
                    asm volatile("st.shared.u32 [%0], %1;" ::"r"(a + (sw ^ 16)), "r"(pk_bf16(kc[i][4], kc[i][5])) : "memory");
                    asm volatile("st.shared.u32 [%0], %1;" ::"r"(a + 2048 + sw), "r"(pk_bf16(kc[i][2], kc[i][3])) : "memory");
                    asm volatile("st.shared.u32 [%0], %1;" ::"r"(a + 2048 + (sw ^ 16)), "r"(pk_bf16(kc[i][6], kc[i][7])) : "memory");
                }
                asm volatile("fence.proxy.async.shared::cta;" ::: "memory");
                bar_sync(8, 512);
            }
#pragma unroll 1
            for (int r = 0; r < 2; r++) {
                const int row = qd * 512 + (r ^ flip) * 256 + warp * 16 + g;
                {
                    float qc[1][8];
                    proj16<1>(qc, x, wqkv, row - g, 0, h * 16, g, t);
#pragma unroll
                    for (int i = 0; i < 4; i++) q[i] = pk_bf16(qc[0][2 * i] * QSCALE, qc[0][2 * i + 1] * QSCALE);
                }
                float o[12];
#pragma unroll
                for (int i = 0; i < 12; i++) o[i] = 0.f;
                float m0 = -INFINITY, m1 = -INFINITY;
#pragma unroll 1
                for (int j = 0; j < 32; j++) {
                    const uint64_t kd = kd0 + (j >> 2) * 1024 + (j & 3) * 128, vd = vd0 + ((j >> 2) * 32 + (j & 3) * 4) * VSTEP;
                    float s[32];
                    uint32_t p[16];
                    wg_fence();
                    wgmma_qk_bf16_zero(s, q, kd);
                    wg_commit();
                    wg_wait<0>();
                    pin<32>(s);
                    pin<12>(o);
                    float n0 = m0, n1 = m1;
#pragma unroll
                    for (int i = 0; i < 8; i++) {
                        n0 = fmaxf(n0, fmaxf(s[4 * i], s[4 * i + 1]));
                        n1 = fmaxf(n1, fmaxf(s[4 * i + 2], s[4 * i + 3]));
                    }
                    n0 = fmaxf(n0, __shfl_xor_sync(0xffffffffu, n0, 1));
                    n1 = fmaxf(n1, __shfl_xor_sync(0xffffffffu, n1, 1));
                    n0 = fmaxf(n0, __shfl_xor_sync(0xffffffffu, n0, 2));
                    n1 = fmaxf(n1, __shfl_xor_sync(0xffffffffu, n1, 2));
                    const float c0 = ex2f(m0 - n0), c1 = ex2f(m1 - n1);
                    m0 = n0;
                    m1 = n1;
#pragma unroll
                    for (int i = 0; i < 3; i++) { o[4 * i] *= c0; o[4 * i + 1] *= c0; o[4 * i + 2] *= c1; o[4 * i + 3] *= c1; }
#pragma unroll
                    for (int i = 0; i < 8; i++) {
                        p[2 * i] = pk_bf16(ex2f(s[4 * i] - m0), ex2f(s[4 * i + 1] - m0));
                        p[2 * i + 1] = pk_bf16(ex2f(s[4 * i + 2] - m1), ex2f(s[4 * i + 3] - m1));
                    }
                    pin<16>(p);
                    pin<12>(o);
                    wg_fence();
#pragma unroll
                    for (int u = 0; u < 4; u++) wgmma_pv(o, p + 4 * u, vd + u * VSTEP);
                    wg_commit();
                }
                wg_wait<0>();
                pin<12>(o);
                store_o(o, op + (r ^ flip) * (4 * NH * 128), ep & 1);
                if (r == 1 && lane == 0) mbar_arrive(bar + B_DONE);
            }
        }
        if (lane == 0 && warp >= 16 - TRIG) mbar_arrive(bar + B_DONE2);
        {
            const uint4* src = gO + (rb * NH + (wg * 2 + (rn ^ 1)) * 4) * 128 + (tid & 127);
            uint4 v[4];
#pragma unroll
            for (int i = 0; i < 4; i++) v[i] = load_o(src + i * 128);
            mbar_wait(bar + B_G2, 0);
            const int lr = (warp & 3) * 16;
            const uint32_t g0 = lds32(sb + OFF_G + (lr + g) * 4), g1 = lds32(sb + OFF_G + (lr + g) * 4 + 32);
            fetch_o<4>(v, src, ep);
            stage_o(v, sb + OFF_R + 65536 + wg * 8192 + (lr + (lane & 15)) * 128, g0, g1, lane);
            __syncwarp();
            if (lane == 0) mbar_arrive(bar + B_T + 32 + 8 * wg);
            if ((tid & 127) == 0) TLM(1, 20 + wg);
        }
    } else {
        if (warp == 16) {
            {
                const int it = lane, s = it % NR;
                const uint32_t below = (1u << it) - 1;
                const bool kv = (KVMASK >> it) & 1, qf = it < 16 && !kv;
                const int nkv = __popc(KVMASK & below), xc = 1 + __popc(XMASK & below);
                const uint32_t wb = it >= 24 + NR ? bar + B_XD + 8 * (it - 24 - NR) : bar + B_E1 + 8 * s;
                const uint32_t wp = it >= 24 + NR ? 0 : ((it / NR) - 1) & 1;
                const uint32_t fb = bar + B_F1 + 8 * it;
                const uint32_t d1 = sb + OFF_R + s * 16384 + rank * (kv ? 8192 : 6144);
                const CUtensorMap* m1p = kv ? &tm.kv : qf ? &tm.q : &tm.f3;
                const int a0 = kv ? nb * 64 : 0, a1 = (kv ? nkv : (it - nkv) & 7) * 64 + rank * 32;
                const int a2 = kv ? 1 : qf ? nb * 2 : nb * 7 + (it < 24 ? 1 : 4);
                const bool two = qf || ((XMASK >> it) & 1);
                const uint32_t d2 = qf ? d1 + 4096 : sb + xc * 16384, fb2 = qf ? fb : bar + B_X + 8 * xc;
                const CUtensorMap* m2p = qf ? &tm.f1 : &tm.x;
                const int b0 = qf ? 0 : xc * 64, b1_ = qf ? a1 : mb * 128, b2_ = qf ? nb * 7 : 0;
                const uint16_t k2 = qf ? 3 : 1 << rank;
#pragma unroll 1
                for (int n = NR; n < 32; n++) {
                    if (lane == n) {
                        mbar_wait(wb, wp);
                        tma3d_m(d1, m1p, a0, a1, a2, fb, 3);
                        if (two) tma3d_m(d2, m2p, b0, b1_, b2_, fb2, k2);
                    }
                    __syncwarp();
                }
            }
            if (lane == 0) {
                mbar_wait(bar + B_SF2, 0);
#pragma unroll
                for (int s = 0; s < 4; s++) {
                    mbar_expect(bar + B_F2 + 8 * s, 24576);
                    tma5d_mc(sb + OFF_R + s * 24576 + 8192 + rank * 8192, &tm.w2, cb * 128 + rank * 64, s * 2, bar + B_F2 + 8 * s);
                }
                cnt_wait(gCntH + mb * 32, epoch() * 8);
                asm volatile("fence.proxy.async.global;" ::: "memory");
                TLM(1, 13);
#pragma unroll
                for (int s = 0; s < 4; s++) tma2d(sb + OFF_R + s * 24576, &tm.h, s * 64, rb * 64, bar + B_F2 + 8 * s);
            }
        } else if (warp == 17) {
            {
                uint32_t bv[4], b2v[2];
#pragma unroll
                for (int i = 0; i < 4; i++) bv[i] = lane + 32 * i < 112 ? *(const uint32_t*)(b1 + nb * 224 + (lane + 32 * i) * 2) : 0;
#pragma unroll
                for (int i = 0; i < 2; i++) b2v[i] = *(const uint32_t*)(b2 + cb * 128 + (lane + 32 * i) * 2);
#pragma unroll
                for (int i = 0; i < 4; i++) {
                    sts32(sb + OFF_ONE + (lane + 32 * i) * 4, 0x3f803f80u);
                    if (lane + 32 * i < 112) sts64(sb + OFF_BIAS + (lane + 32 * i) * 8, bv[i] << 16, bv[i] & 0xffff0000u);
                }
#pragma unroll
                for (int i = 0; i < 2; i++) sts32(sb + OFF_BIAS + 896 + (lane + 32 * i) * 4, b2v[i]);
                asm volatile("fence.proxy.async.shared::cta;" ::: "memory");
                __syncwarp();
                if (lane == 0) mbar_arrive(bar + B_BI);
            }
            mbar_wait(bar + B_X + 8 * PFX, 0);
            if (lane == 0) {
                l2_prefetch((const uint8_t*)wqkv + 128 * 3072 + (size_t)blockIdx.x * 9216, 9216);
                l2_prefetch((const uint8_t*)w1 + (size_t)blockIdx.x * 14336, 14336);
            }
            mbar_wait(bar + B_X + 8 * 7, 0);
            if (lane == 0) {
                l2_prefetch((const uint8_t*)w2 + (size_t)blockIdx.x * 14336, 14336);
                l2_prefetch((const uint8_t*)wo + (size_t)blockIdx.x * 4096, 4096);
                map_prefetch(&tm.h); map_prefetch(&tm.w2); map_prefetch(&tm.wo); map_prefetch(&tm.hs); map_prefetch(&tm.kvs);
                TLM(0, 11);
            }
            bar_sync(10, 288);
            if (lane == 0) {
#pragma unroll 1
                for (int b = 5; b >= 0; b--) {
                    tma5d_st(&tm.kvs, sb + OFF_R + 12288 + b * 16384, (mb >> 3) * 8, (mb & 7) * 2, nb * 8 + (b < 4 ? 2 * b : 2 * b - 7));
                    asm volatile("cp.async.bulk.commit_group;\ncp.async.bulk.wait_group.read %0;" ::"n"(PACE) : "memory");
                    if (b == 4 - PACE) mbar_arrive(bar + B_SF);
                }
                asm volatile("cp.async.bulk.wait_group.read 0;" ::: "memory");
                mbar_arrive(bar + B_SF + 8);
            }
            __syncwarp();
            bar_sync(12, 544);
            if (lane == 0) {
                asm volatile("cp.async.bulk.wait_group 0;\nfence.proxy.async.global;" ::: "memory");
                cnt_add(gCntQ + nb * 32);
                TLM(0, 13);
            }
        } else {
            {
                mbar_wait(bar + B_X + 8 * GDEL, 0);
                const int r0 = mb * 128 + nb * 16 + (warp - 18) * 8;
                uint4 xv[16];
#pragma unroll
                for (int i = 0; i < 16; i++) xv[i] = *(const uint4*)(x + (size_t)(r0 + (i >> 1)) * DM + (i & 1) * 256 + lane * 8);
                const uint4 ga = *(const uint4*)(gate + lane * 8), gb = *(const uint4*)(gate + 256 + lane * 8);
                float z[8];
#pragma unroll
                for (int r = 0; r < 8; r++) z[r] = dot8(xv[2 * r], ga) + dot8(xv[2 * r + 1], gb);
#pragma unroll
                for (int w = 4; w >= 1; w >>= 1)
#pragma unroll
                    for (int r = 0; r < w; r++) {
                        const bool up = lane & w;
                        z[r] = (up ? z[r + w] : z[r]) + __shfl_xor_sync(0xffffffffu, up ? z[r] : z[r + w], w);
                    }
                z[0] += __shfl_xor_sync(0xffffffffu, z[0], 8);
                z[0] += __shfl_xor_sync(0xffffffffu, z[0], 16);
                if (lane < 8) gG[r0 + lane] = 1.f / (1.f + __expf(-z[0]));
                if (tid == 576) TLM(0, 12);
            }
            if (warp == 19) {
#pragma unroll 1
                for (int e = 0; e < 3; e++) {
                    bar_sync(e == 1 ? 14 : 11, 288);
                    if (lane == 0) {
#pragma unroll 1
                        for (int b = e == 0 ? 4 : 0; b < 6; b++) {
                            tma3d_st(&tm.hs, sb + OFF_R + (e == 2 ? 0 : 12288) + b * 16384, 0, mb * 128 + (b & 1) * 64, nb * 7 + e * 3 - 2 + (b >> 1));
                            asm volatile("cp.async.bulk.commit_group;\ncp.async.bulk.wait_group.read %0;" ::"n"(PACE) : "memory");
                        }
                        asm volatile("cp.async.bulk.wait_group.read 0;" ::: "memory");
                        if (e == 0) mbar_arrive(bar + B_SF + 8);
                        if (e == 2) { mbar_arrive_cluster(bar + B_SF2, 0); mbar_arrive_cluster(bar + B_SF2, 1); }
                    }
                    __syncwarp();
                }
                bar_sync(13, 64);
                if (lane == 0) {
                    asm volatile("cp.async.bulk.wait_group 0;\nfence.proxy.async.global;" ::: "memory");
                    cnt_add(gCntH + mb * 32);
                    TLM(0, 15);
                }
            } else {
                bar_arrive(13, 64);
                const int h = cl >> 1, qd = (cl & 1) * 2 + rank;
                const uint32_t ep = epoch();
                if (lane == 0) {
                    cnt_wait(gCntQ + (h >> 2) * 32, ep * 16);
                    mbar_arrive(bar + B_G);
                    TLM(0, 14);
                    asm volatile("fence.proxy.async.global;" ::: "memory");
#pragma unroll
                    for (int c = 0; c < 2; c++) {
                        mbar_wait(bar + B_XD + 8 * c, 0);
                        bulk_mc(sb + c * 16384 + rank * 8192, gKV + (size_t)h * (SEQ * 64) + rank * 65536 + c * 8192, 8192, bar + B_KV + 8 * c);
                    }
                }
                __syncwarp();
            const int hb = h >> 2;
            const uint4 kq = __ldcg((const uint4*)(gN + 1024 + hb * 128 + lane * 4));
            const float qq = ldcg_f(gN + hb * 128 + qd * 32 + lane);
            const float kf = __uint_as_float(__reduce_max_sync(0xffffffffu, max(max(kq.x, kq.y), max(kq.z, kq.w))));
            const float qf = __uint_as_float(__reduce_max_sync(0xffffffffu, __float_as_uint(qq)));
            if (lane == 0) {
                sts32(sb + OFF_G + 256, (ep & 1) | ((kf <= 1.0e6f) && (qf <= 1.0e6f) && (kf * qf <= 2300.f) ? 2 : 0));
                mbar_arrive(bar + B_G3);
                TLM(0, 16);
#pragma unroll
                for (int c = 2; c < 8; c++) {
                    mbar_wait(bar + B_XD + 8 * c, 0);
                    bulk_mc(sb + c * 16384 + rank * 8192, gKV + (size_t)h * (SEQ * 64) + rank * 65536 + c * 8192, 8192, bar + B_KV + 8 * c);
                }
                TLM(0, 10);
            }
            }
        }
        __syncwarp();
        float acc[64];
#pragma unroll
        for (int i = 0; i < 64; i++) acc[i] = 0.f;
#pragma unroll 1
        for (int io = 0; io < 7; io++) {
#pragma unroll
            for (int s = 0; s < 4; s++) {
                const int it = io * 4 + s;
                mbar_wait(bar + B_F2 + 8 * s, io & 1);
                if (tid == 512 && s == 0 && (io == 0 || io == 4)) TLM(1, 14 + io / 4);
                const uint64_t dA = mkdesc(SBD + OFF_R + s * 24576, 16, 1024, 1);
                const uint64_t dB = mkdesc(SBD + OFF_R + s * 24576 + 8192, 8192, 1024, 1);
                wg_fence();
#pragma unroll
                for (int kk = 0; kk < EXP_FKK; kk++) {
                    wgmma_ss_n128(acc, dA + kk * 2, dB + kk * 128);
                    if (kk < 3 && (FSER != 3 || kk == 1)) {
                        wg_commit();
                        wg_wait<0>();
                    }
                }
                wg_commit();
                if (warp < 18 && it >= 2 && it < 26) {
                    const int s2 = (s + 2) & 3;
                    mbar_wait(bar + B_E2 + 8 * s2, (io - (s < 2)) & 1);
                    if (elect()) {
                        if (warp == 16) {
                            mbar_expect(bar + B_F2 + 8 * s2, 24576);
                            tma5d_mc(sb + OFF_R + s2 * 24576 + 8192 + rank * 8192, &tm.w2, cb * 128 + rank * 64, it * 2 + 4, bar + B_F2 + 8 * s2);
                        } else {
                            asm volatile("fence.proxy.async.global;" ::: "memory");
                            tma2d(sb + OFF_R + s2 * 24576, &tm.h, it * 64 + 128, rb * 64, bar + B_F2 + 8 * s2);
                        }
                    }
                    __syncwarp();
                }
                wg_wait<1>();
                if (it >= 1 && lane < 2) mbar_arrive_cluster(bar + B_E2 + 8 * ((s + 3) & 3), lane);
            }
        }
        wg_wait<0>();
        if (lane < 2) mbar_arrive_cluster(bar + B_E2 + 8 * 3, lane);
        pin<64>(acc);
        if (tid == 576) gEpoch[blockIdx.x] = epoch();
        if (warp == 16) {
            if (lane == 0) TLM(1, 16);
            for (int s = 0; s < 4; s++) mbar_wait(bar + B_E2 + 8 * s, 0);
            if (elect()) {
#pragma unroll
                for (int i = 0; i < 4; i++)
                    tma5d_mc(sb + OFF_R + i * 16384 + rank * 8192, &tm.wo, cb * 128 + rank * 64, (i * 2 + rn) * 4, bar + B_T + 8 * i);
            }
            __syncwarp();
        }
        uint32_t pa;
        {
            const int lr = (warp - 16) * 16 + g;
            pa = pk_bf16(ldcg_f(gG + rb * 64 + lr), ldcg_f(gG + rb * 64 + lr + 8));
            if (t == 0) {
                sts32(sb + OFF_G + lr * 4, __byte_perm(pa, pa, 0x1010));
                sts32(sb + OFF_G + lr * 4 + 32, __byte_perm(pa, pa, 0x3232));
            }
            const float ga = bf_lo(pa), gb = bf_hi(pa);
            const float g0 = 1.f - ga, g1 = 1.f - gb;
#pragma unroll
            for (int j = 0; j < 16; j++) {
                const uint32_t bv = lds32(sb + OFF_BIAS + 896 + j * 16 + t * 4);
                acc[4 * j] = fmaf(acc[4 * j], 0.5f, bf_lo(bv)) * g0;
                acc[4 * j + 1] = fmaf(acc[4 * j + 1], 0.5f, bf_hi(bv)) * g0;
                acc[4 * j + 2] = fmaf(acc[4 * j + 2], 0.5f, bf_lo(bv)) * g1;
                acc[4 * j + 3] = fmaf(acc[4 * j + 3], 0.5f, bf_hi(bv)) * g1;
            }
            pin<64>(acc);
        }
        {
            mbar_wait(bar + B_G3, 0);
            const uint32_t ep = lds32(sb + OFF_G + 256);
            const uint4* src = gO + (rb * NH + rn * 4) * 128 + (tid & 127);
            bar_sync(15, 128);
#pragma unroll 1
            for (int e = 0; e < 4; e++) {
                uint4 v[4];
#pragma unroll
                for (int i = 0; i < 4; i++) v[i] = load_o(src + i * 128);
                fetch_o<4>(v, src, ep);
                stage_o(v, sb + OFF_R + 65536 + e * 8192 + ((warp - 16) * 16 + (lane & 15)) * 128, __byte_perm(pa, pa, 0x1010), __byte_perm(pa, pa, 0x3232), lane);
                src += 8 * 128;
            }
            if (warp == 16) {
                mbar_wait(bar + B_DONE, 0);
                if (elect()) {
#pragma unroll
                    for (int i = 0; i < 8; i++)
                        tma5d(sb + i * 8192, &tm.wo, cb * 128 + (i & 1) * 64, ((i >> 1) * 2 + (rn ^ 1)) * 4, bar + B_T + 32 + 8 * (i >> 1));
                }
                __syncwarp();
            }
            bar_sync(15, 128);
            if (tid == 512) TLM(1, 17);
            mbar_wait(bar + B_DONE2, 0);
        }
#pragma unroll 1
        for (int late = 0; late < 2; late++) {
            const uint64_t dB0 = mkdesc(SBD + OFF_R, 8192, 1024, 1) - late * (OFF_R / 16);
#pragma unroll
            for (int i = 0; i < 4; i++) {
                mbar_wait(bar + B_T + late * 32 + 8 * i, 0);
                const uint64_t dA = mkdesc(SBD + OFF_R + 65536 + i * 8192, 16, 1024, 1);
                wg_fence();
#pragma unroll
                for (int kk = 0; kk < 4; kk++) wgmma_ss_n128(acc, dA + kk * 2, dB0 + i * 1024 + kk * 128);
                wg_commit();
            }
            if (!late) {
                wg_wait<0>();
                if (lane == 0) mbar_arrive(bar + B_G2);
            }
        }
        wg_wait<0>();
        pin<64>(acc);
        if (tid == 512) TLM(1, 18);
        {
            const uint32_t st = sb + 98304 + (warp - 16) * 4352;
            const uint32_t wa = st + (lane & 15) * 272 + (lane >> 4) * 16;
#pragma unroll
            for (int j = 0; j < 8; j++)
                asm volatile("stmatrix.sync.aligned.m8n8.x4.shared.b16 [%0], {%1, %2, %3, %4};" ::"r"(wa + j * 32),
                             "r"(pk_bf16(acc[8 * j], acc[8 * j + 1])), "r"(pk_bf16(acc[8 * j + 2], acc[8 * j + 3])),
                             "r"(pk_bf16(acc[8 * j + 4], acc[8 * j + 5])), "r"(pk_bf16(acc[8 * j + 6], acc[8 * j + 7])) : "memory");
            __syncwarp();
            __nv_bfloat16* op = out + (size_t)(rb * 64 + (warp - 16) * 16 + (lane >> 4)) * DM + cb * 128 + (lane & 15) * 8;
#pragma unroll
            for (int j = 0; j < 8; j++) {
                uint4 v;
                asm volatile("ld.shared.v4.u32 {%0, %1, %2, %3}, [%4];" : "=r"(v.x), "=r"(v.y), "=r"(v.z), "=r"(v.w)
                             : "r"(st + (2 * j + (lane >> 4)) * 272 + (lane & 15) * 16));
                *(uint4*)(op + (size_t)j * 2 * DM) = v;
            }
        }
        if (tid == 512) TLM(1, 19);
        TL_DUMP();
    }
}

typedef CUresult (*EncodeFn)(CUtensorMap*, CUtensorMapDataType, cuuint32_t, void*, const cuuint64_t*, const cuuint64_t*, const cuuint32_t*,
                             const cuuint32_t*, CUtensorMapInterleave, CUtensorMapSwizzle, CUtensorMapL2promotion, CUtensorMapFloatOOBfill);

static void make_map(EncodeFn enc, CUtensorMap* m, const void* p, int rank, const cuuint64_t* dims, const cuuint64_t* strides,
                     const cuuint32_t* box, CUtensorMapSwizzle swz) {
    const cuuint32_t es[5] = {1, 1, 1, 1, 1};
    enc(m, CU_TENSOR_MAP_DATA_TYPE_BFLOAT16, rank, (void*)p, dims, strides, box, es, CU_TENSOR_MAP_INTERLEAVE_NONE, swz,
        CU_TENSOR_MAP_L2_PROMOTION_L2_128B, CU_TENSOR_MAP_FLOAT_OOB_FILL_NONE);
}

extern "C" void kernel_launch(void* const* d_in, const int* in_sizes, int n_in, void* d_out, int out_size) {
    const __nv_bfloat16* x = (const __nv_bfloat16*)d_in[0];
    const __nv_bfloat16* wqkv = (const __nv_bfloat16*)d_in[1];
    const __nv_bfloat16* wo = (const __nv_bfloat16*)d_in[2];
    const __nv_bfloat16* w1 = (const __nv_bfloat16*)d_in[4];
    const __nv_bfloat16* b1 = (const __nv_bfloat16*)d_in[5];
    const __nv_bfloat16* w2 = (const __nv_bfloat16*)d_in[6];
    const __nv_bfloat16* b2 = (const __nv_bfloat16*)d_in[7];
    const __nv_bfloat16* gate = (const __nv_bfloat16*)d_in[8];

    void* fp = nullptr;
    cudaDriverEntryPointQueryResult qr;
    cudaGetDriverEntryPoint("cuTensorMapEncodeTiled", &fp, cudaEnableDefault, &qr);
    EncodeFn enc = (EncodeFn)fp;
    void *pH, *pKV;
    cudaGetSymbolAddress(&pH, gH);
    cudaGetSymbolAddress(&pKV, gKV);

    Maps tm;
    const CUtensorMapSwizzle S128 = CU_TENSOR_MAP_SWIZZLE_128B, S64 = CU_TENSOR_MAP_SWIZZLE_64B;
    { cuuint64_t d[3] = {DM, SEQ, 1}, s[2] = {DM * 2, SEQ * DM * 2}; cuuint32_t b[3] = {64, 128, 1}; make_map(enc, &tm.x, x, 3, d, s, b, S128); }
    { cuuint64_t d[3] = {DM, DM, 3}, s[2] = {3 * DM * 2, DM * 2}; cuuint32_t b[3] = {64, 32, 2}; make_map(enc, &tm.kv, wqkv, 3, d, s, b, S128); }
    { cuuint64_t d[3] = {32, DM, 3 * DM / 32}, s[2] = {3 * DM * 2, 64}; cuuint32_t b[3] = {32, 32, 2}; make_map(enc, &tm.q, wqkv, 3, d, s, b, S64); }
    { cuuint64_t d[3] = {32, DM, FF / 32}, s[2] = {FF * 2, 64}; cuuint32_t b[3] = {32, 32, 1}; make_map(enc, &tm.f1, w1, 3, d, s, b, S64); }
    { cuuint64_t d[3] = {32, DM, FF / 32}, s[2] = {FF * 2, 64}; cuuint32_t b[3] = {32, 32, 3}; make_map(enc, &tm.f3, w1, 3, d, s, b, S64); }
    { cuuint64_t d[2] = {FF, SEQ}, s[1] = {FF * 2}; cuuint32_t b[2] = {64, 64}; make_map(enc, &tm.h, pH, 2, d, s, b, S128); }
    { cuuint64_t d[5] = {DM, 2, 4, 4, FF / 32}, s[4] = {1024, 8 * 1024, 2 * 1024, 32 * 1024}; cuuint32_t b[5] = {64, 2, 4, 4, 2};
      make_map(enc, &tm.w2, w2, 5, d, s, b, S128); }
    { cuuint64_t d[5] = {DM, 2, 2, 4, NH}, s[4] = {1024, 8 * 1024, 2 * 1024, 16 * 1024}; cuuint32_t b[5] = {64, 2, 2, 4, 4};
      make_map(enc, &tm.wo, wo, 5, d, s, b, S128); }

    { cuuint64_t d[3] = {32, SEQ, FF / 32}, s[2] = {FF * 2, 64}; cuuint32_t b[3] = {32, 64, 1}; make_map(enc, &tm.hs, pH, 3, d, s, b, CU_TENSOR_MAP_SWIZZLE_NONE); }
    { cuuint64_t d[5] = {64, 16, 16, 2, 2 * NH}, s[4] = {4096, 128, 2048, 65536}; cuuint32_t b[5] = {64, 8, 2, 2, 1};
      make_map(enc, &tm.kvs, pKV, 5, d, s, b, S128); }
    cudaFuncSetAttribute(fused_kernel, cudaFuncAttributeMaxDynamicSharedMemorySize, TL_SMEM);
    fused_kernel<<<128, 640, TL_SMEM, cudaStreamPerThread>>>(tm, x, wqkv, wo, w1, b1, w2, b2, gate, (__nv_bfloat16*)d_out, 0xffffffffu);
}
```

```cpp
#include <cuda_runtime.h>
#include <cuda_bf16.h>
#include <cuda_fp16.h>
#include <cuda.h>
#include <stdint.h>

#define SEQ 2048
#define DM 512
#define FF 1792
#define NH 32

__device__ __align__(1024) uint8_t gQ[NH * SEQ * 32];
__device__ __align__(1024) uint8_t gKV[NH * SEQ * 64];
__device__ __align__(1024) __nv_bfloat16 gH[SEQ * FF];
__device__ __align__(1024) uint4 gO[32 * NH * 128];
__device__ float gG[SEQ];
__device__ __align__(16) float gN[2 * 8 * 128];
__device__ __align__(128) unsigned int gCntQ[8 * 32];
__device__ __align__(128) unsigned int gCntH[16 * 32];
__device__ unsigned int gEpoch[128];

__device__ __forceinline__ uint32_t smem_u32(const void* p) { return (uint32_t)__cvta_generic_to_shared(p); }
__device__ __forceinline__ void mbar_init(uint32_t a, uint32_t c) { asm volatile("mbarrier.init.shared::cta.b64 [%0], %1;" ::"r"(a), "r"(c)); }
__device__ __forceinline__ void mbar_expect(uint32_t a, uint32_t b) { asm volatile("mbarrier.arrive.expect_tx.shared::cta.b64 _, [%0], %1;" ::"r"(a), "r"(b) : "memory"); }
__device__ __forceinline__ void mbar_arrive(uint32_t a) { asm volatile("mbarrier.arrive.shared::cta.b64 _, [%0];" ::"r"(a) : "memory"); }
__device__ __forceinline__ void mbar_wait(uint32_t a, uint32_t ph) {
    asm volatile("{\n.reg .pred p;\n.reg .u32 n;\nmov.u32 n, 0;\nW_%=:\nmbarrier.try_wait.parity.shared::cta.b64 p, [%0], %1;\n@p bra D_%=;\n"
                 "add.u32 n, n, 1;\nsetp.lt.u32 p, n, 0x4000000;\n@p bra W_%=;\ntrap;\nD_%=:\n}" ::"r"(a), "r"(ph) : "memory");
}
__device__ __forceinline__ void mbar_arrive_cluster(uint32_t a, uint32_t cta) {
    asm volatile("{\n.reg .b32 r;\nmapa.shared::cluster.u32 r, %0, %1;\nmbarrier.arrive.shared::cluster.b64 _, [r];\n}" ::"r"(a), "r"(cta) : "memory");
}
__device__ __forceinline__ void bar_sync(int id, int n) { asm volatile("bar.sync %0, %1;" ::"r"(id), "r"(n) : "memory"); }
__device__ __forceinline__ void bar_arrive(int id, int n) { asm volatile("bar.arrive %0, %1;" ::"r"(id), "r"(n) : "memory"); }
__device__ __forceinline__ uint32_t cluster_rank() { uint32_t r; asm("mov.u32 %0, %%cluster_ctarank;" : "=r"(r)); return r; }
__device__ __forceinline__ void cnt_add(unsigned int* c) { asm volatile("red.release.gpu.global.add.u32 [%0], 1;" ::"l"(c) : "memory"); }
__device__ __forceinline__ void cnt_wait(const unsigned int* c, uint32_t target) {
    uint32_t v;
    int spins = 0;
    while (true) {
        asm volatile("ld.acquire.gpu.global.u32 %0, [%1];" : "=r"(v) : "l"(c) : "memory");
        if ((int)(v - target) >= 0) break;
        if (++spins > (1 << 22)) __trap();
        __nanosleep(40);
    }
}
__device__ __forceinline__ void tma2d(uint32_t dst, const CUtensorMap* m, int c0, int c1, uint32_t bar) {
    asm volatile("cp.async.bulk.tensor.2d.shared::cluster.global.mbarrier::complete_tx::bytes [%0], [%1, {%3, %4}], [%2];"
                 ::"r"(dst), "l"(m), "r"(bar), "r"(c0), "r"(c1) : "memory");
}
__device__ __forceinline__ void tma3d_mc(uint32_t dst, const CUtensorMap* m, int c0, int c1, int c2, uint32_t bar) {
    asm volatile("cp.async.bulk.tensor.3d.shared::cluster.global.mbarrier::complete_tx::bytes.multicast::cluster [%0], [%1, {%3, %4, %5}], [%2], %6;"
                 ::"r"(dst), "l"(m), "r"(bar), "r"(c0), "r"(c1), "r"(c2), "h"((uint16_t)3) : "memory");
}
__device__ __forceinline__ void tma5d_mc(uint32_t dst, const CUtensorMap* m, int c0, int c4, uint32_t bar) {
    asm volatile("cp.async.bulk.tensor.5d.shared::cluster.global.mbarrier::complete_tx::bytes.multicast::cluster [%0], [%1, {%3, %5, %5, %5, %4}], [%2], %6;"
                 ::"r"(dst), "l"(m), "r"(bar), "r"(c0), "r"(c4), "r"(0), "h"((uint16_t)3) : "memory");
}
__device__ __forceinline__ void tma5d(uint32_t dst, const CUtensorMap* m, int c0, int c4, uint32_t bar) {
    asm volatile("cp.async.bulk.tensor.5d.shared::cluster.global.mbarrier::complete_tx::bytes [%0], [%1, {%3, %5, %5, %5, %4}], [%2];"
                 ::"r"(dst), "l"(m), "r"(bar), "r"(c0), "r"(c4), "r"(0) : "memory");
}
__device__ __forceinline__ void bulk_mc(uint32_t dst, const void* src, uint32_t bytes, uint32_t bar) {
    asm volatile("cp.async.bulk.shared::cluster.global.mbarrier::complete_tx::bytes.multicast::cluster [%0], [%1], %2, [%3], %4;"
                 ::"r"(dst), "l"(src), "r"(bytes), "r"(bar), "h"((uint16_t)3) : "memory");
}
__device__ __forceinline__ void tma3d_st(const CUtensorMap* m, uint32_t src, int c0, int c1, int c2) {
    asm volatile("cp.async.bulk.tensor.3d.global.shared::cta.bulk_group [%0, {%2, %3, %4}], [%1];" ::"l"(m), "r"(src), "r"(c0), "r"(c1), "r"(c2) : "memory");
}
__device__ __forceinline__ void tma5d_st(const CUtensorMap* m, uint32_t src, int c1, int c2, int c4) {
    asm volatile("cp.async.bulk.tensor.5d.global.shared::cta.bulk_group [%0, {%5, %2, %3, %5, %4}], [%1];"
                 ::"l"(m), "r"(src), "r"(c1), "r"(c2), "r"(c4), "r"(0) : "memory");
}
__device__ __forceinline__ void sts64(uint32_t a, uint32_t x, uint32_t y) { asm volatile("st.shared.v2.u32 [%0], {%1, %2};" ::"r"(a), "r"(x), "r"(y) : "memory"); }
__device__ __forceinline__ void sts128(uint32_t a, const uint32_t* v) {
    asm volatile("st.shared.v4.u32 [%0], {%1, %2, %3, %4};" ::"r"(a), "r"(v[0]), "r"(v[1]), "r"(v[2]), "r"(v[3]) : "memory");
}
__device__ __forceinline__ void l2_prefetch(const void* src, uint32_t bytes) {
    asm volatile("cp.async.bulk.prefetch.L2.global [%0], %1;" ::"l"(src), "r"(bytes) : "memory");
}
__device__ __forceinline__ void map_prefetch(const CUtensorMap* m) { asm volatile("prefetch.tensormap [%0];" ::"l"(m) : "memory"); }
__device__ __forceinline__ void wg_fence() { asm volatile("wgmma.fence.sync.aligned;" ::: "memory"); }
__device__ __forceinline__ void wg_commit() { asm volatile("wgmma.commit_group.sync.aligned;" ::: "memory"); }
template <int N> __device__ __forceinline__ void wg_wait() { asm volatile("wgmma.wait_group.sync.aligned %0;" ::"n"(N) : "memory"); }
template <int N> __device__ __forceinline__ void pin(float* s) {
#pragma unroll
    for (int i = 0; i < N; i++) asm volatile("" : "+f"(s[i])::"memory");
}
template <int N> __device__ __forceinline__ void pin(uint32_t* s) {
#pragma unroll
    for (int i = 0; i < N; i++) asm volatile("" : "+r"(s[i])::"memory");
}
__device__ __forceinline__ uint64_t mkdesc(uint32_t addr, uint32_t lbo, uint32_t sbo, uint32_t swz) {
    return (uint64_t)((addr & 0x3FFFF) >> 4) | ((uint64_t)(lbo >> 4) << 16) | ((uint64_t)(sbo >> 4) << 32) | ((uint64_t)swz << 62);
}
__device__ __forceinline__ float ex2f(float x) { float y; asm("ex2.approx.ftz.f32 %0, %1;" : "=f"(y) : "f"(x)); return y; }
__device__ __forceinline__ float tanhf_(float x) { float y; asm("tanh.approx.f32 %0, %1;" : "=f"(y) : "f"(x)); return y; }
__device__ __forceinline__ uint32_t pk_bf16(float lo, float hi) { uint32_t r; asm("cvt.rn.bf16x2.f32 %0, %1, %2;" : "=r"(r) : "f"(hi), "f"(lo)); return r; }
__device__ __forceinline__ uint32_t pk_f16(float lo, float hi) { uint32_t r; asm("cvt.rn.f16x2.f32 %0, %1, %2;" : "=r"(r) : "f"(hi), "f"(lo)); return r; }
__device__ __forceinline__ float bf_lo(uint32_t v) { return __uint_as_float(v << 16); }
__device__ __forceinline__ float bf_hi(uint32_t v) { return __uint_as_float(v & 0xffff0000u); }
__device__ __forceinline__ float dot8(const uint4& a, const uint4& b) {
    return fmaf(bf_lo(a.x), bf_lo(b.x), fmaf(bf_hi(a.x), bf_hi(b.x), fmaf(bf_lo(a.y), bf_lo(b.y), bf_hi(a.y) * bf_hi(b.y)))) +
           fmaf(bf_lo(a.z), bf_lo(b.z), fmaf(bf_hi(a.z), bf_hi(b.z), fmaf(bf_lo(a.w), bf_lo(b.w), bf_hi(a.w) * bf_hi(b.w))));
}
__device__ __forceinline__ uint32_t epoch() {
    uint32_t v;
    asm volatile("ld.global.u32 %0, [%1];" : "=r"(v) : "l"(gEpoch + blockIdx.x));
    return v + 1;
}
__device__ __forceinline__ float ldcg_f(const float* p) { return __ldcg(p); }

extern __shared__ __align__(1024) uint8_t smem_raw[];

__device__ __forceinline__ void wgmma_ss_n128(float* d, uint64_t da, uint64_t db) {
    asm volatile("wgmma.mma_async.sync.aligned.m64n128k16.f32.bf16.bf16 {"
        "%0, %1, %2, %3, %4, %5, %6, %7, %8, %9, %10, %11, %12, %13, %14, %15,"
        "%16, %17, %18, %19, %20, %21, %22, %23, %24, %25, %26, %27, %28, %29, %30, %31,"
        "%32, %33, %34, %35, %36, %37, %38, %39, %40, %41, %42, %43, %44, %45, %46, %47,"
        "%48, %49, %50, %51, %52, %53, %54, %55, %56, %57, %58, %59, %60, %61, %62, %63}, %64, %65, 1, 1, 1, 0, 1;\n"
        :
        "+f"(d[0]), "+f"(d[1]), "+f"(d[2]), "+f"(d[3]), "+f"(d[4]), "+f"(d[5]), "+f"(d[6]), "+f"(d[7]),
        "+f"(d[8]), "+f"(d[9]), "+f"(d[10]), "+f"(d[11]), "+f"(d[12]), "+f"(d[13]), "+f"(d[14]), "+f"(d[15]),
        "+f"(d[16]), "+f"(d[17]), "+f"(d[18]), "+f"(d[19]), "+f"(d[20]), "+f"(d[21]), "+f"(d[22]), "+f"(d[23]),
        "+f"(d[24]), "+f"(d[25]), "+f"(d[26]), "+f"(d[27]), "+f"(d[28]), "+f"(d[29]), "+f"(d[30]), "+f"(d[31]),
        "+f"(d[32]), "+f"(d[33]), "+f"(d[34]), "+f"(d[35]), "+f"(d[36]), "+f"(d[37]), "+f"(d[38]), "+f"(d[39]),
        "+f"(d[40]), "+f"(d[41]), "+f"(d[42]), "+f"(d[43]), "+f"(d[44]), "+f"(d[45]), "+f"(d[46]), "+f"(d[47]),
        "+f"(d[48]), "+f"(d[49]), "+f"(d[50]), "+f"(d[51]), "+f"(d[52]), "+f"(d[53]), "+f"(d[54]), "+f"(d[55]),
        "+f"(d[56]), "+f"(d[57]), "+f"(d[58]), "+f"(d[59]), "+f"(d[60]), "+f"(d[61]), "+f"(d[62]), "+f"(d[63])
        : "l"(da), "l"(db));
}
__device__ __forceinline__ void wgmma_ss_n96(float* d, uint64_t da, uint64_t db) {
    asm volatile("wgmma.mma_async.sync.aligned.m64n96k16.f32.bf16.bf16 {"
        "%0, %1, %2, %3, %4, %5, %6, %7, %8, %9, %10, %11, %12, %13, %14, %15,"
        "%16, %17, %18, %19, %20, %21, %22, %23, %24, %25, %26, %27, %28, %29, %30, %31,"
        "%32, %33, %34, %35, %36, %37, %38, %39, %40, %41, %42, %43, %44, %45, %46, %47}, %48, %49, 1, 1, 1, 0, 1;\n"
        :
        "+f"(d[0]), "+f"(d[1]), "+f"(d[2]), "+f"(d[3]), "+f"(d[4]), "+f"(d[5]), "+f"(d[6]), "+f"(d[7]),
        "+f"(d[8]), "+f"(d[9]), "+f"(d[10]), "+f"(d[11]), "+f"(d[12]), "+f"(d[13]), "+f"(d[14]), "+f"(d[15]),
        "+f"(d[16]), "+f"(d[17]), "+f"(d[18]), "+f"(d[19]), "+f"(d[20]), "+f"(d[21]), "+f"(d[22]), "+f"(d[23]),
        "+f"(d[24]), "+f"(d[25]), "+f"(d[26]), "+f"(d[27]), "+f"(d[28]), "+f"(d[29]), "+f"(d[30]), "+f"(d[31]),
        "+f"(d[32]), "+f"(d[33]), "+f"(d[34]), "+f"(d[35]), "+f"(d[36]), "+f"(d[37]), "+f"(d[38]), "+f"(d[39]),
        "+f"(d[40]), "+f"(d[41]), "+f"(d[42]), "+f"(d[43]), "+f"(d[44]), "+f"(d[45]), "+f"(d[46]), "+f"(d[47])
        : "l"(da), "l"(db));
}
__device__ __forceinline__ void wgmma_qk_f16_acc(float* d, const uint32_t* a, uint64_t db) {
    asm volatile("wgmma.mma_async.sync.aligned.m64n64k16.f32.f16.f16 {"
        "%0, %1, %2, %3, %4, %5, %6, %7, %8, %9, %10, %11, %12, %13, %14, %15,"
        "%16, %17, %18, %19, %20, %21, %22, %23, %24, %25, %26, %27, %28, %29, %30, %31}, {%32, %33, %34, %35}, %36, 1, 1, 1, 0;\n"
        :
        "+f"(d[0]), "+f"(d[1]), "+f"(d[2]), "+f"(d[3]), "+f"(d[4]), "+f"(d[5]), "+f"(d[6]), "+f"(d[7]),
        "+f"(d[8]), "+f"(d[9]), "+f"(d[10]), "+f"(d[11]), "+f"(d[12]), "+f"(d[13]), "+f"(d[14]), "+f"(d[15]),
        "+f"(d[16]), "+f"(d[17]), "+f"(d[18]), "+f"(d[19]), "+f"(d[20]), "+f"(d[21]), "+f"(d[22]), "+f"(d[23]),
        "+f"(d[24]), "+f"(d[25]), "+f"(d[26]), "+f"(d[27]), "+f"(d[28]), "+f"(d[29]), "+f"(d[30]), "+f"(d[31])
        : "r"(a[0]), "r"(a[1]), "r"(a[2]), "r"(a[3]), "l"(db));
}
__device__ __forceinline__ void wgmma_qk_bf16_zero(float* d, const uint32_t* a, uint64_t db) {
    asm volatile("wgmma.mma_async.sync.aligned.m64n64k16.f32.bf16.bf16 {"
        "%0, %1, %2, %3, %4, %5, %6, %7, %8, %9, %10, %11, %12, %13, %14, %15,"
        "%16, %17, %18, %19, %20, %21, %22, %23, %24, %25, %26, %27, %28, %29, %30, %31}, {%32, %33, %34, %35}, %36, 0, 1, 1, 0;\n"
        :
        "=f"(d[0]), "=f"(d[1]), "=f"(d[2]), "=f"(d[3]), "=f"(d[4]), "=f"(d[5]), "=f"(d[6]), "=f"(d[7]),
        "=f"(d[8]), "=f"(d[9]), "=f"(d[10]), "=f"(d[11]), "=f"(d[12]), "=f"(d[13]), "=f"(d[14]), "=f"(d[15]),
        "=f"(d[16]), "=f"(d[17]), "=f"(d[18]), "=f"(d[19]), "=f"(d[20]), "=f"(d[21]), "=f"(d[22]), "=f"(d[23]),
        "=f"(d[24]), "=f"(d[25]), "=f"(d[26]), "=f"(d[27]), "=f"(d[28]), "=f"(d[29]), "=f"(d[30]), "=f"(d[31])
        : "r"(a[0]), "r"(a[1]), "r"(a[2]), "r"(a[3]), "l"(db));
}
__device__ __forceinline__ void wgmma_pv(float* d, const uint32_t* a, uint64_t db) {
    asm volatile("wgmma.mma_async.sync.aligned.m64n24k16.f32.bf16.bf16 {"
        "%0, %1, %2, %3, %4, %5, %6, %7, %8, %9, %10, %11}, {%12, %13, %14, %15}, %16, 1, 1, 1, 1;\n"
        :
        "+f"(d[0]), "+f"(d[1]), "+f"(d[2]), "+f"(d[3]), "+f"(d[4]), "+f"(d[5]), "+f"(d[6]), "+f"(d[7]),
        "+f"(d[8]), "+f"(d[9]), "+f"(d[10]), "+f"(d[11])
        : "r"(a[0]), "r"(a[1]), "r"(a[2]), "r"(a[3]), "l"(db));
}


template <int N> __device__ __forceinline__ void wgmma_ss(float* d, uint64_t a, uint64_t b) {
    if (N == 128) wgmma_ss_n128(d, a, b);
    if (N == 96) wgmma_ss_n96(d, a, b);
}

#define OFF_R 131072
#define OFF_ONE 229376
#define OFF_BAR 229888
#define OFF_BIAS (OFF_BAR + 736)
#define OFF_G (OFF_BIAS + 1152)
#define SMEM_BYTES (OFF_G + 272)
#define SBD 1024u
#define B_X 0
#define B_E1 64
#define B_DONE 112
#define B_DONE2 120
#define B_KV 160
#define B_F2 224
#define B_E2 256
#define B_T 288
#define B_G 360
#define B_G2 368
#define B_G3 376
#define B_SF 384
#define B_BI 400
#define B_SF2 408
#define B_F1 416
#define B_XD 672
#define NR 6

#define QSCALE 0.36067376022224085f
#define MAGIC 445.4171f
#define MUM 0x5a44
#define FM 5
#define VSTEP ((uint64_t)((long long)32 - ((long long)32 << 16)))

#define KVMASK 0x1D55u
#define XMASK 0x0D55u
__host__ __device__ constexpr int strm_pos(int pass, int i) {
    if (pass == 1 || pass == 2) return 8 + 8 * pass + i;
    int n = 0;
    for (int p = 0; p < 16; p++)
        if ((int)((KVMASK >> p) & 1) == (pass == 3)) { if (n == i) return p; n++; }
    return 0;
}
__host__ __device__ constexpr uint32_t strm_code(int pass) {
    uint32_t c = 0;
    for (int i = 0; i < 7; i++) c |= (uint32_t)(strm_pos(pass, i + 1) - strm_pos(pass, i)) << (4 * i);
    return c;
}

template <int N, int SUB, int KST, int LBO, int SBO, int SWZ>
__device__ __forceinline__ void gemm_pass(float* acc, uint32_t bar, uint64_t dA, int lane, uint32_t pos, uint32_t code, int barNext, bool waitx, bool last) {
    uint32_t prev = 0, slot = pos % NR;
#pragma unroll 1
    for (int i = 0; i < 8; i++) {
        if (waitx) mbar_wait(bar + B_X + 8 * i, 0);
        mbar_wait(bar + B_F1 + 8 * pos, 0);
        const uint64_t dB = mkdesc(SBD + OFF_R, LBO, SBO, SWZ) + slot * 1024;
        wg_fence();
        wgmma_ss<N>(acc, dA, dB);
        wgmma_ss<N>(acc, dA + 2, dB + KST / 16);
        wg_commit();
        wg_wait<1>();
        if (i > 0 && lane < 2) mbar_arrive_cluster(prev, lane);
        wgmma_ss<N>(acc, dA + 4, dB + SUB / 16);
        wgmma_ss<N>(acc, dA + 6, dB + (SUB + KST) / 16);
        wg_commit();
        prev = last ? bar + B_XD + 8 * i : bar + B_E1 + 8 * slot;
        pos += code & 15;
        slot += code & 15;
        if (slot >= NR) slot -= NR;
        code >>= 4;
        dA += 1024;
    }
    if (barNext) bar_arrive(barNext, 512);
    wg_wait<0>();
    if (lane < 2) mbar_arrive_cluster(prev, lane);
    pin<N / 2>(acc);
}

__device__ __forceinline__ uint32_t lds32(uint32_t a) { uint32_t v; asm volatile("ld.shared.u32 %0, [%1];" : "=r"(v) : "r"(a)); return v; }
__device__ __forceinline__ bool elect() {
    uint32_t p;
    asm volatile("{\n.reg .pred p;\nelect.sync _|p, 0xffffffff;\nselp.u32 %0, 1, 0, p;\n}" : "=r"(p));
    return p;
}

template <int G0, int G1> __device__ __forceinline__ void gelu_pack(const float* acc, uint32_t bias, uint32_t* out) {
#pragma unroll
    for (int G = G0; G < G1; G++) {
        uint32_t* o = out + 8 * G;
#pragma unroll
        for (int j = 0; j < 4; j++) {
            float bv[2];
            asm volatile("ld.shared.v2.f32 {%0, %1}, [%2];" : "=f"(bv[0]), "=f"(bv[1]) : "r"(bias + G * 128 + j * 32));
            float y[4];
#pragma unroll
            for (int i = 0; i < 4; i++) {
                const float h = acc[16 * G + 4 * j + i] + bv[i & 1];
                const float z = h * fmaf(h * h, 0.035677408136300125f, 0.7978845608028654f);
                y[i] = fmaf(h, tanhf_(z), h);
            }
            o[j] = pk_bf16(y[0], y[1]);
            o[4 + j] = pk_bf16(y[2], y[3]);
        }
    }
}

__device__ __forceinline__ uint32_t badd2(uint32_t a, uint32_t b) { uint32_t r; asm("add.rn.bf16x2 %0, %1, %2;" : "=r"(r) : "r"(a), "r"(b)); return r; }
__device__ __forceinline__ void norm_part(const float* v, uint32_t* n) {
#pragma unroll
    for (int h = 0; h < 4; h++) {
        const float* u = v + 8 * h;
        n[h] = pk_bf16(fmaf(u[0], u[0], fmaf(u[1], u[1], fmaf(u[4], u[4], u[5] * u[5]))), fmaf(u[2], u[2], fmaf(u[3], u[3], fmaf(u[6], u[6], u[7] * u[7]))));
    }
#pragma unroll
    for (int h = 0; h < 4; h++) n[h] = badd2(n[h], __shfl_xor_sync(0xffffffffu, n[h], 1));
}
__device__ __forceinline__ float norm_finish(uint32_t* n, float sc) {
#pragma unroll
    for (int h = 0; h < 4; h++) n[h] = badd2(n[h], __shfl_xor_sync(0xffffffffu, n[h], 2));
    const uint32_t m = __vimax3_u16x2(__vmaxu2(n[0], n[1]), n[2], n[3]);
    return __uint_as_float(__reduce_max_sync(0xffffffffu, max(m << 16, m & 0xffff0000u))) * (1.03f * sc);
}

__device__ __forceinline__ uint32_t exp2_pair(float a, float b, uint32_t m1) {
    const uint32_t w = __byte_perm(__float_as_uint(a), __float_as_uint(b), 0x6521);
    uint32_t m, r;
    asm("lop3.b32 %0, %1, 0x007f007f, 0x9f809f80, 0xEA;" : "=r"(m) : "r"(w));
    const uint32_t e = m * m1 + w;
    asm("fma.rn.bf16x2 %0, %1, %2, %3;" : "=r"(r) : "r"(w), "r"(m), "r"(e));
    return r;
}

__device__ __forceinline__ void st_o(uint4* dst, uint32_t a, uint32_t b, uint32_t c, uint32_t d) {
    asm volatile("{\n.reg .b128 t;\nmov.b128 t, {%0, %1, %2, %3};\nst.relaxed.gpu.global.b128 [%4], t;\n}" ::"r"(a), "r"(b), "r"(c), "r"(d), "l"(dst) : "memory");
}
__device__ __forceinline__ void store_o(const float* o, uint4* dst, uint32_t par) {
    const float s0 = __fdividef(1.f, o[8]), s1 = __fdividef(1.f, o[10]);
    const uint32_t d0 = __byte_perm(__float_as_uint(o[0] * s0) + 0x10000u, pk_bf16(0.f, o[1] * s0), 0x7632) & ~1u | par;
    st_o(dst, d0, pk_bf16(o[2] * s1, o[3] * s1), pk_bf16(o[4] * s0, o[5] * s0), pk_bf16(o[6] * s1, o[7] * s1));
}
__device__ __forceinline__ uint4 load_o(const uint4* src) {
    uint4 v;
    asm volatile("{\n.reg .b128 t;\nld.relaxed.gpu.global.b128 t, [%4];\nmov.b128 {%0, %1, %2, %3}, t;\n}"
                 : "=r"(v.x), "=r"(v.y), "=r"(v.z), "=r"(v.w) : "l"(src) : "memory");
    return v;
}
template <int N> __device__ __forceinline__ void fetch_o(uint4* v, const uint4* src, uint32_t ep) {
    int spins = 0;
    while (true) {
        uint32_t bad = 0;
#pragma unroll
        for (int k = 0; k < N; k++) bad |= v[k].x ^ ep;
        if (!__any_sync(0xffffffffu, (bad & 1) != 0)) break;
        if (++spins > (1 << 22)) __trap();
#pragma unroll
        for (int k = 0; k < N; k++)
            if (((v[k].x ^ ep) & 1) != 0) v[k] = load_o(src + k * 128);
    }
}
__device__ __forceinline__ uint32_t bmul2(uint32_t a, uint32_t b) { uint32_t r; asm("mul.rn.bf16x2 %0, %1, %2;" : "=r"(r) : "r"(a), "r"(b)); return r; }
__device__ __forceinline__ void sts32(uint32_t a, uint32_t v) { asm volatile("st.shared.u32 [%0], %1;" ::"r"(a), "r"(v) : "memory"); }
__device__ __forceinline__ void stage_o(const uint4* v, uint32_t a0, uint32_t g0, uint32_t g1, int lane) {
#pragma unroll
    for (int i = 0; i < 4; i++)
        asm volatile("stmatrix.sync.aligned.m8n8.x4.shared.b16 [%0], {%1, %2, %3, %4};" ::"r"(a0 + (((i * 2 + (lane >> 4)) ^ (lane & 7)) << 4)),
                     "r"(bmul2(v[i].x & ~1u, g0)), "r"(bmul2(v[i].y, g1)), "r"(bmul2(v[i].z, g0)), "r"(bmul2(v[i].w, g1)) : "memory");
    asm volatile("fence.proxy.async.shared::cta;" ::: "memory");
}
__device__ __forceinline__ void load_q(uint32_t* q, int h, int row, int t) {
    const uint8_t* p = gQ + (size_t)h * (SEQ * 32) + (size_t)row * 32 + t * 4;
    q[0] = __ldcg((const uint32_t*)p); q[1] = __ldcg((const uint32_t*)(p + 256));
    q[2] = __ldcg((const uint32_t*)(p + 16)); q[3] = __ldcg((const uint32_t*)(p + 272));
}

template <int NT>
__device__ __forceinline__ void proj16(float (*c)[8], const __nv_bfloat16* x, const __nv_bfloat16* w, int row0, int rstep, int col, int g, int t) {
#pragma unroll
    for (int i = 0; i < NT; i++)
#pragma unroll
        for (int j = 0; j < 8; j++) c[i][j] = 0.f;
    const unsigned short* wu = (const unsigned short*)w;
#pragma unroll 1
    for (int k = 0; k < DM; k += 16) {
        uint32_t b[4];
#pragma unroll
        for (int j = 0; j < 4; j++) {
            const int kr = k + 2 * t + (j & 1) * 8, cc = col + g + (j >> 1) * 8;
            b[j] = (uint32_t)wu[(size_t)kr * (3 * DM) + cc] | ((uint32_t)wu[(size_t)(kr + 1) * (3 * DM) + cc] << 16);
        }
#pragma unroll
        for (int i = 0; i < NT; i++) {
            const __nv_bfloat16* xp = x + (size_t)(row0 + i * rstep + g) * DM + k + 2 * t;
            const uint32_t a0 = *(const uint32_t*)xp, a1 = *(const uint32_t*)(xp + 8 * DM);
            const uint32_t a2 = *(const uint32_t*)(xp + 8), a3 = *(const uint32_t*)(xp + 8 * DM + 8);
#pragma unroll
            for (int j = 0; j < 2; j++)
                asm volatile("mma.sync.aligned.m16n8k16.row.col.f32.bf16.bf16.f32 {%0,%1,%2,%3}, {%4,%5,%6,%7}, {%8,%9}, {%0,%1,%2,%3};"
                             : "+f"(c[i][4 * j]), "+f"(c[i][4 * j + 1]), "+f"(c[i][4 * j + 2]), "+f"(c[i][4 * j + 3])
                             : "r"(a0), "r"(a1), "r"(a2), "r"(a3), "r"(b[2 * j]), "r"(b[2 * j + 1]));
        }
    }
}

struct Maps { CUtensorMap x, kv, q, f1, f3, h, w2, wo, hs, kvs; };

template <int I0, int I1>
__device__ __forceinline__ void issue_stream(const Maps& tm, uint32_t sb, uint32_t rank, int nb, int mb) {
    const uint32_t bar = sb + OFF_BAR;
    const uint32_t dst = sb + OFF_R;
    const int kr = rank * 32;
#pragma unroll
    for (int it = I0; it < I1; it++) {
        const int s = it % NR;
        const uint32_t fb = bar + B_F1 + 8 * it;
        if (it >= 24 + NR) mbar_wait(bar + B_XD + 8 * (it - 24 - NR), 0);
        else if (it >= NR) mbar_wait(bar + B_E1 + 8 * s, ((it / NR) - 1) & 1);
        const int nkv = __builtin_popcount(KVMASK & ((1u << it) - 1));
        if (it < 16 && ((KVMASK >> it) & 1)) {
            tma3d_mc(dst + s * 16384 + rank * 8192, &tm.kv, nb * 64, nkv * 64 + kr, 1, fb);
        } else if (it < 16) {
            tma3d_mc(dst + s * 16384 + rank * 6144, &tm.q, 0, (it - nkv) * 64 + kr, nb * 2, fb);
            tma3d_mc(dst + s * 16384 + rank * 6144 + 4096, &tm.f1, 0, (it - nkv) * 64 + kr, nb * 7, fb);
        } else {
            tma3d_mc(dst + s * 16384 + rank * 6144, &tm.f3, 0, (it & 7) * 64 + kr, nb * 7 + (it < 24 ? 1 : 4), fb);
        }
        if ((XMASK >> it) & 1) {
            const int xc = 1 + __builtin_popcount(XMASK & ((1u << it) - 1));
            tma2d(sb + xc * 16384, &tm.x, xc * 64, mb * 128, bar + B_X + 8 * xc);
        }
    }
}

__global__ void __cluster_dims__(2, 1, 1) __launch_bounds__(640, 1)
fused_kernel(const __grid_constant__ Maps tm, const __nv_bfloat16* __restrict__ x, const __nv_bfloat16* __restrict__ wqkv,
             const __nv_bfloat16* __restrict__ wo, const __nv_bfloat16* __restrict__ w1, const __nv_bfloat16* __restrict__ b1,
             const __nv_bfloat16* __restrict__ w2, const __nv_bfloat16* __restrict__ b2, const __nv_bfloat16* __restrict__ gate,
             __nv_bfloat16* __restrict__ out, const uint32_t m1) {
    const uint32_t sb = smem_u32(smem_raw);
    const uint32_t bar = sb + OFF_BAR;
    const int tid = threadIdx.x, lane = tid & 31;
    const int warp = __shfl_sync(0xffffffffu, tid >> 5, 0);
    const uint32_t rank = cluster_rank();
    const int cl = blockIdx.x >> 1;
    const int nb = cl & 7, mb = (cl >> 3) * 2 + rank;
    const int g = lane >> 2, t = lane & 3;

    const int cb = nb & 3, rb = mb * 2 + (nb >> 2);
    const int rn = (mb >> 1) & 1;
    if (tid == 512) {
        for (int i = 0; i < 8; i++) { mbar_init(bar + B_X + 8 * i, 1); mbar_init(bar + B_KV + 8 * i, 1); mbar_init(bar + B_T + 8 * i, i < 4 ? 1 : 5); mbar_init(bar + B_XD + 8 * i, 16); }
        for (int i = 0; i < NR; i++) mbar_init(bar + B_E1 + 8 * i, 16);
        for (int i = 0; i < 4; i++) { mbar_init(bar + B_F2 + 8 * i, 1); mbar_init(bar + B_E2 + 8 * i, 8); }
        asm volatile("fence.mbarrier_init.release.cluster;" ::: "memory");
    } else if (tid == 608) {
        for (int i = 0; i < 32; i++) mbar_init(bar + B_F1 + 8 * i, 1);
        mbar_init(bar + B_G, 1);
        mbar_init(bar + B_DONE, 16);
        mbar_init(bar + B_DONE2, 16);
        mbar_init(bar + B_SF, 1);
        mbar_init(bar + B_SF + 8, 2);
        mbar_init(bar + B_BI, 1);
        mbar_init(bar + B_SF2, 2);
        mbar_init(bar + B_G3, 1);
        mbar_init(bar + B_G2, 4);
        asm volatile("fence.mbarrier_init.release.cluster;" ::: "memory");
    }
    __syncwarp();
    asm volatile("barrier.cluster.arrive.relaxed.aligned;" ::: "memory");
    if (warp == 19) mbar_expect(bar + B_F1 + 8 * lane, ((KVMASK >> lane) & 1) ? 16384 : 12288);
    if (warp == 16 && lane < 24) mbar_expect(bar + (lane < 8 ? B_X : lane < 16 ? B_KV - 64 : B_T - 128) + 8 * lane, 16384);
    if (tid == 512) {
        tma2d(sb, &tm.x, 0, mb * 128, bar + B_X);
    } else if (tid == 544) {
        map_prefetch(&tm.kv);
        l2_prefetch((const uint8_t*)wqkv + (size_t)blockIdx.x * 3072, 3072);
        l2_prefetch((const uint8_t*)w1 + (size_t)blockIdx.x * 1792, 1792);
        map_prefetch(&tm.q); map_prefetch(&tm.f1); map_prefetch(&tm.f3);
    }
    if (warp == 18) {
#pragma unroll
        for (int i = 0; i < 2; i++)
            asm volatile("prefetch.global.L2 [%0];" ::"l"(x + (size_t)(mb * 128 + nb * 16 + (lane & 15)) * DM + ((lane >> 4) + 2 * i) * 64));
    }
    if ((sb & 0xFFFFFF) != SBD) __trap();
    __syncwarp();
    asm volatile("barrier.cluster.wait.aligned;" ::: "memory");
    if (warp == 16 && elect()) issue_stream<0, NR>(tm, sb, rank, nb, mb);

    if (warp < 16) {
        const int wg = warp >> 2;
        const int h = cl >> 1, qd = (cl & 1) * 2 + rank;
        const int flip = (h >> 2) & 1;
        uint32_t q[4];
        {
            const int w8 = warp & 7;
            const int T = mb * 8 + w8, row0 = T * 16 + g;
            const uint64_t dA0 = mkdesc(SBD + (wg & 1) * 8192, 16, 1024, 1);
            if (wg < 2) {
                float acc[64];
#pragma unroll
                for (int i = 0; i < 64; i++) acc[i] = 0.f;
                gemm_pass<128, 8192, 2048, 4096, 1024, 1>(acc, bar, dA0, lane, strm_pos(3, 0), strm_code(3), 0, true, false);
                {
                    uint32_t pv[16];
#pragma unroll
                    for (int i = 0; i < 16; i++) pv[i] = pk_bf16(acc[32 + 2 * i], acc[33 + 2 * i]);
                    uint8_t* vp = gKV + (size_t)(nb * 4) * (SEQ * 64) + 65536 + (((T >> 6) * 16 + 2 * g) * 64 + (T & 63)) * 32 + ((t * 8) ^ ((w8 >> 2) << 4));
#pragma unroll
                    for (int hh = 2; hh < 4; hh++) {
                        *(uint2*)(vp + (size_t)hh * (SEQ * 64)) = make_uint2(pv[4 * hh], pv[4 * hh + 2]);
                        *(uint2*)(vp + (size_t)hh * (SEQ * 64) + 2048) = make_uint2(pv[4 * hh + 1], pv[4 * hh + 3]);
                    }
                    const uint32_t kp = sb + OFF_R + 12288 + (w8 >> 2) * 1024 + g * 128 + ((((w8 & 3) * 2 + ((t >> 1) ^ (w8 >> 2))) ^ g) << 4) + (t & 1) * 8;
                    bar_sync(9, 256);
#pragma unroll
                    for (int hh = 0; hh < 2; hh++) {
                        sts64(kp + (4 + hh) * 16384, pv[4 * hh], pv[4 * hh + 2]);
                        sts64(kp + (4 + hh) * 16384 + 2048, pv[4 * hh + 1], pv[4 * hh + 3]);
                    }
                    const float gm = g == 0 ? 0.f : -1.f;
#pragma unroll
                    for (int hh = 0; hh < 4; hh++) {
                        const float* v = acc + 8 * hh;
                        const float p0 = __shfl_up_sync(0xffffffffu, v[2], 4), p1 = __shfl_up_sync(0xffffffffu, v[3], 4);
                        const float p2 = __shfl_up_sync(0xffffffffu, v[6], 4), p3 = __shfl_up_sync(0xffffffffu, v[7], 4);
                        sts64(kp + hh * 16384, pk_f16(fmaf(p0, gm, v[0]), fmaf(p1, gm, v[1])), pk_f16(fmaf(p2, gm, v[4]), fmaf(p3, gm, v[5])));
                        sts64(kp + hh * 16384 + 2048, pk_f16(v[2] - v[0], v[3] - v[1]), pk_f16(v[6] - v[4], v[7] - v[5]));
                    }
                    uint32_t big = 0;
#pragma unroll
                    for (int i = 0; i < 16; i++) big |= pv[i] & (pv[i] << 1);
                    uint32_t nn[4];
                    norm_part(acc, nn);
                    if (big & 0x40004000u) nn[0] = 0x7f007f00u;
                    const float km = norm_finish(nn, 1.f);
                    if (lane == 0) gN[1024 + nb * 128 + T] = km;
                }
                asm volatile("fence.proxy.async.shared::cta;" ::: "memory");
                bar_arrive(10, 288);
            }
#pragma unroll 1
            for (int p = wg < 2 ? 1 : 0; p < 3; p += 2) {
                float acc[48];
#pragma unroll
                for (int i = 0; i < 48; i++) acc[i] = 0.f;
                pin<48>(acc);
                if (p) bar_sync(5 + p, 512);
                gemm_pass<96, 6144, 1024, 2048, 512, 2>(acc, bar, dA0, lane, p == 0 ? strm_pos(0, 0) : 8 + 8 * p, p == 0 ? strm_code(0) : strm_code(1), p < 2 ? 6 + p : 0, p == 0, p == 2);
                const uint32_t hp = sb + OFF_R + (p == 2 ? 0 : 12288) + (wg & 1) * 16384 + ((warp & 3) * 16 + g) * 64 + t * 16;
                const uint32_t bp = sb + OFF_BIAS + p * 384 - 256 + t * 8;
                uint32_t ho[24];
                mbar_wait(bar + B_BI, 0);
                if (p == 0) {
                    uint32_t nn[4];
                    norm_part(acc, nn);
                    const float qm = norm_finish(nn, QSCALE * QSCALE);
                    if (lane == 0) gN[nb * 128 + T] = qm;
                    uint8_t* qp = gQ + (size_t)(nb * 4) * (SEQ * 32) + (size_t)row0 * 32 + t * 8;
#pragma unroll
                    for (int hh = 0; hh < 4; hh++) {
                        const float* v = acc + 8 * hh;
                        *(uint2*)(qp + hh * (SEQ * 32)) = make_uint2(pk_f16(v[0] * QSCALE, v[1] * QSCALE), pk_f16(v[4] * QSCALE, v[5] * QSCALE));
                        *(uint2*)(qp + hh * (SEQ * 32) + 256) = make_uint2(pk_f16(v[2] * QSCALE, v[3] * QSCALE), pk_f16(v[6] * QSCALE, v[7] * QSCALE));
                    }
                    bar_arrive(12, 288);
                } else {
                    gelu_pack<0, 2>(acc, bp, ho);
                    pin<16>(ho);
                    mbar_wait(bar + B_G, 0);
                    load_q(q, h, qd * 512 + flip * 256 + warp * 16 + g, t);
                }
                gelu_pack<2, 3>(acc, bp, ho);
                pin<8>(ho + 16);
                if (p == 2) bar_sync(9, 256);
                else mbar_wait(bar + B_SF + 8 * p, 0);
                if (p) {
#pragma unroll
                    for (int i = 0; i < 4; i++) sts128(hp + (i >> 1) * 32768 + (i & 1) * 512, ho + 4 * i);
                }
                sts128(hp + 65536, ho + 16);
                sts128(hp + 65536 + 512, ho + 20);
                asm volatile("fence.proxy.async.shared::cta;" ::: "memory");
                bar_arrive(1 + p, 288);
            }
        }
        uint32_t ep = 2;
        uint4* const op = gO + ((qd * 8 + wg) * NH + h) * 128 + (tid & 127);
        const uint64_t kd0 = mkdesc(SBD, 16, 256, 3);
        const uint64_t vd0 = mkdesc(SBD + 8192, OFF_ONE - 8192, 256, 3);
        {
            float o[12];
#pragma unroll 1
            for (int rh = 0; rh < 4; rh++) {
                if (rh == 1) {
                    mbar_wait(bar + B_G3, 0);
                    ep = lds32(sb + OFF_G + 256);
                    if (!(ep & 2)) break;
                }
                if (rh == 3 && lane == 0) mbar_arrive(bar + B_DONE);
                if (!(rh & 1)) {
#pragma unroll
                    for (int i = 0; i < 12; i++) o[i] = 0.f;
                }
                uint64_t kd = kd0 + (rh & 1) * 4096, vd = vd0 + (rh & 1) * (128 * VSTEP);
                uint32_t kvb = bar + B_KV + (rh & 1) * 32;
                float s[32];
#pragma unroll
                for (int i = 0; i < 32; i++) s[i] = ((MUM >> (i >> 1)) & 1) ? 0.f : MAGIC;
#pragma unroll 1
                for (int c = 0; c < 4; c++) {
                    mbar_wait(kvb, 0);
                    kvb += 8;
#pragma unroll
                    for (int j = 0; j < 4; j++) {
                        uint32_t p[16];
                        if (j == 0) {
                            wg_fence();
                            wgmma_qk_f16_acc(s, q, kd + j * 128);
                            wg_commit();
                        }
                        wg_wait<0>();
                        pin<32>(s);
#pragma unroll
                        for (int u = 0; u < 4; u++) {
#pragma unroll
                            for (int i = 4 * u; i < 4 * u + 4; i++)
                                p[i] = ((MUM >> i) & 1) ? pk_bf16(ex2f(s[2 * i]), ex2f(s[2 * i + 1])) : exp2_pair(s[2 * i], s[2 * i + 1], m1);
                            pin<4>(p + 4 * u);
                            if (u == 3 || ((FM >> u) & 1)) {
                                wg_fence();
#pragma unroll
                                for (int v = 0; v <= u; v++)
                                    if (((FM & ((1 << u) - 1)) >> v) == 0) wgmma_pv(o, p + 4 * v, vd + (j * 4 + v) * VSTEP);
                            }
                        }
                        if (j < 3) wgmma_qk_f16_acc(s, q, kd + (j + 1) * 128);
                        wg_commit();
                    }
                    kd += 1024;
                    vd += 32 * VSTEP;
                }
                wg_wait<0>();
                pin<12>(o);
                if (rh & 1) {
                    if (rh == 1) {
                        load_q(q, h, qd * 512 + (flip ^ 1) * 256 + warp * 16 + g, t);
                        st_o(op + (flip ^ 1) * (4 * NH * 128), ~ep & 1, 0, 0, 0);
                    }
                    store_o(o, op + ((rh >> 1) ^ flip) * (4 * NH * 128), ep & 1);
                }
            }
        }
        if (!(ep & 2)) {
            bar_sync(8, 512);
            for (int c = 0; c < 8; c++) mbar_wait(bar + B_KV + 8 * c, 0);
            {
                float kc[8][8];
                proj16<8>(kc, x, wqkv, warp * 16, 256, DM + h * 16, g, t);
#pragma unroll
                for (int i = 0; i < 8; i++) {
                    const int T = warp + i * 16;
                    const int pos = ((T >> 6) * 16 + 2 * g) * 64 + (T & 63);
                    const uint32_t a = sb + (pos >> 8) * 16384 + (pos & 255) * 32 + t * 4, sw = ((T >> 2) & 1) << 4;
                    asm volatile("st.shared.u32 [%0], %1;" ::"r"(a + sw), "r"(pk_bf16(kc[i][0], kc[i][1])) : "memory");
                    asm volatile("st.shared.u32 [%0], %1;" ::"r"(a + (sw ^ 16)), "r"(pk_bf16(kc[i][4], kc[i][5])) : "memory");
                    asm volatile("st.shared.u32 [%0], %1;" ::"r"(a + 2048 + sw), "r"(pk_bf16(kc[i][2], kc[i][3])) : "memory");
                    asm volatile("st.shared.u32 [%0], %1;" ::"r"(a + 2048 + (sw ^ 16)), "r"(pk_bf16(kc[i][6], kc[i][7])) : "memory");
                }
                asm volatile("fence.proxy.async.shared::cta;" ::: "memory");
                bar_sync(8, 512);
            }
#pragma unroll 1
            for (int r = 0; r < 2; r++) {
                const int row = qd * 512 + (r ^ flip) * 256 + warp * 16 + g;
                {
                    float qc[1][8];
                    proj16<1>(qc, x, wqkv, row - g, 0, h * 16, g, t);
#pragma unroll
                    for (int i = 0; i < 4; i++) q[i] = pk_bf16(qc[0][2 * i], qc[0][2 * i + 1]);
                }
                float o[12];
#pragma unroll
                for (int i = 0; i < 12; i++) o[i] = 0.f;
                float ma = -INFINITY, mb_ = -INFINITY;
#pragma unroll 1
                for (int j = 0; j < 32; j++) {
                    const uint64_t kd = kd0 + (j >> 2) * 1024 + (j & 3) * 128, vd = vd0 + ((j >> 2) * 32 + (j & 3) * 4) * VSTEP;
                    float s[32];
                    uint32_t p[16];
                    wg_fence();
                    wgmma_qk_bf16_zero(s, q, kd);
                    wg_commit();
                    wg_wait<0>();
                    pin<32>(s);
                    pin<12>(o);
#pragma unroll
                    for (int i = 0; i < 16; i++) {
                        const uint32_t u = pk_bf16(s[2 * i], s[2 * i + 1]);
                        s[2 * i] = bf_lo(u);
                        s[2 * i + 1] = bf_hi(u);
                    }
                    float n0 = ma, n1 = mb_;
#pragma unroll
                    for (int i = 0; i < 8; i++) {
                        n0 = fmaxf(n0, fmaxf(s[4 * i], s[4 * i + 1]));
                        n1 = fmaxf(n1, fmaxf(s[4 * i + 2], s[4 * i + 3]));
                    }
                    n0 = fmaxf(n0, __shfl_xor_sync(0xffffffffu, n0, 1));
                    n1 = fmaxf(n1, __shfl_xor_sync(0xffffffffu, n1, 1));
                    n0 = fmaxf(n0, __shfl_xor_sync(0xffffffffu, n0, 2));
                    n1 = fmaxf(n1, __shfl_xor_sync(0xffffffffu, n1, 2));
                    const float c0 = ex2f((ma - n0) * QSCALE), c1 = ex2f((mb_ - n1) * QSCALE);
                    ma = n0;
                    mb_ = n1;
#pragma unroll
                    for (int i = 0; i < 3; i++) { o[4 * i] *= c0; o[4 * i + 1] *= c0; o[4 * i + 2] *= c1; o[4 * i + 3] *= c1; }
#pragma unroll
                    for (int i = 0; i < 8; i++) {
                        p[2 * i] = pk_bf16(ex2f((s[4 * i] - n0) * QSCALE), ex2f((s[4 * i + 1] - n0) * QSCALE));
                        p[2 * i + 1] = pk_bf16(ex2f((s[4 * i + 2] - n1) * QSCALE), ex2f((s[4 * i + 3] - n1) * QSCALE));
                    }
                    pin<16>(p);
                    pin<12>(o);
                    wg_fence();
#pragma unroll
                    for (int u = 0; u < 4; u++) wgmma_pv(o, p + 4 * u, vd + u * VSTEP);
                    wg_commit();
                }
                wg_wait<0>();
                pin<12>(o);
                store_o(o, op + (r ^ flip) * (4 * NH * 128), ep & 1);
                if (r == 1 && lane == 0) mbar_arrive(bar + B_DONE);
            }
        }
        if (lane == 0) mbar_arrive(bar + B_DONE2);
        {
            const uint4* src = gO + (rb * NH + (wg * 2 + (rn ^ 1)) * 4) * 128 + (tid & 127);
            uint4 v[4];
#pragma unroll
            for (int i = 0; i < 4; i++) v[i] = load_o(src + i * 128);
            mbar_wait(bar + B_G2, 0);
            const int lr = (warp & 3) * 16;
            const uint32_t g0 = lds32(sb + OFF_G + (lr + g) * 4), g1 = lds32(sb + OFF_G + (lr + g) * 4 + 32);
            fetch_o<4>(v, src, ep);
            mbar_wait(bar + B_DONE2, 0);
            stage_o(v, sb + 65536 + wg * 8192 + (lr + (lane & 15)) * 128, g0, g1, lane);
            __syncwarp();
            if (lane == 0) mbar_arrive(bar + B_T + 32 + 8 * wg);
        }
    } else {
        if (warp == 16) {
            if (elect()) issue_stream<NR, 18>(tm, sb, rank, nb, mb);
            __syncwarp();
#pragma unroll 1
            for (int o = 0; o < 2; o++) {
#pragma unroll 1
                for (int s = 0; s < NR; s++) {
                    mbar_wait(bar + B_E1 + 8 * s, o);
                    if (elect())
                        tma3d_mc(sb + OFF_R + s * 16384 + rank * 6144, &tm.f3, 0, (o ? s : s + 2) * 64 + rank * 32, nb * 7 + 1 + 3 * o, bar + B_F1 + 8 * (18 + o * NR + s));
                }
            }
            if (elect()) {
                issue_stream<30, 32>(tm, sb, rank, nb, mb);
                mbar_wait(bar + B_SF2, 0);
#pragma unroll
                for (int s = 0; s < 4; s++) {
                    mbar_expect(bar + B_F2 + 8 * s, 24576);
                    tma5d_mc(sb + OFF_R + s * 24576 + 8192 + rank * 8192, &tm.w2, cb * 128 + rank * 64, s * 2, bar + B_F2 + 8 * s);
                }
                cnt_wait(gCntH + mb * 32, epoch() * 8);
                asm volatile("fence.proxy.async.global;" ::: "memory");
#pragma unroll
                for (int s = 0; s < 4; s++) tma2d(sb + OFF_R + s * 24576, &tm.h, s * 64, rb * 64, bar + B_F2 + 8 * s);
            }
        } else if (warp == 17) {
            {
                uint32_t bv[4], b2v[2];
#pragma unroll
                for (int i = 0; i < 4; i++) bv[i] = lane + 32 * i < 112 ? *(const uint32_t*)(b1 + nb * 224 + (lane + 32 * i) * 2) : 0;
#pragma unroll
                for (int i = 0; i < 2; i++) b2v[i] = *(const uint32_t*)(b2 + cb * 128 + (lane + 32 * i) * 2);
#pragma unroll
                for (int i = 0; i < 4; i++) {
                    sts32(sb + OFF_ONE + (lane + 32 * i) * 4, 0x3f803f80u);
                    if (lane + 32 * i < 112) sts64(sb + OFF_BIAS + (lane + 32 * i) * 8, bv[i] << 16, bv[i] & 0xffff0000u);
                }
#pragma unroll
                for (int i = 0; i < 2; i++) sts32(sb + OFF_BIAS + 896 + (lane + 32 * i) * 4, b2v[i]);
                asm volatile("fence.proxy.async.shared::cta;" ::: "memory");
                __syncwarp();
                if (lane == 0) mbar_arrive(bar + B_BI);
            }
            mbar_wait(bar + B_X, 0);
            if (lane == 0) {
                l2_prefetch((const uint8_t*)wqkv + 128 * 3072 + (size_t)blockIdx.x * 9216, 9216);
                l2_prefetch((const uint8_t*)w1 + (size_t)blockIdx.x * 14336, 14336);
            }
            mbar_wait(bar + B_X + 8 * 7, 0);
            if (lane == 0) {
                l2_prefetch((const uint8_t*)w2 + (size_t)blockIdx.x * 14336, 14336);
                l2_prefetch((const uint8_t*)wo + (size_t)blockIdx.x * 4096, 4096);
                map_prefetch(&tm.h); map_prefetch(&tm.w2); map_prefetch(&tm.wo); map_prefetch(&tm.hs); map_prefetch(&tm.kvs);
            }
            bar_sync(10, 288);
            if (lane == 0) {
#pragma unroll 1
                for (int b = 5; b >= 0; b--) {
                    tma5d_st(&tm.kvs, sb + OFF_R + 12288 + b * 16384, (mb >> 3) * 8, (mb & 7) * 2, nb * 8 + (b < 4 ? 2 * b : 2 * b - 7));
                    asm volatile("cp.async.bulk.commit_group;\ncp.async.bulk.wait_group.read 1;" ::: "memory");
                    if (b == 3) mbar_arrive(bar + B_SF);
                }
                asm volatile("cp.async.bulk.wait_group.read 0;" ::: "memory");
                mbar_arrive(bar + B_SF + 8);
            }
            __syncwarp();
            bar_sync(12, 288);
            if (lane == 0) {
                asm volatile("cp.async.bulk.wait_group 0;\nfence.proxy.async.global;" ::: "memory");
                cnt_add(gCntQ + nb * 32);
            }
        } else {
            {
                mbar_wait(bar + B_X + 8 * 7, 0);
                const int r0 = mb * 128 + nb * 16 + (warp - 18) * 8;
                uint4 xv[16];
#pragma unroll
                for (int i = 0; i < 16; i++) xv[i] = *(const uint4*)(x + (size_t)(r0 + (i >> 1)) * DM + (i & 1) * 256 + lane * 8);
                const uint4 ga = *(const uint4*)(gate + lane * 8), gb = *(const uint4*)(gate + 256 + lane * 8);
                float z[8];
#pragma unroll
                for (int r = 0; r < 8; r++) z[r] = dot8(xv[2 * r], ga) + dot8(xv[2 * r + 1], gb);
#pragma unroll
                for (int w = 4; w >= 1; w >>= 1)
#pragma unroll
                    for (int r = 0; r < w; r++) {
                        const bool up = lane & w;
                        z[r] = (up ? z[r + w] : z[r]) + __shfl_xor_sync(0xffffffffu, up ? z[r] : z[r + w], w);
                    }
                z[0] += __shfl_xor_sync(0xffffffffu, z[0], 8);
                z[0] += __shfl_xor_sync(0xffffffffu, z[0], 16);
                if (lane < 8) gG[r0 + lane] = 1.f / (1.f + __expf(-z[0]));
            }
            if (warp == 19) {
#pragma unroll 1
                for (int e = 0; e < 3; e++) {
                    bar_sync(1 + e, 288);
                    if (lane == 0) {
#pragma unroll 1
                        for (int b = e == 0 ? 4 : 0; b < 6; b++) {
                            tma3d_st(&tm.hs, sb + OFF_R + (e == 2 ? 0 : 12288) + b * 16384, 0, mb * 128 + (b & 1) * 64, nb * 7 + e * 3 - 2 + (b >> 1));
                            asm volatile("cp.async.bulk.commit_group;\ncp.async.bulk.wait_group.read 1;" ::: "memory");
                        }
                        asm volatile("cp.async.bulk.wait_group.read 0;" ::: "memory");
                        if (e == 0) mbar_arrive(bar + B_SF + 8);
                        if (e == 2) { mbar_arrive_cluster(bar + B_SF2, 0); mbar_arrive_cluster(bar + B_SF2, 1); }
                    }
                    __syncwarp();
                }
                bar_sync(13, 64);
                if (lane == 0) {
                    asm volatile("cp.async.bulk.wait_group 0;\nfence.proxy.async.global;" ::: "memory");
                    cnt_add(gCntH + mb * 32);
                }
            } else {
                bar_arrive(13, 64);
                const int h = cl >> 1, qd = (cl & 1) * 2 + rank;
                const uint32_t ep = epoch();
                if (lane == 0) {
                    cnt_wait(gCntQ + (h >> 2) * 32, ep * 16);
                    mbar_arrive(bar + B_G);
                    asm volatile("fence.proxy.async.global;" ::: "memory");
#pragma unroll
                    for (int c = 0; c < 2; c++) {
                        mbar_wait(bar + B_XD + 8 * c, 0);
                        bulk_mc(sb + c * 16384 + rank * 8192, gKV + (size_t)h * (SEQ * 64) + rank * 65536 + c * 8192, 8192, bar + B_KV + 8 * c);
                    }
                }
                __syncwarp();
                const int hb = h >> 2;
                const uint4 kq = __ldcg((const uint4*)(gN + 1024 + hb * 128 + lane * 4));
                const float qq = ldcg_f(gN + hb * 128 + qd * 32 + lane);
                const float kf = __uint_as_float(__reduce_max_sync(0xffffffffu, max(max(kq.x, kq.y), max(kq.z, kq.w))));
                const float qf = __uint_as_float(__reduce_max_sync(0xffffffffu, __float_as_uint(qq)));
                if (lane == 0) {
                    sts32(sb + OFF_G + 256, (ep & 1) | ((kf <= 1.0e6f) && (qf <= 1.0e6f) && (kf * qf <= 2300.f) ? 2 : 0));
                    mbar_arrive(bar + B_G3);
#pragma unroll
                    for (int c = 2; c < 8; c++) {
                        mbar_wait(bar + B_XD + 8 * c, 0);
                        bulk_mc(sb + c * 16384 + rank * 8192, gKV + (size_t)h * (SEQ * 64) + rank * 65536 + c * 8192, 8192, bar + B_KV + 8 * c);
                    }
                }
            }
        }
        __syncwarp();
        float acc[64];
#pragma unroll
        for (int i = 0; i < 64; i++) acc[i] = 0.f;
#pragma unroll 1
        for (int io = 0; io < 7; io++) {
#pragma unroll
            for (int s = 0; s < 4; s++) {
                const int it = io * 4 + s;
                mbar_wait(bar + B_F2 + 8 * s, io & 1);
                const uint64_t dA = mkdesc(SBD + OFF_R + s * 24576, 16, 1024, 1);
                const uint64_t dB = mkdesc(SBD + OFF_R + s * 24576 + 8192, 8192, 1024, 1);
                wg_fence();
#pragma unroll
                for (int kk = 0; kk < 4; kk++) {
                    wgmma_ss_n128(acc, dA + kk * 2, dB + kk * 128);
                    if (kk < 3) {
                        wg_commit();
                        wg_wait<0>();
                    }
                }
                wg_commit();
                if (warp == 16 + s && it >= 2 && it < 26) {
                    const int s2 = (s + 2) & 3;
                    mbar_wait(bar + B_E2 + 8 * s2, (io - (s < 2)) & 1);
                    if (elect()) {
                        mbar_expect(bar + B_F2 + 8 * s2, 24576);
                        tma5d_mc(sb + OFF_R + s2 * 24576 + 8192 + rank * 8192, &tm.w2, cb * 128 + rank * 64, it * 2 + 4, bar + B_F2 + 8 * s2);
                        asm volatile("fence.proxy.async.global;" ::: "memory");
                        tma2d(sb + OFF_R + s2 * 24576, &tm.h, it * 64 + 128, rb * 64, bar + B_F2 + 8 * s2);
                    }
                    __syncwarp();
                }
                wg_wait<1>();
                if (it >= 1 && lane < 2) mbar_arrive_cluster(bar + B_E2 + 8 * ((s + 3) & 3), lane);
            }
        }
        wg_wait<0>();
        if (lane < 2) mbar_arrive_cluster(bar + B_E2 + 8 * 3, lane);
        pin<64>(acc);
        if (tid == 576) gEpoch[blockIdx.x] = epoch();
        if (warp == 16) {
            for (int s = 0; s < 4; s++) mbar_wait(bar + B_E2 + 8 * s, 0);
            if (elect()) {
#pragma unroll
                for (int i = 0; i < 4; i++)
                    tma5d_mc(sb + OFF_R + i * 16384 + rank * 8192, &tm.wo, cb * 128 + rank * 64, (i * 2 + rn) * 4, bar + B_T + 8 * i);
            }
            __syncwarp();
        }
        uint32_t pa;
        {
            const int lr = (warp - 16) * 16 + g;
            pa = pk_bf16(ldcg_f(gG + rb * 64 + lr), ldcg_f(gG + rb * 64 + lr + 8));
            if (t == 0) {
                sts32(sb + OFF_G + lr * 4, __byte_perm(pa, pa, 0x1010));
                sts32(sb + OFF_G + lr * 4 + 32, __byte_perm(pa, pa, 0x3232));
            }
            __syncwarp();
            if (lane == 0) mbar_arrive(bar + B_G2);
            const float ga = bf_lo(pa), gb = bf_hi(pa);
            const float g0 = 1.f - ga, g1 = 1.f - gb;
#pragma unroll
            for (int j = 0; j < 16; j++) {
                const uint32_t bv = lds32(sb + OFF_BIAS + 896 + j * 16 + t * 4);
                acc[4 * j] = fmaf(acc[4 * j], 0.5f, bf_lo(bv)) * g0;
                acc[4 * j + 1] = fmaf(acc[4 * j + 1], 0.5f, bf_hi(bv)) * g0;
                acc[4 * j + 2] = fmaf(acc[4 * j + 2], 0.5f, bf_lo(bv)) * g1;
                acc[4 * j + 3] = fmaf(acc[4 * j + 3], 0.5f, bf_hi(bv)) * g1;
            }
            pin<64>(acc);
        }
        {
            mbar_wait(bar + B_G3, 0);
            const uint32_t ep = lds32(sb + OFF_G + 256);
            const uint4* src = gO + (rb * NH + rn * 4) * 128 + (tid & 127);
            bar_sync(15, 128);
#pragma unroll 1
            for (int e = 0; e < 4; e++) {
                uint4 v[4];
#pragma unroll
                for (int i = 0; i < 4; i++) v[i] = load_o(src + i * 128);
                fetch_o<4>(v, src, ep);
                stage_o(v, sb + OFF_R + 65536 + e * 8192 + ((warp - 16) * 16 + (lane & 15)) * 128, __byte_perm(pa, pa, 0x1010), __byte_perm(pa, pa, 0x3232), lane);
                src += 8 * 128;
            }
            if (warp == 16) {
                mbar_wait(bar + B_DONE, 0);
                if (elect()) {
#pragma unroll
                    for (int i = 0; i < 8; i++)
                        tma5d(sb + i * 8192, &tm.wo, cb * 128 + (i & 1) * 64, ((i >> 1) * 2 + (rn ^ 1)) * 4, bar + B_T + 32 + 8 * (i >> 1));
                }
                __syncwarp();
            }
            bar_sync(15, 128);
            mbar_wait(bar + B_DONE2, 0);
        }
#pragma unroll 1
        for (int late = 0; late < 2; late++) {
            const uint64_t dB0 = mkdesc(SBD + OFF_R, 8192, 1024, 1) - late * (OFF_R / 16);
#pragma unroll
            for (int i = 0; i < 4; i++) {
                mbar_wait(bar + B_T + late * 32 + 8 * i, 0);
                const uint64_t dA = mkdesc(SBD + OFF_R + 65536 + i * 8192, 16, 1024, 1) - late * (OFF_R / 16);
                wg_fence();
#pragma unroll
                for (int kk = 0; kk < 4; kk++) wgmma_ss_n128(acc, dA + kk * 2, dB0 + i * 1024 + kk * 128);
                wg_commit();
            }
        }
        wg_wait<0>();
        pin<64>(acc);
        {
            const uint32_t st = sb + 98304 + (warp - 16) * 4352;
            const uint32_t wa = st + (lane & 15) * 272 + (lane >> 4) * 16;
#pragma unroll
            for (int j = 0; j < 8; j++)
                asm volatile("stmatrix.sync.aligned.m8n8.x4.shared.b16 [%0], {%1, %2, %3, %4};" ::"r"(wa + j * 32),
                             "r"(pk_bf16(acc[8 * j], acc[8 * j + 1])), "r"(pk_bf16(acc[8 * j + 2], acc[8 * j + 3])),
                             "r"(pk_bf16(acc[8 * j + 4], acc[8 * j + 5])), "r"(pk_bf16(acc[8 * j + 6], acc[8 * j + 7])) : "memory");
            __syncwarp();
            __nv_bfloat16* op = out + (size_t)(rb * 64 + (warp - 16) * 16 + (lane >> 4)) * DM + cb * 128 + (lane & 15) * 8;
#pragma unroll
            for (int j = 0; j < 8; j++) {
                uint4 v;
                asm volatile("ld.shared.v4.u32 {%0, %1, %2, %3}, [%4];" : "=r"(v.x), "=r"(v.y), "=r"(v.z), "=r"(v.w)
                             : "r"(st + (2 * j + (lane >> 4)) * 272 + (lane & 15) * 16));
                *(uint4*)(op + (size_t)j * 2 * DM) = v;
            }
        }
    }
}

typedef CUresult (*EncodeFn)(CUtensorMap*, CUtensorMapDataType, cuuint32_t, void*, const cuuint64_t*, const cuuint64_t*, const cuuint32_t*,
                             const cuuint32_t*, CUtensorMapInterleave, CUtensorMapSwizzle, CUtensorMapL2promotion, CUtensorMapFloatOOBfill);

static void make_map(EncodeFn enc, CUtensorMap* m, const void* p, int rank, const cuuint64_t* dims, const cuuint64_t* strides,
                     const cuuint32_t* box, CUtensorMapSwizzle swz) {
    const cuuint32_t es[5] = {1, 1, 1, 1, 1};
    enc(m, CU_TENSOR_MAP_DATA_TYPE_BFLOAT16, rank, (void*)p, dims, strides, box, es, CU_TENSOR_MAP_INTERLEAVE_NONE, swz,
        CU_TENSOR_MAP_L2_PROMOTION_L2_128B, CU_TENSOR_MAP_FLOAT_OOB_FILL_NONE);
}

extern "C" void kernel_launch(void* const* d_in, const int* in_sizes, int n_in, void* d_out, int out_size) {
    const __nv_bfloat16* x = (const __nv_bfloat16*)d_in[0];
    const __nv_bfloat16* wqkv = (const __nv_bfloat16*)d_in[1];
    const __nv_bfloat16* wo = (const __nv_bfloat16*)d_in[2];
    const __nv_bfloat16* w1 = (const __nv_bfloat16*)d_in[4];
    const __nv_bfloat16* b1 = (const __nv_bfloat16*)d_in[5];
    const __nv_bfloat16* w2 = (const __nv_bfloat16*)d_in[6];
    const __nv_bfloat16* b2 = (const __nv_bfloat16*)d_in[7];
    const __nv_bfloat16* gate = (const __nv_bfloat16*)d_in[8];

    void* fp = nullptr;
    cudaDriverEntryPointQueryResult qr;
    cudaGetDriverEntryPoint("cuTensorMapEncodeTiled", &fp, cudaEnableDefault, &qr);
    EncodeFn enc = (EncodeFn)fp;
    void *pH, *pKV;
    cudaGetSymbolAddress(&pH, gH);
    cudaGetSymbolAddress(&pKV, gKV);

    Maps tm;
    const CUtensorMapSwizzle S128 = CU_TENSOR_MAP_SWIZZLE_128B, S64 = CU_TENSOR_MAP_SWIZZLE_64B;
    { cuuint64_t d[2] = {DM, SEQ}, s[1] = {DM * 2}; cuuint32_t b[2] = {64, 128}; make_map(enc, &tm.x, x, 2, d, s, b, S128); }
    { cuuint64_t d[3] = {DM, DM, 3}, s[2] = {3 * DM * 2, DM * 2}; cuuint32_t b[3] = {64, 32, 2}; make_map(enc, &tm.kv, wqkv, 3, d, s, b, S128); }
    { cuuint64_t d[3] = {32, DM, 3 * DM / 32}, s[2] = {3 * DM * 2, 64}; cuuint32_t b[3] = {32, 32, 2}; make_map(enc, &tm.q, wqkv, 3, d, s, b, S64); }
    { cuuint64_t d[3] = {32, DM, FF / 32}, s[2] = {FF * 2, 64}; cuuint32_t b[3] = {32, 32, 1}; make_map(enc, &tm.f1, w1, 3, d, s, b, S64); }
    { cuuint64_t d[3] = {32, DM, FF / 32}, s[2] = {FF * 2, 64}; cuuint32_t b[3] = {32, 32, 3}; make_map(enc, &tm.f3, w1, 3, d, s, b, S64); }
    { cuuint64_t d[2] = {FF, SEQ}, s[1] = {FF * 2}; cuuint32_t b[2] = {64, 64}; make_map(enc, &tm.h, pH, 2, d, s, b, S128); }
    { cuuint64_t d[5] = {DM, 2, 4, 4, FF / 32}, s[4] = {1024, 8 * 1024, 2 * 1024, 32 * 1024}; cuuint32_t b[5] = {64, 2, 4, 4, 2};
      make_map(enc, &tm.w2, w2, 5, d, s, b, S128); }
    { cuuint64_t d[5] = {DM, 2, 2, 4, NH}, s[4] = {1024, 8 * 1024, 2 * 1024, 16 * 1024}; cuuint32_t b[5] = {64, 2, 2, 4, 4};
      make_map(enc, &tm.wo, wo, 5, d, s, b, S128); }

    { cuuint64_t d[3] = {32, SEQ, FF / 32}, s[2] = {FF * 2, 64}; cuuint32_t b[3] = {32, 64, 1}; make_map(enc, &tm.hs, pH, 3, d, s, b, CU_TENSOR_MAP_SWIZZLE_NONE); }
    { cuuint64_t d[5] = {64, 16, 16, 2, 2 * NH}, s[4] = {4096, 128, 2048, 65536}; cuuint32_t b[5] = {64, 8, 2, 2, 1};
      make_map(enc, &tm.kvs, pKV, 5, d, s, b, S128); }
    cudaFuncSetAttribute(fused_kernel, cudaFuncAttributeMaxDynamicSharedMemorySize, SMEM_BYTES);
    fused_kernel<<<128, 640, SMEM_BYTES, cudaStreamPerThread>>>(tm, x, wqkv, wo, w1, b1, w2, b2, gate, (__nv_bfloat16*)d_out, 0xffffffffu);
}
```
